```python
import torch

def _softmax(x, axis=-1):
    return torch.softmax(x, dim=axis)
def _gelu(x):
    return torch.nn.functional.gelu(x, approximate="tanh")
def _silu(x):
    return torch.nn.functional.silu(x)
def _sigmoid(x):
    return torch.sigmoid(x)
def _layernorm(x, axis=-1, eps=1e-5):
    m = x.mean(dim=axis, keepdim=True)
    v = x.var(dim=axis, keepdim=True, unbiased=False)
    return (x - m) / torch.sqrt(v + eps)
def _scatter_add(tgt, idx, src, axis=0):
    return tgt.clone().index_add_(axis, idx, src)
def _segment_sum(src, seg, n):
    out = torch.zeros((n,) + src.shape[1:], dtype=src.dtype)
    return out.index_add_(0, seg, src)
def _pad(x, pw):
    flat = tuple(v for pair in reversed(pw) for v in pair)
    return torch.nn.functional.pad(x, flat)

kernel_name = 'concat_heads__gqa_block_cached__gqa_block_cached__near_ridge'

def setup_inputs():

    _w = (lambda a: (lambda t: t.to(torch.bfloat16) if t.is_floating_point() else t)(torch.as_tensor(a)))
    def _A_setup():
        B, Sq, D = 8, 256, 640
        Hq, Hkv, Sk, Dh = 32, 32, 1024, 192
        assert Hq % Hkv == 0, (Hq, Hkv)
        return {
            "x": _w((lambda *s: torch.randn(*s, dtype=torch.bfloat16) * 0.8)(B, Sq, D)),
            "k_cache": _w((lambda *s: torch.randn(*s, dtype=torch.bfloat16) * 0.8)(B, Hkv, Sk, Dh)),
            "v_cache": _w((lambda *s: torch.randn(*s, dtype=torch.bfloat16) * 0.05)(B, Hkv, Sk, Dh)),
            "wq": _w((lambda *s: torch.randn(*s, dtype=torch.bfloat16) * 0.8)(D, Hq * Dh) * (D ** -0.5)),
            "wo": _w((lambda *s: torch.randn(*s, dtype=torch.bfloat16) * 0.05)(Hq * Dh, D) * ((Hq * Dh) ** -0.5)),
        }
    _A_in = _A_setup()

    def _B_setup():
        B, Sq, D = 8, 256, 640
        Hq, Hkv, Sk, Dh = 32, 32, 1024, 192
        assert Hq % Hkv == 0, (Hq, Hkv)
        return {
            "x": _w((lambda *s: torch.randn(*s, dtype=torch.bfloat16) * 0.8)(B, Sq, D)),
            "k_cache": _w((lambda *s: torch.randn(*s, dtype=torch.bfloat16) * 0.8)(B, Hkv, Sk, Dh)),
            "v_cache": _w((lambda *s: torch.randn(*s, dtype=torch.bfloat16) * 0.05)(B, Hkv, Sk, Dh)),
            "wq": _w((lambda *s: torch.randn(*s, dtype=torch.bfloat16) * 0.8)(D, Hq * Dh) * (D ** -0.5)),
            "wo": _w((lambda *s: torch.randn(*s, dtype=torch.bfloat16) * 0.05)(Hq * Dh, D) * ((Hq * Dh) ** -0.5)),
        }
    _B_in = _B_setup()

    return {
        "A_x": _A_in["x"],
        "A_k_cache": _A_in["k_cache"],
        "A_v_cache": _A_in["v_cache"],
        "A_wq": _A_in["wq"],
        "A_wo": _A_in["wo"],
        "B_x": _B_in["x"],
        "B_k_cache": _B_in["k_cache"],
        "B_v_cache": _B_in["v_cache"],
        "B_wq": _B_in["wq"],
        "B_wo": _B_in["wo"],
    }

def reference(A_x, A_k_cache, A_v_cache, A_wq, A_wo, B_x, B_k_cache, B_v_cache, B_wq, B_wo):
    def _A_ref(x, k_cache, v_cache, wq, wo):
        B, Sq, D = x.shape
        Hq, Dh = 32, 192
        Hkv = k_cache.shape[1]
        rep = Hq // Hkv
        q = (lambda x, *d: x.permute(*d))((x @ wq).reshape(B, Sq, Hq, Dh), 0, 2, 1, 3)
        k = (lambda x, n, axis: torch.repeat_interleave(x, n, dim=axis))(k_cache, rep, axis=1)
        v = (lambda x, n, axis: torch.repeat_interleave(x, n, dim=axis))(v_cache, rep, axis=1)
        scores = torch.einsum("bhqd,bhkd->bhqk", q, k) * (Dh ** -0.5)
        p = _softmax(scores, axis=-1)
        o = torch.einsum("bhqk,bhkd->bhqd", p, v)
        return (lambda x, *d: x.permute(*d))(o, 0, 2, 1, 3).reshape(B, Sq, Hq * Dh) @ wo

    def _B_ref(x, k_cache, v_cache, wq, wo):
        B, Sq, D = x.shape
        Hq, Dh = 32, 192
        Hkv = k_cache.shape[1]
        rep = Hq // Hkv
        q = (lambda x, *d: x.permute(*d))((x @ wq).reshape(B, Sq, Hq, Dh), 0, 2, 1, 3)
        k = (lambda x, n, axis: torch.repeat_interleave(x, n, dim=axis))(k_cache, rep, axis=1)
        v = (lambda x, n, axis: torch.repeat_interleave(x, n, dim=axis))(v_cache, rep, axis=1)
        scores = torch.einsum("bhqd,bhkd->bhqk", q, k) * (Dh ** -0.5)
        p = _softmax(scores, axis=-1)
        o = torch.einsum("bhqk,bhkd->bhqd", p, v)
        return (lambda x, *d: x.permute(*d))(o, 0, 2, 1, 3).reshape(B, Sq, Hq * Dh) @ wo

    a = _A_ref(A_x, A_k_cache, A_v_cache, A_wq, A_wo)
    b = _B_ref(B_x, B_k_cache, B_v_cache, B_wq, B_wo)
    return torch.concatenate([a, b], axis=-1)
```

```cpp
#include <cuda_runtime.h>
#include <cuda_bf16.h>
#include <cuda.h>
#include <stdint.h>
#include <stdio.h>

namespace {

constexpr int kB = 8, kSq = 256, kD = 640, kH = 32, kSk = 1024, kDh = 192;
constexpr int kHD = kH * kDh;
#define RING_KB 224
constexpr uint32_t RING = RING_KB * 1024;
constexpr uint32_t SZ_KV = 24576;
constexpr uint32_t SZ_Q = 16384 + 24576;
constexpr uint32_t SZ_O = 16384 + 20480;
constexpr uint32_t SZ_PARK = 49152;
constexpr uint32_t SZ_PART = 40960;
constexpr int NBAR = 10;
constexpr int EARLY = 3;
constexpr uint32_t KV_CH = 64, KV_SBO = 3072;
constexpr int SMEM_BYTES = RING + 512 + 1024;
constexpr int N_TEAM = 16, N_CL = 64, N_HELP = 2, MAX_OPS = 24, MAX_PARK = 4;
enum { OP_END = 0, OP_Q = 1, OP_A = 2, OP_O = 3, F_PARK = 1 << 9, F_LD = 1 << 12, F_ST = 1 << 13, F_LAZY = 1 << 14, F_HELP = 1 << 12, F_SOON = 1 << 28 };

struct alignas(64) Params {
  uint32_t first[32];
  CUtensorMap x[2], wq[2], k[2], v[2], wo[2], out;
  uint32_t ops[N_TEAM + 2 * N_HELP][MAX_OPS];
  uint32_t slot[8];
  uint32_t dbg;
};

__device__ uint4 g_o[N_TEAM * 2 * 96 * 1024];
__device__ uint4 g_park[N_CL * 2 * MAX_PARK * 12 * 256];
__device__ uint4 g_part[N_CL * 2 * 5 * 1024];
__device__ unsigned int g_done[N_TEAM * 2 * 8];
__device__ unsigned int g_help[N_CL * 2 * MAX_PARK];
__device__ unsigned int g_seen[N_TEAM * 2 * 8];

template <int TB, int TA = 0>
__device__ __forceinline__ void wgmma_ss_n64(float (&d)[32], uint64_t da, uint64_t db, int scale_d) {
  asm volatile("{\n.reg .pred p;\nsetp.ne.b32 p, %34, 0;\n"
    "wgmma.mma_async.sync.aligned.m64n64k16.f32.bf16.bf16 {%0, %1, %2, %3, %4, %5, %6, %7, %8, %9, %10, %11, %12, %13, %14, %15, %16, %17, %18, %19, %20, %21, %22, %23, %24, %25, %26, %27, %28, %29, %30, %31}, %32, %33, p, 1, 1, %35, %36;\n}\n"
    : "+f"(d[0]), "+f"(d[1]), "+f"(d[2]), "+f"(d[3]), "+f"(d[4]), "+f"(d[5]), "+f"(d[6]), "+f"(d[7]), "+f"(d[8]), "+f"(d[9]), "+f"(d[10]), "+f"(d[11]), "+f"(d[12]), "+f"(d[13]), "+f"(d[14]), "+f"(d[15]), "+f"(d[16]), "+f"(d[17]), "+f"(d[18]), "+f"(d[19]), "+f"(d[20]), "+f"(d[21]), "+f"(d[22]), "+f"(d[23]), "+f"(d[24]), "+f"(d[25]), "+f"(d[26]), "+f"(d[27]), "+f"(d[28]), "+f"(d[29]), "+f"(d[30]), "+f"(d[31])
    : "l"(da), "l"(db), "r"(scale_d), "n"(TA), "n"(TB));
}
template <int TB>
__device__ __forceinline__ void wgmma_rs_n64(float (&d)[32], uint32_t a0, uint32_t a1, uint32_t a2, uint32_t a3, uint64_t db, int scale_d) {
  asm volatile("{\n.reg .pred p;\nsetp.ne.b32 p, %37, 0;\n"
    "wgmma.mma_async.sync.aligned.m64n64k16.f32.bf16.bf16 {%0, %1, %2, %3, %4, %5, %6, %7, %8, %9, %10, %11, %12, %13, %14, %15, %16, %17, %18, %19, %20, %21, %22, %23, %24, %25, %26, %27, %28, %29, %30, %31}, {%32, %33, %34, %35}, %36, p, 1, 1, %38;\n}\n"
    : "+f"(d[0]), "+f"(d[1]), "+f"(d[2]), "+f"(d[3]), "+f"(d[4]), "+f"(d[5]), "+f"(d[6]), "+f"(d[7]), "+f"(d[8]), "+f"(d[9]), "+f"(d[10]), "+f"(d[11]), "+f"(d[12]), "+f"(d[13]), "+f"(d[14]), "+f"(d[15]), "+f"(d[16]), "+f"(d[17]), "+f"(d[18]), "+f"(d[19]), "+f"(d[20]), "+f"(d[21]), "+f"(d[22]), "+f"(d[23]), "+f"(d[24]), "+f"(d[25]), "+f"(d[26]), "+f"(d[27]), "+f"(d[28]), "+f"(d[29]), "+f"(d[30]), "+f"(d[31])
    : "r"(a0), "r"(a1), "r"(a2), "r"(a3), "l"(db), "r"(scale_d), "n"(TB));
}
template <int TB, int TA = 0>
__device__ __forceinline__ void wgmma_ss_n160(float (&d)[80], uint64_t da, uint64_t db, int scale_d) {
  asm volatile("{\n.reg .pred p;\nsetp.ne.b32 p, %82, 0;\n"
    "wgmma.mma_async.sync.aligned.m64n160k16.f32.bf16.bf16 {%0, %1, %2, %3, %4, %5, %6, %7, %8, %9, %10, %11, %12, %13, %14, %15, %16, %17, %18, %19, %20, %21, %22, %23, %24, %25, %26, %27, %28, %29, %30, %31, %32, %33, %34, %35, %36, %37, %38, %39, %40, %41, %42, %43, %44, %45, %46, %47, %48, %49, %50, %51, %52, %53, %54, %55, %56, %57, %58, %59, %60, %61, %62, %63, %64, %65, %66, %67, %68, %69, %70, %71, %72, %73, %74, %75, %76, %77, %78, %79}, %80, %81, p, 1, 1, %83, %84;\n}\n"
    : "+f"(d[0]), "+f"(d[1]), "+f"(d[2]), "+f"(d[3]), "+f"(d[4]), "+f"(d[5]), "+f"(d[6]), "+f"(d[7]), "+f"(d[8]), "+f"(d[9]), "+f"(d[10]), "+f"(d[11]), "+f"(d[12]), "+f"(d[13]), "+f"(d[14]), "+f"(d[15]), "+f"(d[16]), "+f"(d[17]), "+f"(d[18]), "+f"(d[19]), "+f"(d[20]), "+f"(d[21]), "+f"(d[22]), "+f"(d[23]), "+f"(d[24]), "+f"(d[25]), "+f"(d[26]), "+f"(d[27]), "+f"(d[28]), "+f"(d[29]), "+f"(d[30]), "+f"(d[31]), "+f"(d[32]), "+f"(d[33]), "+f"(d[34]), "+f"(d[35]), "+f"(d[36]), "+f"(d[37]), "+f"(d[38]), "+f"(d[39]), "+f"(d[40]), "+f"(d[41]), "+f"(d[42]), "+f"(d[43]), "+f"(d[44]), "+f"(d[45]), "+f"(d[46]), "+f"(d[47]), "+f"(d[48]), "+f"(d[49]), "+f"(d[50]), "+f"(d[51]), "+f"(d[52]), "+f"(d[53]), "+f"(d[54]), "+f"(d[55]), "+f"(d[56]), "+f"(d[57]), "+f"(d[58]), "+f"(d[59]), "+f"(d[60]), "+f"(d[61]), "+f"(d[62]), "+f"(d[63]), "+f"(d[64]), "+f"(d[65]), "+f"(d[66]), "+f"(d[67]), "+f"(d[68]), "+f"(d[69]), "+f"(d[70]), "+f"(d[71]), "+f"(d[72]), "+f"(d[73]), "+f"(d[74]), "+f"(d[75]), "+f"(d[76]), "+f"(d[77]), "+f"(d[78]), "+f"(d[79])
    : "l"(da), "l"(db), "r"(scale_d), "n"(TA), "n"(TB));
}
template <int TB>
__device__ __forceinline__ void wgmma_rs_n160(float (&d)[80], uint32_t a0, uint32_t a1, uint32_t a2, uint32_t a3, uint64_t db, int scale_d) {
  asm volatile("{\n.reg .pred p;\nsetp.ne.b32 p, %85, 0;\n"
    "wgmma.mma_async.sync.aligned.m64n160k16.f32.bf16.bf16 {%0, %1, %2, %3, %4, %5, %6, %7, %8, %9, %10, %11, %12, %13, %14, %15, %16, %17, %18, %19, %20, %21, %22, %23, %24, %25, %26, %27, %28, %29, %30, %31, %32, %33, %34, %35, %36, %37, %38, %39, %40, %41, %42, %43, %44, %45, %46, %47, %48, %49, %50, %51, %52, %53, %54, %55, %56, %57, %58, %59, %60, %61, %62, %63, %64, %65, %66, %67, %68, %69, %70, %71, %72, %73, %74, %75, %76, %77, %78, %79}, {%80, %81, %82, %83}, %84, p, 1, 1, %86;\n}\n"
    : "+f"(d[0]), "+f"(d[1]), "+f"(d[2]), "+f"(d[3]), "+f"(d[4]), "+f"(d[5]), "+f"(d[6]), "+f"(d[7]), "+f"(d[8]), "+f"(d[9]), "+f"(d[10]), "+f"(d[11]), "+f"(d[12]), "+f"(d[13]), "+f"(d[14]), "+f"(d[15]), "+f"(d[16]), "+f"(d[17]), "+f"(d[18]), "+f"(d[19]), "+f"(d[20]), "+f"(d[21]), "+f"(d[22]), "+f"(d[23]), "+f"(d[24]), "+f"(d[25]), "+f"(d[26]), "+f"(d[27]), "+f"(d[28]), "+f"(d[29]), "+f"(d[30]), "+f"(d[31]), "+f"(d[32]), "+f"(d[33]), "+f"(d[34]), "+f"(d[35]), "+f"(d[36]), "+f"(d[37]), "+f"(d[38]), "+f"(d[39]), "+f"(d[40]), "+f"(d[41]), "+f"(d[42]), "+f"(d[43]), "+f"(d[44]), "+f"(d[45]), "+f"(d[46]), "+f"(d[47]), "+f"(d[48]), "+f"(d[49]), "+f"(d[50]), "+f"(d[51]), "+f"(d[52]), "+f"(d[53]), "+f"(d[54]), "+f"(d[55]), "+f"(d[56]), "+f"(d[57]), "+f"(d[58]), "+f"(d[59]), "+f"(d[60]), "+f"(d[61]), "+f"(d[62]), "+f"(d[63]), "+f"(d[64]), "+f"(d[65]), "+f"(d[66]), "+f"(d[67]), "+f"(d[68]), "+f"(d[69]), "+f"(d[70]), "+f"(d[71]), "+f"(d[72]), "+f"(d[73]), "+f"(d[74]), "+f"(d[75]), "+f"(d[76]), "+f"(d[77]), "+f"(d[78]), "+f"(d[79])
    : "r"(a0), "r"(a1), "r"(a2), "r"(a3), "l"(db), "r"(scale_d), "n"(TB));
}
template <int TB, int TA = 0>
__device__ __forceinline__ void wgmma_ss_n192(float (&d)[96], uint64_t da, uint64_t db, int scale_d) {
  asm volatile("{\n.reg .pred p;\nsetp.ne.b32 p, %98, 0;\n"
    "wgmma.mma_async.sync.aligned.m64n192k16.f32.bf16.bf16 {%0, %1, %2, %3, %4, %5, %6, %7, %8, %9, %10, %11, %12, %13, %14, %15, %16, %17, %18, %19, %20, %21, %22, %23, %24, %25, %26, %27, %28, %29, %30, %31, %32, %33, %34, %35, %36, %37, %38, %39, %40, %41, %42, %43, %44, %45, %46, %47, %48, %49, %50, %51, %52, %53, %54, %55, %56, %57, %58, %59, %60, %61, %62, %63, %64, %65, %66, %67, %68, %69, %70, %71, %72, %73, %74, %75, %76, %77, %78, %79, %80, %81, %82, %83, %84, %85, %86, %87, %88, %89, %90, %91, %92, %93, %94, %95}, %96, %97, p, 1, 1, %99, %100;\n}\n"
    : "+f"(d[0]), "+f"(d[1]), "+f"(d[2]), "+f"(d[3]), "+f"(d[4]), "+f"(d[5]), "+f"(d[6]), "+f"(d[7]), "+f"(d[8]), "+f"(d[9]), "+f"(d[10]), "+f"(d[11]), "+f"(d[12]), "+f"(d[13]), "+f"(d[14]), "+f"(d[15]), "+f"(d[16]), "+f"(d[17]), "+f"(d[18]), "+f"(d[19]), "+f"(d[20]), "+f"(d[21]), "+f"(d[22]), "+f"(d[23]), "+f"(d[24]), "+f"(d[25]), "+f"(d[26]), "+f"(d[27]), "+f"(d[28]), "+f"(d[29]), "+f"(d[30]), "+f"(d[31]), "+f"(d[32]), "+f"(d[33]), "+f"(d[34]), "+f"(d[35]), "+f"(d[36]), "+f"(d[37]), "+f"(d[38]), "+f"(d[39]), "+f"(d[40]), "+f"(d[41]), "+f"(d[42]), "+f"(d[43]), "+f"(d[44]), "+f"(d[45]), "+f"(d[46]), "+f"(d[47]), "+f"(d[48]), "+f"(d[49]), "+f"(d[50]), "+f"(d[51]), "+f"(d[52]), "+f"(d[53]), "+f"(d[54]), "+f"(d[55]), "+f"(d[56]), "+f"(d[57]), "+f"(d[58]), "+f"(d[59]), "+f"(d[60]), "+f"(d[61]), "+f"(d[62]), "+f"(d[63]), "+f"(d[64]), "+f"(d[65]), "+f"(d[66]), "+f"(d[67]), "+f"(d[68]), "+f"(d[69]), "+f"(d[70]), "+f"(d[71]), "+f"(d[72]), "+f"(d[73]), "+f"(d[74]), "+f"(d[75]), "+f"(d[76]), "+f"(d[77]), "+f"(d[78]), "+f"(d[79]), "+f"(d[80]), "+f"(d[81]), "+f"(d[82]), "+f"(d[83]), "+f"(d[84]), "+f"(d[85]), "+f"(d[86]), "+f"(d[87]), "+f"(d[88]), "+f"(d[89]), "+f"(d[90]), "+f"(d[91]), "+f"(d[92]), "+f"(d[93]), "+f"(d[94]), "+f"(d[95])
    : "l"(da), "l"(db), "r"(scale_d), "n"(TA), "n"(TB));
}
template <int TB>
__device__ __forceinline__ void wgmma_rs_n192(float (&d)[96], uint32_t a0, uint32_t a1, uint32_t a2, uint32_t a3, uint64_t db, int scale_d) {
  asm volatile("{\n.reg .pred p;\nsetp.ne.b32 p, %101, 0;\n"
    "wgmma.mma_async.sync.aligned.m64n192k16.f32.bf16.bf16 {%0, %1, %2, %3, %4, %5, %6, %7, %8, %9, %10, %11, %12, %13, %14, %15, %16, %17, %18, %19, %20, %21, %22, %23, %24, %25, %26, %27, %28, %29, %30, %31, %32, %33, %34, %35, %36, %37, %38, %39, %40, %41, %42, %43, %44, %45, %46, %47, %48, %49, %50, %51, %52, %53, %54, %55, %56, %57, %58, %59, %60, %61, %62, %63, %64, %65, %66, %67, %68, %69, %70, %71, %72, %73, %74, %75, %76, %77, %78, %79, %80, %81, %82, %83, %84, %85, %86, %87, %88, %89, %90, %91, %92, %93, %94, %95}, {%96, %97, %98, %99}, %100, p, 1, 1, %102;\n}\n"
    : "+f"(d[0]), "+f"(d[1]), "+f"(d[2]), "+f"(d[3]), "+f"(d[4]), "+f"(d[5]), "+f"(d[6]), "+f"(d[7]), "+f"(d[8]), "+f"(d[9]), "+f"(d[10]), "+f"(d[11]), "+f"(d[12]), "+f"(d[13]), "+f"(d[14]), "+f"(d[15]), "+f"(d[16]), "+f"(d[17]), "+f"(d[18]), "+f"(d[19]), "+f"(d[20]), "+f"(d[21]), "+f"(d[22]), "+f"(d[23]), "+f"(d[24]), "+f"(d[25]), "+f"(d[26]), "+f"(d[27]), "+f"(d[28]), "+f"(d[29]), "+f"(d[30]), "+f"(d[31]), "+f"(d[32]), "+f"(d[33]), "+f"(d[34]), "+f"(d[35]), "+f"(d[36]), "+f"(d[37]), "+f"(d[38]), "+f"(d[39]), "+f"(d[40]), "+f"(d[41]), "+f"(d[42]), "+f"(d[43]), "+f"(d[44]), "+f"(d[45]), "+f"(d[46]), "+f"(d[47]), "+f"(d[48]), "+f"(d[49]), "+f"(d[50]), "+f"(d[51]), "+f"(d[52]), "+f"(d[53]), "+f"(d[54]), "+f"(d[55]), "+f"(d[56]), "+f"(d[57]), "+f"(d[58]), "+f"(d[59]), "+f"(d[60]), "+f"(d[61]), "+f"(d[62]), "+f"(d[63]), "+f"(d[64]), "+f"(d[65]), "+f"(d[66]), "+f"(d[67]), "+f"(d[68]), "+f"(d[69]), "+f"(d[70]), "+f"(d[71]), "+f"(d[72]), "+f"(d[73]), "+f"(d[74]), "+f"(d[75]), "+f"(d[76]), "+f"(d[77]), "+f"(d[78]), "+f"(d[79]), "+f"(d[80]), "+f"(d[81]), "+f"(d[82]), "+f"(d[83]), "+f"(d[84]), "+f"(d[85]), "+f"(d[86]), "+f"(d[87]), "+f"(d[88]), "+f"(d[89]), "+f"(d[90]), "+f"(d[91]), "+f"(d[92]), "+f"(d[93]), "+f"(d[94]), "+f"(d[95])
    : "r"(a0), "r"(a1), "r"(a2), "r"(a3), "l"(db), "r"(scale_d), "n"(TB));
}

__device__ __forceinline__ uint32_t smem_u32(const void* p) { return (uint32_t)__cvta_generic_to_shared(p); }
__device__ __forceinline__ void wg_fence() { asm volatile("wgmma.fence.sync.aligned;" ::: "memory"); }
__device__ __forceinline__ void wg_commit() { asm volatile("wgmma.commit_group.sync.aligned;" ::: "memory"); }
template <int N> __device__ __forceinline__ void wg_wait() { asm volatile("wgmma.wait_group.sync.aligned %0;" ::"n"(N) : "memory"); }
__device__ __forceinline__ void sched_fence(uint32_t& keep) {
  asm volatile("{\n.reg .u32 c;\nmov.u32 c, %%clock;\nxor.b32 %0, %0, c;\n}\n" : "+r"(keep)::"memory");
}
template <int N> __device__ __forceinline__ void fence_regs(float (&r)[N]) {
#pragma unroll
  for (int i = 0; i < N; i++) asm volatile("" : "+f"(r[i])::"memory");
}
template <int N> __device__ __forceinline__ void fence_regs(uint32_t (&r)[N]) {
#pragma unroll
  for (int i = 0; i < N; i++) asm volatile("" : "+r"(r[i])::"memory");
}
__device__ __forceinline__ uint64_t mk_desc(uint32_t a16, uint32_t lbo, uint32_t sbo, uint32_t swz) {
  uint64_t d;
  asm("mov.b64 %0, {%1, %2};" : "=l"(d) : "r"(a16 + ((lbo >> 4) << 16)), "r"((sbo >> 4) | (swz << 30)));
  return d;
}
__device__ __forceinline__ void mbar_init(uint32_t bar, uint32_t cnt) {
  asm volatile("mbarrier.init.shared::cta.b64 [%0], %1;" ::"r"(bar), "r"(cnt) : "memory");
}
__device__ __forceinline__ void mbar_expect(uint32_t bar, uint32_t tx) {
  asm volatile("mbarrier.arrive.expect_tx.shared::cta.b64 _, [%0], %1;" ::"r"(bar), "r"(tx) : "memory");
}
__device__ __forceinline__ bool mbar_test(uint32_t bar, uint32_t ph) {
  uint32_t ok;
  asm volatile("{\n.reg .pred p;\nmbarrier.test_wait.parity.shared::cta.b64 p, [%1], %2;\nselp.u32 %0, 1, 0, p;\n}\n"
               : "=r"(ok) : "r"(bar), "r"(ph) : "memory");
  return ok;
}
__device__ __forceinline__ void mbar_wait(uint32_t bar, uint32_t ph) {
  asm volatile("{\n.reg .pred p;\n.reg .u32 n;\n"
               "mbarrier.try_wait.parity.shared::cta.b64 p, [%0], %1;\n@p bra DONE;\n"
               "mov.u32 n, 0;\n"
               "LOOP:\nmbarrier.try_wait.parity.shared::cta.b64 p, [%0], %1;\n@p bra DONE;\n"
               "add.u32 n, n, 1;\nsetp.lt.u32 p, n, 0x1000000;\n@p bra LOOP;\ntrap;\n"
               "DONE:\n}\n" ::"r"(bar), "r"(ph) : "memory");
}
template <int NS> __device__ __forceinline__ void mbar_wait_slow(uint32_t bar, uint32_t ph) {
  asm volatile("{\n.reg .pred p;\n.reg .u32 n;\nmov.u32 n, 0;\n"
               "LOOP:\nmbarrier.test_wait.parity.shared::cta.b64 p, [%0], %1;\n@p bra DONE;\n"
               "nanosleep.u32 %2;\nadd.u32 n, n, 1;\nsetp.lt.u32 p, n, 0x400000;\n@p bra LOOP;\ntrap;\n"
               "DONE:\n}\n" ::"r"(bar), "r"(ph), "n"(NS) : "memory");
}
__device__ __forceinline__ void mbar_arrive_cluster(uint32_t addr) {
  asm volatile("mbarrier.arrive.shared::cluster.b64 _, [%0];" ::"r"(addr) : "memory");
}
__device__ __forceinline__ void tma2d(uint32_t dst, const CUtensorMap* m, uint32_t bar, int c0, int c1) {
  asm volatile("cp.async.bulk.tensor.2d.shared::cluster.global.mbarrier::complete_tx::bytes [%0], [%1, {%3, %4}], [%2];"
               ::"r"(dst), "l"(m), "r"(bar), "r"(c0), "r"(c1) : "memory");
}
__device__ __forceinline__ void tma3d(uint32_t dst, const CUtensorMap* m, uint32_t bar, int c0, int c1, int c2) {
  asm volatile("cp.async.bulk.tensor.3d.shared::cluster.global.mbarrier::complete_tx::bytes [%0], [%1, {%3, %4, %5}], [%2];"
               ::"r"(dst), "l"(m), "r"(bar), "r"(c0), "r"(c1), "r"(c2) : "memory");
}
__device__ __forceinline__ void tma3d_mc(uint32_t dst, const CUtensorMap* m, uint32_t bar, int c0, int c1, int c2) {
  asm volatile("cp.async.bulk.tensor.3d.shared::cluster.global.mbarrier::complete_tx::bytes.multicast::cluster"
               " [%0], [%1, {%3, %4, %5}], [%2], %6;"
               ::"r"(dst), "l"(m), "r"(bar), "r"(c0), "r"(c1), "r"(c2), "h"((uint16_t)3) : "memory");
}
__device__ __forceinline__ void tma3d_store(const CUtensorMap* m, uint32_t src, int c0, int c1, int c2) {
  asm volatile("cp.async.bulk.tensor.3d.global.shared::cta.bulk_group [%0, {%2, %3, %4}], [%1];"
               ::"l"(m), "r"(src), "r"(c0), "r"(c1), "r"(c2) : "memory");
}
__device__ __forceinline__ void bar_sync(int id, int n) { asm volatile("bar.sync %0, %1;" ::"r"(id), "r"(n) : "memory"); }
__device__ __forceinline__ uint32_t pack_bf16(float lo, float hi) {
  uint32_t r;
  asm("cvt.rn.bf16x2.f32 %0, %1, %2;" : "=r"(r) : "f"(hi), "f"(lo));
  return r;
}
__device__ __forceinline__ float ex2(float x) {
  float y;
  asm("ex2.approx.ftz.f32 %0, %1;" : "=f"(y) : "f"(x));
  return y;
}
__device__ __forceinline__ float rcp(float x) {
  float y;
  asm("rcp.approx.ftz.f32 %0, %1;" : "=f"(y) : "f"(x));
  return y;
}
__device__ __forceinline__ void stsm4(uint32_t addr, uint32_t a, uint32_t b, uint32_t c, uint32_t d) {
  asm volatile("stmatrix.sync.aligned.m8n8.x4.shared.b16 [%0], {%1, %2, %3, %4};" ::"r"(addr), "r"(a), "r"(b), "r"(c), "r"(d) : "memory");
}

__device__ __forceinline__ void tma4d_mc_hint(uint32_t dst, const CUtensorMap* m, uint32_t bar, int c3, uint64_t pol) {
  asm volatile("cp.async.bulk.tensor.4d.shared::cluster.global.mbarrier::complete_tx::bytes.multicast::cluster.L2::cache_hint"
               " [%0], [%1, {%3, %3, %3, %4}], [%2], %5, %6;"
               ::"r"(dst), "l"(m), "r"(bar), "r"(0), "r"(c3), "h"((uint16_t)3), "l"(pol) : "memory");
}
__device__ __forceinline__ void tma5d_mc(uint32_t dst, const CUtensorMap* m, uint32_t bar, int c2, int c4) {
  asm volatile("cp.async.bulk.tensor.5d.shared::cluster.global.mbarrier::complete_tx::bytes.multicast::cluster"
               " [%0], [%1, {%3, %3, %4, %3, %5}], [%2], %6;"
               ::"r"(dst), "l"(m), "r"(bar), "r"(0), "r"(c2), "r"(c4), "h"((uint16_t)3) : "memory");
}
__device__ __forceinline__ void bulk_load_hint(uint32_t dst, const void* src, uint32_t bytes, uint32_t bar, uint64_t pol) {
  asm volatile("cp.async.bulk.shared::cluster.global.mbarrier::complete_tx::bytes.L2::cache_hint [%0], [%1], %2, [%3], %4;"
               ::"r"(dst), "l"(src), "r"(bytes), "r"(bar), "l"(pol) : "memory");
}
__device__ __forceinline__ void stg128_hint(void* p, uint32_t a, uint32_t b, uint32_t c, uint32_t d, uint64_t pol) {
  asm volatile("st.global.L2::cache_hint.v4.b32 [%0], {%1, %2, %3, %4}, %5;" ::"l"(p), "r"(a), "r"(b), "r"(c), "r"(d), "l"(pol) : "memory");
}
__device__ __forceinline__ void stg2_if(bool on, void* p, uint32_t a, uint32_t b, uint32_t c, uint32_t d, uint32_t e, uint32_t f,
                                        uint32_t g, uint32_t h, uint64_t pol) {
  asm volatile("{\n.reg .pred p;\nsetp.ne.b32 p, %10, 0;\n"
               "@p st.global.L2::cache_hint.v4.b32 [%0], {%1, %2, %3, %4}, %9;\n"
               "@p st.global.L2::cache_hint.v4.b32 [%0 + 512], {%5, %6, %7, %8}, %9;\n}\n"
               ::"l"(p), "r"(a), "r"(b), "r"(c), "r"(d), "r"(e), "r"(f), "r"(g), "r"(h), "l"(pol), "r"((int)on) : "memory");
}
__device__ __forceinline__ uint64_t make_policy(bool first) {
  uint64_t pf, pn;
  asm("createpolicy.fractional.L2::evict_first.b64 %0, 1.0;" : "=l"(pf));
  asm("createpolicy.fractional.L2::evict_normal.b64 %0, 1.0;" : "=l"(pn));
  return first ? pf : pn;
}
__device__ __forceinline__ bool elect() {
  uint32_t ok;
  asm volatile("{\n.reg .pred p;\nelect.sync _|p, 0xffffffff;\nselp.u32 %0, 1, 0, p;\n}\n" : "=r"(ok));
  return ok;
}
__device__ __forceinline__ void mbar_arrive(uint32_t bar) {
  asm volatile("mbarrier.arrive.shared::cta.b64 _, [%0];" ::"r"(bar) : "memory");
}
__device__ __forceinline__ void stg128(void* p, uint32_t a, uint32_t b, uint32_t c, uint32_t d) {
  asm volatile("st.global.v4.b32 [%0], {%1, %2, %3, %4};" ::"l"(p), "r"(a), "r"(b), "r"(c), "r"(d) : "memory");
}
__device__ __forceinline__ void lds128(uint32_t p, uint32_t& a, uint32_t& b, uint32_t& c, uint32_t& d) {
  asm volatile("ld.shared.v4.b32 {%0, %1, %2, %3}, [%4];" : "=r"(a), "=r"(b), "=r"(c), "=r"(d) : "r"(p) : "memory");
}
__device__ __forceinline__ void wait_count(const unsigned int* p, uint32_t target) {
  asm volatile("{\n.reg .pred p;\n.reg .u32 n, v;\nmov.u32 n, 0;\n"
               "LOOP:\nld.acquire.gpu.global.u32 v, [%0];\nsetp.ge.u32 p, v, %1;\n@p bra DONE;\n"
               "nanosleep.u32 %2;\nadd.u32 n, n, 1;\nsetp.lt.u32 p, n, 0x400000;\n@p bra LOOP;\ntrap;\n"
               "DONE:\n}\n" ::"l"(p), "r"(target), "n"(200) : "memory");
}

__host__ __device__ __forceinline__ int o_wave(int a, int b, int i, int lag) {
  if (lag == 0) return a + i;
  const int p = lag < b - a - 1 ? lag : b - a - 1;
  return i < p ? b - 2 - i : i == p ? b - 1 : b - 1 - i;
}

struct Cursor {
  int bi;
  uint32_t ph;
  __device__ __forceinline__ void next() {
    if (++bi == NBAR) { bi = 0; ph ^= 1; }
  }
};

constexpr float kScaleLog2 = 0.07216878364870322f * 1.4426950408889634f;
constexpr float kSumLimit = 1048576.0f;

__global__ void __cluster_dims__(2, 1, 1) __launch_bounds__(384, 1)
fused_kernel(const __grid_constant__ Params P) {
  extern __shared__ uint8_t smem_raw[];
  const uint32_t sbase = (smem_u32(smem_raw) + 1023) & ~1023u;
  const uint32_t full0 = sbase + RING, empty0 = full0 + 8 * NBAR, odone = empty0 + 8 * NBAR, oready0 = odone + 8;
  const uint32_t fenced = oready0 + 64, hready0 = fenced + 8;
  const uint32_t rank = blockIdx.x & 1;
  const int role = blockIdx.x >> 1;
  const bool helper = role >= N_CL;
  const int team = helper ? 0 : role >> 2, nt = role & 3, blk = team >> 3;
  const uint32_t* prog = P.ops[helper ? N_TEAM + 2 * (role - N_CL) : team];
  auto q_role = [&](uint32_t op) { return helper ? (int)(((op >> 3) & 60) | ((op >> 12) & 3)) : role; };
  auto o_role = [&](uint32_t op) { return helper ? (int)(((op >> 26) & 56) | ((op >> 9) & 7)) : role; };
  const int wid = __shfl_sync(0xffffffffu, (int)(threadIdx.x >> 5), 0);
  const int wg = wid >> 2;

  const uint32_t op0 = P.first[helper ? N_TEAM + role - N_CL : team];
  if (__builtin_expect(wid == 8, 1)) {
    if (elect()) {
#pragma unroll
      for (int k = 0; k < EARLY; k++) mbar_init(full0 + 8 * k, 1);
      asm volatile("fence.mbarrier_init.release.cluster;" ::: "memory");
      if ((op0 & 3) == OP_Q) {
        const int qr = q_role(op0);
#pragma unroll
        for (int k = 0; k < EARLY; k++) {
          mbar_expect(full0 + 8 * k, SZ_Q);
          tma2d(sbase + k * SZ_Q, &P.x[qr >> 5], full0 + 8 * k, 64 * k, ((qr >> 2) & 7) * kSq + rank * 128);
          tma3d(sbase + k * SZ_Q + 16384, &P.wq[qr >> 5], full0 + 8 * k, 0, 64 * k, 3 * (4 * ((op0 >> 2) & 7) + (qr & 3)));
        }
      }
      asm volatile("prefetch.tensormap [%0];" ::"l"(rank ? &P.v[blk] : &P.k[blk]) : "memory");
    }
  } else if (threadIdx.x == 0) {
#pragma unroll
    for (int i = EARLY; i < 2 * NBAR + 10 + MAX_PARK; i++) mbar_init(full0 + 8 * i, i < NBAR ? 1 : i < 2 * NBAR ? 16 : i == 2 * NBAR ? 8 : 1);
    asm volatile("fence.mbarrier_init.release.cluster;" ::: "memory");
  }
  __syncwarp();
  asm volatile("barrier.cluster.arrive.relaxed.aligned;\nbarrier.cluster.wait.aligned;" ::: "memory");

  if (wg == 2) {
    asm volatile("setmaxnreg.dec.sync.aligned.u32 24;");
    if (wid == 8) {
      Cursor tail{0, 0};
      int head = 0, sh = 0;
      uint32_t cur = 0, used = 0;
      uint64_t fifo = 0;
      uint32_t dst, bar, oready = oready0;
      uint64_t pol;
      asm volatile("createpolicy.fractional.L2::evict_first.b64 %0, 1.0;" : "=l"(pol));
      const uint64_t pol_o = make_policy(P.dbg & 1), pol_p = make_policy(!(P.dbg & 4));
      const CUtensorMap* kv_map = rank ? &P.v[blk] : &P.k[blk];
      auto acquire = [&](uint32_t bytes) {
        uint32_t fp = bytes >> 12;
        if (cur + fp > (RING >> 12)) { fp += (RING >> 12) - cur; cur = 0; }
        used += fp;
        while (used > (RING >> 12) || sh == 5 * NBAR) {
          mbar_wait(empty0 + 8 * tail.bi, tail.ph);
          tail.next();
          used -= (uint32_t)fifo & 31;
          fifo >>= 5;
          sh -= 5;
        }
        fifo |= (uint64_t)fp << sh;
        sh += 5;
        dst = sbase + (cur << 12);
        bar = full0 + 8 * head;
        cur += bytes >> 12;
        if (++head == NBAR) head = 0;
      };
      for (int pc = 0;; pc++) {
        const uint32_t op = prog[pc];
        const int type = op & 3, a = (op >> 2) & 7;
        if (type == OP_END) break;
        if (type == OP_Q) {
          const int qr = q_role(op);
#pragma unroll 1
          for (int k = 0; k < 10; k++) {
            acquire(SZ_Q);
            if ((pc > 0 || k >= EARLY) && elect()) {
              mbar_expect(bar, SZ_Q);
              tma2d(dst, &P.x[qr >> 5], bar, 64 * k, ((qr >> 2) & 7) * kSq + rank * 128);
              if ((k & 1) == rank) tma3d_mc(dst + 16384, &P.wq[qr >> 5], bar, 0, 64 * k, 3 * (4 * a + (qr & 3)));
            }
          }
        } else if (type == OP_A) {
          const int row0 = ((team & 7) * kH + 4 * a + nt) * kSk;
          if (op & F_PARK) {
            mbar_wait((op & F_HELP) ? hready0 + 8 * ((op >> 10) & 3) : fenced, 0);
            asm volatile("fence.proxy.async.global;" ::: "memory");
            acquire(SZ_PARK);
            if (elect()) {
              mbar_expect(bar, SZ_PARK);
              bulk_load_hint(dst, &g_park[((role * 2 + rank) * MAX_PARK + ((op >> 10) & 3)) * 3072], SZ_PARK, bar, pol_p);
            }
          }
#pragma unroll 1
          for (int t = 0; t < 32; t++) {
            const int isv = t == 31 ? 1 : (t == 0 ? 0 : (~t & 1));
            const int j = isv ? (t - 1) >> 1 : (t + 1) >> 1;
            acquire(SZ_KV);
            if (elect()) {
              mbar_expect(bar, SZ_KV);
              if (isv == (int)rank) tma4d_mc_hint(dst, kv_map, bar, row0 / 8 + 8 * j, pol);
            }
          }
        } else {
          const int b = (op >> 5) & 15, ro = o_role(op);
#pragma unroll 1
          for (int i = 0; i < b - a; i++) {
            const int w = o_wave(a, b, i, (P.dbg >> 4) & 7);
            mbar_wait(oready, 0);
            oready += 8;
            asm volatile("fence.proxy.async.global;" ::: "memory");
#pragma unroll 1
            for (int k = 12 * w; k < 12 * w + 12; k++) {
              acquire(SZ_O);
              if (elect()) {
                mbar_expect(bar, SZ_O);
                tma5d_mc(dst + 16384 + rank * 10240, &P.wo[ro >> 5], bar, 8 * k + 4 * rank, 5 * (ro & 3));
                bulk_load_hint(dst, &g_o[(((ro >> 2) * 2 + rank) * 96 + k - 12 * (w - P.slot[w])) * 1024], 16384, bar, pol_o);
              }
            }
          }
          if (op & F_LD) {
            if (op & F_PARK) {
              mbar_wait(hready0 + 8 * (MAX_PARK - 1), 0);
              asm volatile("fence.proxy.async.global;" ::: "memory");
            }
#pragma unroll 1
            for (int i = 0; i < 2; i++) {
              acquire(SZ_PART);
              if (elect()) {
                mbar_expect(bar, SZ_PART);
                bulk_load_hint(dst, &g_part[(role * 2 + rank) * 5120 + i * 2560], SZ_PART, bar, pol_p);
              }
            }
          }
        }
      }
    } else if (threadIdx.x == 288) {
      uint32_t ph = 0;
      bool first = true;
      for (int pc = 0;; pc++) {
        const uint32_t op = prog[pc];
        if ((op & 3) == OP_END) break;
        if ((op & 3) != OP_A && !helper) continue;
        mbar_wait_slow<400>(odone, ph);
        ph ^= 1;
        unsigned int* flag = !helper ? &g_done[(team * 2 + rank) * 8 + ((op >> 2) & 7)]
                             : (op & 3) == OP_Q ? &g_help[(q_role(op) * 2 + rank) * MAX_PARK + ((op >> 10) & 3)]
                                                : &g_help[(o_role(op) * 2 + rank) * MAX_PARK + MAX_PARK - 1];
        asm volatile("red.release.gpu.global.add.u32 [%0], 1;" ::"l"(flag) : "memory");
        if (first) mbar_arrive(fenced);
        first = false;
      }
    } else if (threadIdx.x == 320) {
      uint32_t oready = oready0;
      for (int pc = 0;; pc++) {
        const uint32_t op = prog[pc];
        if ((op & 3) == OP_END) break;
        if ((op & 3) == OP_O) {
          const int a = (op >> 2) & 7, b = (op >> 5) & 15;
          for (int i = 0; i < b - a; i++) {
            const int ci = ((o_role(op) >> 2) * 2 + rank) * 8 + o_wave(a, b, i, (P.dbg >> 4) & 7);
            wait_count(&g_done[ci], 4);
            mbar_arrive(oready);
            oready += 8;
            if (atomicAdd(&g_seen[ci], 1u) == 3u) { g_seen[ci] = 0; g_done[ci] = 0; }
          }
        }
        if ((op & 3) != OP_Q && (op & F_HELP) && (op & F_PARK)) {
          unsigned int* flag = &g_help[(role * 2 + rank) * MAX_PARK + ((op >> 10) & 3)];
          wait_count(flag, 1);
          mbar_arrive(hready0 + 8 * ((op >> 10) & 3));
          *flag = 0;
        }
      }
    }
    __syncwarp();
    asm volatile("barrier.cluster.arrive.relaxed;\nbarrier.cluster.wait;" ::: "memory");
  } else {
    asm volatile("setmaxnreg.inc.sync.aligned.u32 240;");
    const int lane = threadIdx.x & 31, warp = wid & 3;
    uint32_t empty_rem;
    asm volatile("mapa.shared::cluster.u32 %0, %1, %2;" : "=r"(empty_rem) : "r"(empty0), "r"(lane & 1));
    auto release = [&](int slot) { if (lane < 2) mbar_arrive_cluster(empty_rem + 8 * slot); };
    Cursor r{0, 0};
    const uint32_t ring16 = (sbase & 0x3FFFF) >> 4;
    uint32_t cur = ring16;
    bool rdy0 = false, rdy1 = false;
    auto probe1 = [&]() { rdy0 = mbar_test(full0 + 8 * r.bi, r.ph); };
    auto probe2 = [&]() {
      Cursor n = r;
      rdy0 = mbar_test(full0 + 8 * n.bi, n.ph);
      n.next();
      rdy1 = mbar_test(full0 + 8 * n.bi, n.ph);
    };
    auto take = [&](bool rdy, uint32_t bytes, uint32_t& addr) {
      const int bi = r.bi;
      if (!__all_sync(0xffffffffu, rdy)) mbar_wait(full0 + 8 * r.bi, r.ph);
      r.next();
      if (cur > ring16 + ((RING - bytes) >> 4)) cur = ring16;
      addr = cur;
      cur += bytes >> 4;
      return bi;
    };
    uint32_t keep = 0;
    uint32_t q[48];
#pragma unroll
    for (int i = 0; i < 48; i++) q[i] = 0;
    const int row = wg * 64 + warp * 16 + (lane >> 2);
    const int img0 = row * 4 + ((lane & 3) ^ ((row >> 1) & 3));
    uint4* pend = nullptr;
    bool pend_any = false, pend_o = false;
    uint64_t spol;
    auto drain = [&](int c) {
      if (!pend_any || c >= 6) return;
#pragma unroll
      for (int i = 0; i < 6; i++)
        stg2_if(c == i, pend + i * 512, q[8 * i], q[8 * i + 1], q[8 * i + 2], q[8 * i + 3],
                q[8 * i + 4], q[8 * i + 5], q[8 * i + 6], q[8 * i + 7], spol);
      if (pend_o && c == 5) {
        __syncwarp();
        if (lane == 0) mbar_arrive(odone);
      }
    };

    for (int pc = 0;; pc++) {
      uint32_t op = prog[pc];
      const int type = op & 3;
      int a = (op >> 2) & 7;
      auto enter = [&]() {
        r.bi = (op >> 15) & 15; r.ph = (op >> 19) & 1; cur = ring16 + (((op >> 20) & 63) << 8);
      };
      enter();
      pend_o = ((op >> 26) & 3) == 1;
      pend_any = ((op >> 26) & 3) != 0;
      spol = make_policy(!(op & F_SOON));
      if (type == OP_END) {
        for (int c = 0; c < 6; c++) drain(c);
        asm volatile("barrier.cluster.arrive.relaxed;" ::: "memory");
        break;
      }
      if (type != OP_O) {
        float s[32];
        uint32_t ad0;
        int bi0;
        uint32_t pa[16], pb[16];
        float mc0, mc1, l0, l1;
        auto expo = [&](float (&s)[32], uint32_t (&pout)[16], float& b0, float& b1) {
          float c0 = 0.f, c1 = 0.f;
          b0 = 0.f; b1 = 0.f;
#pragma unroll
          for (int i = 0; i < 8; i++) {
            const float e0 = ex2(fmaf(s[4 * i], kScaleLog2, -mc0)), e1 = ex2(fmaf(s[4 * i + 1], kScaleLog2, -mc0));
            const float e2 = ex2(fmaf(s[4 * i + 2], kScaleLog2, -mc1)), e3 = ex2(fmaf(s[4 * i + 3], kScaleLog2, -mc1));
            b0 += e0; c0 += e1; b1 += e2; c1 += e3;
            pout[2 * i] = pack_bf16(e0, e1); pout[2 * i + 1] = pack_bf16(e2, e3);
          }
          b0 += c0; b1 += c1;
        };
        auto rowmax = [&](float (&s)[32], float& m0, float& m1) {
          m0 = fmaxf(s[0], s[1]); m1 = fmaxf(s[2], s[3]);
#pragma unroll
          for (int i = 1; i < 8; i++) { m0 = fmaxf(m0, fmaxf(s[4 * i], s[4 * i + 1])); m1 = fmaxf(m1, fmaxf(s[4 * i + 2], s[4 * i + 3])); }
          m0 = fmaxf(m0, __shfl_xor_sync(0xffffffffu, m0, 1)); m1 = fmaxf(m1, __shfl_xor_sync(0xffffffffu, m1, 1));
          m0 = fmaxf(m0, __shfl_xor_sync(0xffffffffu, m0, 2)); m1 = fmaxf(m1, __shfl_xor_sync(0xffffffffu, m1, 2));
          m0 *= kScaleLog2; m1 *= kScaleLog2;
        };
        auto first = [&](int sk0, auto mid) {
          fence_regs(s);
          release(sk0);
          mc0 = __shfl_sync(0xffffffffu, s[0], lane & ~3) * kScaleLog2;
          mc1 = __shfl_sync(0xffffffffu, s[2], lane & ~3) * kScaleLog2;
          float c0 = 0.f, c1 = 0.f;
          l0 = 0.f; l1 = 0.f;
#pragma unroll
          for (int i = 0; i < 8; i++) {
            const float e0 = ex2(fmaf(s[4 * i], kScaleLog2, -mc0)), e1 = ex2(fmaf(s[4 * i + 1], kScaleLog2, -mc0));
            const float e2 = ex2(fmaf(s[4 * i + 2], kScaleLog2, -mc1)), e3 = ex2(fmaf(s[4 * i + 3], kScaleLog2, -mc1));
            l0 += e0; c0 += e1; l1 += e2; c1 += e3;
            pa[2 * i] = pack_bf16(e0, e1); pa[2 * i + 1] = pack_bf16(e2, e3);
            if (i & 1) mid(i >> 1);
          }
          l0 += c0; l1 += c1;
          if (__any_sync(0xffffffffu, !(fmaxf(l0, l1) <= kSumLimit))) {
            rowmax(s, mc0, mc1);
            expo(s, pa, l0, l1);
          }
        };
        auto qk4 = [&](uint32_t ak, int c) {
#pragma unroll
          for (int kk = 4 * c; kk < 4 * c + 4; kk++)
            wgmma_rs_n64<0>(s, q[4 * kk], q[4 * kk + 1], q[4 * kk + 2], q[4 * kk + 3], mk_desc(ak + c * KV_CH + (kk & 3) * 2, 16, KV_SBO, 1), kk != 0);
        };
        auto unpark = [&]() {
          uint32_t ad, ak;
          const int bi = take(rdy0, SZ_PARK, ad);
#pragma unroll
          for (int i = 0; i < 12; i++) lds128(sbase + (ad - ring16 + img0) * 16 + (i >> 1) * 8192 + (i & 1) * 512, q[4 * i], q[4 * i + 1], q[4 * i + 2], q[4 * i + 3]);
          const int sk0 = take(false, SZ_KV, ak);
          fence_regs(q);
          release(bi);
          wg_fence();
#pragma unroll
          for (int c = 0; c < 3; c++) qk4(ak, c);
          wg_commit();
          probe2();
          return sk0;
        };
        if (type == OP_Q) {
          bi0 = take(rdy0, SZ_Q, ad0);
        next_head:
          float o[96];
          auto issue = [&](int acc) {
            uint32_t ad = ad0;
            const int bi = acc ? take(rdy0, SZ_Q, ad) : bi0;
            wg_fence();
#pragma unroll
            for (int kk = 0; kk < 4; kk++)
              wgmma_ss_n192<1>(o, mk_desc(ad + wg * 512 + kk * 2, 16, 1024, 1), mk_desc(ad + 1024 + kk * 128, 8192, 1024, 1), acc || kk != 0);
            wg_commit();
            return bi;
          };
          auto kstep = [&](int acc, int k) {
            const int bi = issue(acc);
            drain(k);
            probe1();
            wg_wait<0>();
            release(bi);
          };
          kstep(0, 0);
#pragma unroll 1
          for (int k = 1; k < 9; k++) kstep(1, k);
          if (op & F_PARK) {
            kstep(1, 9);
            fence_regs(o);
#pragma unroll
            for (int i = 0; i < 48; i++) q[i] = pack_bf16(o[2 * i], o[2 * i + 1]);
            pend = &g_park[((q_role(op) * 2 + rank) * MAX_PARK + ((op >> 10) & 3)) * 3072 + img0];
            continue;
          }
          const int bi = issue(1);
          pc++;
          uint32_t ak;
          const int sk0 = take(false, SZ_KV, ak);
          wg_wait<0>();
          fence_regs(o);
          release(bi);
#pragma unroll
          for (int c = 0; c < 3; c++) {
#pragma unroll
            for (int i = 16 * c; i < 16 * c + 16; i++) q[i] = pack_bf16(o[2 * i], o[2 * i + 1]);
            wg_fence();
            qk4(ak, c);
          }
          wg_commit();
          probe2();
          wg_wait<0>();
          first(sk0, [](int) {});
        } else {
          const int sk0 = unpark();
          wg_wait<0>();
          first(sk0, [](int) {});
        }
        float o[96];
        auto qk = [&](float (&s)[32], uint32_t ak) {
#pragma unroll
          for (int kk = 0; kk < 12; kk++)
            wgmma_rs_n64<0>(s, q[4 * kk], q[4 * kk + 1], q[4 * kk + 2], q[4 * kk + 3], mk_desc(ak + (kk >> 2) * KV_CH + (kk & 3) * 2, 16, KV_SBO, 1), kk != 0);
          wg_commit();
        };
        auto pv = [&](uint32_t (&pin)[16], uint32_t av, int acc) {
#pragma unroll
          for (int kk = 0; kk < 4; kk++)
            wgmma_rs_n192<1>(o, pin[4 * kk], pin[4 * kk + 1], pin[4 * kk + 2], pin[4 * kk + 3], mk_desc(av + kk * (KV_SBO / 8), KV_CH * 16, KV_SBO, 1), acc || (kk != 0));
          wg_commit();
        };
        auto soft = [&](uint32_t (&pout)[16]) {
          float b0, b1;
          expo(s, pout, b0, b1);
          if (__any_sync(0xffffffffu, !(fmaxf(b0, b1) <= kSumLimit))) {
            float m0, m1;
            rowmax(s, m0, m1);
            m0 = fmaxf(mc0, m0); m1 = fmaxf(mc1, m1);
            const float a0 = ex2(mc0 - m0), a1 = ex2(mc1 - m1);
            mc0 = m0; mc1 = m1;
            l0 *= a0; l1 *= a1;
            wg_wait<0>();
            fence_regs(o);
#pragma unroll
            for (int i = 0; i < 24; i++) { o[4 * i] *= a0; o[4 * i + 1] *= a0; o[4 * i + 2] *= a1; o[4 * i + 3] *= a1; }
            expo(s, pout, b0, b1);
          }
          l0 += b0; l1 += b1;
        };
        auto step = [&](uint32_t (&pin)[16], uint32_t (&pout)[16], int acc) {
          uint32_t ak, av;
          const int sk = take(rdy0, SZ_KV, ak), sv = take(rdy1, SZ_KV, av);
          wg_fence();
          qk(s, ak);
          pv(pin, av, acc);
          probe2();
          wg_wait<1>();
          fence_regs(s);
          release(sk);
          soft(pout);
          wg_wait<0>();
          fence_regs(o);
          release(sv);
        };
        for (int wave = a;;) {
          step(pa, pb, 0);
          const uint32_t nop = prog[pc + 1];
#pragma unroll 1
          for (int jj = 0; jj < 7; jj++) {
            step(pb, pa, 1);
            step(pa, pb, 1);
          }
          float i0, i1;
          auto last = [&]() {
            uint32_t av;
            const int sv = take(rdy0, SZ_KV, av);
            wg_fence();
            pv(pb, av, 1);
            probe1();
            l0 += __shfl_xor_sync(0xffffffffu, l0, 1); l1 += __shfl_xor_sync(0xffffffffu, l1, 1);
            l0 += __shfl_xor_sync(0xffffffffu, l0, 2); l1 += __shfl_xor_sync(0xffffffffu, l1, 2);
            i0 = rcp(l0); i1 = rcp(l1);
            pend = &g_o[((team * 2 + rank) * 96 + 3 * (4 * P.slot[wave] + nt)) * 1024 + img0];
            return sv;
          };
          auto normalise = [&](uint32_t (&d)[48], auto mid) {
#pragma unroll
            for (int i = 0; i < 24; i++) {
              d[8 * (i >> 2) + (i & 3)] = pack_bf16(o[4 * i] * i0, o[4 * i + 1] * i0);
              d[8 * (i >> 2) + (i & 3) + 4] = pack_bf16(o[4 * i + 2] * i1, o[4 * i + 3] * i1);
              if ((i & 3) == 3 && i != 23) { sched_fence(keep); mid(i >> 2); }
            }
          };
          if ((nop & 3) != OP_A) {
            const int sv = last();
            if ((nop & 3) == OP_Q) {
              op = nop; a = (op >> 2) & 7;
              enter();
              pend_o = pend_any = true;
              spol = make_policy(!(op & F_SOON));
              bi0 = take(rdy0, SZ_Q, ad0);
            }
            wg_wait<0>();
            fence_regs(o);
            release(sv);
            normalise(q, [](int) {});
            if ((nop & 3) != OP_Q) break;
            pc++;
            goto next_head;
          }
          const int sv = last();
          const int sk0 = unpark();
          wg_wait<1>();
          fence_regs(o);
          release(sv);
          uint32_t t[48];
          spol = make_policy(!(nop & F_SOON));
          auto st = [&](int i) {
            stg2_if(true, pend + i * 512, t[8 * i], t[8 * i + 1], t[8 * i + 2], t[8 * i + 3], t[8 * i + 4], t[8 * i + 5], t[8 * i + 6], t[8 * i + 7], spol);
          };
          normalise(t, [&](int i) { if (!(i & 1)) st(i >> 1); });
          wg_wait<0>();
          first(sk0, [&](int i) { if (i < 3) { sched_fence(keep); st(3 + i); } });
          __syncwarp();
          if (lane == 0) mbar_arrive(odone);
          pc++;
          wave = (nop >> 2) & 7;
        }
      } else {
        float c[80];
        const int nk = 12 * (((op >> 5) & 15) - a);
        uint4* part = &g_part[(o_role(op) * 2 + rank) * 5120];
        int prev = 0;
        auto kstep = [&](int acc, int k, bool hooks) {
          uint32_t ad;
          const int bi = take(rdy0, SZ_O, ad);
          const uint32_t da = ad + wg * 256, db = ad + 1024;
          wg_fence();
          wgmma_ss_n160<1>(c, mk_desc(da, 16, 512, 2), mk_desc(db, 2048, 512, 2), acc);
          wgmma_ss_n160<1>(c, mk_desc(da + 2, 16, 512, 2), mk_desc(db + 64, 2048, 512, 2), 1);
          wg_commit();
          if (acc) { wg_wait<1>(); release(prev); }
          wgmma_ss_n160<1>(c, mk_desc(da + 512, 16, 512, 2), mk_desc(db + 640, 2048, 512, 2), 1);
          wgmma_ss_n160<1>(c, mk_desc(da + 514, 16, 512, 2), mk_desc(db + 704, 2048, 512, 2), 1);
          wg_commit();
          prev = bi;
          if (hooks) drain(k);
          probe1();
          wg_wait<1>();
        };
        kstep(0, 0, true);
#pragma unroll 1
        for (int k = 1; k < 6; k++) kstep(1, k, true);
#pragma unroll 1
        for (int k = 6; k < nk; k++) {
          kstep(1, k, false);
        }
        if (op & F_LD) {
          uint32_t t[80], ad0, ad1;
          const int b0 = take(rdy0, SZ_PART, ad0), b1 = take(false, SZ_PART, ad1);
          probe1();
#pragma unroll
          for (int i = 0; i < 20; i++)
            lds128(sbase + ((i < 10 ? ad0 : ad1) - ring16 + img0) * 16 + ((i % 10) >> 1) * 8192 + (i & 1) * 512, t[4 * i], t[4 * i + 1], t[4 * i + 2], t[4 * i + 3]);
          fence_regs(t);
          wg_wait<0>();
          fence_regs(c);
          release(prev);
          release(b0); release(b1);
#pragma unroll
          for (int i = 0; i < 80; i++) c[i] += __uint_as_float(t[i]);
        } else {
          wg_wait<0>();
          fence_regs(c);
          release(prev);
        }
        if (op & F_LAZY) {
#pragma unroll
          for (int i = 0; i < 48; i++) q[i] = __float_as_uint(c[i]);
          pend = part + img0;
#pragma unroll
          for (int i = 12; i < 20; i++)
            stg128_hint(pend + (i >> 1) * 512 + (i & 1) * 32, __float_as_uint(c[4 * i]), __float_as_uint(c[4 * i + 1]),
                        __float_as_uint(c[4 * i + 2]), __float_as_uint(c[4 * i + 3]), spol);
          continue;
        }
        if (op & F_ST) {
#pragma unroll
          for (int i = 0; i < 20; i++)
            stg128(part + (i >> 1) * 512 + (i & 1) * 32 + img0, __float_as_uint(c[4 * i]), __float_as_uint(c[4 * i + 1]),
                   __float_as_uint(c[4 * i + 2]), __float_as_uint(c[4 * i + 3]));
        } else {
          asm volatile("barrier.cluster.arrive.relaxed;" ::: "memory");
          bar_sync(1, 256);
          const uint32_t wstage = sbase + (wg * 4 + warp) * 5120;
          const uint32_t sa = wstage + (lane & 15) * 64;
#pragma unroll
          for (int i = 0; i < 10; i++) {
            const int u = (i & 1) * 2 + (lane >> 4);
            stsm4(sa + (i >> 1) * 1024 + ((u ^ ((lane >> 1) & 3)) << 4), pack_bf16(c[8 * i], c[8 * i + 1]), pack_bf16(c[8 * i + 2], c[8 * i + 3]),
                  pack_bf16(c[8 * i + 4], c[8 * i + 5]), pack_bf16(c[8 * i + 6], c[8 * i + 7]));
          }
          asm volatile("fence.proxy.async.shared::cta;" ::: "memory");
          __syncwarp();
          if (lane == 0) {
            tma3d_store(&P.out, wstage, 0, (team & 7) * kSq + rank * 128 + wg * 64 + warp * 16, blk * 20 + nt * 5);
            asm volatile("cp.async.bulk.commit_group;\ncp.async.bulk.wait_group.read 0;" ::: "memory");
          }
          __syncwarp();
          break;
        }
#pragma unroll
        for (int i = 0; i < 48; i++) q[i] = 0;
      }
    }
    if (P.dbg == 0xffffffffu) g_seen[0] = keep;
    asm volatile("barrier.cluster.wait;" ::: "memory");
  }
}

typedef CUresult (*EncodeFn)(CUtensorMap*, CUtensorMapDataType, cuuint32_t, void*, const cuuint64_t*, const cuuint64_t*,
                             const cuuint32_t*, const cuuint32_t*, CUtensorMapInterleave, CUtensorMapSwizzle,
                             CUtensorMapL2promotion, CUtensorMapFloatOOBfill);

void encode(EncodeFn fn, CUtensorMap* m, const void* ptr, int rank, const cuuint64_t* dims, const cuuint64_t* strides,
            const cuuint32_t* box, CUtensorMapSwizzle swz) {
  const cuuint32_t es[5] = {1, 1, 1, 1, 1};
  CUresult r = fn(m, CU_TENSOR_MAP_DATA_TYPE_BFLOAT16, rank, const_cast<void*>(ptr), dims, strides, box, es,
                  CU_TENSOR_MAP_INTERLEAVE_NONE, swz, CU_TENSOR_MAP_L2_PROMOTION_L2_128B, CU_TENSOR_MAP_FLOAT_OOB_FILL_NONE);
  if (r != CUDA_SUCCESS) fprintf(stderr, "cuTensorMapEncodeTiled failed: %d\n", (int)r);
}

void annotate(uint32_t* ops, int n, bool helper) {
  uint32_t items = 0, cur = 0, pend = 0;
  auto item = [&](uint32_t bytes, int count) {
    for (int i = 0; i < count; i++) { if (cur + bytes > RING) cur = 0; cur += bytes; items++; }
  };
  for (int i = 0; i <= n; i++) {
    const uint32_t op = ops[i];
    ops[i] |= (items % NBAR) << 15 | ((items / NBAR) & 1) << 19 | (cur >> 12) << 20 | pend << 26;
    if ((op & 3) == OP_Q) { item(SZ_Q, 10); pend = (op & F_PARK) ? (helper ? 1 : 2) : 0; }
    if ((op & 3) == OP_A) { if (op & F_PARK) item(SZ_PARK, 1); item(SZ_KV, 32); pend = 1; }
    if ((op & 3) == OP_O) {
      item(SZ_O, 12 * (((op >> 5) & 15) - ((op >> 2) & 7)));
      if (op & F_LD) item(SZ_PART, 2);
      pend = (op & F_LAZY) ? (helper ? 1 : 2) : 0;
    }
  }
}

void compile_programs(const char* const* text, bool helpers, Params& P) {
  struct Req { int when, team, wave, slot; } req[N_TEAM * MAX_PARK];
  int n_req = 0;
  for (int t = 0; t < N_TEAM; t++) {
    uint32_t* ops = P.ops[t];
    int n = 0, flags[8] = {0, 0, 0, 0, 0, 0, 0, 0}, n_park = 0, last_o = -1, when = 0, given = 0;
    for (const char* s = text[t]; *s; s++) {
      const int a = s[1] - '0';
      if (*s == 'Q' || (*s == 'H' && !helpers)) { ops[n++] = OP_Q | a << 2; when += 10; }
      else if (*s == 'P') { flags[a] = F_PARK | n_park++ << 10; ops[n++] = OP_Q | a << 2 | flags[a]; when += 10; }
      else if (*s == 'H') { req[n_req++] = {when, t, a, n_park}; flags[a] = F_PARK | F_HELP | n_park++ << 10; }
      else if (*s == 'A') { ops[n++] = OP_A | a << 2 | flags[a]; when += 32; }
      else if (*s == 'G') { given = a; if (helpers) req[n_req++] = {1000, t, 0, -a}; }
      else if (*s == 'O') {
        ops[n] = OP_O | a << 2 | (s[2] - '0') << 5;
        if (given) ops[n] = helpers ? ops[n] | F_LD | F_PARK | (MAX_PARK - 1) << 10 : ops[n] & ~(7u << 2);
        if (last_o >= 0) { ops[last_o] |= F_ST; ops[n] |= F_LD; }
        last_o = n++;
        when += 10 * (s[2] - s[1]);
      }
    }
    for (int i = 0; i + 1 < n; i++)
      if ((ops[i] & 3) == OP_O && (ops[i] & F_ST) && (ops[i + 1] & 3) == OP_Q) ops[i] |= F_LAZY;
    for (int i = n; i < MAX_OPS; i++) ops[i] = OP_END;
    annotate(ops, n, false);
    for (int i = 0; i < n; i++) {
      if ((ops[i] & 3) != OP_A && (P.dbg & 8)) ops[i + 1] |= F_SOON;
      if ((ops[i] & 3) != OP_A) continue;
      const int w = (ops[i] >> 2) & 7;
      int dist = 0;
      for (int j = i + 1; j < n; j++) {
        const int a = (ops[j] >> 2) & 7, b = (ops[j] >> 5) & 15;
        if ((ops[j] & 3) == OP_O && w < b) {
          for (int k = 0; k < b - a && o_wave(a, b, k, (P.dbg >> 4) & 7) != w; k++) dist += 10;
          break;
        }
        dist += (ops[j] & 3) == OP_Q ? 10 : (ops[j] & 3) == OP_A ? 32 : 10 * (b - a);
      }
      if (dist <= (int)((P.dbg >> 8) & 255)) ops[i + 1] |= F_SOON;
    }
  }
  for (int i = 1; i < n_req; i++)
    for (int j = i; j > 0 && req[j].when < req[j - 1].when; j--) { Req r = req[j]; req[j] = req[j - 1]; req[j - 1] = r; }
  for (int h = 0; h < N_HELP; h++) {
    uint32_t* ops = P.ops[N_TEAM + 2 * h];
    int n = 0;
    for (int i = 0; i < n_req; i++)
      for (int m = h; m < 4; m += N_HELP) {
        const uint32_t ro = 4 * req[i].team + m;
        ops[n++] = req[i].slot >= 0 ? OP_Q | req[i].wave << 2 | req[i].team << 5 | F_PARK | req[i].slot << 10 | m << 12
                                    : OP_O | -req[i].slot << 5 | F_ST | F_LAZY | F_SOON | (ro & 7) << 9 | (ro >> 3) << 29;
      }
    for (int i = n; i < 2 * MAX_OPS; i++) ops[i] = OP_END | F_SOON;
    annotate(ops, n, true);
  }
  for (int i = 0; i < 32; i++) P.first[i] = i < N_TEAM ? P.ops[i][0] : i < N_TEAM + N_HELP ? P.ops[2 * i - N_TEAM][0] : 0;
}

const char* const kPrograms[N_TEAM] = {
  "Q0A0Q1A1H2A2Q3A3Q4A4Q5A5Q6A6Q7A7O08",
  "Q0A0Q1A1H2A2Q3A3O02Q4A4Q5A5Q6A6Q7A7O28",
  "Q0A0H1A1Q2A2Q3A3Q4A4Q5A5Q6A6Q7A7O08",
  "Q0A0Q1A1Q2A2Q3A3O02Q4A4Q5A5Q6A6H7A7O28",
  "Q0A0Q1A1Q2A2O03Q3A3Q4A4Q5A5H6A6Q7A7O38",
  "Q0A0Q1A1Q2A2Q3A3Q4A4O05Q5A5H6A6Q7A7O58",
  "Q0A0Q1A1Q2A2Q3A3Q4A4O05Q5A5Q6A6H7A7O58",
  "Q0A0Q1A1Q2A2O03Q3A3H4A4Q5A5Q6A6Q7A7O38",
  "P7Q0A0Q1A1O01Q2A2Q3A3Q4A4Q5A5H6A6A7O18",
  "P7Q0A0Q1A1Q2A2Q3A3Q4A4Q5A5H6A6A7O08",
  "Q0A0Q1A1Q2A2H3A3Q4A4Q5A5Q6A6Q7A7O08",
  "P3P7Q0A0Q1A1H2A2A3Q4A4Q5A5Q6A6A7O08",
  "Q0A0Q1A1Q2A2O01Q3A3Q4A4H5A5Q6A6Q7A7O18",
  "P3Q0A0Q1A1Q2A2A3Q4A4Q5A5Q6A6Q7A7G1O18",
  "P2Q0A0Q1A1A2Q3A3Q4A4Q5A5H6A6Q7A7O08",
  "P7Q0A0Q1A1Q2A2Q3A3H4A4Q5A5Q6A6A7O08",
};

const char* const* bench_programs() {
  return kPrograms;
}

}

extern "C" void kernel_launch(void* const* d_in, const int* in_sizes, int n_in, void* d_out, int out_size) {
  (void)in_sizes; (void)n_in; (void)out_size;
  static EncodeFn fn = nullptr;
  static int n_clusters = 0;
  if (!fn) {
    cudaDriverEntryPointQueryResult qr;
    void* f = nullptr;
    cudaGetDriverEntryPoint("cuTensorMapEncodeTiled", &f, cudaEnableDefault, &qr);
    fn = (EncodeFn)f;
    cudaFuncSetAttribute(fused_kernel, cudaFuncAttributeMaxDynamicSharedMemorySize, SMEM_BYTES);
    cudaLaunchConfig_t cfg = {};
    cfg.gridDim = dim3(132); cfg.blockDim = dim3(384); cfg.dynamicSmemBytes = SMEM_BYTES;
    cudaLaunchAttribute at[1];
    at[0].id = cudaLaunchAttributeClusterDimension; at[0].val.clusterDim.x = 2; at[0].val.clusterDim.y = 1; at[0].val.clusterDim.z = 1;
    cfg.attrs = at; cfg.numAttrs = 1;
    if (cudaOccupancyMaxActiveClusters(&n_clusters, fused_kernel, &cfg) != cudaSuccess || n_clusters < 1) n_clusters = 1;
    (void)cudaGetLastError();
  }
  Params P;
  const CUtensorMapSwizzle S128 = CU_TENSOR_MAP_SWIZZLE_128B, S64 = CU_TENSOR_MAP_SWIZZLE_64B;
  for (int blk = 0; blk < 2; blk++) {
    void* const* in = d_in + 5 * blk;
    { const cuuint64_t d[] = {kD, kB * kSq}, s[] = {kD * 2}; const cuuint32_t b[] = {64, 128};
      encode(fn, &P.x[blk], in[0], 2, d, s, b, S128); }
    { const cuuint64_t d[] = {64, 8, 3, (cuuint64_t)kB * kH * kSk / 8}, s[] = {kDh * 2, 128, 8 * kDh * 2}; const cuuint32_t b[] = {64, 8, 3, 8};
      encode(fn, &P.k[blk], in[1], 4, d, s, b, S128);
      encode(fn, &P.v[blk], in[2], 4, d, s, b, S128); }
    { const cuuint64_t d[] = {64, kD, kHD / 64}, s[] = {kHD * 2, 128}; const cuuint32_t b[] = {64, 64, 3};
      encode(fn, &P.wq[blk], in[3], 3, d, s, b, S128); }
    { const cuuint64_t d[] = {32, 2, kHD / 8, 4, kD / 32}, s[] = {kD * 2, 8 * kD * 2, 2 * kD * 2, 64}; const cuuint32_t b[] = {32, 2, 4, 4, 5};
      encode(fn, &P.wo[blk], in[4], 5, d, s, b, S64); }
  }
  { const cuuint64_t d[] = {32, kB * kSq, 2 * kD / 32}, s[] = {2 * kD * 2, 64}; const cuuint32_t b[] = {32, 16, 5};
    encode(fn, &P.out, d_out, 3, d, s, b, S64); }

  P.dbg = 0x5030;
  for (int w = 0; w < 8; w++) P.slot[w] = (P.dbg >> 16) & 15 ? w % ((P.dbg >> 16) & 15) : w;
  if (n_clusters >= N_CL) {
    const bool helpers = n_clusters >= N_CL + N_HELP;
    compile_programs(bench_programs(), helpers, P);
    fused_kernel<<<2 * (N_CL + (helpers ? N_HELP : 0)), 384, SMEM_BYTES>>>(P);
  } else {
    for (int phase = 0; phase < 2; phase++) {
      const char* text[N_TEAM];
      for (int t = 0; t < N_TEAM; t++) text[t] = phase ? "O08" : "Q0A0Q1A1Q2A2Q3A3Q4A4Q5A5Q6A6Q7A7";
      compile_programs(text, false, P);
      fused_kernel<<<2 * N_CL, 384, SMEM_BYTES>>>(P);
    }
  }
}
```

```cpp
#include <cuda_runtime.h>
#include <cuda_bf16.h>
#include <cuda.h>
#include <stdint.h>
#include <stdio.h>

namespace {

constexpr int kB = 8, kSq = 256, kD = 640, kH = 32, kSk = 1024, kDh = 192;
constexpr int kHD = kH * kDh;
#define S1A 8
#define RING_KB 224
constexpr uint32_t RING = RING_KB * 1024;
constexpr uint32_t SZ_KV = 24576;
constexpr uint32_t SZ_Q = 16384 + 24576;
constexpr uint32_t SZ_O = 16384 + 20480;
constexpr uint32_t SZ_PARK = 49152;
constexpr uint32_t SZ_PART = 40960;
constexpr int NBAR = 10;
constexpr int EARLY = 3;
constexpr uint32_t KV_CH = 64, KV_SBO = 3072;
constexpr int SMEM_BYTES = RING + 512 + 1024;
constexpr int N_TEAM = 16, N_CL = 64, N_HELP = 2, MAX_OPS = 24, MAX_PARK = 4;
enum { OP_END = 0, OP_Q = 1, OP_A = 2, OP_O = 3, F_PARK = 1 << 9, F_LD = 1 << 12, F_ST = 1 << 13, F_LAZY = 1 << 14, F_HELP = 1 << 12, F_SOON = 1 << 28 };

struct alignas(64) Params {
  uint32_t first[32];
  CUtensorMap x[2], wq[2], k[2], v[2], wo[2], out;
  uint32_t ops[N_TEAM + 2 * N_HELP][MAX_OPS];
  uint32_t slot[8];
  uint32_t dbg;
};

__device__ uint4 g_o[N_TEAM * 2 * 96 * 1024];
__device__ uint4 g_park[N_CL * 2 * MAX_PARK * 12 * 256];
__device__ uint4 g_part[N_CL * 2 * 5 * 1024];
__device__ unsigned int g_done[N_TEAM * 2 * 8];
__device__ unsigned int g_help[N_CL * 2 * MAX_PARK];
__device__ unsigned int g_seen[N_TEAM * 2 * 8];

template <int TB, int TA = 0>
__device__ __forceinline__ void wgmma_ss_n64(float (&d)[32], uint64_t da, uint64_t db, int scale_d) {
  asm volatile("{\n.reg .pred p;\nsetp.ne.b32 p, %34, 0;\n"
    "wgmma.mma_async.sync.aligned.m64n64k16.f32.bf16.bf16 {%0, %1, %2, %3, %4, %5, %6, %7, %8, %9, %10, %11, %12, %13, %14, %15, %16, %17, %18, %19, %20, %21, %22, %23, %24, %25, %26, %27, %28, %29, %30, %31}, %32, %33, p, 1, 1, %35, %36;\n}\n"
    : "+f"(d[0]), "+f"(d[1]), "+f"(d[2]), "+f"(d[3]), "+f"(d[4]), "+f"(d[5]), "+f"(d[6]), "+f"(d[7]), "+f"(d[8]), "+f"(d[9]), "+f"(d[10]), "+f"(d[11]), "+f"(d[12]), "+f"(d[13]), "+f"(d[14]), "+f"(d[15]), "+f"(d[16]), "+f"(d[17]), "+f"(d[18]), "+f"(d[19]), "+f"(d[20]), "+f"(d[21]), "+f"(d[22]), "+f"(d[23]), "+f"(d[24]), "+f"(d[25]), "+f"(d[26]), "+f"(d[27]), "+f"(d[28]), "+f"(d[29]), "+f"(d[30]), "+f"(d[31])
    : "l"(da), "l"(db), "r"(scale_d), "n"(TA), "n"(TB));
}
template <int TB>
__device__ __forceinline__ void wgmma_rs_n64(float (&d)[32], uint32_t a0, uint32_t a1, uint32_t a2, uint32_t a3, uint64_t db, int scale_d) {
  asm volatile("{\n.reg .pred p;\nsetp.ne.b32 p, %37, 0;\n"
    "wgmma.mma_async.sync.aligned.m64n64k16.f32.bf16.bf16 {%0, %1, %2, %3, %4, %5, %6, %7, %8, %9, %10, %11, %12, %13, %14, %15, %16, %17, %18, %19, %20, %21, %22, %23, %24, %25, %26, %27, %28, %29, %30, %31}, {%32, %33, %34, %35}, %36, p, 1, 1, %38;\n}\n"
    : "+f"(d[0]), "+f"(d[1]), "+f"(d[2]), "+f"(d[3]), "+f"(d[4]), "+f"(d[5]), "+f"(d[6]), "+f"(d[7]), "+f"(d[8]), "+f"(d[9]), "+f"(d[10]), "+f"(d[11]), "+f"(d[12]), "+f"(d[13]), "+f"(d[14]), "+f"(d[15]), "+f"(d[16]), "+f"(d[17]), "+f"(d[18]), "+f"(d[19]), "+f"(d[20]), "+f"(d[21]), "+f"(d[22]), "+f"(d[23]), "+f"(d[24]), "+f"(d[25]), "+f"(d[26]), "+f"(d[27]), "+f"(d[28]), "+f"(d[29]), "+f"(d[30]), "+f"(d[31])
    : "r"(a0), "r"(a1), "r"(a2), "r"(a3), "l"(db), "r"(scale_d), "n"(TB));
}
template <int TB, int TA = 0>
__device__ __forceinline__ void wgmma_ss_n160(float (&d)[80], uint64_t da, uint64_t db, int scale_d) {
  asm volatile("{\n.reg .pred p;\nsetp.ne.b32 p, %82, 0;\n"
    "wgmma.mma_async.sync.aligned.m64n160k16.f32.bf16.bf16 {%0, %1, %2, %3, %4, %5, %6, %7, %8, %9, %10, %11, %12, %13, %14, %15, %16, %17, %18, %19, %20, %21, %22, %23, %24, %25, %26, %27, %28, %29, %30, %31, %32, %33, %34, %35, %36, %37, %38, %39, %40, %41, %42, %43, %44, %45, %46, %47, %48, %49, %50, %51, %52, %53, %54, %55, %56, %57, %58, %59, %60, %61, %62, %63, %64, %65, %66, %67, %68, %69, %70, %71, %72, %73, %74, %75, %76, %77, %78, %79}, %80, %81, p, 1, 1, %83, %84;\n}\n"
    : "+f"(d[0]), "+f"(d[1]), "+f"(d[2]), "+f"(d[3]), "+f"(d[4]), "+f"(d[5]), "+f"(d[6]), "+f"(d[7]), "+f"(d[8]), "+f"(d[9]), "+f"(d[10]), "+f"(d[11]), "+f"(d[12]), "+f"(d[13]), "+f"(d[14]), "+f"(d[15]), "+f"(d[16]), "+f"(d[17]), "+f"(d[18]), "+f"(d[19]), "+f"(d[20]), "+f"(d[21]), "+f"(d[22]), "+f"(d[23]), "+f"(d[24]), "+f"(d[25]), "+f"(d[26]), "+f"(d[27]), "+f"(d[28]), "+f"(d[29]), "+f"(d[30]), "+f"(d[31]), "+f"(d[32]), "+f"(d[33]), "+f"(d[34]), "+f"(d[35]), "+f"(d[36]), "+f"(d[37]), "+f"(d[38]), "+f"(d[39]), "+f"(d[40]), "+f"(d[41]), "+f"(d[42]), "+f"(d[43]), "+f"(d[44]), "+f"(d[45]), "+f"(d[46]), "+f"(d[47]), "+f"(d[48]), "+f"(d[49]), "+f"(d[50]), "+f"(d[51]), "+f"(d[52]), "+f"(d[53]), "+f"(d[54]), "+f"(d[55]), "+f"(d[56]), "+f"(d[57]), "+f"(d[58]), "+f"(d[59]), "+f"(d[60]), "+f"(d[61]), "+f"(d[62]), "+f"(d[63]), "+f"(d[64]), "+f"(d[65]), "+f"(d[66]), "+f"(d[67]), "+f"(d[68]), "+f"(d[69]), "+f"(d[70]), "+f"(d[71]), "+f"(d[72]), "+f"(d[73]), "+f"(d[74]), "+f"(d[75]), "+f"(d[76]), "+f"(d[77]), "+f"(d[78]), "+f"(d[79])
    : "l"(da), "l"(db), "r"(scale_d), "n"(TA), "n"(TB));
}
template <int TB>
__device__ __forceinline__ void wgmma_rs_n160(float (&d)[80], uint32_t a0, uint32_t a1, uint32_t a2, uint32_t a3, uint64_t db, int scale_d) {
  asm volatile("{\n.reg .pred p;\nsetp.ne.b32 p, %85, 0;\n"
    "wgmma.mma_async.sync.aligned.m64n160k16.f32.bf16.bf16 {%0, %1, %2, %3, %4, %5, %6, %7, %8, %9, %10, %11, %12, %13, %14, %15, %16, %17, %18, %19, %20, %21, %22, %23, %24, %25, %26, %27, %28, %29, %30, %31, %32, %33, %34, %35, %36, %37, %38, %39, %40, %41, %42, %43, %44, %45, %46, %47, %48, %49, %50, %51, %52, %53, %54, %55, %56, %57, %58, %59, %60, %61, %62, %63, %64, %65, %66, %67, %68, %69, %70, %71, %72, %73, %74, %75, %76, %77, %78, %79}, {%80, %81, %82, %83}, %84, p, 1, 1, %86;\n}\n"
    : "+f"(d[0]), "+f"(d[1]), "+f"(d[2]), "+f"(d[3]), "+f"(d[4]), "+f"(d[5]), "+f"(d[6]), "+f"(d[7]), "+f"(d[8]), "+f"(d[9]), "+f"(d[10]), "+f"(d[11]), "+f"(d[12]), "+f"(d[13]), "+f"(d[14]), "+f"(d[15]), "+f"(d[16]), "+f"(d[17]), "+f"(d[18]), "+f"(d[19]), "+f"(d[20]), "+f"(d[21]), "+f"(d[22]), "+f"(d[23]), "+f"(d[24]), "+f"(d[25]), "+f"(d[26]), "+f"(d[27]), "+f"(d[28]), "+f"(d[29]), "+f"(d[30]), "+f"(d[31]), "+f"(d[32]), "+f"(d[33]), "+f"(d[34]), "+f"(d[35]), "+f"(d[36]), "+f"(d[37]), "+f"(d[38]), "+f"(d[39]), "+f"(d[40]), "+f"(d[41]), "+f"(d[42]), "+f"(d[43]), "+f"(d[44]), "+f"(d[45]), "+f"(d[46]), "+f"(d[47]), "+f"(d[48]), "+f"(d[49]), "+f"(d[50]), "+f"(d[51]), "+f"(d[52]), "+f"(d[53]), "+f"(d[54]), "+f"(d[55]), "+f"(d[56]), "+f"(d[57]), "+f"(d[58]), "+f"(d[59]), "+f"(d[60]), "+f"(d[61]), "+f"(d[62]), "+f"(d[63]), "+f"(d[64]), "+f"(d[65]), "+f"(d[66]), "+f"(d[67]), "+f"(d[68]), "+f"(d[69]), "+f"(d[70]), "+f"(d[71]), "+f"(d[72]), "+f"(d[73]), "+f"(d[74]), "+f"(d[75]), "+f"(d[76]), "+f"(d[77]), "+f"(d[78]), "+f"(d[79])
    : "r"(a0), "r"(a1), "r"(a2), "r"(a3), "l"(db), "r"(scale_d), "n"(TB));
}
template <int TB, int TA = 0>
__device__ __forceinline__ void wgmma_ss_n192(float (&d)[96], uint64_t da, uint64_t db, int scale_d) {
  asm volatile("{\n.reg .pred p;\nsetp.ne.b32 p, %98, 0;\n"
    "wgmma.mma_async.sync.aligned.m64n192k16.f32.bf16.bf16 {%0, %1, %2, %3, %4, %5, %6, %7, %8, %9, %10, %11, %12, %13, %14, %15, %16, %17, %18, %19, %20, %21, %22, %23, %24, %25, %26, %27, %28, %29, %30, %31, %32, %33, %34, %35, %36, %37, %38, %39, %40, %41, %42, %43, %44, %45, %46, %47, %48, %49, %50, %51, %52, %53, %54, %55, %56, %57, %58, %59, %60, %61, %62, %63, %64, %65, %66, %67, %68, %69, %70, %71, %72, %73, %74, %75, %76, %77, %78, %79, %80, %81, %82, %83, %84, %85, %86, %87, %88, %89, %90, %91, %92, %93, %94, %95}, %96, %97, p, 1, 1, %99, %100;\n}\n"
    : "+f"(d[0]), "+f"(d[1]), "+f"(d[2]), "+f"(d[3]), "+f"(d[4]), "+f"(d[5]), "+f"(d[6]), "+f"(d[7]), "+f"(d[8]), "+f"(d[9]), "+f"(d[10]), "+f"(d[11]), "+f"(d[12]), "+f"(d[13]), "+f"(d[14]), "+f"(d[15]), "+f"(d[16]), "+f"(d[17]), "+f"(d[18]), "+f"(d[19]), "+f"(d[20]), "+f"(d[21]), "+f"(d[22]), "+f"(d[23]), "+f"(d[24]), "+f"(d[25]), "+f"(d[26]), "+f"(d[27]), "+f"(d[28]), "+f"(d[29]), "+f"(d[30]), "+f"(d[31]), "+f"(d[32]), "+f"(d[33]), "+f"(d[34]), "+f"(d[35]), "+f"(d[36]), "+f"(d[37]), "+f"(d[38]), "+f"(d[39]), "+f"(d[40]), "+f"(d[41]), "+f"(d[42]), "+f"(d[43]), "+f"(d[44]), "+f"(d[45]), "+f"(d[46]), "+f"(d[47]), "+f"(d[48]), "+f"(d[49]), "+f"(d[50]), "+f"(d[51]), "+f"(d[52]), "+f"(d[53]), "+f"(d[54]), "+f"(d[55]), "+f"(d[56]), "+f"(d[57]), "+f"(d[58]), "+f"(d[59]), "+f"(d[60]), "+f"(d[61]), "+f"(d[62]), "+f"(d[63]), "+f"(d[64]), "+f"(d[65]), "+f"(d[66]), "+f"(d[67]), "+f"(d[68]), "+f"(d[69]), "+f"(d[70]), "+f"(d[71]), "+f"(d[72]), "+f"(d[73]), "+f"(d[74]), "+f"(d[75]), "+f"(d[76]), "+f"(d[77]), "+f"(d[78]), "+f"(d[79]), "+f"(d[80]), "+f"(d[81]), "+f"(d[82]), "+f"(d[83]), "+f"(d[84]), "+f"(d[85]), "+f"(d[86]), "+f"(d[87]), "+f"(d[88]), "+f"(d[89]), "+f"(d[90]), "+f"(d[91]), "+f"(d[92]), "+f"(d[93]), "+f"(d[94]), "+f"(d[95])
    : "l"(da), "l"(db), "r"(scale_d), "n"(TA), "n"(TB));
}
template <int TB>
__device__ __forceinline__ void wgmma_rs_n192(float (&d)[96], uint32_t a0, uint32_t a1, uint32_t a2, uint32_t a3, uint64_t db, int scale_d) {
  asm volatile("{\n.reg .pred p;\nsetp.ne.b32 p, %101, 0;\n"
    "wgmma.mma_async.sync.aligned.m64n192k16.f32.bf16.bf16 {%0, %1, %2, %3, %4, %5, %6, %7, %8, %9, %10, %11, %12, %13, %14, %15, %16, %17, %18, %19, %20, %21, %22, %23, %24, %25, %26, %27, %28, %29, %30, %31, %32, %33, %34, %35, %36, %37, %38, %39, %40, %41, %42, %43, %44, %45, %46, %47, %48, %49, %50, %51, %52, %53, %54, %55, %56, %57, %58, %59, %60, %61, %62, %63, %64, %65, %66, %67, %68, %69, %70, %71, %72, %73, %74, %75, %76, %77, %78, %79, %80, %81, %82, %83, %84, %85, %86, %87, %88, %89, %90, %91, %92, %93, %94, %95}, {%96, %97, %98, %99}, %100, p, 1, 1, %102;\n}\n"
    : "+f"(d[0]), "+f"(d[1]), "+f"(d[2]), "+f"(d[3]), "+f"(d[4]), "+f"(d[5]), "+f"(d[6]), "+f"(d[7]), "+f"(d[8]), "+f"(d[9]), "+f"(d[10]), "+f"(d[11]), "+f"(d[12]), "+f"(d[13]), "+f"(d[14]), "+f"(d[15]), "+f"(d[16]), "+f"(d[17]), "+f"(d[18]), "+f"(d[19]), "+f"(d[20]), "+f"(d[21]), "+f"(d[22]), "+f"(d[23]), "+f"(d[24]), "+f"(d[25]), "+f"(d[26]), "+f"(d[27]), "+f"(d[28]), "+f"(d[29]), "+f"(d[30]), "+f"(d[31]), "+f"(d[32]), "+f"(d[33]), "+f"(d[34]), "+f"(d[35]), "+f"(d[36]), "+f"(d[37]), "+f"(d[38]), "+f"(d[39]), "+f"(d[40]), "+f"(d[41]), "+f"(d[42]), "+f"(d[43]), "+f"(d[44]), "+f"(d[45]), "+f"(d[46]), "+f"(d[47]), "+f"(d[48]), "+f"(d[49]), "+f"(d[50]), "+f"(d[51]), "+f"(d[52]), "+f"(d[53]), "+f"(d[54]), "+f"(d[55]), "+f"(d[56]), "+f"(d[57]), "+f"(d[58]), "+f"(d[59]), "+f"(d[60]), "+f"(d[61]), "+f"(d[62]), "+f"(d[63]), "+f"(d[64]), "+f"(d[65]), "+f"(d[66]), "+f"(d[67]), "+f"(d[68]), "+f"(d[69]), "+f"(d[70]), "+f"(d[71]), "+f"(d[72]), "+f"(d[73]), "+f"(d[74]), "+f"(d[75]), "+f"(d[76]), "+f"(d[77]), "+f"(d[78]), "+f"(d[79]), "+f"(d[80]), "+f"(d[81]), "+f"(d[82]), "+f"(d[83]), "+f"(d[84]), "+f"(d[85]), "+f"(d[86]), "+f"(d[87]), "+f"(d[88]), "+f"(d[89]), "+f"(d[90]), "+f"(d[91]), "+f"(d[92]), "+f"(d[93]), "+f"(d[94]), "+f"(d[95])
    : "r"(a0), "r"(a1), "r"(a2), "r"(a3), "l"(db), "r"(scale_d), "n"(TB));
}

__device__ __forceinline__ uint32_t smem_u32(const void* p) { return (uint32_t)__cvta_generic_to_shared(p); }
__device__ __forceinline__ void wg_fence() { asm volatile("wgmma.fence.sync.aligned;" ::: "memory"); }
__device__ __forceinline__ void wg_commit() { asm volatile("wgmma.commit_group.sync.aligned;" ::: "memory"); }
template <int N> __device__ __forceinline__ void wg_wait() { asm volatile("wgmma.wait_group.sync.aligned %0;" ::"n"(N) : "memory"); }
__device__ __forceinline__ void sched_fence(uint32_t& keep) {
  asm volatile("{\n.reg .u32 c;\nmov.u32 c, %%clock;\nxor.b32 %0, %0, c;\n}\n" : "+r"(keep)::"memory");
}
template <int N> __device__ __forceinline__ void fence_regs(float (&r)[N]) {
#pragma unroll
  for (int i = 0; i < N; i++) asm volatile("" : "+f"(r[i])::"memory");
}
template <int N> __device__ __forceinline__ void fence_regs(uint32_t (&r)[N]) {
#pragma unroll
  for (int i = 0; i < N; i++) asm volatile("" : "+r"(r[i])::"memory");
}
__device__ __forceinline__ uint64_t mk_desc(uint32_t a16, uint32_t lbo, uint32_t sbo, uint32_t swz) {
  uint64_t d;
  asm("mov.b64 %0, {%1, %2};" : "=l"(d) : "r"(a16 + ((lbo >> 4) << 16)), "r"((sbo >> 4) | (swz << 30)));
  return d;
}
__device__ __forceinline__ void mbar_init(uint32_t bar, uint32_t cnt) {
  asm volatile("mbarrier.init.shared::cta.b64 [%0], %1;" ::"r"(bar), "r"(cnt) : "memory");
}
__device__ __forceinline__ void mbar_expect(uint32_t bar, uint32_t tx) {
  asm volatile("mbarrier.arrive.expect_tx.shared::cta.b64 _, [%0], %1;" ::"r"(bar), "r"(tx) : "memory");
}
__device__ __forceinline__ bool mbar_test(uint32_t bar, uint32_t ph) {
  uint32_t ok;
  asm volatile("{\n.reg .pred p;\nmbarrier.test_wait.parity.shared::cta.b64 p, [%1], %2;\nselp.u32 %0, 1, 0, p;\n}\n"
               : "=r"(ok) : "r"(bar), "r"(ph) : "memory");
  return ok;
}
__device__ __forceinline__ void mbar_wait(uint32_t bar, uint32_t ph) {
  asm volatile("{\n.reg .pred p;\n.reg .u32 n;\n"
               "mbarrier.try_wait.parity.shared::cta.b64 p, [%0], %1;\n@p bra DONE;\n"
               "mov.u32 n, 0;\n"
               "LOOP:\nmbarrier.try_wait.parity.shared::cta.b64 p, [%0], %1;\n@p bra DONE;\n"
               "add.u32 n, n, 1;\nsetp.lt.u32 p, n, 0x1000000;\n@p bra LOOP;\ntrap;\n"
               "DONE:\n}\n" ::"r"(bar), "r"(ph) : "memory");
}
template <int NS> __device__ __forceinline__ void mbar_wait_slow(uint32_t bar, uint32_t ph) {
  asm volatile("{\n.reg .pred p;\n.reg .u32 n;\nmov.u32 n, 0;\n"
               "LOOP:\nmbarrier.test_wait.parity.shared::cta.b64 p, [%0], %1;\n@p bra DONE;\n"
               "nanosleep.u32 %2;\nadd.u32 n, n, 1;\nsetp.lt.u32 p, n, 0x400000;\n@p bra LOOP;\ntrap;\n"
               "DONE:\n}\n" ::"r"(bar), "r"(ph), "n"(NS) : "memory");
}
__device__ __forceinline__ void mbar_arrive_cluster_if(bool on, uint32_t addr) {
  asm volatile("{\n.reg .pred p;\nsetp.ne.b32 p, %1, 0;\n@p mbarrier.arrive.shared::cluster.b64 _, [%0];\n}\n" ::"r"(addr), "r"((int)on) : "memory");
}
__device__ __forceinline__ void mbar_arrive_if(bool on, uint32_t addr) {
  asm volatile("{\n.reg .pred p;\nsetp.ne.b32 p, %1, 0;\n@p mbarrier.arrive.shared::cta.b64 _, [%0];\n}\n" ::"r"(addr), "r"((int)on) : "memory");
}
__device__ __forceinline__ void tma2d(uint32_t dst, const CUtensorMap* m, uint32_t bar, int c0, int c1) {
  asm volatile("cp.async.bulk.tensor.2d.shared::cluster.global.mbarrier::complete_tx::bytes [%0], [%1, {%3, %4}], [%2];"
               ::"r"(dst), "l"(m), "r"(bar), "r"(c0), "r"(c1) : "memory");
}
__device__ __forceinline__ void tma3d(uint32_t dst, const CUtensorMap* m, uint32_t bar, int c0, int c1, int c2) {
  asm volatile("cp.async.bulk.tensor.3d.shared::cluster.global.mbarrier::complete_tx::bytes [%0], [%1, {%3, %4, %5}], [%2];"
               ::"r"(dst), "l"(m), "r"(bar), "r"(c0), "r"(c1), "r"(c2) : "memory");
}
__device__ __forceinline__ void tma3d_mc(uint32_t dst, const CUtensorMap* m, uint32_t bar, int c0, int c1, int c2) {
  asm volatile("cp.async.bulk.tensor.3d.shared::cluster.global.mbarrier::complete_tx::bytes.multicast::cluster"
               " [%0], [%1, {%3, %4, %5}], [%2], %6;"
               ::"r"(dst), "l"(m), "r"(bar), "r"(c0), "r"(c1), "r"(c2), "h"((uint16_t)3) : "memory");
}
__device__ __forceinline__ void tma3d_store(const CUtensorMap* m, uint32_t src, int c0, int c1, int c2) {
  asm volatile("cp.async.bulk.tensor.3d.global.shared::cta.bulk_group [%0, {%2, %3, %4}], [%1];"
               ::"l"(m), "r"(src), "r"(c0), "r"(c1), "r"(c2) : "memory");
}
__device__ __forceinline__ void bar_sync(int id, int n) { asm volatile("bar.sync %0, %1;" ::"r"(id), "r"(n) : "memory"); }
__device__ __forceinline__ uint32_t pack_bf16(float lo, float hi) {
  uint32_t r;
  asm("cvt.rn.bf16x2.f32 %0, %1, %2;" : "=r"(r) : "f"(hi), "f"(lo));
  return r;
}
__device__ __forceinline__ float ex2(float x) {
  float y;
  asm("ex2.approx.ftz.f32 %0, %1;" : "=f"(y) : "f"(x));
  return y;
}
__device__ __forceinline__ float fadd(float a, float b) {
  float y;
  asm("add.f32 %0, %1, %2;" : "=f"(y) : "f"(a), "f"(b));
  return y;
}
__device__ __forceinline__ float rcp(float x) {
  float y;
  asm("rcp.approx.ftz.f32 %0, %1;" : "=f"(y) : "f"(x));
  return y;
}
__device__ __forceinline__ void stsm4(uint32_t addr, uint32_t a, uint32_t b, uint32_t c, uint32_t d) {
  asm volatile("stmatrix.sync.aligned.m8n8.x4.shared.b16 [%0], {%1, %2, %3, %4};" ::"r"(addr), "r"(a), "r"(b), "r"(c), "r"(d) : "memory");
}

__device__ __forceinline__ void tma4d_mc_hint(uint32_t dst, const CUtensorMap* m, uint32_t bar, int c3, uint64_t pol) {
  asm volatile("cp.async.bulk.tensor.4d.shared::cluster.global.mbarrier::complete_tx::bytes.multicast::cluster.L2::cache_hint"
               " [%0], [%1, {%3, %3, %3, %4}], [%2], %5, %6;"
               ::"r"(dst), "l"(m), "r"(bar), "r"(0), "r"(c3), "h"((uint16_t)3), "l"(pol) : "memory");
}
__device__ __forceinline__ void tma5d_mc(uint32_t dst, const CUtensorMap* m, uint32_t bar, int c2, int c4) {
  asm volatile("cp.async.bulk.tensor.5d.shared::cluster.global.mbarrier::complete_tx::bytes.multicast::cluster"
               " [%0], [%1, {%3, %3, %4, %3, %5}], [%2], %6;"
               ::"r"(dst), "l"(m), "r"(bar), "r"(0), "r"(c2), "r"(c4), "h"((uint16_t)3) : "memory");
}
__device__ __forceinline__ void bulk_load_hint(uint32_t dst, const void* src, uint32_t bytes, uint32_t bar, uint64_t pol) {
  asm volatile("cp.async.bulk.shared::cluster.global.mbarrier::complete_tx::bytes.L2::cache_hint [%0], [%1], %2, [%3], %4;"
               ::"r"(dst), "l"(src), "r"(bytes), "r"(bar), "l"(pol) : "memory");
}
__device__ __forceinline__ void stg128_hint(void* p, uint32_t a, uint32_t b, uint32_t c, uint32_t d, uint64_t pol) {
  asm volatile("st.global.L2::cache_hint.v4.b32 [%0], {%1, %2, %3, %4}, %5;" ::"l"(p), "r"(a), "r"(b), "r"(c), "r"(d), "l"(pol) : "memory");
}
__device__ __forceinline__ void stg2_if(bool on, void* p, uint32_t a, uint32_t b, uint32_t c, uint32_t d, uint32_t e, uint32_t f,
                                        uint32_t g, uint32_t h, uint64_t pol) {
  asm volatile("{\n.reg .pred p;\nsetp.ne.b32 p, %10, 0;\n"
               "@p st.global.L2::cache_hint.v4.b32 [%0], {%1, %2, %3, %4}, %9;\n"
               "@p st.global.L2::cache_hint.v4.b32 [%0 + 512], {%5, %6, %7, %8}, %9;\n}\n"
               ::"l"(p), "r"(a), "r"(b), "r"(c), "r"(d), "r"(e), "r"(f), "r"(g), "r"(h), "l"(pol), "r"((int)on) : "memory");
}
__device__ __forceinline__ uint64_t make_policy(bool first) {
  uint64_t pf, pn;
  asm("createpolicy.fractional.L2::evict_first.b64 %0, 1.0;" : "=l"(pf));
  asm("createpolicy.fractional.L2::evict_normal.b64 %0, 1.0;" : "=l"(pn));
  return first ? pf : pn;
}
__device__ __forceinline__ bool elect() {
  uint32_t ok;
  asm volatile("{\n.reg .pred p;\nelect.sync _|p, 0xffffffff;\nselp.u32 %0, 1, 0, p;\n}\n" : "=r"(ok));
  return ok;
}
__device__ __forceinline__ void mbar_arrive(uint32_t bar) {
  asm volatile("mbarrier.arrive.shared::cta.b64 _, [%0];" ::"r"(bar) : "memory");
}
__device__ __forceinline__ void stg128(void* p, uint32_t a, uint32_t b, uint32_t c, uint32_t d) {
  asm volatile("st.global.v4.b32 [%0], {%1, %2, %3, %4};" ::"l"(p), "r"(a), "r"(b), "r"(c), "r"(d) : "memory");
}
__device__ __forceinline__ void lds128(uint32_t p, uint32_t& a, uint32_t& b, uint32_t& c, uint32_t& d) {
  asm volatile("ld.shared.v4.b32 {%0, %1, %2, %3}, [%4];" : "=r"(a), "=r"(b), "=r"(c), "=r"(d) : "r"(p) : "memory");
}
__device__ __forceinline__ void wait_count(const unsigned int* p, uint32_t target) {
  asm volatile("{\n.reg .pred p;\n.reg .u32 n, v;\nmov.u32 n, 0;\n"
               "LOOP:\nld.acquire.gpu.global.u32 v, [%0];\nsetp.ge.u32 p, v, %1;\n@p bra DONE;\n"
               "nanosleep.u32 %2;\nadd.u32 n, n, 1;\nsetp.lt.u32 p, n, 0x400000;\n@p bra LOOP;\ntrap;\n"
               "DONE:\n}\n" ::"l"(p), "r"(target), "n"(200) : "memory");
}

__host__ __device__ __forceinline__ int o_wave(int a, int b, int i, int lag) {
  if (lag == 0) return a + i;
  const int p = lag < b - a - 1 ? lag : b - a - 1;
  return i < p ? b - 2 - i : i == p ? b - 1 : b - 1 - i;
}

struct Cursor {
  int bi;
  uint32_t ph;
  __device__ __forceinline__ void next() {
    if (++bi == NBAR) { bi = 0; ph ^= 1; }
  }
};

constexpr float kScaleLog2 = 0.07216878364870322f * 1.4426950408889634f;
constexpr float kSumLimit = 1048576.0f;
constexpr float kMaxLag = 8.0f;

__global__ void __cluster_dims__(2, 1, 1) __launch_bounds__(384, 1)
fused_kernel(const __grid_constant__ Params P) {
  extern __shared__ uint8_t smem_raw[];
  const uint32_t sbase = (smem_u32(smem_raw) + 1023) & ~1023u;
  const uint32_t full0 = sbase + RING, empty0 = full0 + 8 * NBAR, odone = empty0 + 8 * NBAR, oready0 = odone + 8;
  const uint32_t fenced = oready0 + 64, hready0 = fenced + 8;
  const uint32_t rank = blockIdx.x & 1;
  const int role = blockIdx.x >> 1;
  const bool helper = role >= N_CL;
  const int team = helper ? 0 : role >> 2, nt = role & 3, blk = team >> 3;
  const uint32_t* prog = P.ops[helper ? N_TEAM + 2 * (role - N_CL) : team];
  auto q_role = [&](uint32_t op) { return helper ? (int)(((op >> 3) & 60) | ((op >> 12) & 3)) : role; };
  auto o_role = [&](uint32_t op) { return helper ? (int)(((op >> 26) & 56) | ((op >> 9) & 7)) : role; };
  const int wid = __shfl_sync(0xffffffffu, (int)(threadIdx.x >> 5), 0);
  const int wg = wid >> 2;

  const uint32_t op0 = P.first[helper ? N_TEAM + role - N_CL : team];
  if (__builtin_expect(wid == 8, 1)) {
    if (elect()) {
#pragma unroll
      for (int k = 0; k < EARLY; k++) mbar_init(full0 + 8 * k, 1);
      asm volatile("fence.mbarrier_init.release.cluster;" ::: "memory");
      if ((op0 & 3) == OP_Q) {
        const int qr = q_role(op0);
#pragma unroll
        for (int k = 0; k < EARLY; k++) {
          mbar_expect(full0 + 8 * k, SZ_Q);
          tma2d(sbase + k * SZ_Q, &P.x[qr >> 5], full0 + 8 * k, 64 * k, ((qr >> 2) & 7) * kSq + rank * 128);
          tma3d(sbase + k * SZ_Q + 16384, &P.wq[qr >> 5], full0 + 8 * k, 0, 64 * k, 3 * (4 * ((op0 >> 2) & 7) + (qr & 3)));
        }
      }
      asm volatile("prefetch.tensormap [%0];" ::"l"(rank ? &P.v[blk] : &P.k[blk]) : "memory");
    }
  } else if (threadIdx.x == 0) {
#pragma unroll
    for (int i = EARLY; i < 2 * NBAR + 10 + MAX_PARK; i++) mbar_init(full0 + 8 * i, i < NBAR ? 1 : i < 2 * NBAR ? 16 : i == 2 * NBAR ? 8 : 1);
    asm volatile("fence.mbarrier_init.release.cluster;" ::: "memory");
  }
  __syncwarp();
  asm volatile("barrier.cluster.arrive.relaxed.aligned;\nbarrier.cluster.wait.aligned;" ::: "memory");

  if (wg == 2) {
    asm volatile("setmaxnreg.dec.sync.aligned.u32 24;");
    if (wid == 8) {
      Cursor tail{0, 0};
      int head = 0, sh = 0;
      uint32_t cur = 0, used = 0;
      uint64_t fifo = 0;
      uint32_t dst, bar, oready = oready0;
      uint64_t pol;
      asm volatile("createpolicy.fractional.L2::evict_first.b64 %0, 1.0;" : "=l"(pol));
      const uint64_t pol_o = make_policy(P.dbg & 1), pol_p = make_policy(!(P.dbg & 4));
      const CUtensorMap* kv_map = rank ? &P.v[blk] : &P.k[blk];
      auto acquire = [&](uint32_t bytes) {
        uint32_t fp = bytes >> 12;
        if (cur + fp > (RING >> 12)) { fp += (RING >> 12) - cur; cur = 0; }
        used += fp;
        while (used > (RING >> 12) || sh == 5 * NBAR) {
          mbar_wait(empty0 + 8 * tail.bi, tail.ph);
          tail.next();
          used -= (uint32_t)fifo & 31;
          fifo >>= 5;
          sh -= 5;
        }
        fifo |= (uint64_t)fp << sh;
        sh += 5;
        dst = sbase + (cur << 12);
        bar = full0 + 8 * head;
        cur += bytes >> 12;
        if (++head == NBAR) head = 0;
      };
      for (int pc = 0;; pc++) {
        const uint32_t op = prog[pc];
        const int type = op & 3, a = (op >> 2) & 7;
        if (type == OP_END) break;
        if (type == OP_Q) {
          const int qr = q_role(op);
#pragma unroll 1
          for (int k = 0; k < 10; k++) {
            acquire(SZ_Q);
            if ((pc > 0 || k >= EARLY) && elect()) {
              mbar_expect(bar, SZ_Q);
              tma2d(dst, &P.x[qr >> 5], bar, 64 * k, ((qr >> 2) & 7) * kSq + rank * 128);
              if ((k & 1) == rank) tma3d_mc(dst + 16384, &P.wq[qr >> 5], bar, 0, 64 * k, 3 * (4 * a + (qr & 3)));
            }
          }
        } else if (type == OP_A) {
          const uint32_t nop = prog[pc + 1];
          auto kv = [&](int isv, int wave, int j) {
            const int row0 = ((team & 7) * kH + 4 * wave + nt) * kSk;
            acquire(SZ_KV);
            if (elect()) {
              mbar_expect(bar, SZ_KV);
              if (isv == (int)rank) tma4d_mc_hint(dst, kv_map, bar, row0 / 8 + 8 * j, pol);
            }
          };
#pragma unroll 1
          for (int t = (op & F_PARK) ? 1 : 0; t < 31; t++) {
            const int isv = t == 0 ? 0 : (~t & 1);
            kv(isv, a, isv ? (t - 1) >> 1 : (t + 1) >> 1);
          }
          if ((nop & 3) == OP_A) {
            mbar_wait((nop & F_HELP) ? hready0 + 8 * ((nop >> 10) & 3) : fenced, 0);
            asm volatile("fence.proxy.async.global;" ::: "memory");
            acquire(SZ_PARK);
            if (elect()) {
              mbar_expect(bar, SZ_PARK);
              bulk_load_hint(dst, &g_park[((role * 2 + rank) * MAX_PARK + ((nop >> 10) & 3)) * 3072], SZ_PARK, bar, pol_p);
            }
            kv(0, (nop >> 2) & 7, 0);
          }
          kv(1, a, 15);
        } else {
          const int b = (op >> 5) & 15, ro = o_role(op);
#pragma unroll 1
          for (int i = 0; i < b - a; i++) {
            const int w = o_wave(a, b, i, (P.dbg >> 4) & 7);
            mbar_wait(oready, 0);
            oready += 8;
            asm volatile("fence.proxy.async.global;" ::: "memory");
#pragma unroll 1
            for (int k = 12 * w; k < 12 * w + 12; k++) {
              acquire(SZ_O);
              if (elect()) {
                mbar_expect(bar, SZ_O);
                tma5d_mc(dst + 16384 + rank * 10240, &P.wo[ro >> 5], bar, 8 * k + 4 * rank, 5 * (ro & 3));
                bulk_load_hint(dst, &g_o[(((ro >> 2) * 2 + rank) * 96 + k - 12 * (w - P.slot[w])) * 1024], 16384, bar, pol_o);
              }
            }
          }
          if (op & F_LD) {
            if (op & F_PARK) {
              mbar_wait(hready0 + 8 * (MAX_PARK - 1), 0);
              asm volatile("fence.proxy.async.global;" ::: "memory");
            }
#pragma unroll 1
            for (int i = 0; i < 2; i++) {
              acquire(SZ_PART);
              if (elect()) {
                mbar_expect(bar, SZ_PART);
                bulk_load_hint(dst, &g_part[(role * 2 + rank) * 5120 + i * 2560], SZ_PART, bar, pol_p);
              }
            }
          }
        }
      }
    } else if (threadIdx.x == 288) {
      uint32_t ph = 0;
      bool first = true;
      for (int pc = 0;; pc++) {
        const uint32_t op = prog[pc];
        if ((op & 3) == OP_END) break;
        if ((op & 3) != OP_A && !helper) continue;
        mbar_wait_slow<400>(odone, ph);
        ph ^= 1;
        unsigned int* flag = !helper ? &g_done[(team * 2 + rank) * 8 + ((op >> 2) & 7)]
                             : (op & 3) == OP_Q ? &g_help[(q_role(op) * 2 + rank) * MAX_PARK + ((op >> 10) & 3)]
                                                : &g_help[(o_role(op) * 2 + rank) * MAX_PARK + MAX_PARK - 1];
        asm volatile("red.release.gpu.global.add.u32 [%0], 1;" ::"l"(flag) : "memory");
        if (first) mbar_arrive(fenced);
        first = false;
      }
    } else if (threadIdx.x == 320) {
      uint32_t oready = oready0;
      for (int pc = 0;; pc++) {
        const uint32_t op = prog[pc];
        if ((op & 3) == OP_END) break;
        if ((op & 3) == OP_O) {
          const int a = (op >> 2) & 7, b = (op >> 5) & 15;
          for (int i = 0; i < b - a; i++) {
            const int ci = ((o_role(op) >> 2) * 2 + rank) * 8 + o_wave(a, b, i, (P.dbg >> 4) & 7);
            wait_count(&g_done[ci], 4);
            mbar_arrive(oready);
            oready += 8;
            if (atomicAdd(&g_seen[ci], 1u) == 3u) { g_seen[ci] = 0; g_done[ci] = 0; }
          }
        }
        if ((op & 3) != OP_Q && (op & F_HELP) && (op & F_PARK)) {
          unsigned int* flag = &g_help[(role * 2 + rank) * MAX_PARK + ((op >> 10) & 3)];
          wait_count(flag, 1);
          mbar_arrive(hready0 + 8 * ((op >> 10) & 3));
          *flag = 0;
        }
      }
    }
    __syncwarp();
    asm volatile("barrier.cluster.arrive.relaxed;\nbarrier.cluster.wait;" ::: "memory");
  } else {
    asm volatile("setmaxnreg.inc.sync.aligned.u32 240;");
    const int lane = threadIdx.x & 31, warp = wid & 3;
    uint32_t empty_rem;
    asm volatile("mapa.shared::cluster.u32 %0, %1, %2;" : "=r"(empty_rem) : "r"(empty0), "r"(lane & 1));
    auto release = [&](int slot) { mbar_arrive_cluster_if(lane < 2, empty_rem + 8 * slot); };
    Cursor r{0, 0};
    const uint32_t ring16 = (sbase & 0x3FFFF) >> 4;
    uint32_t cur = ring16;
    bool rdy0 = false, rdy1 = false;
    auto probe1 = [&]() { rdy0 = mbar_test(full0 + 8 * r.bi, r.ph); };
    auto probe2 = [&]() {
      Cursor n = r;
      rdy0 = mbar_test(full0 + 8 * n.bi, n.ph);
      n.next();
      rdy1 = mbar_test(full0 + 8 * n.bi, n.ph);
    };
    auto take = [&](bool rdy, uint32_t bytes, uint32_t& addr) {
      const int bi = r.bi;
      if (!__all_sync(0xffffffffu, rdy)) mbar_wait(full0 + 8 * r.bi, r.ph);
      r.next();
      if (cur > ring16 + ((RING - bytes) >> 4)) cur = ring16;
      addr = cur;
      cur += bytes >> 4;
      return bi;
    };
    uint32_t keep = 0;
    uint32_t q[48];
#pragma unroll
    for (int i = 0; i < 48; i++) q[i] = 0;
    const int row = wg * 64 + warp * 16 + (lane >> 2);
    const int img0 = row * 4 + ((lane & 3) ^ ((row >> 1) & 3));
    uint4* pend = nullptr;
    uint64_t spol;
    auto drain = [&](uint32_t op, int c) {
      if (!(op & (3u << 26)) || c >= 6) return;
#pragma unroll
      for (int i = 0; i < 6; i++)
        stg2_if(c == i, pend + i * 512, q[8 * i], q[8 * i + 1], q[8 * i + 2], q[8 * i + 3],
                q[8 * i + 4], q[8 * i + 5], q[8 * i + 6], q[8 * i + 7], spol);
      if ((op & (1u << 26)) && c == 5) {
        __syncwarp();
        mbar_arrive_if(lane == 0, odone);
      }
    };

    for (int pc = 0;; pc++) {
      uint32_t op = prog[pc];
      const int type = op & 3;
      int a = (op >> 2) & 7;
      auto enter = [&]() {
        r.bi = (op >> 15) & 15; r.ph = (op >> 19) & 1; cur = ring16 + (((op >> 20) & 63) << 8);
      };
      enter();
      spol = make_policy(!(op & F_SOON));
      if (type == OP_END) {
        for (int c = 0; c < 6; c++) drain(op, c);
        asm volatile("barrier.cluster.arrive.relaxed;" ::: "memory");
        break;
      }
      if (type == OP_Q) {
        float s[32], o[96];
        uint32_t pa[16], pb[16];
        float mc0, mc1, l0, l1;
        bool gen;
        int bi0, sk1;
        uint32_t ak1;
        auto expo = [&](float (&s)[32], uint32_t (&pout)[16], float& b0, float& b1, bool sub) {
#pragma unroll
          for (int i = 0; i < 8; i++) {
            const float e1 = ex2(sub ? s[4 * i + 1] - mc0 : s[4 * i + 1]), e0 = ex2(sub ? s[4 * i] - mc0 : s[4 * i]);
            const float e3 = ex2(sub ? s[4 * i + 3] - mc1 : s[4 * i + 3]), e2 = ex2(sub ? s[4 * i + 2] - mc1 : s[4 * i + 2]);
            pout[2 * i] = pack_bf16(e0, e1);
            b0 = i ? b0 + fadd(e1, e0) : fadd(e1, e0);
            pout[2 * i + 1] = pack_bf16(e2, e3);
            b1 = i ? b1 + fadd(e3, e2) : fadd(e3, e2);
          }
        };
        auto rowmax = [&](float (&s)[32], float& m0, float& m1) {
          m0 = fmaxf(s[0], s[1]); m1 = fmaxf(s[2], s[3]);
#pragma unroll
          for (int i = 1; i < 8; i++) { m0 = fmaxf(m0, fmaxf(s[4 * i], s[4 * i + 1])); m1 = fmaxf(m1, fmaxf(s[4 * i + 2], s[4 * i + 3])); }
          m0 = fmaxf(m0, __shfl_xor_sync(0xffffffffu, m0, 1)); m1 = fmaxf(m1, __shfl_xor_sync(0xffffffffu, m1, 1));
          m0 = fmaxf(m0, __shfl_xor_sync(0xffffffffu, m0, 2)); m1 = fmaxf(m1, __shfl_xor_sync(0xffffffffu, m1, 2));
        };
        auto first = [&](float (&s)[32]) {
          mc0 = 0.f; mc1 = 0.f;
          expo(s, pa, l0, l1, false);
          gen = __any_sync(0xffffffffu, !(fmaxf(l0, l1) <= kSumLimit && fminf(l0, l1) >= 1.0f / kSumLimit));
          if (gen) {
            rowmax(s, mc0, mc1);
            expo(s, pa, l0, l1, true);
          }
        };
        auto soft = [&](uint32_t (&pout)[16]) {
          float b0, b1;
          if (!gen) {
            expo(s, pout, b0, b1, false);
            gen = __any_sync(0xffffffffu, !(fmaxf(b0, b1) <= kSumLimit));
          }
          if (gen) {
            float m0, m1;
            rowmax(s, m0, m1);
            if (__any_sync(0xffffffffu, !(m0 <= mc0 + kMaxLag && m1 <= mc1 + kMaxLag))) {
              m0 = fmaxf(mc0, m0); m1 = fmaxf(mc1, m1);
              const float a0 = ex2(mc0 - m0), a1 = ex2(mc1 - m1);
              mc0 = m0; mc1 = m1;
              l0 *= a0; l1 *= a1;
              wg_wait<0>();
              fence_regs(o);
#pragma unroll
              for (int i = 0; i < 24; i++) { o[4 * i] *= a0; o[4 * i + 1] *= a0; o[4 * i + 2] *= a1; o[4 * i + 3] *= a1; }
            }
            expo(s, pout, b0, b1, true);
          }
          l0 += b0; l1 += b1;
        };
        auto qk = [&](float (&s)[32], uint32_t ak, int k0, int k1) {
#pragma unroll
          for (int kk = k0; kk < k1; kk++)
            wgmma_rs_n64<0>(s, q[4 * kk], q[4 * kk + 1], q[4 * kk + 2], q[4 * kk + 3], mk_desc(ak + (kk >> 2) * KV_CH + (kk & 3) * 2, 16, KV_SBO, 1), kk != 0);
          wg_commit();
        };
        auto pv = [&](uint32_t (&pin)[16], uint32_t av, int acc) {
#pragma unroll
          for (int kk = 0; kk < 4; kk++)
            wgmma_rs_n192<1>(o, pin[4 * kk], pin[4 * kk + 1], pin[4 * kk + 2], pin[4 * kk + 3], mk_desc(av + kk * (KV_SBO / 8), KV_CH * 16, KV_SBO, 1), acc || (kk != 0));
          wg_commit();
        };
        auto xw = [&](uint32_t ad, int acc) {
          wg_fence();
#pragma unroll
          for (int kk = 0; kk < 4; kk++)
            wgmma_ss_n192<1>(o, mk_desc(ad + wg * 512 + kk * 2, 16, 1024, 1), mk_desc(ad + 1024 + kk * 128, 8192, 1024, 1), acc || kk != 0);
          wg_commit();
        };
        {
          uint32_t ad;
          bi0 = take(rdy0, SZ_Q, ad);
          xw(ad, 0);
        }
      next_head:
        drain(op, 0);
        probe1();
        wg_wait<0>();
        release(bi0);
        {
          auto kstep = [&](int k) {
            uint32_t ad;
            const int bi = take(rdy0, SZ_Q, ad);
            xw(ad, 1);
            drain(op, k);
            probe1();
            wg_wait<0>();
            release(bi);
          };
#pragma unroll 1
          for (int k = 1; k < 8; k++) kstep(k);
          uint32_t ad, ak0;
          const int bi8 = take(rdy0, SZ_Q, ad);
          xw(ad, 1);
          const int bi9 = take(false, SZ_Q, ad);
          xw(ad, 1);
          if (op & F_PARK) {
            probe1();
            wg_wait<1>();
            release(bi8);
            wg_wait<0>();
            fence_regs(o);
            release(bi9);
#pragma unroll
            for (int i = 0; i < 48; i++) q[i] = pack_bf16(o[2 * i] * kScaleLog2, o[2 * i + 1] * kScaleLog2);
            pend = &g_park[((q_role(op) * 2 + rank) * MAX_PARK + ((op >> 10) & 3)) * 3072 + img0];
            continue;
          }
          pc++;
          wg_wait<1>();
          release(bi8);
          const int sk0 = take(false, SZ_KV, ak0);
          probe1();
          wg_wait<0>();
          fence_regs(o);
          release(bi9);
          float s0[32];
#pragma unroll
          for (int i = 0; i < 48; i++) q[i] = pack_bf16(o[2 * i] * kScaleLog2, o[2 * i + 1] * kScaleLog2);
          wg_fence();
          qk(s0, ak0, 0, 12);
          sk1 = take(rdy0, SZ_KV, ak1);
          wg_fence();
          qk(s, ak1, 0, S1A);
          probe1();
          wg_wait<1>();
          fence_regs(s0);
          release(sk0);
          first(s0);
        }
        for (int wave = a;;) {
          const uint32_t nop = prog[pc + 1];
          {
            uint32_t av;
            const int sv = take(rdy0, SZ_KV, av);
            wg_fence();
            qk(s, ak1, S1A, 12);
            pv(pa, av, 0);
            probe2();
            wg_wait<1>();
            fence_regs(s);
            release(sk1);
            soft(pb);
            wg_wait<0>();
            fence_regs(o);
            release(sv);
          }
          auto step = [&](uint32_t (&pin)[16], uint32_t (&pout)[16], bool unpark) {
            uint32_t ak, av;
            const int sk = take(rdy0, SZ_KV, ak), sv = take(rdy1, SZ_KV, av);
            wg_fence();
            qk(s, ak, 0, 12);
            pv(pin, av, 1);
            probe2();
            wg_wait<1>();
            fence_regs(s);
            release(sk);
            if (unpark) {
              uint32_t ad;
              const int bi = take(rdy0, SZ_PARK, ad);
#pragma unroll
              for (int i = 0; i < 12; i++) lds128(sbase + (ad - ring16 + img0) * 16 + (i >> 1) * 8192 + (i & 1) * 512, q[4 * i], q[4 * i + 1], q[4 * i + 2], q[4 * i + 3]);
              release(bi);
            }
            soft(pout);
            wg_wait<0>();
            fence_regs(o);
            release(sv);
          };
          const int jpark = (nop & 3) == OP_A ? 6 : -1;
#pragma unroll 1
          for (int jj = 0; jj < 7; jj++) {
            step(pb, pa, false);
            step(pa, pb, jj == jpark);
          }
          float i0, i1;
          auto sums = [&]() {
            l0 += __shfl_xor_sync(0xffffffffu, l0, 1); l1 += __shfl_xor_sync(0xffffffffu, l1, 1);
            l0 += __shfl_xor_sync(0xffffffffu, l0, 2); l1 += __shfl_xor_sync(0xffffffffu, l1, 2);
            i0 = rcp(l0); i1 = rcp(l1);
            asm volatile("" : "+f"(i0), "+f"(i1));
          };
          auto target = [&]() {
            pend = &g_o[((team * 2 + rank) * 96 + 3 * (4 * P.slot[wave] + nt)) * 1024 + img0];
            asm volatile("" : "+l"(pend));
          };
          if ((nop & 3) != OP_A) {
            uint32_t av, ad;
            const int sv = take(rdy0, SZ_KV, av);
            wg_fence();
            pv(pb, av, 1);
            probe1();
            sums();
            target();
            sched_fence(keep);
            if ((nop & 3) == OP_Q) {
              op = nop; a = (op >> 2) & 7;
              enter();
              spol = make_policy(!(op & F_SOON));
              bi0 = take(rdy0, SZ_Q, ad);
            }
            wg_wait<0>();
            fence_regs(o);
            release(sv);
            float u[96];
#pragma unroll
            for (int i = 0; i < 96; i++) u[i] = o[i] * (i & 2 ? i1 : i0);
            auto convert = [&]() {
#pragma unroll
              for (int i = 0; i < 24; i++) {
                q[8 * (i >> 2) + (i & 3)] = pack_bf16(u[4 * i], u[4 * i + 1]);
                q[8 * (i >> 2) + (i & 3) + 4] = pack_bf16(u[4 * i + 2], u[4 * i + 3]);
              }
            };
            if ((nop & 3) != OP_Q) { convert(); break; }
            pc++;
            fence_regs(u);
            xw(ad, 0);
            sched_fence(keep);
            fence_regs(u);
            convert();
            goto next_head;
          }
          uint32_t ak, av;
          const int sk0 = take(rdy1, SZ_KV, ak), sv = take(false, SZ_KV, av);
          wg_fence();
          qk(s, ak, 0, 12);
          pv(pb, av, 1);
          probe2();
          sums();
          sched_fence(keep);
          spol = make_policy(!(nop & F_SOON));
          wg_wait<1>();
          fence_regs(s);
          release(sk0);
          first(s);
          sk1 = take(rdy0, SZ_KV, ak1);
          rdy0 = rdy1;
          wg_fence();
          qk(s, ak1, 0, S1A);
          wg_wait<1>();
          target();
          fence_regs(o);
          release(sv);
          uint32_t t[48];
#pragma unroll
          for (int c = 0; c <= 6; c++) {
            if (c < 6) {
#pragma unroll
              for (int i = 0; i < 4; i++) {
                t[8 * c + i] = pack_bf16(o[16 * c + 4 * i] * i0, o[16 * c + 4 * i + 1] * i0);
                t[8 * c + i + 4] = pack_bf16(o[16 * c + 4 * i + 2] * i1, o[16 * c + 4 * i + 3] * i1);
              }
#pragma unroll
              for (int i = 0; i < 8; i++) asm volatile("" : "+r"(t[8 * c + i]));
              sched_fence(keep);
            }
            if (c > 0) stg2_if(true, pend + (c - 1) * 512, t[8 * c - 8], t[8 * c - 7], t[8 * c - 6], t[8 * c - 5], t[8 * c - 4], t[8 * c - 3], t[8 * c - 2], t[8 * c - 1], spol);
          }
          __syncwarp();
          mbar_arrive_if(lane == 0, odone);
          pc++;
          wave = (nop >> 2) & 7;
        }
      } else {
        float c[80];
        const int nk = 12 * (((op >> 5) & 15) - a);
        uint4* part = &g_part[(o_role(op) * 2 + rank) * 5120];
        int prev = 0;
        auto kstep = [&](int acc, int k, bool hooks) {
          uint32_t ad;
          const int bi = take(rdy0, SZ_O, ad);
          const uint32_t da = ad + wg * 256, db = ad + 1024;
          wg_fence();
          wgmma_ss_n160<1>(c, mk_desc(da, 16, 512, 2), mk_desc(db, 2048, 512, 2), acc);
          wgmma_ss_n160<1>(c, mk_desc(da + 2, 16, 512, 2), mk_desc(db + 64, 2048, 512, 2), 1);
          wg_commit();
          if (acc) { wg_wait<1>(); release(prev); }
          wgmma_ss_n160<1>(c, mk_desc(da + 512, 16, 512, 2), mk_desc(db + 640, 2048, 512, 2), 1);
          wgmma_ss_n160<1>(c, mk_desc(da + 514, 16, 512, 2), mk_desc(db + 704, 2048, 512, 2), 1);
          wg_commit();
          prev = bi;
          if (hooks) drain(op, k);
          probe1();
          wg_wait<1>();
        };
        kstep(0, 0, true);
#pragma unroll 1
        for (int k = 1; k < 6; k++) kstep(1, k, true);
#pragma unroll 1
        for (int k = 6; k < nk; k++) {
          kstep(1, k, false);
        }
        if (op & F_LD) {
          uint32_t t[80], ad0, ad1;
          const int b0 = take(rdy0, SZ_PART, ad0), b1 = take(false, SZ_PART, ad1);
          probe1();
#pragma unroll
          for (int i = 0; i < 20; i++)
            lds128(sbase + ((i < 10 ? ad0 : ad1) - ring16 + img0) * 16 + ((i % 10) >> 1) * 8192 + (i & 1) * 512, t[4 * i], t[4 * i + 1], t[4 * i + 2], t[4 * i + 3]);
          fence_regs(t);
          wg_wait<0>();
          fence_regs(c);
          release(prev);
          release(b0); release(b1);
#pragma unroll
          for (int i = 0; i < 80; i++) c[i] += __uint_as_float(t[i]);
        } else {
          wg_wait<0>();
          fence_regs(c);
          release(prev);
        }
        if (op & F_LAZY) {
#pragma unroll
          for (int i = 0; i < 48; i++) q[i] = __float_as_uint(c[i]);
          pend = part + img0;
#pragma unroll
          for (int i = 12; i < 20; i++)
            stg128_hint(pend + (i >> 1) * 512 + (i & 1) * 32, __float_as_uint(c[4 * i]), __float_as_uint(c[4 * i + 1]),
                        __float_as_uint(c[4 * i + 2]), __float_as_uint(c[4 * i + 3]), spol);
          continue;
        }
        if (op & F_ST) {
#pragma unroll
          for (int i = 0; i < 20; i++)
            stg128(part + (i >> 1) * 512 + (i & 1) * 32 + img0, __float_as_uint(c[4 * i]), __float_as_uint(c[4 * i + 1]),
                   __float_as_uint(c[4 * i + 2]), __float_as_uint(c[4 * i + 3]));
        } else {
          asm volatile("barrier.cluster.arrive.relaxed;" ::: "memory");
          bar_sync(1, 256);
          const uint32_t wstage = sbase + (wg * 4 + warp) * 5120;
          const uint32_t sa = wstage + (lane & 15) * 64;
#pragma unroll
          for (int i = 0; i < 10; i++) {
            const int u = (i & 1) * 2 + (lane >> 4);
            stsm4(sa + (i >> 1) * 1024 + ((u ^ ((lane >> 1) & 3)) << 4), pack_bf16(c[8 * i], c[8 * i + 1]), pack_bf16(c[8 * i + 2], c[8 * i + 3]),
                  pack_bf16(c[8 * i + 4], c[8 * i + 5]), pack_bf16(c[8 * i + 6], c[8 * i + 7]));
          }
          asm volatile("fence.proxy.async.shared::cta;" ::: "memory");
          __syncwarp();
          if (lane == 0) {
            tma3d_store(&P.out, wstage, 0, (team & 7) * kSq + rank * 128 + wg * 64 + warp * 16, blk * 20 + nt * 5);
            asm volatile("cp.async.bulk.commit_group;\ncp.async.bulk.wait_group.read 0;" ::: "memory");
          }
          __syncwarp();
          break;
        }
#pragma unroll
        for (int i = 0; i < 48; i++) q[i] = 0;
      }
    }
    if (P.dbg == 0xffffffffu) g_seen[0] = keep;
    asm volatile("barrier.cluster.wait;" ::: "memory");
  }
}

typedef CUresult (*EncodeFn)(CUtensorMap*, CUtensorMapDataType, cuuint32_t, void*, const cuuint64_t*, const cuuint64_t*,
                             const cuuint32_t*, const cuuint32_t*, CUtensorMapInterleave, CUtensorMapSwizzle,
                             CUtensorMapL2promotion, CUtensorMapFloatOOBfill);

void encode(EncodeFn fn, CUtensorMap* m, const void* ptr, int rank, const cuuint64_t* dims, const cuuint64_t* strides,
            const cuuint32_t* box, CUtensorMapSwizzle swz) {
  const cuuint32_t es[5] = {1, 1, 1, 1, 1};
  CUresult r = fn(m, CU_TENSOR_MAP_DATA_TYPE_BFLOAT16, rank, const_cast<void*>(ptr), dims, strides, box, es,
                  CU_TENSOR_MAP_INTERLEAVE_NONE, swz, CU_TENSOR_MAP_L2_PROMOTION_L2_128B, CU_TENSOR_MAP_FLOAT_OOB_FILL_NONE);
  if (r != CUDA_SUCCESS) fprintf(stderr, "cuTensorMapEncodeTiled failed: %d\n", (int)r);
}

void annotate(uint32_t* ops, int n, bool helper) {
  uint32_t items = 0, cur = 0, pend = 0;
  auto item = [&](uint32_t bytes, int count) {
    for (int i = 0; i < count; i++) { if (cur + bytes > RING) cur = 0; cur += bytes; items++; }
  };
  for (int i = 0; i <= n; i++) {
    const uint32_t op = ops[i];
    ops[i] |= (items % NBAR) << 15 | ((items / NBAR) & 1) << 19 | (cur >> 12) << 20 | pend << 26;
    if ((op & 3) == OP_Q) { item(SZ_Q, 10); pend = (op & F_PARK) ? (helper ? 1 : 2) : 0; }
    if ((op & 3) == OP_A) {
      item(SZ_KV, (op & F_PARK) ? 30 : 31);
      if ((ops[i + 1] & 3) == OP_A) { item(SZ_PARK, 1); item(SZ_KV, 1); }
      item(SZ_KV, 1);
      pend = 1;
    }
    if ((op & 3) == OP_O) {
      item(SZ_O, 12 * (((op >> 5) & 15) - ((op >> 2) & 7)));
      if (op & F_LD) item(SZ_PART, 2);
      pend = (op & F_LAZY) ? (helper ? 1 : 2) : 0;
    }
  }
}

void compile_programs(const char* const* text, bool helpers, Params& P) {
  struct Req { int when, team, wave, slot; } req[N_TEAM * MAX_PARK];
  int n_req = 0;
  for (int t = 0; t < N_TEAM; t++) {
    uint32_t* ops = P.ops[t];
    int n = 0, flags[8] = {0, 0, 0, 0, 0, 0, 0, 0}, n_park = 0, last_o = -1, when = 0, given = 0;
    for (const char* s = text[t]; *s; s++) {
      const int a = s[1] - '0';
      if (*s == 'Q' || (*s == 'H' && !helpers)) { ops[n++] = OP_Q | a << 2; when += 10; }
      else if (*s == 'P') { flags[a] = F_PARK | n_park++ << 10; ops[n++] = OP_Q | a << 2 | flags[a]; when += 10; }
      else if (*s == 'H') { req[n_req++] = {when, t, a, n_park}; flags[a] = F_PARK | F_HELP | n_park++ << 10; }
      else if (*s == 'A') { ops[n++] = OP_A | a << 2 | flags[a]; when += 32; }
      else if (*s == 'G') { given = a; if (helpers) req[n_req++] = {1000, t, 0, -a}; }
      else if (*s == 'O') {
        ops[n] = OP_O | a << 2 | (s[2] - '0') << 5;
        if (given) ops[n] = helpers ? ops[n] | F_LD | F_PARK | (MAX_PARK - 1) << 10 : ops[n] & ~(7u << 2);
        if (last_o >= 0) { ops[last_o] |= F_ST; ops[n] |= F_LD; }
        last_o = n++;
        when += 10 * (s[2] - s[1]);
      }
    }
    for (int i = 0; i + 1 < n; i++)
      if ((ops[i] & 3) == OP_O && (ops[i] & F_ST) && (ops[i + 1] & 3) == OP_Q) ops[i] |= F_LAZY;
    for (int i = n; i < MAX_OPS; i++) ops[i] = OP_END;
    annotate(ops, n, false);
    for (int i = 0; i < n; i++) {
      if ((ops[i] & 3) != OP_A && (P.dbg & 8)) ops[i + 1] |= F_SOON;
      if ((ops[i] & 3) != OP_A) continue;
      const int w = (ops[i] >> 2) & 7;
      int dist = 0;
      for (int j = i + 1; j < n; j++) {
        const int a = (ops[j] >> 2) & 7, b = (ops[j] >> 5) & 15;
        if ((ops[j] & 3) == OP_O && w < b) {
          for (int k = 0; k < b - a && o_wave(a, b, k, (P.dbg >> 4) & 7) != w; k++) dist += 10;
          break;
        }
        dist += (ops[j] & 3) == OP_Q ? 10 : (ops[j] & 3) == OP_A ? 32 : 10 * (b - a);
      }
      if (dist <= (int)((P.dbg >> 8) & 255)) ops[i + 1] |= F_SOON;
    }
  }
  for (int i = 1; i < n_req; i++)
    for (int j = i; j > 0 && req[j].when < req[j - 1].when; j--) { Req r = req[j]; req[j] = req[j - 1]; req[j - 1] = r; }
  for (int h = 0; h < N_HELP; h++) {
    uint32_t* ops = P.ops[N_TEAM + 2 * h];
    int n = 0;
    for (int i = 0; i < n_req; i++)
      for (int m = h; m < 4; m += N_HELP) {
        const uint32_t ro = 4 * req[i].team + m;
        ops[n++] = req[i].slot >= 0 ? OP_Q | req[i].wave << 2 | req[i].team << 5 | F_PARK | req[i].slot << 10 | m << 12
                                    : OP_O | -req[i].slot << 5 | F_ST | F_LAZY | F_SOON | (ro & 7) << 9 | (ro >> 3) << 29;
      }
    for (int i = n; i < 2 * MAX_OPS; i++) ops[i] = OP_END | F_SOON;
    annotate(ops, n, true);
  }
  for (int i = 0; i < 32; i++) P.first[i] = i < N_TEAM ? P.ops[i][0] : i < N_TEAM + N_HELP ? P.ops[2 * i - N_TEAM][0] : 0;
}

const char* const kPrograms[N_TEAM] = {
  "Q0A0Q1A1H2A2O03Q3A3Q4A4Q5A5Q6A6Q7A7O38",
  "Q0A0Q1A1Q2A2H3A3Q4A4O03Q5A5Q6A6Q7A7O38",
  "Q0A0H1A1Q2A2Q3A3O04Q4A4Q5A5Q6A6Q7A7O48",
  "Q0A0Q1A1Q2A2Q3A3O02Q4A4Q5A5Q6A6H7A7O28",
  "Q0A0Q1A1Q2A2O03Q3A3Q4A4Q5A5Q6A6H7A7O38",
  "Q0A0Q1A1Q2A2Q3A3Q4A4O05Q5A5Q6A6H7A7O58",
  "Q0A0Q1A1Q2A2Q3A3Q4A4O05Q5A5Q6A6H7A7O58",
  "Q0A0Q1A1Q2A2O03Q3A3Q4A4H5A5Q6A6Q7A7O38",
  "P7Q0A0Q1A1O01Q2A2H3A3Q4A4Q5A5Q6A6A7O18",
  "P3P5Q0A0Q1A1Q2A2A3Q4A4A5H6A6Q7A7O08",
  "P7Q0A0Q1A1Q2A2Q3A3H4A4Q5A5Q6A6A7O08",
  "P3P7Q0A0Q1A1H2A2A3Q4A4Q5A5Q6A6A7O08",
  "Q0A0Q1A1Q2A2O01Q3A3Q4A4H5A5Q6A6Q7A7O18",
  "P3Q0A0Q1A1Q2A2A3Q4A4Q5A5Q6A6Q7A7G1O18",
  "P6Q0A0Q1A1Q2A2Q3A3Q4A4Q5A5A6Q7A7G1O18",
  "P2P6Q0A0Q1A1A2Q3A3H4A4Q5A5A6Q7A7O08",
};

const char* const* bench_programs() {
  return kPrograms;
}

}

extern "C" void kernel_launch(void* const* d_in, const int* in_sizes, int n_in, void* d_out, int out_size) {
  (void)in_sizes; (void)n_in; (void)out_size;
  static EncodeFn fn = nullptr;
  static int n_clusters = 0;
  if (!fn) {
    cudaDriverEntryPointQueryResult qr;
    void* f = nullptr;
    cudaGetDriverEntryPoint("cuTensorMapEncodeTiled", &f, cudaEnableDefault, &qr);
    fn = (EncodeFn)f;
    cudaFuncSetAttribute(fused_kernel, cudaFuncAttributeMaxDynamicSharedMemorySize, SMEM_BYTES);
    cudaLaunchConfig_t cfg = {};
    cfg.gridDim = dim3(132); cfg.blockDim = dim3(384); cfg.dynamicSmemBytes = SMEM_BYTES;
    cudaLaunchAttribute at[1];
    at[0].id = cudaLaunchAttributeClusterDimension; at[0].val.clusterDim.x = 2; at[0].val.clusterDim.y = 1; at[0].val.clusterDim.z = 1;
    cfg.attrs = at; cfg.numAttrs = 1;
    if (cudaOccupancyMaxActiveClusters(&n_clusters, fused_kernel, &cfg) != cudaSuccess || n_clusters < 1) n_clusters = 1;
    (void)cudaGetLastError();
  }
  Params P;
  const CUtensorMapSwizzle S128 = CU_TENSOR_MAP_SWIZZLE_128B, S64 = CU_TENSOR_MAP_SWIZZLE_64B;
  for (int blk = 0; blk < 2; blk++) {
    void* const* in = d_in + 5 * blk;
    { const cuuint64_t d[] = {kD, kB * kSq}, s[] = {kD * 2}; const cuuint32_t b[] = {64, 128};
      encode(fn, &P.x[blk], in[0], 2, d, s, b, S128); }
    { const cuuint64_t d[] = {64, 8, 3, (cuuint64_t)kB * kH * kSk / 8}, s[] = {kDh * 2, 128, 8 * kDh * 2}; const cuuint32_t b[] = {64, 8, 3, 8};
      encode(fn, &P.k[blk], in[1], 4, d, s, b, S128);
      encode(fn, &P.v[blk], in[2], 4, d, s, b, S128); }
    { const cuuint64_t d[] = {64, kD, kHD / 64}, s[] = {kHD * 2, 128}; const cuuint32_t b[] = {64, 64, 3};
      encode(fn, &P.wq[blk], in[3], 3, d, s, b, S128); }
    { const cuuint64_t d[] = {32, 2, kHD / 8, 4, kD / 32}, s[] = {kD * 2, 8 * kD * 2, 2 * kD * 2, 64}; const cuuint32_t b[] = {32, 2, 4, 4, 5};
      encode(fn, &P.wo[blk], in[4], 5, d, s, b, S64); }
  }
  { const cuuint64_t d[] = {32, kB * kSq, 2 * kD / 32}, s[] = {2 * kD * 2, 64}; const cuuint32_t b[] = {32, 16, 5};
    encode(fn, &P.out, d_out, 3, d, s, b, S64); }

  P.dbg = 0x5030;
  for (int w = 0; w < 8; w++) P.slot[w] = (P.dbg >> 16) & 15 ? w % ((P.dbg >> 16) & 15) : w;
  if (n_clusters >= N_CL) {
    const bool helpers = n_clusters >= N_CL + N_HELP;
    compile_programs(bench_programs(), helpers, P);
    fused_kernel<<<2 * (N_CL + (helpers ? N_HELP : 0)), 384, SMEM_BYTES>>>(P);
  } else {
    for (int phase = 0; phase < 2; phase++) {
      const char* text[N_TEAM];
      for (int t = 0; t < N_TEAM; t++) text[t] = phase ? "O08" : "Q0A0Q1A1Q2A2Q3A3Q4A4Q5A5Q6A6Q7A7";
      compile_programs(text, false, P);
      fused_kernel<<<2 * N_CL, 384, SMEM_BYTES>>>(P);
    }
  }
}
```

```cpp
#include <cuda_runtime.h>
#include <cuda_bf16.h>
#include <cuda.h>
#include <stdint.h>
#include <stdio.h>

namespace {

constexpr int kB = 8, kSq = 256, kD = 640, kH = 32, kSk = 1024, kDh = 192;
constexpr int kHD = kH * kDh;
#define S1A 8
#define UC0 2
#define UC1 5
#define RING_KB 224
constexpr uint32_t RING = RING_KB * 1024;
constexpr uint32_t SZ_KV = 24576;
constexpr uint32_t SZ_Q = 16384 + 24576;
constexpr uint32_t SZ_O = 16384 + 20480;
constexpr uint32_t SZ_PARK = 24576;
constexpr uint32_t SZ_PART = 40960;
constexpr int NBAR = 10;
constexpr int EARLY = 3;
constexpr uint32_t KV_CH = 64, KV_SBO = 3072;
constexpr int SMEM_BYTES = RING + 512 + 1024;
constexpr int N_TEAM = 16, N_CL = 64, N_HELP = 2, MAX_OPS = 24, MAX_PARK = 4;
enum { OP_END = 0, OP_Q = 1, OP_A = 2, OP_O = 3, F_PARK = 1 << 9, F_LD = 1 << 12, F_ST = 1 << 13, F_LAZY = 1 << 14, F_HELP = 1 << 12, F_SOON = 1 << 28 };

struct alignas(64) Params {
  uint32_t first[32];
  CUtensorMap x[2], wq[2], k[2], v[2], wo[2], out;
  uint32_t ops[N_TEAM + 2 * N_HELP][MAX_OPS];
  uint32_t zero;
  uint32_t slot[8];
  uint32_t dbg;
};

__device__ uint4 g_o[N_TEAM * 2 * 96 * 1024];
__device__ uint4 g_park[N_CL * 2 * MAX_PARK * 12 * 256];
__device__ uint4 g_part[N_CL * 2 * 5 * 1024];
__device__ unsigned int g_done[N_TEAM * 2 * 8];
__device__ unsigned int g_help[N_CL * 2 * MAX_PARK];
__device__ unsigned int g_seen[N_TEAM * 2 * 8];

template <int TB, int TA = 0>
__device__ __forceinline__ void wgmma_ss_n64(float (&d)[32], uint64_t da, uint64_t db, int scale_d) {
  asm volatile("{\n.reg .pred p;\nsetp.ne.b32 p, %34, 0;\n"
    "wgmma.mma_async.sync.aligned.m64n64k16.f32.bf16.bf16 {%0, %1, %2, %3, %4, %5, %6, %7, %8, %9, %10, %11, %12, %13, %14, %15, %16, %17, %18, %19, %20, %21, %22, %23, %24, %25, %26, %27, %28, %29, %30, %31}, %32, %33, p, 1, 1, %35, %36;\n}\n"
    : "+f"(d[0]), "+f"(d[1]), "+f"(d[2]), "+f"(d[3]), "+f"(d[4]), "+f"(d[5]), "+f"(d[6]), "+f"(d[7]), "+f"(d[8]), "+f"(d[9]), "+f"(d[10]), "+f"(d[11]), "+f"(d[12]), "+f"(d[13]), "+f"(d[14]), "+f"(d[15]), "+f"(d[16]), "+f"(d[17]), "+f"(d[18]), "+f"(d[19]), "+f"(d[20]), "+f"(d[21]), "+f"(d[22]), "+f"(d[23]), "+f"(d[24]), "+f"(d[25]), "+f"(d[26]), "+f"(d[27]), "+f"(d[28]), "+f"(d[29]), "+f"(d[30]), "+f"(d[31])
    : "l"(da), "l"(db), "r"(scale_d), "n"(TA), "n"(TB));
}
template <int TB>
__device__ __forceinline__ void wgmma_rs_n64(float (&d)[32], uint32_t a0, uint32_t a1, uint32_t a2, uint32_t a3, uint64_t db, int scale_d) {
  asm volatile("{\n.reg .pred p;\nsetp.ne.b32 p, %37, 0;\n"
    "wgmma.mma_async.sync.aligned.m64n64k16.f32.bf16.bf16 {%0, %1, %2, %3, %4, %5, %6, %7, %8, %9, %10, %11, %12, %13, %14, %15, %16, %17, %18, %19, %20, %21, %22, %23, %24, %25, %26, %27, %28, %29, %30, %31}, {%32, %33, %34, %35}, %36, p, 1, 1, %38;\n}\n"
    : "+f"(d[0]), "+f"(d[1]), "+f"(d[2]), "+f"(d[3]), "+f"(d[4]), "+f"(d[5]), "+f"(d[6]), "+f"(d[7]), "+f"(d[8]), "+f"(d[9]), "+f"(d[10]), "+f"(d[11]), "+f"(d[12]), "+f"(d[13]), "+f"(d[14]), "+f"(d[15]), "+f"(d[16]), "+f"(d[17]), "+f"(d[18]), "+f"(d[19]), "+f"(d[20]), "+f"(d[21]), "+f"(d[22]), "+f"(d[23]), "+f"(d[24]), "+f"(d[25]), "+f"(d[26]), "+f"(d[27]), "+f"(d[28]), "+f"(d[29]), "+f"(d[30]), "+f"(d[31])
    : "r"(a0), "r"(a1), "r"(a2), "r"(a3), "l"(db), "r"(scale_d), "n"(TB));
}
template <int TB, int TA = 0>
__device__ __forceinline__ void wgmma_ss_n160(float (&d)[80], uint64_t da, uint64_t db, int scale_d) {
  asm volatile("{\n.reg .pred p;\nsetp.ne.b32 p, %82, 0;\n"
    "wgmma.mma_async.sync.aligned.m64n160k16.f32.bf16.bf16 {%0, %1, %2, %3, %4, %5, %6, %7, %8, %9, %10, %11, %12, %13, %14, %15, %16, %17, %18, %19, %20, %21, %22, %23, %24, %25, %26, %27, %28, %29, %30, %31, %32, %33, %34, %35, %36, %37, %38, %39, %40, %41, %42, %43, %44, %45, %46, %47, %48, %49, %50, %51, %52, %53, %54, %55, %56, %57, %58, %59, %60, %61, %62, %63, %64, %65, %66, %67, %68, %69, %70, %71, %72, %73, %74, %75, %76, %77, %78, %79}, %80, %81, p, 1, 1, %83, %84;\n}\n"
    : "+f"(d[0]), "+f"(d[1]), "+f"(d[2]), "+f"(d[3]), "+f"(d[4]), "+f"(d[5]), "+f"(d[6]), "+f"(d[7]), "+f"(d[8]), "+f"(d[9]), "+f"(d[10]), "+f"(d[11]), "+f"(d[12]), "+f"(d[13]), "+f"(d[14]), "+f"(d[15]), "+f"(d[16]), "+f"(d[17]), "+f"(d[18]), "+f"(d[19]), "+f"(d[20]), "+f"(d[21]), "+f"(d[22]), "+f"(d[23]), "+f"(d[24]), "+f"(d[25]), "+f"(d[26]), "+f"(d[27]), "+f"(d[28]), "+f"(d[29]), "+f"(d[30]), "+f"(d[31]), "+f"(d[32]), "+f"(d[33]), "+f"(d[34]), "+f"(d[35]), "+f"(d[36]), "+f"(d[37]), "+f"(d[38]), "+f"(d[39]), "+f"(d[40]), "+f"(d[41]), "+f"(d[42]), "+f"(d[43]), "+f"(d[44]), "+f"(d[45]), "+f"(d[46]), "+f"(d[47]), "+f"(d[48]), "+f"(d[49]), "+f"(d[50]), "+f"(d[51]), "+f"(d[52]), "+f"(d[53]), "+f"(d[54]), "+f"(d[55]), "+f"(d[56]), "+f"(d[57]), "+f"(d[58]), "+f"(d[59]), "+f"(d[60]), "+f"(d[61]), "+f"(d[62]), "+f"(d[63]), "+f"(d[64]), "+f"(d[65]), "+f"(d[66]), "+f"(d[67]), "+f"(d[68]), "+f"(d[69]), "+f"(d[70]), "+f"(d[71]), "+f"(d[72]), "+f"(d[73]), "+f"(d[74]), "+f"(d[75]), "+f"(d[76]), "+f"(d[77]), "+f"(d[78]), "+f"(d[79])
    : "l"(da), "l"(db), "r"(scale_d), "n"(TA), "n"(TB));
}
template <int TB>
__device__ __forceinline__ void wgmma_rs_n160(float (&d)[80], uint32_t a0, uint32_t a1, uint32_t a2, uint32_t a3, uint64_t db, int scale_d) {
  asm volatile("{\n.reg .pred p;\nsetp.ne.b32 p, %85, 0;\n"
    "wgmma.mma_async.sync.aligned.m64n160k16.f32.bf16.bf16 {%0, %1, %2, %3, %4, %5, %6, %7, %8, %9, %10, %11, %12, %13, %14, %15, %16, %17, %18, %19, %20, %21, %22, %23, %24, %25, %26, %27, %28, %29, %30, %31, %32, %33, %34, %35, %36, %37, %38, %39, %40, %41, %42, %43, %44, %45, %46, %47, %48, %49, %50, %51, %52, %53, %54, %55, %56, %57, %58, %59, %60, %61, %62, %63, %64, %65, %66, %67, %68, %69, %70, %71, %72, %73, %74, %75, %76, %77, %78, %79}, {%80, %81, %82, %83}, %84, p, 1, 1, %86;\n}\n"
    : "+f"(d[0]), "+f"(d[1]), "+f"(d[2]), "+f"(d[3]), "+f"(d[4]), "+f"(d[5]), "+f"(d[6]), "+f"(d[7]), "+f"(d[8]), "+f"(d[9]), "+f"(d[10]), "+f"(d[11]), "+f"(d[12]), "+f"(d[13]), "+f"(d[14]), "+f"(d[15]), "+f"(d[16]), "+f"(d[17]), "+f"(d[18]), "+f"(d[19]), "+f"(d[20]), "+f"(d[21]), "+f"(d[22]), "+f"(d[23]), "+f"(d[24]), "+f"(d[25]), "+f"(d[26]), "+f"(d[27]), "+f"(d[28]), "+f"(d[29]), "+f"(d[30]), "+f"(d[31]), "+f"(d[32]), "+f"(d[33]), "+f"(d[34]), "+f"(d[35]), "+f"(d[36]), "+f"(d[37]), "+f"(d[38]), "+f"(d[39]), "+f"(d[40]), "+f"(d[41]), "+f"(d[42]), "+f"(d[43]), "+f"(d[44]), "+f"(d[45]), "+f"(d[46]), "+f"(d[47]), "+f"(d[48]), "+f"(d[49]), "+f"(d[50]), "+f"(d[51]), "+f"(d[52]), "+f"(d[53]), "+f"(d[54]), "+f"(d[55]), "+f"(d[56]), "+f"(d[57]), "+f"(d[58]), "+f"(d[59]), "+f"(d[60]), "+f"(d[61]), "+f"(d[62]), "+f"(d[63]), "+f"(d[64]), "+f"(d[65]), "+f"(d[66]), "+f"(d[67]), "+f"(d[68]), "+f"(d[69]), "+f"(d[70]), "+f"(d[71]), "+f"(d[72]), "+f"(d[73]), "+f"(d[74]), "+f"(d[75]), "+f"(d[76]), "+f"(d[77]), "+f"(d[78]), "+f"(d[79])
    : "r"(a0), "r"(a1), "r"(a2), "r"(a3), "l"(db), "r"(scale_d), "n"(TB));
}
template <int TB, int TA = 0>
__device__ __forceinline__ void wgmma_ss_n192(float (&d)[96], uint64_t da, uint64_t db, int scale_d) {
  asm volatile("{\n.reg .pred p;\nsetp.ne.b32 p, %98, 0;\n"
    "wgmma.mma_async.sync.aligned.m64n192k16.f32.bf16.bf16 {%0, %1, %2, %3, %4, %5, %6, %7, %8, %9, %10, %11, %12, %13, %14, %15, %16, %17, %18, %19, %20, %21, %22, %23, %24, %25, %26, %27, %28, %29, %30, %31, %32, %33, %34, %35, %36, %37, %38, %39, %40, %41, %42, %43, %44, %45, %46, %47, %48, %49, %50, %51, %52, %53, %54, %55, %56, %57, %58, %59, %60, %61, %62, %63, %64, %65, %66, %67, %68, %69, %70, %71, %72, %73, %74, %75, %76, %77, %78, %79, %80, %81, %82, %83, %84, %85, %86, %87, %88, %89, %90, %91, %92, %93, %94, %95}, %96, %97, p, 1, 1, %99, %100;\n}\n"
    : "+f"(d[0]), "+f"(d[1]), "+f"(d[2]), "+f"(d[3]), "+f"(d[4]), "+f"(d[5]), "+f"(d[6]), "+f"(d[7]), "+f"(d[8]), "+f"(d[9]), "+f"(d[10]), "+f"(d[11]), "+f"(d[12]), "+f"(d[13]), "+f"(d[14]), "+f"(d[15]), "+f"(d[16]), "+f"(d[17]), "+f"(d[18]), "+f"(d[19]), "+f"(d[20]), "+f"(d[21]), "+f"(d[22]), "+f"(d[23]), "+f"(d[24]), "+f"(d[25]), "+f"(d[26]), "+f"(d[27]), "+f"(d[28]), "+f"(d[29]), "+f"(d[30]), "+f"(d[31]), "+f"(d[32]), "+f"(d[33]), "+f"(d[34]), "+f"(d[35]), "+f"(d[36]), "+f"(d[37]), "+f"(d[38]), "+f"(d[39]), "+f"(d[40]), "+f"(d[41]), "+f"(d[42]), "+f"(d[43]), "+f"(d[44]), "+f"(d[45]), "+f"(d[46]), "+f"(d[47]), "+f"(d[48]), "+f"(d[49]), "+f"(d[50]), "+f"(d[51]), "+f"(d[52]), "+f"(d[53]), "+f"(d[54]), "+f"(d[55]), "+f"(d[56]), "+f"(d[57]), "+f"(d[58]), "+f"(d[59]), "+f"(d[60]), "+f"(d[61]), "+f"(d[62]), "+f"(d[63]), "+f"(d[64]), "+f"(d[65]), "+f"(d[66]), "+f"(d[67]), "+f"(d[68]), "+f"(d[69]), "+f"(d[70]), "+f"(d[71]), "+f"(d[72]), "+f"(d[73]), "+f"(d[74]), "+f"(d[75]), "+f"(d[76]), "+f"(d[77]), "+f"(d[78]), "+f"(d[79]), "+f"(d[80]), "+f"(d[81]), "+f"(d[82]), "+f"(d[83]), "+f"(d[84]), "+f"(d[85]), "+f"(d[86]), "+f"(d[87]), "+f"(d[88]), "+f"(d[89]), "+f"(d[90]), "+f"(d[91]), "+f"(d[92]), "+f"(d[93]), "+f"(d[94]), "+f"(d[95])
    : "l"(da), "l"(db), "r"(scale_d), "n"(TA), "n"(TB));
}
template <int TB>
__device__ __forceinline__ void wgmma_rs_n192(float (&d)[96], uint32_t a0, uint32_t a1, uint32_t a2, uint32_t a3, uint64_t db, int scale_d) {
  asm volatile("{\n.reg .pred p;\nsetp.ne.b32 p, %101, 0;\n"
    "wgmma.mma_async.sync.aligned.m64n192k16.f32.bf16.bf16 {%0, %1, %2, %3, %4, %5, %6, %7, %8, %9, %10, %11, %12, %13, %14, %15, %16, %17, %18, %19, %20, %21, %22, %23, %24, %25, %26, %27, %28, %29, %30, %31, %32, %33, %34, %35, %36, %37, %38, %39, %40, %41, %42, %43, %44, %45, %46, %47, %48, %49, %50, %51, %52, %53, %54, %55, %56, %57, %58, %59, %60, %61, %62, %63, %64, %65, %66, %67, %68, %69, %70, %71, %72, %73, %74, %75, %76, %77, %78, %79, %80, %81, %82, %83, %84, %85, %86, %87, %88, %89, %90, %91, %92, %93, %94, %95}, {%96, %97, %98, %99}, %100, p, 1, 1, %102;\n}\n"
    : "+f"(d[0]), "+f"(d[1]), "+f"(d[2]), "+f"(d[3]), "+f"(d[4]), "+f"(d[5]), "+f"(d[6]), "+f"(d[7]), "+f"(d[8]), "+f"(d[9]), "+f"(d[10]), "+f"(d[11]), "+f"(d[12]), "+f"(d[13]), "+f"(d[14]), "+f"(d[15]), "+f"(d[16]), "+f"(d[17]), "+f"(d[18]), "+f"(d[19]), "+f"(d[20]), "+f"(d[21]), "+f"(d[22]), "+f"(d[23]), "+f"(d[24]), "+f"(d[25]), "+f"(d[26]), "+f"(d[27]), "+f"(d[28]), "+f"(d[29]), "+f"(d[30]), "+f"(d[31]), "+f"(d[32]), "+f"(d[33]), "+f"(d[34]), "+f"(d[35]), "+f"(d[36]), "+f"(d[37]), "+f"(d[38]), "+f"(d[39]), "+f"(d[40]), "+f"(d[41]), "+f"(d[42]), "+f"(d[43]), "+f"(d[44]), "+f"(d[45]), "+f"(d[46]), "+f"(d[47]), "+f"(d[48]), "+f"(d[49]), "+f"(d[50]), "+f"(d[51]), "+f"(d[52]), "+f"(d[53]), "+f"(d[54]), "+f"(d[55]), "+f"(d[56]), "+f"(d[57]), "+f"(d[58]), "+f"(d[59]), "+f"(d[60]), "+f"(d[61]), "+f"(d[62]), "+f"(d[63]), "+f"(d[64]), "+f"(d[65]), "+f"(d[66]), "+f"(d[67]), "+f"(d[68]), "+f"(d[69]), "+f"(d[70]), "+f"(d[71]), "+f"(d[72]), "+f"(d[73]), "+f"(d[74]), "+f"(d[75]), "+f"(d[76]), "+f"(d[77]), "+f"(d[78]), "+f"(d[79]), "+f"(d[80]), "+f"(d[81]), "+f"(d[82]), "+f"(d[83]), "+f"(d[84]), "+f"(d[85]), "+f"(d[86]), "+f"(d[87]), "+f"(d[88]), "+f"(d[89]), "+f"(d[90]), "+f"(d[91]), "+f"(d[92]), "+f"(d[93]), "+f"(d[94]), "+f"(d[95])
    : "r"(a0), "r"(a1), "r"(a2), "r"(a3), "l"(db), "r"(scale_d), "n"(TB));
}

__device__ __forceinline__ uint32_t smem_u32(const void* p) { return (uint32_t)__cvta_generic_to_shared(p); }
__device__ __forceinline__ void wg_fence() { asm volatile("wgmma.fence.sync.aligned;" ::: "memory"); }
__device__ __forceinline__ void wg_commit() { asm volatile("wgmma.commit_group.sync.aligned;" ::: "memory"); }
template <int N> __device__ __forceinline__ void wg_wait() { asm volatile("wgmma.wait_group.sync.aligned %0;" ::"n"(N) : "memory"); }
__device__ __forceinline__ void sched_fence(uint32_t& keep) {
  asm volatile("{\n.reg .u32 c;\nmov.u32 c, %%clock;\nxor.b32 %0, %0, c;\n}\n" : "+r"(keep)::"memory");
}
template <int N> __device__ __forceinline__ void fence_regs(float (&r)[N]) {
#pragma unroll
  for (int i = 0; i < N; i++) asm volatile("" : "+f"(r[i])::"memory");
}
template <int N> __device__ __forceinline__ void fence_regs(uint32_t (&r)[N]) {
#pragma unroll
  for (int i = 0; i < N; i++) asm volatile("" : "+r"(r[i])::"memory");
}
__device__ __forceinline__ uint64_t mk_desc(uint32_t a16, uint32_t lbo, uint32_t sbo, uint32_t swz) {
  uint64_t d;
  asm("mov.b64 %0, {%1, %2};" : "=l"(d) : "r"(a16 + ((lbo >> 4) << 16)), "r"((sbo >> 4) | (swz << 30)));
  return d;
}
__device__ __forceinline__ void mbar_init(uint32_t bar, uint32_t cnt) {
  asm volatile("mbarrier.init.shared::cta.b64 [%0], %1;" ::"r"(bar), "r"(cnt) : "memory");
}
__device__ __forceinline__ void mbar_expect(uint32_t bar, uint32_t tx) {
  asm volatile("mbarrier.arrive.expect_tx.shared::cta.b64 _, [%0], %1;" ::"r"(bar), "r"(tx) : "memory");
}
__device__ __forceinline__ bool mbar_test(uint32_t bar, uint32_t ph) {
  uint32_t ok;
  asm volatile("{\n.reg .pred p;\nmbarrier.test_wait.parity.shared::cta.b64 p, [%1], %2;\nselp.u32 %0, 1, 0, p;\n}\n"
               : "=r"(ok) : "r"(bar), "r"(ph) : "memory");
  return ok;
}
__device__ __forceinline__ void mbar_wait(uint32_t bar, uint32_t ph) {
  asm volatile("{\n.reg .pred p;\n.reg .u32 n;\n"
               "mbarrier.try_wait.parity.shared::cta.b64 p, [%0], %1;\n@p bra DONE;\n"
               "mov.u32 n, 0;\n"
               "LOOP:\nmbarrier.try_wait.parity.shared::cta.b64 p, [%0], %1;\n@p bra DONE;\n"
               "add.u32 n, n, 1;\nsetp.lt.u32 p, n, 0x1000000;\n@p bra LOOP;\ntrap;\n"
               "DONE:\n}\n" ::"r"(bar), "r"(ph) : "memory");
}
template <int NS> __device__ __forceinline__ void mbar_wait_slow(uint32_t bar, uint32_t ph) {
  asm volatile("{\n.reg .pred p;\n.reg .u32 n;\nmov.u32 n, 0;\n"
               "LOOP:\nmbarrier.test_wait.parity.shared::cta.b64 p, [%0], %1;\n@p bra DONE;\n"
               "nanosleep.u32 %2;\nadd.u32 n, n, 1;\nsetp.lt.u32 p, n, 0x400000;\n@p bra LOOP;\ntrap;\n"
               "DONE:\n}\n" ::"r"(bar), "r"(ph), "n"(NS) : "memory");
}
__device__ __forceinline__ void mbar_arrive_cluster_if(bool on, uint32_t addr) {
  asm volatile("{\n.reg .pred p;\nsetp.ne.b32 p, %1, 0;\n@p mbarrier.arrive.shared::cluster.b64 _, [%0];\n}\n" ::"r"(addr), "r"((int)on) : "memory");
}
__device__ __forceinline__ void mbar_arrive_if(bool on, uint32_t addr) {
  asm volatile("{\n.reg .pred p;\nsetp.ne.b32 p, %1, 0;\n@p mbarrier.arrive.shared::cta.b64 _, [%0];\n}\n" ::"r"(addr), "r"((int)on) : "memory");
}
__device__ __forceinline__ void tma2d(uint32_t dst, const CUtensorMap* m, uint32_t bar, int c0, int c1) {
  asm volatile("cp.async.bulk.tensor.2d.shared::cluster.global.mbarrier::complete_tx::bytes [%0], [%1, {%3, %4}], [%2];"
               ::"r"(dst), "l"(m), "r"(bar), "r"(c0), "r"(c1) : "memory");
}
__device__ __forceinline__ void tma3d(uint32_t dst, const CUtensorMap* m, uint32_t bar, int c0, int c1, int c2) {
  asm volatile("cp.async.bulk.tensor.3d.shared::cluster.global.mbarrier::complete_tx::bytes [%0], [%1, {%3, %4, %5}], [%2];"
               ::"r"(dst), "l"(m), "r"(bar), "r"(c0), "r"(c1), "r"(c2) : "memory");
}
__device__ __forceinline__ void tma3d_mc(uint32_t dst, const CUtensorMap* m, uint32_t bar, int c0, int c1, int c2) {
  asm volatile("cp.async.bulk.tensor.3d.shared::cluster.global.mbarrier::complete_tx::bytes.multicast::cluster"
               " [%0], [%1, {%3, %4, %5}], [%2], %6;"
               ::"r"(dst), "l"(m), "r"(bar), "r"(c0), "r"(c1), "r"(c2), "h"((uint16_t)3) : "memory");
}
__device__ __forceinline__ void tma3d_store(const CUtensorMap* m, uint32_t src, int c0, int c1, int c2) {
  asm volatile("cp.async.bulk.tensor.3d.global.shared::cta.bulk_group [%0, {%2, %3, %4}], [%1];"
               ::"l"(m), "r"(src), "r"(c0), "r"(c1), "r"(c2) : "memory");
}
__device__ __forceinline__ void bar_sync(int id, int n) { asm volatile("bar.sync %0, %1;" ::"r"(id), "r"(n) : "memory"); }
__device__ __forceinline__ uint32_t pack_bf16(float lo, float hi) {
  uint32_t r;
  asm("cvt.rn.bf16x2.f32 %0, %1, %2;" : "=r"(r) : "f"(hi), "f"(lo));
  return r;
}
__device__ __forceinline__ float ex2(float x) {
  float y;
  asm("ex2.approx.ftz.f32 %0, %1;" : "=f"(y) : "f"(x));
  return y;
}
__device__ __forceinline__ float fadd(float a, float b) {
  float y;
  asm("add.f32 %0, %1, %2;" : "=f"(y) : "f"(a), "f"(b));
  return y;
}
__device__ __forceinline__ float rcp(float x) {
  float y;
  asm("rcp.approx.ftz.f32 %0, %1;" : "=f"(y) : "f"(x));
  return y;
}
__device__ __forceinline__ void stsm4(uint32_t addr, uint32_t a, uint32_t b, uint32_t c, uint32_t d) {
  asm volatile("stmatrix.sync.aligned.m8n8.x4.shared.b16 [%0], {%1, %2, %3, %4};" ::"r"(addr), "r"(a), "r"(b), "r"(c), "r"(d) : "memory");
}

__device__ __forceinline__ void tma4d_mc_hint(uint32_t dst, const CUtensorMap* m, uint32_t bar, int c3, uint64_t pol) {
  asm volatile("cp.async.bulk.tensor.4d.shared::cluster.global.mbarrier::complete_tx::bytes.multicast::cluster.L2::cache_hint"
               " [%0], [%1, {%3, %3, %3, %4}], [%2], %5, %6;"
               ::"r"(dst), "l"(m), "r"(bar), "r"(0), "r"(c3), "h"((uint16_t)3), "l"(pol) : "memory");
}
__device__ __forceinline__ void tma5d_mc(uint32_t dst, const CUtensorMap* m, uint32_t bar, int c2, int c4) {
  asm volatile("cp.async.bulk.tensor.5d.shared::cluster.global.mbarrier::complete_tx::bytes.multicast::cluster"
               " [%0], [%1, {%3, %3, %4, %3, %5}], [%2], %6;"
               ::"r"(dst), "l"(m), "r"(bar), "r"(0), "r"(c2), "r"(c4), "h"((uint16_t)3) : "memory");
}
__device__ __forceinline__ void bulk_load_hint(uint32_t dst, const void* src, uint32_t bytes, uint32_t bar, uint64_t pol) {
  asm volatile("cp.async.bulk.shared::cluster.global.mbarrier::complete_tx::bytes.L2::cache_hint [%0], [%1], %2, [%3], %4;"
               ::"r"(dst), "l"(src), "r"(bytes), "r"(bar), "l"(pol) : "memory");
}
__device__ __forceinline__ void stg128_hint(void* p, uint32_t a, uint32_t b, uint32_t c, uint32_t d, uint64_t pol) {
  asm volatile("st.global.L2::cache_hint.v4.b32 [%0], {%1, %2, %3, %4}, %5;" ::"l"(p), "r"(a), "r"(b), "r"(c), "r"(d), "l"(pol) : "memory");
}
__device__ __forceinline__ void stg2_if(bool on, void* p, uint32_t a, uint32_t b, uint32_t c, uint32_t d, uint32_t e, uint32_t f,
                                        uint32_t g, uint32_t h, uint64_t pol) {
  asm volatile("{\n.reg .pred p;\nsetp.ne.b32 p, %10, 0;\n"
               "@p st.global.L2::cache_hint.v4.b32 [%0], {%1, %2, %3, %4}, %9;\n"
               "@p st.global.L2::cache_hint.v4.b32 [%0 + 512], {%5, %6, %7, %8}, %9;\n}\n"
               ::"l"(p), "r"(a), "r"(b), "r"(c), "r"(d), "r"(e), "r"(f), "r"(g), "r"(h), "l"(pol), "r"((int)on) : "memory");
}
__device__ __forceinline__ uint64_t make_policy(bool first) {
  uint64_t pf, pn;
  asm("createpolicy.fractional.L2::evict_first.b64 %0, 1.0;" : "=l"(pf));
  asm("createpolicy.fractional.L2::evict_normal.b64 %0, 1.0;" : "=l"(pn));
  return first ? pf : pn;
}
__device__ __forceinline__ bool elect() {
  uint32_t ok;
  asm volatile("{\n.reg .pred p;\nelect.sync _|p, 0xffffffff;\nselp.u32 %0, 1, 0, p;\n}\n" : "=r"(ok));
  return ok;
}
__device__ __forceinline__ void mbar_arrive(uint32_t bar) {
  asm volatile("mbarrier.arrive.shared::cta.b64 _, [%0];" ::"r"(bar) : "memory");
}
__device__ __forceinline__ void stg128(void* p, uint32_t a, uint32_t b, uint32_t c, uint32_t d) {
  asm volatile("st.global.v4.b32 [%0], {%1, %2, %3, %4};" ::"l"(p), "r"(a), "r"(b), "r"(c), "r"(d) : "memory");
}
__device__ __forceinline__ void lds128(uint32_t p, uint32_t& a, uint32_t& b, uint32_t& c, uint32_t& d) {
  asm volatile("ld.shared.v4.b32 {%0, %1, %2, %3}, [%4];" : "=r"(a), "=r"(b), "=r"(c), "=r"(d) : "r"(p) : "memory");
}
__device__ __forceinline__ void wait_count(const unsigned int* p, uint32_t target) {
  asm volatile("{\n.reg .pred p;\n.reg .u32 n, v;\nmov.u32 n, 0;\n"
               "LOOP:\nld.acquire.gpu.global.u32 v, [%0];\nsetp.ge.u32 p, v, %1;\n@p bra DONE;\n"
               "nanosleep.u32 %2;\nadd.u32 n, n, 1;\nsetp.lt.u32 p, n, 0x400000;\n@p bra LOOP;\ntrap;\n"
               "DONE:\n}\n" ::"l"(p), "r"(target), "n"(200) : "memory");
}

__host__ __device__ __forceinline__ int o_wave(int a, int b, int i, int lag) {
  if (lag == 0) return a + i;
  const int p = lag < b - a - 1 ? lag : b - a - 1;
  return i < p ? b - 2 - i : i == p ? b - 1 : b - 1 - i;
}

struct Cursor {
  int bi;
  uint32_t ph;
  __device__ __forceinline__ void next() {
    if (++bi == NBAR) { bi = 0; ph ^= 1; }
  }
};

constexpr float kScaleLog2 = 0.07216878364870322f * 1.4426950408889634f;
constexpr float kSumLimit = 1048576.0f;
constexpr float kMaxLag = 8.0f;

__global__ void __cluster_dims__(2, 1, 1) __launch_bounds__(384, 1)
fused_kernel(const __grid_constant__ Params P) {
  extern __shared__ uint8_t smem_raw[];
  const uint32_t sbase = (smem_u32(smem_raw) + 1023) & ~1023u;
  const uint32_t full0 = sbase + RING, empty0 = full0 + 8 * NBAR, odone = empty0 + 8 * NBAR, oready0 = odone + 8;
  const uint32_t fenced = oready0 + 64, hready0 = fenced + 8;
  const uint32_t rank = blockIdx.x & 1;
  const int role = blockIdx.x >> 1;
  const bool helper = role >= N_CL;
  const int team = helper ? 0 : role >> 2, nt = role & 3, blk = team >> 3;
  const uint32_t* prog = P.ops[helper ? N_TEAM + 2 * (role - N_CL) : team];
  auto q_role = [&](uint32_t op) { return helper ? (int)(((op >> 3) & 60) | ((op >> 12) & 3)) : role; };
  auto o_role = [&](uint32_t op) { return helper ? (int)(((op >> 26) & 56) | ((op >> 9) & 7)) : role; };
  const int wid = __shfl_sync(0xffffffffu, (int)(threadIdx.x >> 5), 0);
  const int wg = wid >> 2;

  const uint32_t op0 = P.first[helper ? N_TEAM + role - N_CL : team];
  if (__builtin_expect(wid == 8, 1)) {
    if (elect()) {
#pragma unroll
      for (int k = 0; k < EARLY; k++) mbar_init(full0 + 8 * k, 1);
      asm volatile("fence.mbarrier_init.release.cluster;" ::: "memory");
      if ((op0 & 3) == OP_Q) {
        const int qr = q_role(op0);
#pragma unroll
        for (int k = 0; k < EARLY; k++) {
          mbar_expect(full0 + 8 * k, SZ_Q);
          tma2d(sbase + k * SZ_Q, &P.x[qr >> 5], full0 + 8 * k, 64 * k, ((qr >> 2) & 7) * kSq + rank * 128);
          tma3d(sbase + k * SZ_Q + 16384, &P.wq[qr >> 5], full0 + 8 * k, 0, 64 * k, 3 * (4 * ((op0 >> 2) & 7) + (qr & 3)));
        }
      }
      asm volatile("prefetch.tensormap [%0];" ::"l"(rank ? &P.v[blk] : &P.k[blk]) : "memory");
    }
  } else if (threadIdx.x == 0) {
#pragma unroll
    for (int i = EARLY; i < 2 * NBAR + 10 + MAX_PARK; i++) mbar_init(full0 + 8 * i, i < NBAR ? 1 : i < 2 * NBAR ? 16 : i == 2 * NBAR ? 8 : 1);
    asm volatile("fence.mbarrier_init.release.cluster;" ::: "memory");
  }
  __syncwarp();
  asm volatile("barrier.cluster.arrive.relaxed.aligned;\nbarrier.cluster.wait.aligned;" ::: "memory");

  if (wg == 2) {
    asm volatile("setmaxnreg.dec.sync.aligned.u32 24;");
    if (wid == 8) {
      Cursor tail{0, 0};
      int head = 0, sh = 0;
      uint32_t cur = 0, used = 0;
      uint64_t fifo = 0;
      uint32_t dst, bar, oready = oready0;
      uint64_t pol;
      asm volatile("createpolicy.fractional.L2::evict_first.b64 %0, 1.0;" : "=l"(pol));
      const uint64_t pol_o = make_policy(P.dbg & 1), pol_p = make_policy(!(P.dbg & 4));
      const CUtensorMap* kv_map = rank ? &P.v[blk] : &P.k[blk];
      auto acquire = [&](uint32_t bytes) {
        uint32_t fp = bytes >> 12;
        if (cur + fp > (RING >> 12)) { fp += (RING >> 12) - cur; cur = 0; }
        used += fp;
        while (used > (RING >> 12) || sh == 5 * NBAR) {
          mbar_wait(empty0 + 8 * tail.bi, tail.ph);
          tail.next();
          used -= (uint32_t)fifo & 31;
          fifo >>= 5;
          sh -= 5;
        }
        fifo |= (uint64_t)fp << sh;
        sh += 5;
        dst = sbase + (cur << 12);
        bar = full0 + 8 * head;
        cur += bytes >> 12;
        if (++head == NBAR) head = 0;
      };
      for (int pc = 0;; pc++) {
        const uint32_t op = prog[pc];
        const int type = op & 3, a = (op >> 2) & 7;
        if (type == OP_END) break;
        if (type == OP_Q) {
          const int qr = q_role(op);
#pragma unroll 1
          for (int k = 0; k < 10; k++) {
            acquire(SZ_Q);
            if ((pc > 0 || k >= EARLY) && elect()) {
              mbar_expect(bar, SZ_Q);
              tma2d(dst, &P.x[qr >> 5], bar, 64 * k, ((qr >> 2) & 7) * kSq + rank * 128);
              if ((k & 1) == rank) tma3d_mc(dst + 16384, &P.wq[qr >> 5], bar, 0, 64 * k, 3 * (4 * a + (qr & 3)));
            }
          }
        } else if (type == OP_A) {
          const uint32_t nop = prog[pc + 1];
          auto kv = [&](int isv, int wave, int j) {
            const int row0 = ((team & 7) * kH + 4 * wave + nt) * kSk;
            acquire(SZ_KV);
            if (elect()) {
              mbar_expect(bar, SZ_KV);
              if (isv == (int)rank) tma4d_mc_hint(dst, kv_map, bar, row0 / 8 + 8 * j, pol);
            }
          };
#pragma unroll 1
          for (int t = (op & F_PARK) ? 1 : 0; t < 31; t++) {
            const int isv = t == 0 ? 0 : (~t & 1);
            kv(isv, a, isv ? (t - 1) >> 1 : (t + 1) >> 1);
          }
          if ((nop & 3) == OP_A) {
            mbar_wait((nop & F_HELP) ? hready0 + 8 * ((nop >> 10) & 3) : fenced, 0);
            asm volatile("fence.proxy.async.global;" ::: "memory");
#pragma unroll 1
            for (int i = 0; i < 2; i++) {
              acquire(SZ_PARK);
              if (elect()) {
                mbar_expect(bar, SZ_PARK);
                bulk_load_hint(dst, &g_park[((role * 2 + rank) * MAX_PARK + ((nop >> 10) & 3)) * 3072 + i * 1536], SZ_PARK, bar, pol_p);
              }
            }
            kv(0, (nop >> 2) & 7, 0);
          }
          kv(1, a, 15);
        } else {
          const int b = (op >> 5) & 15, ro = o_role(op);
#pragma unroll 1
          for (int i = 0; i < b - a; i++) {
            const int w = o_wave(a, b, i, (P.dbg >> 4) & 7);
            mbar_wait(oready, 0);
            oready += 8;
            asm volatile("fence.proxy.async.global;" ::: "memory");
#pragma unroll 1
            for (int k = 12 * w; k < 12 * w + 12; k++) {
              acquire(SZ_O);
              if (elect()) {
                mbar_expect(bar, SZ_O);
                tma5d_mc(dst + 16384 + rank * 10240, &P.wo[ro >> 5], bar, 8 * k + 4 * rank, 5 * (ro & 3));
                bulk_load_hint(dst, &g_o[(((ro >> 2) * 2 + rank) * 96 + k - 12 * (w - P.slot[w])) * 1024], 16384, bar, pol_o);
              }
            }
          }
          if (op & F_LD) {
            if (op & F_PARK) {
              mbar_wait(hready0 + 8 * (MAX_PARK - 1), 0);
              asm volatile("fence.proxy.async.global;" ::: "memory");
            }
#pragma unroll 1
            for (int i = 0; i < 2; i++) {
              acquire(SZ_PART);
              if (elect()) {
                mbar_expect(bar, SZ_PART);
                bulk_load_hint(dst, &g_part[(role * 2 + rank) * 5120 + i * 2560], SZ_PART, bar, pol_p);
              }
            }
          }
        }
      }
    } else if (threadIdx.x == 288) {
      uint32_t ph = 0;
      bool first = true;
      for (int pc = 0;; pc++) {
        const uint32_t op = prog[pc];
        if ((op & 3) == OP_END) break;
        if ((op & 3) != OP_A && !helper) continue;
        mbar_wait_slow<400>(odone, ph);
        ph ^= 1;
        unsigned int* flag = !helper ? &g_done[(team * 2 + rank) * 8 + ((op >> 2) & 7)]
                             : (op & 3) == OP_Q ? &g_help[(q_role(op) * 2 + rank) * MAX_PARK + ((op >> 10) & 3)]
                                                : &g_help[(o_role(op) * 2 + rank) * MAX_PARK + MAX_PARK - 1];
        asm volatile("red.release.gpu.global.add.u32 [%0], 1;" ::"l"(flag) : "memory");
        if (first) mbar_arrive(fenced);
        first = false;
      }
    } else if (threadIdx.x == 320) {
      uint32_t oready = oready0;
      for (int pc = 0;; pc++) {
        const uint32_t op = prog[pc];
        if ((op & 3) == OP_END) break;
        if ((op & 3) == OP_O) {
          const int a = (op >> 2) & 7, b = (op >> 5) & 15;
          for (int i = 0; i < b - a; i++) {
            const int ci = ((o_role(op) >> 2) * 2 + rank) * 8 + o_wave(a, b, i, (P.dbg >> 4) & 7);
            wait_count(&g_done[ci], 4);
            mbar_arrive(oready);
            oready += 8;
            if (atomicAdd(&g_seen[ci], 1u) == 3u) { g_seen[ci] = 0; g_done[ci] = 0; }
          }
        }
        if ((op & 3) != OP_Q && (op & F_HELP) && (op & F_PARK)) {
          unsigned int* flag = &g_help[(role * 2 + rank) * MAX_PARK + ((op >> 10) & 3)];
          wait_count(flag, 1);
          mbar_arrive(hready0 + 8 * ((op >> 10) & 3));
          *flag = 0;
        }
      }
    }
    __syncwarp();
    asm volatile("barrier.cluster.arrive.relaxed;\nbarrier.cluster.wait;" ::: "memory");
  } else {
    asm volatile("setmaxnreg.inc.sync.aligned.u32 240;");
    const int lane = threadIdx.x & 31, warp = wid & 3;
    uint32_t empty_rem;
    asm volatile("mapa.shared::cluster.u32 %0, %1, %2;" : "=r"(empty_rem) : "r"(empty0), "r"(lane & 1));
    auto release = [&](int slot) { mbar_arrive_cluster_if(lane < 2, empty_rem + 8 * slot); };
    Cursor r{0, 0};
    const uint32_t ring16 = (sbase & 0x3FFFF) >> 4;
    uint32_t cur = ring16;
    bool rdy0 = false, rdy1 = false;
    auto probe1 = [&]() { rdy0 = mbar_test(full0 + 8 * r.bi, r.ph); };
    auto probe2 = [&]() {
      Cursor n = r;
      rdy0 = mbar_test(full0 + 8 * n.bi, n.ph);
      n.next();
      rdy1 = mbar_test(full0 + 8 * n.bi, n.ph);
    };
    auto take = [&](bool rdy, uint32_t bytes, uint32_t& addr) {
      const int bi = r.bi;
      if (!__all_sync(0xffffffffu, rdy)) mbar_wait(full0 + 8 * r.bi, r.ph);
      r.next();
      if (cur > ring16 + ((RING - bytes) >> 4)) cur = ring16;
      addr = cur;
      cur += bytes >> 4;
      return bi;
    };
    uint32_t keep = 0;
    const int row = wg * 64 + warp * 16 + (lane >> 2);
    const int img0 = row * 4 + ((lane & 3) ^ ((row >> 1) & 3));
    uint4* pend = nullptr;
    uint64_t spol;
    int pc = 0;
    uint32_t op = prog[0];
    auto enter = [&]() {
      r.bi = (op >> 15) & 15; r.ph = (op >> 19) & 1; cur = ring16 + (((op >> 20) & 63) << 8);
      spol = make_policy(!(op & F_SOON));
    };
    auto drain = [&](uint32_t (&t)[48], uint32_t c) {
      if (!(op & (3u << 26)) || c >= 6) return;
#pragma unroll
      for (int i = 0; i < 6; i++)
        stg2_if(c == i, pend + i * 512, t[8 * i], t[8 * i + 1], t[8 * i + 2], t[8 * i + 3],
                t[8 * i + 4], t[8 * i + 5], t[8 * i + 6], t[8 * i + 7], spol);
      if ((op & (1u << 26)) && c == 5) {
        __syncwarp();
        mbar_arrive_if(lane == 0, odone);
      }
    };
    float s[32], o[96], c[80];
    uint32_t q[48], pa[16], pb[16];
    float mc0, mc1, l0, l1;
    bool gen;
    auto expo = [&](float (&s)[32], uint32_t (&pout)[16], float& b0, float& b1, bool sub) {
#pragma unroll
      for (int i = 0; i < 8; i++) {
        const float e1 = ex2(sub ? s[4 * i + 1] - mc0 : s[4 * i + 1]), e0 = ex2(sub ? s[4 * i] - mc0 : s[4 * i]);
        const float e3 = ex2(sub ? s[4 * i + 3] - mc1 : s[4 * i + 3]), e2 = ex2(sub ? s[4 * i + 2] - mc1 : s[4 * i + 2]);
        pout[2 * i] = pack_bf16(e0, e1);
        b0 = i ? b0 + fadd(e1, e0) : fadd(e1, e0);
        pout[2 * i + 1] = pack_bf16(e2, e3);
        b1 = i ? b1 + fadd(e3, e2) : fadd(e3, e2);
      }
    };
    auto rowmax = [&](float (&s)[32], float& m0, float& m1) {
      m0 = fmaxf(s[0], s[1]); m1 = fmaxf(s[2], s[3]);
#pragma unroll
      for (int i = 1; i < 8; i++) { m0 = fmaxf(m0, fmaxf(s[4 * i], s[4 * i + 1])); m1 = fmaxf(m1, fmaxf(s[4 * i + 2], s[4 * i + 3])); }
      m0 = fmaxf(m0, __shfl_xor_sync(0xffffffffu, m0, 1)); m1 = fmaxf(m1, __shfl_xor_sync(0xffffffffu, m1, 1));
      m0 = fmaxf(m0, __shfl_xor_sync(0xffffffffu, m0, 2)); m1 = fmaxf(m1, __shfl_xor_sync(0xffffffffu, m1, 2));
    };
    auto first = [&](float (&s)[32]) {
      mc0 = 0.f; mc1 = 0.f;
      expo(s, pa, l0, l1, false);
      gen = __any_sync(0xffffffffu, !(fmaxf(l0, l1) <= kSumLimit && fminf(l0, l1) >= 1.0f / kSumLimit));
      if (gen) {
        rowmax(s, mc0, mc1);
        expo(s, pa, l0, l1, true);
      }
    };
    auto soft = [&](uint32_t (&pout)[16]) {
      float b0, b1;
      if (!gen) {
        expo(s, pout, b0, b1, false);
        gen = __any_sync(0xffffffffu, !(fmaxf(b0, b1) <= kSumLimit));
      }
      if (gen) {
        float m0, m1;
        rowmax(s, m0, m1);
        if (__any_sync(0xffffffffu, !(m0 <= mc0 + kMaxLag && m1 <= mc1 + kMaxLag))) {
          m0 = fmaxf(mc0, m0); m1 = fmaxf(mc1, m1);
          const float a0 = ex2(mc0 - m0), a1 = ex2(mc1 - m1);
          mc0 = m0; mc1 = m1;
          l0 *= a0; l1 *= a1;
          wg_wait<0>();
          fence_regs(o);
#pragma unroll
          for (int i = 0; i < 24; i++) { o[4 * i] *= a0; o[4 * i + 1] *= a0; o[4 * i + 2] *= a1; o[4 * i + 3] *= a1; }
        }
        expo(s, pout, b0, b1, true);
      }
      l0 += b0; l1 += b1;
    };
    auto qk = [&](float (&s)[32], uint32_t ak, int k0, int k1) {
#pragma unroll
      for (int kk = k0; kk < k1; kk++)
        wgmma_rs_n64<0>(s, q[4 * kk], q[4 * kk + 1], q[4 * kk + 2], q[4 * kk + 3], mk_desc(ak + (kk >> 2) * KV_CH + (kk & 3) * 2, 16, KV_SBO, 1), kk != 0);
      wg_commit();
    };
    auto pv = [&](uint32_t (&pin)[16], uint32_t av, int acc) {
#pragma unroll
      for (int kk = 0; kk < 4; kk++)
        wgmma_rs_n192<1>(o, pin[4 * kk], pin[4 * kk + 1], pin[4 * kk + 2], pin[4 * kk + 3], mk_desc(av + kk * (KV_SBO / 8), KV_CH * 16, KV_SBO, 1), acc || (kk != 0));
      wg_commit();
    };
    auto xw = [&](uint32_t ad, int acc) {
      wg_fence();
#pragma unroll
      for (int kk = 0; kk < 4; kk++)
        wgmma_ss_n192<1>(o, mk_desc(ad + wg * 512 + kk * 2, 16, 1024, 1), mk_desc(ad + 1024 + kk * 128, 8192, 1024, 1), acc || kk != 0);
      wg_commit();
    };
    auto ow = [&](int acc, int prev) {
      uint32_t ad;
      const int bi = take(rdy0, SZ_O, ad);
      const uint32_t da = ad + wg * 256, db = ad + 1024;
      wg_fence();
      wgmma_ss_n160<1>(c, mk_desc(da, 16, 512, 2), mk_desc(db, 2048, 512, 2), acc);
      wgmma_ss_n160<1>(c, mk_desc(da + 2, 16, 512, 2), mk_desc(db + 64, 2048, 512, 2), 1);
      wg_commit();
      if (acc) { wg_wait<1>(); release(prev); }
      wgmma_ss_n160<1>(c, mk_desc(da + 512, 16, 512, 2), mk_desc(db + 640, 2048, 512, 2), 1);
      wgmma_ss_n160<1>(c, mk_desc(da + 514, 16, 512, 2), mk_desc(db + 704, 2048, 512, 2), 1);
      wg_commit();
      return bi;
    };
    auto o_run = [&](uint32_t (&t)[48], int bi) {
      const int nk = 12 * (((op >> 5) & 15) - ((op >> 2) & 7));
#pragma unroll 1
      for (int k = 0; k < 6; k++) {
        drain(t, k);
        probe1();
        wg_wait<1>();
        bi = ow(1, bi);
      }
#pragma unroll 1
      for (int k = 7; k < nk; k++) {
        probe1();
        wg_wait<1>();
        bi = ow(1, bi);
      }
      probe1();
      return bi;
    };
    auto st_part = [&](int i) {
      stg2_if(true, pend + i * 512, __float_as_uint(c[8 * i]), __float_as_uint(c[8 * i + 1]), __float_as_uint(c[8 * i + 2]), __float_as_uint(c[8 * i + 3]),
              __float_as_uint(c[8 * i + 4]), __float_as_uint(c[8 * i + 5]), __float_as_uint(c[8 * i + 6]), __float_as_uint(c[8 * i + 7]), spol);
    };
#pragma unroll
    for (int i = 0; i < 48; i++) q[i] = 0;
    enter();

    if ((op & 3) == OP_Q) {
      uint32_t ad;
      int bi0 = take(false, SZ_Q, ad), k = 0, lag = 0;
      xw(ad, 0);
      for (;;) {
#pragma unroll 1
        do {
          drain(q, k - lag);
          probe1();
          wg_wait<0>();
          release(bi0);
          bi0 = take(rdy0, SZ_Q, ad);
          xw(ad, 1);
        } while (++k < 8);
        const int bi9 = take(false, SZ_Q, ad);
        xw(ad, 1);
        k = 0; lag = 0;
        uint32_t nop = prog[++pc];
        if (op & F_PARK) {
          pend = &g_park[((q_role(op) * 2 + rank) * MAX_PARK + ((op >> 10) & 3)) * 3072 + img0];
          op = nop;
          enter();
          wg_wait<1>();
          release(bi0);
          if ((op & 3) == OP_Q) bi0 = take(false, SZ_Q, ad);
          wg_wait<0>();
          fence_regs(o);
          release(bi9);
#pragma unroll
          for (int i = 0; i < 48; i++) q[i] = pack_bf16(o[2 * i] * kScaleLog2, o[2 * i + 1] * kScaleLog2);
          if ((op & 3) != OP_Q) break;
          xw(ad, 0);
          continue;
        }
        int wave = (op >> 2) & 7, sk1;
        uint32_t ak1;
        {
          wg_wait<1>();
          release(bi0);
          const int sk0 = take(false, SZ_KV, ad);
          probe1();
          wg_wait<0>();
          fence_regs(o);
          release(bi9);
          float s0[32];
#pragma unroll
          for (int i = 0; i < 48; i++) q[i] = pack_bf16(o[2 * i] * kScaleLog2, o[2 * i + 1] * kScaleLog2);
          wg_fence();
          qk(s0, ad, 0, 12);
          sk1 = take(rdy0, SZ_KV, ak1);
          wg_fence();
          qk(s, ak1, 0, S1A);
          probe1();
          wg_wait<1>();
          fence_regs(s0);
          release(sk0);
          first(s0);
        }
        float i0, i1;
        auto sums = [&]() {
          l0 += __shfl_xor_sync(0xffffffffu, l0, 1); l1 += __shfl_xor_sync(0xffffffffu, l1, 1);
          l0 += __shfl_xor_sync(0xffffffffu, l0, 2); l1 += __shfl_xor_sync(0xffffffffu, l1, 2);
          i0 = rcp(l0); i1 = rcp(l1);
          asm volatile("" : "+f"(i0), "+f"(i1));
        };
        auto target = [&]() {
          pend = &g_o[((team * 2 + rank) * 96 + 3 * (4 * P.slot[wave] + nt)) * 1024 + img0];
          asm volatile("" : "+l"(pend));
        };
        for (;;) {
          nop = prog[++pc];
          {
            uint32_t av;
            const int sv = take(rdy0, SZ_KV, av);
            wg_fence();
            qk(s, ak1, S1A, 12);
            pv(pa, av, 0);
            probe2();
            wg_wait<1>();
            fence_regs(s);
            release(sk1);
            soft(pb);
            wg_wait<0>();
            fence_regs(o);
            release(sv);
          }
          auto step = [&](uint32_t (&pin)[16], uint32_t (&pout)[16]) {
            uint32_t ak, av;
            const int sk = take(rdy0, SZ_KV, ak), sv = take(rdy1, SZ_KV, av);
            wg_fence();
            qk(s, ak, 0, 12);
            pv(pin, av, 1);
            probe2();
            wg_wait<1>();
            fence_regs(s);
            release(sk);
            soft(pout);
            wg_wait<0>();
            fence_regs(o);
            release(sv);
          };
#pragma unroll 1
          for (int jj = 0; jj < 7; jj++) {
            step(pb, pa);
            step(pa, pb);
          }
          if ((nop & 3) != OP_A) break;
          uint32_t ak, av;
          {
            const int b0 = take(rdy0, SZ_PARK, ak), b1 = take(rdy1, SZ_PARK, av);
            const uint32_t ad0 = ak, ad1 = av;
            probe2();
#pragma unroll
            for (int i = 0; i < 12; i++)
              lds128(sbase + ((i < 6 ? ad0 : ad1) - ring16 + img0) * 16 + ((i % 6) >> 1) * 8192 + (i & 1) * 512, q[4 * i], q[4 * i + 1], q[4 * i + 2], q[4 * i + 3]);
            release(b0); release(b1);
          }
          const int sk0 = take(rdy0, SZ_KV, ak), sv = take(rdy1, SZ_KV, av);
          wg_fence();
          qk(s, ak, 0, 8);
          sched_fence(keep);
          sums();
          sched_fence(keep);
          qk(s, ak, 8, 12);
          pv(pb, av, 1);
          probe2();
          spol = make_policy(!(nop & F_SOON));
          wg_wait<1>();
          fence_regs(s);
          release(sk0);
          first(s);
          sk1 = take(rdy0, SZ_KV, ak1);
          rdy0 = rdy1;
          wg_wait<0>();
          target();
          fence_regs(o);
          release(sv);
          uint32_t t[48];
#pragma unroll
          for (int j = 0; j < 6; j++) {
#pragma unroll
            for (int i = 0; i < 4; i++) {
              t[8 * j + i] = pack_bf16(o[16 * j + 4 * i] * i0, o[16 * j + 4 * i + 1] * i0);
              t[8 * j + i + 4] = pack_bf16(o[16 * j + 4 * i + 2] * i1, o[16 * j + 4 * i + 3] * i1);
            }
            stg2_if(true, pend + j * 512, t[8 * j], t[8 * j + 1], t[8 * j + 2], t[8 * j + 3], t[8 * j + 4], t[8 * j + 5], t[8 * j + 6], t[8 * j + 7], spol);
            if (j == UC0) { wg_fence(); qk(s, ak1, 0, 4); }
            if (j == UC1) { wg_fence(); qk(s, ak1, 4, S1A); }
            sched_fence(keep);
          }
          if (P.zero) {
#pragma unroll
            for (int j = 0; j < 5; j++)
              stg2_if(true, pend, t[8 * j], t[8 * j + 1], t[8 * j + 2], t[8 * j + 3], t[8 * j + 4], t[8 * j + 5], t[8 * j + 6], t[8 * j + 7], spol);
          }
          __syncwarp();
          mbar_arrive_if(lane == 0, odone);
          wave = (nop >> 2) & 7;
        }
        const int sv = take(rdy0, SZ_KV, ad);
        wg_fence();
        pv(pb, ad, 1);
        sums();
        target();
        op = nop;
        enter();
        rdy0 = rdy1;
        auto convert = [&](uint32_t (&t)[48], float (&u)[96]) {
#pragma unroll
          for (int i = 0; i < 24; i++) {
            t[8 * (i >> 2) + (i & 3)] = pack_bf16(u[4 * i], u[4 * i + 1]);
            t[8 * (i >> 2) + (i & 3) + 4] = pack_bf16(u[4 * i + 2], u[4 * i + 3]);
          }
        };
        if ((op & 3) != OP_O) {
          if ((op & 3) == OP_Q) bi0 = take(rdy0, SZ_Q, ad);
          wg_wait<0>();
          fence_regs(o);
          release(sv);
          float u[96];
#pragma unroll
          for (int i = 0; i < 96; i++) u[i] = o[i] * (i & 2 ? i1 : i0);
          if ((op & 3) != OP_Q) { convert(q, u); break; }
          fence_regs(u);
          xw(ad, 0);
          sched_fence(keep);
          fence_regs(u);
          convert(q, u);
          continue;
        }
        int bi = ow(0, 0);
        wg_wait<2>();
        fence_regs(o);
        release(sv);
        {
          uint32_t t[48];
#pragma unroll
          for (int i = 0; i < 96; i++) o[i] *= i & 2 ? i1 : i0;
          convert(t, o);
          bi = o_run(t, bi);
        }
        nop = prog[++pc];
        if (op & F_LD) {
          uint32_t t[80], ad0, ad1;
          const int b0 = take(rdy0, SZ_PART, ad0), b1 = take(false, SZ_PART, ad1);
          rdy0 = false;
#pragma unroll
          for (int i = 0; i < 20; i++)
            lds128(sbase + ((i < 10 ? ad0 : ad1) - ring16 + img0) * 16 + ((i % 10) >> 1) * 8192 + (i & 1) * 512, t[4 * i], t[4 * i + 1], t[4 * i + 2], t[4 * i + 3]);
          fence_regs(t);
          wg_wait<0>();
          fence_regs(c);
          release(b0); release(b1);
#pragma unroll
          for (int i = 0; i < 80; i++) c[i] += __uint_as_float(t[i]);
        }
        if (!(op & F_ST)) {
          wg_wait<0>();
          fence_regs(c);
          goto finish;
        }
        op = nop;
        enter();
        bi0 = take(rdy0, SZ_Q, ad);
        xw(ad, 0);
        pend = &g_part[(role * 2 + rank) * 5120 + img0];
        probe1();
        wg_wait<1>();
        fence_regs(c);
        release(bi);
        st_part(6); st_part(7);
        wg_wait<0>();
        release(bi0);
        bi0 = take(rdy0, SZ_Q, ad);
        xw(ad, 1);
        st_part(8); st_part(9);
#pragma unroll
        for (int i = 0; i < 48; i++) q[i] = __float_as_uint(c[i]);
        k = 1; lag = 2;
      }
    }
    rdy0 = false;
    {
      uint32_t t[48];
#pragma unroll
      for (int i = 0; i < 48; i++) t[i] = q[i] ^ P.zero;
      while ((op & 3) == OP_O) {
        const int bi = o_run(t, ow(0, 0));
        wg_wait<0>();
        fence_regs(c);
        pc++;
        if (!(op & F_ST)) goto finish;
        release(bi);
        pend = &g_part[(o_role(op) * 2 + rank) * 5120 + img0];
#pragma unroll
        for (int i = 6; i < 10; i++) st_part(i);
#pragma unroll
        for (int i = 0; i < 48; i++) t[i] = __float_as_uint(c[i]) ^ P.zero;
        op = prog[pc];
        enter();
      }
      for (int i = 0; i < 6; i++) drain(t, i);
    }
    asm volatile("barrier.cluster.arrive.relaxed;" ::: "memory");
    if (false) {
    finish:
      asm volatile("barrier.cluster.arrive.relaxed;" ::: "memory");
      bar_sync(1, 256);
      const uint32_t wstage = sbase + (wg * 4 + warp) * 5120;
      const uint32_t sa = wstage + (lane & 15) * 64;
#pragma unroll
      for (int i = 0; i < 10; i++) {
        const int u = (i & 1) * 2 + (lane >> 4);
        stsm4(sa + (i >> 1) * 1024 + ((u ^ ((lane >> 1) & 3)) << 4), pack_bf16(c[8 * i], c[8 * i + 1]), pack_bf16(c[8 * i + 2], c[8 * i + 3]),
              pack_bf16(c[8 * i + 4], c[8 * i + 5]), pack_bf16(c[8 * i + 6], c[8 * i + 7]));
      }
      asm volatile("fence.proxy.async.shared::cta;" ::: "memory");
      __syncwarp();
      if (lane == 0) {
        tma3d_store(&P.out, wstage, 0, (team & 7) * kSq + rank * 128 + wg * 64 + warp * 16, blk * 20 + nt * 5);
        asm volatile("cp.async.bulk.commit_group;\ncp.async.bulk.wait_group.read 0;" ::: "memory");
      }
      __syncwarp();
    }
    if (P.dbg == 0xffffffffu) g_seen[0] = keep;
    asm volatile("barrier.cluster.wait;" ::: "memory");
  }
}

typedef CUresult (*EncodeFn)(CUtensorMap*, CUtensorMapDataType, cuuint32_t, void*, const cuuint64_t*, const cuuint64_t*,
                             const cuuint32_t*, const cuuint32_t*, CUtensorMapInterleave, CUtensorMapSwizzle,
                             CUtensorMapL2promotion, CUtensorMapFloatOOBfill);

void encode(EncodeFn fn, CUtensorMap* m, const void* ptr, int rank, const cuuint64_t* dims, const cuuint64_t* strides,
            const cuuint32_t* box, CUtensorMapSwizzle swz) {
  const cuuint32_t es[5] = {1, 1, 1, 1, 1};
  CUresult r = fn(m, CU_TENSOR_MAP_DATA_TYPE_BFLOAT16, rank, const_cast<void*>(ptr), dims, strides, box, es,
                  CU_TENSOR_MAP_INTERLEAVE_NONE, swz, CU_TENSOR_MAP_L2_PROMOTION_L2_128B, CU_TENSOR_MAP_FLOAT_OOB_FILL_NONE);
  if (r != CUDA_SUCCESS) fprintf(stderr, "cuTensorMapEncodeTiled failed: %d\n", (int)r);
}

void annotate(uint32_t* ops, int n, bool helper) {
  uint32_t items = 0, cur = 0, pend = 0;
  auto item = [&](uint32_t bytes, int count) {
    for (int i = 0; i < count; i++) { if (cur + bytes > RING) cur = 0; cur += bytes; items++; }
  };
  for (int i = 0; i <= n; i++) {
    const uint32_t op = ops[i];
    ops[i] |= (items % NBAR) << 15 | ((items / NBAR) & 1) << 19 | (cur >> 12) << 20 | pend << 26;
    if ((op & 3) == OP_Q) { item(SZ_Q, 10); pend = (op & F_PARK) ? (helper ? 1 : 2) : 0; }
    if ((op & 3) == OP_A) {
      item(SZ_KV, (op & F_PARK) ? 30 : 31);
      if ((ops[i + 1] & 3) == OP_A) { item(SZ_PARK, 2); item(SZ_KV, 1); }
      item(SZ_KV, 1);
      pend = 1;
    }
    if ((op & 3) == OP_O) {
      item(SZ_O, 12 * (((op >> 5) & 15) - ((op >> 2) & 7)));
      if (op & F_LD) item(SZ_PART, 2);
      pend = (op & F_LAZY) ? (helper ? 1 : 2) : 0;
    }
  }
}

void compile_programs(const char* const* text, bool helpers, Params& P) {
  struct Req { int when, team, wave, slot; } req[N_TEAM * MAX_PARK];
  int n_req = 0;
  for (int t = 0; t < N_TEAM; t++) {
    uint32_t* ops = P.ops[t];
    int n = 0, flags[8] = {0, 0, 0, 0, 0, 0, 0, 0}, n_park = 0, last_o = -1, when = 0, given = 0;
    for (const char* s = text[t]; *s; s++) {
      const int a = s[1] - '0';
      if (*s == 'Q' || (*s == 'H' && !helpers)) { ops[n++] = OP_Q | a << 2; when += 10; }
      else if (*s == 'P') { flags[a] = F_PARK | n_park++ << 10; ops[n++] = OP_Q | a << 2 | flags[a]; when += 10; }
      else if (*s == 'H') { req[n_req++] = {when, t, a, n_park}; flags[a] = F_PARK | F_HELP | n_park++ << 10; }
      else if (*s == 'A') { ops[n++] = OP_A | a << 2 | flags[a]; when += 32; }
      else if (*s == 'G') { given = a; if (helpers) req[n_req++] = {1000, t, 0, -a}; }
      else if (*s == 'O') {
        ops[n] = OP_O | a << 2 | (s[2] - '0') << 5;
        if (given) ops[n] = helpers ? ops[n] | F_LD | F_PARK | (MAX_PARK - 1) << 10 : ops[n] & ~(7u << 2);
        if (last_o >= 0) { ops[last_o] |= F_ST; ops[n] |= F_LD; }
        last_o = n++;
        when += 10 * (s[2] - s[1]);
      }
    }
    for (int i = 0; i + 1 < n; i++)
      if ((ops[i] & 3) == OP_O && (ops[i] & F_ST) && (ops[i + 1] & 3) == OP_Q) ops[i] |= F_LAZY;
    for (int i = n; i < MAX_OPS; i++) ops[i] = OP_END;
    annotate(ops, n, false);
    for (int i = 0; i < n; i++) {
      if ((ops[i] & 3) != OP_A && (P.dbg & 8)) ops[i + 1] |= F_SOON;
      if ((ops[i] & 3) != OP_A) continue;
      const int w = (ops[i] >> 2) & 7;
      int dist = 0;
      for (int j = i + 1; j < n; j++) {
        const int a = (ops[j] >> 2) & 7, b = (ops[j] >> 5) & 15;
        if ((ops[j] & 3) == OP_O && w < b) {
          for (int k = 0; k < b - a && o_wave(a, b, k, (P.dbg >> 4) & 7) != w; k++) dist += 10;
          break;
        }
        dist += (ops[j] & 3) == OP_Q ? 10 : (ops[j] & 3) == OP_A ? 32 : 10 * (b - a);
      }
      if (dist <= (int)((P.dbg >> 8) & 255)) ops[i + 1] |= F_SOON;
    }
  }
  for (int i = 1; i < n_req; i++)
    for (int j = i; j > 0 && req[j].when < req[j - 1].when; j--) { Req r = req[j]; req[j] = req[j - 1]; req[j - 1] = r; }
  for (int h = 0; h < N_HELP; h++) {
    uint32_t* ops = P.ops[N_TEAM + 2 * h];
    int n = 0;
    for (int i = 0; i < n_req; i++)
      for (int m = h; m < 4; m += N_HELP) {
        const uint32_t ro = 4 * req[i].team + m;
        ops[n++] = req[i].slot >= 0 ? OP_Q | req[i].wave << 2 | req[i].team << 5 | F_PARK | req[i].slot << 10 | m << 12
                                    : OP_O | -req[i].slot << 5 | F_ST | F_LAZY | F_SOON | (ro & 7) << 9 | (ro >> 3) << 29;
      }
    for (int i = n; i < 2 * MAX_OPS; i++) ops[i] = OP_END | F_SOON;
    annotate(ops, n, true);
  }
  for (int i = 0; i < 32; i++) P.first[i] = i < N_TEAM ? P.ops[i][0] : i < N_TEAM + N_HELP ? P.ops[2 * i - N_TEAM][0] : 0;
}

const char* const kPrograms[N_TEAM] = {
  "Q0A0Q1A1H2A2O03Q3A3Q4A4Q5A5Q6A6Q7A7O38",
  "Q0A0Q1A1Q2A2H3A3Q4A4O03Q5A5Q6A6Q7A7O38",
  "Q0A0H1A1Q2A2Q3A3O04Q4A4Q5A5Q6A6Q7A7O48",
  "Q0A0Q1A1Q2A2Q3A3O02Q4A4Q5A5Q6A6H7A7O28",
  "Q0A0Q1A1Q2A2O03Q3A3Q4A4Q5A5Q6A6H7A7O38",
  "Q0A0Q1A1Q2A2Q3A3Q4A4O05Q5A5Q6A6H7A7O58",
  "Q0A0Q1A1Q2A2Q3A3Q4A4O05Q5A5Q6A6H7A7O58",
  "Q0A0Q1A1Q2A2O03Q3A3Q4A4H5A5Q6A6Q7A7O38",
  "P7Q0A0Q1A1O01Q2A2H3A3Q4A4Q5A5Q6A6A7O18",
  "P3P5Q0A0Q1A1Q2A2A3Q4A4A5H6A6Q7A7O08",
  "P7Q0A0Q1A1Q2A2Q3A3H4A4Q5A5Q6A6A7O08",
  "P3P7Q0A0Q1A1H2A2A3Q4A4Q5A5Q6A6A7O08",
  "Q0A0Q1A1Q2A2O01Q3A3Q4A4H5A5Q6A6Q7A7O18",
  "P3Q0A0Q1A1Q2A2A3Q4A4Q5A5Q6A6Q7A7G1O18",
  "P6Q0A0Q1A1Q2A2Q3A3Q4A4Q5A5A6Q7A7G1O18",
  "P2P6Q0A0Q1A1A2Q3A3H4A4Q5A5A6Q7A7O08",
};

const char* const* bench_programs() {
  return kPrograms;
}

}

extern "C" void kernel_launch(void* const* d_in, const int* in_sizes, int n_in, void* d_out, int out_size) {
  (void)in_sizes; (void)n_in; (void)out_size;
  static EncodeFn fn = nullptr;
  static int n_clusters = 0;
  if (!fn) {
    cudaDriverEntryPointQueryResult qr;
    void* f = nullptr;
    cudaGetDriverEntryPoint("cuTensorMapEncodeTiled", &f, cudaEnableDefault, &qr);
    fn = (EncodeFn)f;
    cudaFuncSetAttribute(fused_kernel, cudaFuncAttributeMaxDynamicSharedMemorySize, SMEM_BYTES);
    cudaLaunchConfig_t cfg = {};
    cfg.gridDim = dim3(132); cfg.blockDim = dim3(384); cfg.dynamicSmemBytes = SMEM_BYTES;
    cudaLaunchAttribute at[1];
    at[0].id = cudaLaunchAttributeClusterDimension; at[0].val.clusterDim.x = 2; at[0].val.clusterDim.y = 1; at[0].val.clusterDim.z = 1;
    cfg.attrs = at; cfg.numAttrs = 1;
    if (cudaOccupancyMaxActiveClusters(&n_clusters, fused_kernel, &cfg) != cudaSuccess || n_clusters < 1) n_clusters = 1;
    (void)cudaGetLastError();
  }
  Params P;
  const CUtensorMapSwizzle S128 = CU_TENSOR_MAP_SWIZZLE_128B, S64 = CU_TENSOR_MAP_SWIZZLE_64B;
  for (int blk = 0; blk < 2; blk++) {
    void* const* in = d_in + 5 * blk;
    { const cuuint64_t d[] = {kD, kB * kSq}, s[] = {kD * 2}; const cuuint32_t b[] = {64, 128};
      encode(fn, &P.x[blk], in[0], 2, d, s, b, S128); }
    { const cuuint64_t d[] = {64, 8, 3, (cuuint64_t)kB * kH * kSk / 8}, s[] = {kDh * 2, 128, 8 * kDh * 2}; const cuuint32_t b[] = {64, 8, 3, 8};
      encode(fn, &P.k[blk], in[1], 4, d, s, b, S128);
      encode(fn, &P.v[blk], in[2], 4, d, s, b, S128); }
    { const cuuint64_t d[] = {64, kD, kHD / 64}, s[] = {kHD * 2, 128}; const cuuint32_t b[] = {64, 64, 3};
      encode(fn, &P.wq[blk], in[3], 3, d, s, b, S128); }
    { const cuuint64_t d[] = {32, 2, kHD / 8, 4, kD / 32}, s[] = {kD * 2, 8 * kD * 2, 2 * kD * 2, 64}; const cuuint32_t b[] = {32, 2, 4, 4, 5};
      encode(fn, &P.wo[blk], in[4], 5, d, s, b, S64); }
  }
  { const cuuint64_t d[] = {32, kB * kSq, 2 * kD / 32}, s[] = {2 * kD * 2, 64}; const cuuint32_t b[] = {32, 16, 5};
    encode(fn, &P.out, d_out, 3, d, s, b, S64); }

  P.zero = 0;
  P.dbg = 0x5030;
  for (int w = 0; w < 8; w++) P.slot[w] = (P.dbg >> 16) & 15 ? w % ((P.dbg >> 16) & 15) : w;
  if (n_clusters >= N_CL) {
    const bool helpers = n_clusters >= N_CL + N_HELP;
    compile_programs(bench_programs(), helpers, P);
    fused_kernel<<<2 * (N_CL + (helpers ? N_HELP : 0)), 384, SMEM_BYTES>>>(P);
  } else {
    for (int phase = 0; phase < 2; phase++) {
      const char* text[N_TEAM];
      for (int t = 0; t < N_TEAM; t++) text[t] = phase ? "O08" : "Q0A0Q1A1Q2A2Q3A3Q4A4Q5A5Q6A6Q7A7";
      compile_programs(text, false, P);
      fused_kernel<<<2 * N_CL, 384, SMEM_BYTES>>>(P);
    }
  }
}
```

```cpp
#include <cuda_runtime.h>
#include <cuda_bf16.h>
#include <cuda.h>
#include <stdint.h>
#include <stdio.h>

namespace {

constexpr int kB = 8, kSq = 256, kD = 640, kH = 32, kSk = 1024, kDh = 192;
constexpr int kHD = kH * kDh;
#define S1A 8
#define UC0 2
#define UC1 5
#define RING_KB 224
constexpr uint32_t RING = RING_KB * 1024;
constexpr uint32_t SZ_KV = 24576;
constexpr uint32_t SZ_Q = 16384 + 24576;
constexpr uint32_t SZ_O = 16384 + 20480;
constexpr uint32_t SZ_PARK = 24576;
constexpr uint32_t SZ_PART = 40960;
constexpr int NBAR = 10;
constexpr int EARLY = 3;
constexpr uint32_t KV_CH = 64, KV_SBO = 3072;
constexpr int SMEM_BYTES = RING + 512 + 1024;
constexpr int N_TEAM = 16, N_CL = 64, N_HELP = 2, MAX_OPS = 24, MAX_PARK = 4;
enum { OP_END = 0, OP_Q = 1, OP_A = 2, OP_O = 3, F_PARK = 1 << 9, F_LD = 1 << 12, F_ST = 1 << 13, F_LAZY = 1 << 14, F_HELP = 1 << 12, F_SOON = 1 << 28 };

struct alignas(64) Params {
  uint32_t first[32];
  CUtensorMap x[2], wq[2], k[2], v[2], wo[2], out;
  uint32_t ops[N_TEAM + 2 * N_HELP][MAX_OPS];
  uint32_t zero;
  uint32_t slot[8];
  uint32_t dbg;
};

__device__ uint4 g_o[N_TEAM * 2 * 96 * 1024];
__device__ uint4 g_park[N_CL * 2 * MAX_PARK * 12 * 256];
__device__ uint4 g_part[N_CL * 2 * 5 * 1024];
__device__ unsigned int g_done[N_TEAM * 2 * 8];
__device__ unsigned int g_help[N_CL * 2 * MAX_PARK];
__device__ unsigned int g_seen[N_TEAM * 2 * 8];

template <int TB, int TA = 0>
__device__ __forceinline__ void wgmma_ss_n64(float (&d)[32], uint64_t da, uint64_t db, int scale_d) {
  asm volatile("{\n.reg .pred p;\nsetp.ne.b32 p, %34, 0;\n"
    "wgmma.mma_async.sync.aligned.m64n64k16.f32.bf16.bf16 {%0, %1, %2, %3, %4, %5, %6, %7, %8, %9, %10, %11, %12, %13, %14, %15, %16, %17, %18, %19, %20, %21, %22, %23, %24, %25, %26, %27, %28, %29, %30, %31}, %32, %33, p, 1, 1, %35, %36;\n}\n"
    : "+f"(d[0]), "+f"(d[1]), "+f"(d[2]), "+f"(d[3]), "+f"(d[4]), "+f"(d[5]), "+f"(d[6]), "+f"(d[7]), "+f"(d[8]), "+f"(d[9]), "+f"(d[10]), "+f"(d[11]), "+f"(d[12]), "+f"(d[13]), "+f"(d[14]), "+f"(d[15]), "+f"(d[16]), "+f"(d[17]), "+f"(d[18]), "+f"(d[19]), "+f"(d[20]), "+f"(d[21]), "+f"(d[22]), "+f"(d[23]), "+f"(d[24]), "+f"(d[25]), "+f"(d[26]), "+f"(d[27]), "+f"(d[28]), "+f"(d[29]), "+f"(d[30]), "+f"(d[31])
    : "l"(da), "l"(db), "r"(scale_d), "n"(TA), "n"(TB));
}
template <int TB>
__device__ __forceinline__ void wgmma_rs_n64(float (&d)[32], uint32_t a0, uint32_t a1, uint32_t a2, uint32_t a3, uint64_t db, int scale_d) {
  asm volatile("{\n.reg .pred p;\nsetp.ne.b32 p, %37, 0;\n"
    "wgmma.mma_async.sync.aligned.m64n64k16.f32.bf16.bf16 {%0, %1, %2, %3, %4, %5, %6, %7, %8, %9, %10, %11, %12, %13, %14, %15, %16, %17, %18, %19, %20, %21, %22, %23, %24, %25, %26, %27, %28, %29, %30, %31}, {%32, %33, %34, %35}, %36, p, 1, 1, %38;\n}\n"
    : "+f"(d[0]), "+f"(d[1]), "+f"(d[2]), "+f"(d[3]), "+f"(d[4]), "+f"(d[5]), "+f"(d[6]), "+f"(d[7]), "+f"(d[8]), "+f"(d[9]), "+f"(d[10]), "+f"(d[11]), "+f"(d[12]), "+f"(d[13]), "+f"(d[14]), "+f"(d[15]), "+f"(d[16]), "+f"(d[17]), "+f"(d[18]), "+f"(d[19]), "+f"(d[20]), "+f"(d[21]), "+f"(d[22]), "+f"(d[23]), "+f"(d[24]), "+f"(d[25]), "+f"(d[26]), "+f"(d[27]), "+f"(d[28]), "+f"(d[29]), "+f"(d[30]), "+f"(d[31])
    : "r"(a0), "r"(a1), "r"(a2), "r"(a3), "l"(db), "r"(scale_d), "n"(TB));
}
template <int TB, int TA = 0>
__device__ __forceinline__ void wgmma_ss_n160(float (&d)[80], uint64_t da, uint64_t db, int scale_d) {
  asm volatile("{\n.reg .pred p;\nsetp.ne.b32 p, %82, 0;\n"
    "wgmma.mma_async.sync.aligned.m64n160k16.f32.bf16.bf16 {%0, %1, %2, %3, %4, %5, %6, %7, %8, %9, %10, %11, %12, %13, %14, %15, %16, %17, %18, %19, %20, %21, %22, %23, %24, %25, %26, %27, %28, %29, %30, %31, %32, %33, %34, %35, %36, %37, %38, %39, %40, %41, %42, %43, %44, %45, %46, %47, %48, %49, %50, %51, %52, %53, %54, %55, %56, %57, %58, %59, %60, %61, %62, %63, %64, %65, %66, %67, %68, %69, %70, %71, %72, %73, %74, %75, %76, %77, %78, %79}, %80, %81, p, 1, 1, %83, %84;\n}\n"
    : "+f"(d[0]), "+f"(d[1]), "+f"(d[2]), "+f"(d[3]), "+f"(d[4]), "+f"(d[5]), "+f"(d[6]), "+f"(d[7]), "+f"(d[8]), "+f"(d[9]), "+f"(d[10]), "+f"(d[11]), "+f"(d[12]), "+f"(d[13]), "+f"(d[14]), "+f"(d[15]), "+f"(d[16]), "+f"(d[17]), "+f"(d[18]), "+f"(d[19]), "+f"(d[20]), "+f"(d[21]), "+f"(d[22]), "+f"(d[23]), "+f"(d[24]), "+f"(d[25]), "+f"(d[26]), "+f"(d[27]), "+f"(d[28]), "+f"(d[29]), "+f"(d[30]), "+f"(d[31]), "+f"(d[32]), "+f"(d[33]), "+f"(d[34]), "+f"(d[35]), "+f"(d[36]), "+f"(d[37]), "+f"(d[38]), "+f"(d[39]), "+f"(d[40]), "+f"(d[41]), "+f"(d[42]), "+f"(d[43]), "+f"(d[44]), "+f"(d[45]), "+f"(d[46]), "+f"(d[47]), "+f"(d[48]), "+f"(d[49]), "+f"(d[50]), "+f"(d[51]), "+f"(d[52]), "+f"(d[53]), "+f"(d[54]), "+f"(d[55]), "+f"(d[56]), "+f"(d[57]), "+f"(d[58]), "+f"(d[59]), "+f"(d[60]), "+f"(d[61]), "+f"(d[62]), "+f"(d[63]), "+f"(d[64]), "+f"(d[65]), "+f"(d[66]), "+f"(d[67]), "+f"(d[68]), "+f"(d[69]), "+f"(d[70]), "+f"(d[71]), "+f"(d[72]), "+f"(d[73]), "+f"(d[74]), "+f"(d[75]), "+f"(d[76]), "+f"(d[77]), "+f"(d[78]), "+f"(d[79])
    : "l"(da), "l"(db), "r"(scale_d), "n"(TA), "n"(TB));
}
template <int TB>
__device__ __forceinline__ void wgmma_rs_n160(float (&d)[80], uint32_t a0, uint32_t a1, uint32_t a2, uint32_t a3, uint64_t db, int scale_d) {
  asm volatile("{\n.reg .pred p;\nsetp.ne.b32 p, %85, 0;\n"
    "wgmma.mma_async.sync.aligned.m64n160k16.f32.bf16.bf16 {%0, %1, %2, %3, %4, %5, %6, %7, %8, %9, %10, %11, %12, %13, %14, %15, %16, %17, %18, %19, %20, %21, %22, %23, %24, %25, %26, %27, %28, %29, %30, %31, %32, %33, %34, %35, %36, %37, %38, %39, %40, %41, %42, %43, %44, %45, %46, %47, %48, %49, %50, %51, %52, %53, %54, %55, %56, %57, %58, %59, %60, %61, %62, %63, %64, %65, %66, %67, %68, %69, %70, %71, %72, %73, %74, %75, %76, %77, %78, %79}, {%80, %81, %82, %83}, %84, p, 1, 1, %86;\n}\n"
    : "+f"(d[0]), "+f"(d[1]), "+f"(d[2]), "+f"(d[3]), "+f"(d[4]), "+f"(d[5]), "+f"(d[6]), "+f"(d[7]), "+f"(d[8]), "+f"(d[9]), "+f"(d[10]), "+f"(d[11]), "+f"(d[12]), "+f"(d[13]), "+f"(d[14]), "+f"(d[15]), "+f"(d[16]), "+f"(d[17]), "+f"(d[18]), "+f"(d[19]), "+f"(d[20]), "+f"(d[21]), "+f"(d[22]), "+f"(d[23]), "+f"(d[24]), "+f"(d[25]), "+f"(d[26]), "+f"(d[27]), "+f"(d[28]), "+f"(d[29]), "+f"(d[30]), "+f"(d[31]), "+f"(d[32]), "+f"(d[33]), "+f"(d[34]), "+f"(d[35]), "+f"(d[36]), "+f"(d[37]), "+f"(d[38]), "+f"(d[39]), "+f"(d[40]), "+f"(d[41]), "+f"(d[42]), "+f"(d[43]), "+f"(d[44]), "+f"(d[45]), "+f"(d[46]), "+f"(d[47]), "+f"(d[48]), "+f"(d[49]), "+f"(d[50]), "+f"(d[51]), "+f"(d[52]), "+f"(d[53]), "+f"(d[54]), "+f"(d[55]), "+f"(d[56]), "+f"(d[57]), "+f"(d[58]), "+f"(d[59]), "+f"(d[60]), "+f"(d[61]), "+f"(d[62]), "+f"(d[63]), "+f"(d[64]), "+f"(d[65]), "+f"(d[66]), "+f"(d[67]), "+f"(d[68]), "+f"(d[69]), "+f"(d[70]), "+f"(d[71]), "+f"(d[72]), "+f"(d[73]), "+f"(d[74]), "+f"(d[75]), "+f"(d[76]), "+f"(d[77]), "+f"(d[78]), "+f"(d[79])
    : "r"(a0), "r"(a1), "r"(a2), "r"(a3), "l"(db), "r"(scale_d), "n"(TB));
}
template <int TB, int TA = 0>
__device__ __forceinline__ void wgmma_ss_n192(float (&d)[96], uint64_t da, uint64_t db, int scale_d) {
  asm volatile("{\n.reg .pred p;\nsetp.ne.b32 p, %98, 0;\n"
    "wgmma.mma_async.sync.aligned.m64n192k16.f32.bf16.bf16 {%0, %1, %2, %3, %4, %5, %6, %7, %8, %9, %10, %11, %12, %13, %14, %15, %16, %17, %18, %19, %20, %21, %22, %23, %24, %25, %26, %27, %28, %29, %30, %31, %32, %33, %34, %35, %36, %37, %38, %39, %40, %41, %42, %43, %44, %45, %46, %47, %48, %49, %50, %51, %52, %53, %54, %55, %56, %57, %58, %59, %60, %61, %62, %63, %64, %65, %66, %67, %68, %69, %70, %71, %72, %73, %74, %75, %76, %77, %78, %79, %80, %81, %82, %83, %84, %85, %86, %87, %88, %89, %90, %91, %92, %93, %94, %95}, %96, %97, p, 1, 1, %99, %100;\n}\n"
    : "+f"(d[0]), "+f"(d[1]), "+f"(d[2]), "+f"(d[3]), "+f"(d[4]), "+f"(d[5]), "+f"(d[6]), "+f"(d[7]), "+f"(d[8]), "+f"(d[9]), "+f"(d[10]), "+f"(d[11]), "+f"(d[12]), "+f"(d[13]), "+f"(d[14]), "+f"(d[15]), "+f"(d[16]), "+f"(d[17]), "+f"(d[18]), "+f"(d[19]), "+f"(d[20]), "+f"(d[21]), "+f"(d[22]), "+f"(d[23]), "+f"(d[24]), "+f"(d[25]), "+f"(d[26]), "+f"(d[27]), "+f"(d[28]), "+f"(d[29]), "+f"(d[30]), "+f"(d[31]), "+f"(d[32]), "+f"(d[33]), "+f"(d[34]), "+f"(d[35]), "+f"(d[36]), "+f"(d[37]), "+f"(d[38]), "+f"(d[39]), "+f"(d[40]), "+f"(d[41]), "+f"(d[42]), "+f"(d[43]), "+f"(d[44]), "+f"(d[45]), "+f"(d[46]), "+f"(d[47]), "+f"(d[48]), "+f"(d[49]), "+f"(d[50]), "+f"(d[51]), "+f"(d[52]), "+f"(d[53]), "+f"(d[54]), "+f"(d[55]), "+f"(d[56]), "+f"(d[57]), "+f"(d[58]), "+f"(d[59]), "+f"(d[60]), "+f"(d[61]), "+f"(d[62]), "+f"(d[63]), "+f"(d[64]), "+f"(d[65]), "+f"(d[66]), "+f"(d[67]), "+f"(d[68]), "+f"(d[69]), "+f"(d[70]), "+f"(d[71]), "+f"(d[72]), "+f"(d[73]), "+f"(d[74]), "+f"(d[75]), "+f"(d[76]), "+f"(d[77]), "+f"(d[78]), "+f"(d[79]), "+f"(d[80]), "+f"(d[81]), "+f"(d[82]), "+f"(d[83]), "+f"(d[84]), "+f"(d[85]), "+f"(d[86]), "+f"(d[87]), "+f"(d[88]), "+f"(d[89]), "+f"(d[90]), "+f"(d[91]), "+f"(d[92]), "+f"(d[93]), "+f"(d[94]), "+f"(d[95])
    : "l"(da), "l"(db), "r"(scale_d), "n"(TA), "n"(TB));
}
template <int TB>
__device__ __forceinline__ void wgmma_rs_n192(float (&d)[96], uint32_t a0, uint32_t a1, uint32_t a2, uint32_t a3, uint64_t db, int scale_d) {
  asm volatile("{\n.reg .pred p;\nsetp.ne.b32 p, %101, 0;\n"
    "wgmma.mma_async.sync.aligned.m64n192k16.f32.bf16.bf16 {%0, %1, %2, %3, %4, %5, %6, %7, %8, %9, %10, %11, %12, %13, %14, %15, %16, %17, %18, %19, %20, %21, %22, %23, %24, %25, %26, %27, %28, %29, %30, %31, %32, %33, %34, %35, %36, %37, %38, %39, %40, %41, %42, %43, %44, %45, %46, %47, %48, %49, %50, %51, %52, %53, %54, %55, %56, %57, %58, %59, %60, %61, %62, %63, %64, %65, %66, %67, %68, %69, %70, %71, %72, %73, %74, %75, %76, %77, %78, %79, %80, %81, %82, %83, %84, %85, %86, %87, %88, %89, %90, %91, %92, %93, %94, %95}, {%96, %97, %98, %99}, %100, p, 1, 1, %102;\n}\n"
    : "+f"(d[0]), "+f"(d[1]), "+f"(d[2]), "+f"(d[3]), "+f"(d[4]), "+f"(d[5]), "+f"(d[6]), "+f"(d[7]), "+f"(d[8]), "+f"(d[9]), "+f"(d[10]), "+f"(d[11]), "+f"(d[12]), "+f"(d[13]), "+f"(d[14]), "+f"(d[15]), "+f"(d[16]), "+f"(d[17]), "+f"(d[18]), "+f"(d[19]), "+f"(d[20]), "+f"(d[21]), "+f"(d[22]), "+f"(d[23]), "+f"(d[24]), "+f"(d[25]), "+f"(d[26]), "+f"(d[27]), "+f"(d[28]), "+f"(d[29]), "+f"(d[30]), "+f"(d[31]), "+f"(d[32]), "+f"(d[33]), "+f"(d[34]), "+f"(d[35]), "+f"(d[36]), "+f"(d[37]), "+f"(d[38]), "+f"(d[39]), "+f"(d[40]), "+f"(d[41]), "+f"(d[42]), "+f"(d[43]), "+f"(d[44]), "+f"(d[45]), "+f"(d[46]), "+f"(d[47]), "+f"(d[48]), "+f"(d[49]), "+f"(d[50]), "+f"(d[51]), "+f"(d[52]), "+f"(d[53]), "+f"(d[54]), "+f"(d[55]), "+f"(d[56]), "+f"(d[57]), "+f"(d[58]), "+f"(d[59]), "+f"(d[60]), "+f"(d[61]), "+f"(d[62]), "+f"(d[63]), "+f"(d[64]), "+f"(d[65]), "+f"(d[66]), "+f"(d[67]), "+f"(d[68]), "+f"(d[69]), "+f"(d[70]), "+f"(d[71]), "+f"(d[72]), "+f"(d[73]), "+f"(d[74]), "+f"(d[75]), "+f"(d[76]), "+f"(d[77]), "+f"(d[78]), "+f"(d[79]), "+f"(d[80]), "+f"(d[81]), "+f"(d[82]), "+f"(d[83]), "+f"(d[84]), "+f"(d[85]), "+f"(d[86]), "+f"(d[87]), "+f"(d[88]), "+f"(d[89]), "+f"(d[90]), "+f"(d[91]), "+f"(d[92]), "+f"(d[93]), "+f"(d[94]), "+f"(d[95])
    : "r"(a0), "r"(a1), "r"(a2), "r"(a3), "l"(db), "r"(scale_d), "n"(TB));
}

__device__ __forceinline__ uint32_t smem_u32(const void* p) { return (uint32_t)__cvta_generic_to_shared(p); }
__device__ __forceinline__ void wg_fence() { asm volatile("wgmma.fence.sync.aligned;" ::: "memory"); }
__device__ __forceinline__ void wg_commit() { asm volatile("wgmma.commit_group.sync.aligned;" ::: "memory"); }
template <int N> __device__ __forceinline__ void wg_wait() { asm volatile("wgmma.wait_group.sync.aligned %0;" ::"n"(N) : "memory"); }
__device__ __forceinline__ void sched_fence(uint32_t& keep) {
  asm volatile("{\n.reg .u32 c;\nmov.u32 c, %%clock;\nxor.b32 %0, %0, c;\n}\n" : "+r"(keep)::"memory");
}
template <int N> __device__ __forceinline__ void fence_regs(float (&r)[N]) {
#pragma unroll
  for (int i = 0; i < N; i++) asm volatile("" : "+f"(r[i])::"memory");
}
template <int N> __device__ __forceinline__ void fence_regs(uint32_t (&r)[N]) {
#pragma unroll
  for (int i = 0; i < N; i++) asm volatile("" : "+r"(r[i])::"memory");
}
__device__ __forceinline__ uint64_t mk_desc(uint32_t a16, uint32_t lbo, uint32_t sbo, uint32_t swz) {
  uint64_t d;
  asm("mov.b64 %0, {%1, %2};" : "=l"(d) : "r"(a16 + ((lbo >> 4) << 16)), "r"((sbo >> 4) | (swz << 30)));
  return d;
}
__device__ __forceinline__ void mbar_init(uint32_t bar, uint32_t cnt) {
  asm volatile("mbarrier.init.shared::cta.b64 [%0], %1;" ::"r"(bar), "r"(cnt) : "memory");
}
__device__ __forceinline__ void mbar_expect(uint32_t bar, uint32_t tx) {
  asm volatile("mbarrier.arrive.expect_tx.shared::cta.b64 _, [%0], %1;" ::"r"(bar), "r"(tx) : "memory");
}
__device__ __forceinline__ bool mbar_test(uint32_t bar, uint32_t ph) {
  uint32_t ok;
  asm volatile("{\n.reg .pred p;\nmbarrier.test_wait.parity.shared::cta.b64 p, [%1], %2;\nselp.u32 %0, 1, 0, p;\n}\n"
               : "=r"(ok) : "r"(bar), "r"(ph) : "memory");
  return ok;
}
__device__ __forceinline__ void mbar_wait(uint32_t bar, uint32_t ph) {
  asm volatile("{\n.reg .pred p;\n.reg .u32 n;\n"
               "mbarrier.try_wait.parity.shared::cta.b64 p, [%0], %1;\n@p bra DONE;\n"
               "mov.u32 n, 0;\n"
               "LOOP:\nmbarrier.try_wait.parity.shared::cta.b64 p, [%0], %1;\n@p bra DONE;\n"
               "add.u32 n, n, 1;\nsetp.lt.u32 p, n, 0x1000000;\n@p bra LOOP;\ntrap;\n"
               "DONE:\n}\n" ::"r"(bar), "r"(ph) : "memory");
}
template <int NS> __device__ __forceinline__ void mbar_wait_slow(uint32_t bar, uint32_t ph) {
  asm volatile("{\n.reg .pred p;\n.reg .u32 n;\nmov.u32 n, 0;\n"
               "LOOP:\nmbarrier.test_wait.parity.shared::cta.b64 p, [%0], %1;\n@p bra DONE;\n"
               "nanosleep.u32 %2;\nadd.u32 n, n, 1;\nsetp.lt.u32 p, n, 0x400000;\n@p bra LOOP;\ntrap;\n"
               "DONE:\n}\n" ::"r"(bar), "r"(ph), "n"(NS) : "memory");
}
__device__ __forceinline__ void mbar_arrive_cluster_if(bool on, uint32_t addr) {
  asm volatile("{\n.reg .pred p;\nsetp.ne.b32 p, %1, 0;\n@p mbarrier.arrive.shared::cluster.b64 _, [%0];\n}\n" ::"r"(addr), "r"((int)on) : "memory");
}
__device__ __forceinline__ void mbar_arrive_if(bool on, uint32_t addr) {
  asm volatile("{\n.reg .pred p;\nsetp.ne.b32 p, %1, 0;\n@p mbarrier.arrive.shared::cta.b64 _, [%0];\n}\n" ::"r"(addr), "r"((int)on) : "memory");
}
__device__ __forceinline__ void tma2d(uint32_t dst, const CUtensorMap* m, uint32_t bar, int c0, int c1) {
  asm volatile("cp.async.bulk.tensor.2d.shared::cluster.global.mbarrier::complete_tx::bytes [%0], [%1, {%3, %4}], [%2];"
               ::"r"(dst), "l"(m), "r"(bar), "r"(c0), "r"(c1) : "memory");
}
__device__ __forceinline__ void tma3d(uint32_t dst, const CUtensorMap* m, uint32_t bar, int c0, int c1, int c2) {
  asm volatile("cp.async.bulk.tensor.3d.shared::cluster.global.mbarrier::complete_tx::bytes [%0], [%1, {%3, %4, %5}], [%2];"
               ::"r"(dst), "l"(m), "r"(bar), "r"(c0), "r"(c1), "r"(c2) : "memory");
}
__device__ __forceinline__ void tma3d_mc(uint32_t dst, const CUtensorMap* m, uint32_t bar, int c0, int c1, int c2) {
  asm volatile("cp.async.bulk.tensor.3d.shared::cluster.global.mbarrier::complete_tx::bytes.multicast::cluster"
               " [%0], [%1, {%3, %4, %5}], [%2], %6;"
               ::"r"(dst), "l"(m), "r"(bar), "r"(c0), "r"(c1), "r"(c2), "h"((uint16_t)3) : "memory");
}
__device__ __forceinline__ void tma3d_store(const CUtensorMap* m, uint32_t src, int c0, int c1, int c2) {
  asm volatile("cp.async.bulk.tensor.3d.global.shared::cta.bulk_group [%0, {%2, %3, %4}], [%1];"
               ::"l"(m), "r"(src), "r"(c0), "r"(c1), "r"(c2) : "memory");
}
__device__ __forceinline__ void bar_sync(int id, int n) { asm volatile("bar.sync %0, %1;" ::"r"(id), "r"(n) : "memory"); }
__device__ __forceinline__ uint32_t pack_bf16(float lo, float hi) {
  uint32_t r;
  asm("cvt.rn.bf16x2.f32 %0, %1, %2;" : "=r"(r) : "f"(hi), "f"(lo));
  return r;
}
__device__ __forceinline__ float ex2(float x) {
  float y;
  asm("ex2.approx.ftz.f32 %0, %1;" : "=f"(y) : "f"(x));
  return y;
}
__device__ __forceinline__ float fadd(float a, float b) {
  float y;
  asm("add.f32 %0, %1, %2;" : "=f"(y) : "f"(a), "f"(b));
  return y;
}
__device__ __forceinline__ float rcp(float x) {
  float y;
  asm("rcp.approx.ftz.f32 %0, %1;" : "=f"(y) : "f"(x));
  return y;
}
__device__ __forceinline__ void stsm4(uint32_t addr, uint32_t a, uint32_t b, uint32_t c, uint32_t d) {
  asm volatile("stmatrix.sync.aligned.m8n8.x4.shared.b16 [%0], {%1, %2, %3, %4};" ::"r"(addr), "r"(a), "r"(b), "r"(c), "r"(d) : "memory");
}

__device__ __forceinline__ void tma4d_mc_hint(uint32_t dst, const CUtensorMap* m, uint32_t bar, int c3, uint64_t pol) {
  asm volatile("cp.async.bulk.tensor.4d.shared::cluster.global.mbarrier::complete_tx::bytes.multicast::cluster.L2::cache_hint"
               " [%0], [%1, {%3, %3, %3, %4}], [%2], %5, %6;"
               ::"r"(dst), "l"(m), "r"(bar), "r"(0), "r"(c3), "h"((uint16_t)3), "l"(pol) : "memory");
}
__device__ __forceinline__ void tma5d_mc(uint32_t dst, const CUtensorMap* m, uint32_t bar, int c2, int c4) {
  asm volatile("cp.async.bulk.tensor.5d.shared::cluster.global.mbarrier::complete_tx::bytes.multicast::cluster"
               " [%0], [%1, {%3, %3, %4, %3, %5}], [%2], %6;"
               ::"r"(dst), "l"(m), "r"(bar), "r"(0), "r"(c2), "r"(c4), "h"((uint16_t)3) : "memory");
}
__device__ __forceinline__ void bulk_load_hint(uint32_t dst, const void* src, uint32_t bytes, uint32_t bar, uint64_t pol) {
  asm volatile("cp.async.bulk.shared::cluster.global.mbarrier::complete_tx::bytes.L2::cache_hint [%0], [%1], %2, [%3], %4;"
               ::"r"(dst), "l"(src), "r"(bytes), "r"(bar), "l"(pol) : "memory");
}
__device__ __forceinline__ void stg128_hint(void* p, uint32_t a, uint32_t b, uint32_t c, uint32_t d, uint64_t pol) {
  asm volatile("st.global.L2::cache_hint.v4.b32 [%0], {%1, %2, %3, %4}, %5;" ::"l"(p), "r"(a), "r"(b), "r"(c), "r"(d), "l"(pol) : "memory");
}
__device__ __forceinline__ void stg2_if(bool on, void* p, uint32_t a, uint32_t b, uint32_t c, uint32_t d, uint32_t e, uint32_t f,
                                        uint32_t g, uint32_t h, uint64_t pol) {
  asm volatile("{\n.reg .pred p;\nsetp.ne.b32 p, %10, 0;\n"
               "@p st.global.L2::cache_hint.v4.b32 [%0], {%1, %2, %3, %4}, %9;\n"
               "@p st.global.L2::cache_hint.v4.b32 [%0 + 512], {%5, %6, %7, %8}, %9;\n}\n"
               ::"l"(p), "r"(a), "r"(b), "r"(c), "r"(d), "r"(e), "r"(f), "r"(g), "r"(h), "l"(pol), "r"((int)on) : "memory");
}
__device__ __forceinline__ uint64_t make_policy(bool first) {
  uint64_t pf, pn;
  asm("createpolicy.fractional.L2::evict_first.b64 %0, 1.0;" : "=l"(pf));
  asm("createpolicy.fractional.L2::evict_normal.b64 %0, 1.0;" : "=l"(pn));
  return first ? pf : pn;
}
__device__ __forceinline__ bool elect() {
  uint32_t ok;
  asm volatile("{\n.reg .pred p;\nelect.sync _|p, 0xffffffff;\nselp.u32 %0, 1, 0, p;\n}\n" : "=r"(ok));
  return ok;
}
__device__ __forceinline__ void mbar_arrive(uint32_t bar) {
  asm volatile("mbarrier.arrive.shared::cta.b64 _, [%0];" ::"r"(bar) : "memory");
}
__device__ __forceinline__ void stg128(void* p, uint32_t a, uint32_t b, uint32_t c, uint32_t d) {
  asm volatile("st.global.v4.b32 [%0], {%1, %2, %3, %4};" ::"l"(p), "r"(a), "r"(b), "r"(c), "r"(d) : "memory");
}
__device__ __forceinline__ void lds128(uint32_t p, uint32_t& a, uint32_t& b, uint32_t& c, uint32_t& d) {
  asm volatile("ld.shared.v4.b32 {%0, %1, %2, %3}, [%4];" : "=r"(a), "=r"(b), "=r"(c), "=r"(d) : "r"(p) : "memory");
}
__device__ __forceinline__ void wait_count(const unsigned int* p, uint32_t target) {
  asm volatile("{\n.reg .pred p;\n.reg .u32 n, v;\nmov.u32 n, 0;\n"
               "LOOP:\nld.acquire.gpu.global.u32 v, [%0];\nsetp.ge.u32 p, v, %1;\n@p bra DONE;\n"
               "nanosleep.u32 %2;\nadd.u32 n, n, 1;\nsetp.lt.u32 p, n, 0x400000;\n@p bra LOOP;\ntrap;\n"
               "DONE:\n}\n" ::"l"(p), "r"(target), "n"(200) : "memory");
}

__host__ __device__ __forceinline__ int o_wave(int a, int b, int i, int lag) {
  if (lag == 0) return a + i;
  const int p = lag < b - a - 1 ? lag : b - a - 1;
  return i < p ? b - 2 - i : i == p ? b - 1 : b - 1 - i;
}

struct Cursor {
  int bi;
  uint32_t ph;
  __device__ __forceinline__ void next() {
    if (++bi == NBAR) { bi = 0; ph ^= 1; }
  }
};

constexpr float kScaleLog2 = 0.07216878364870322f * 1.4426950408889634f;
constexpr float kSumLimit = 1048576.0f;
constexpr float kMaxLag = 8.0f;

__global__ void __cluster_dims__(2, 1, 1) __launch_bounds__(384, 1)
fused_kernel(const __grid_constant__ Params P) {
  extern __shared__ uint8_t smem_raw[];
  const uint32_t sbase = (smem_u32(smem_raw) + 1023) & ~1023u;
  const uint32_t full0 = sbase + RING, empty0 = full0 + 8 * NBAR, odone = empty0 + 8 * NBAR, oready0 = odone + 8;
  const uint32_t fenced = oready0 + 64, hready0 = fenced + 8;
  const uint32_t rank = blockIdx.x & 1;
  const int role = blockIdx.x >> 1;
  const bool helper = role >= N_CL;
  const int team = helper ? 0 : role >> 2, nt = role & 3, blk = team >> 3;
  const uint32_t* prog = P.ops[helper ? N_TEAM + 2 * (role - N_CL) : team];
  auto q_role = [&](uint32_t op) { return helper ? (int)(((op >> 3) & 60) | ((op >> 12) & 3)) : role; };
  auto o_role = [&](uint32_t op) { return helper ? (int)(((op >> 26) & 56) | ((op >> 9) & 7)) : role; };
  const int wid = __shfl_sync(0xffffffffu, (int)(threadIdx.x >> 5), 0);
  const int wg = wid >> 2;

  const uint32_t op0 = P.first[helper ? N_TEAM + role - N_CL : team];
  if (__builtin_expect(wid == 8, 1)) {
    if (elect()) {
#pragma unroll
      for (int k = 0; k < EARLY; k++) mbar_init(full0 + 8 * k, 1);
      asm volatile("fence.mbarrier_init.release.cluster;" ::: "memory");
      if ((op0 & 3) == OP_Q) {
        const int qr = q_role(op0);
#pragma unroll
        for (int k = 0; k < EARLY; k++) {
          mbar_expect(full0 + 8 * k, SZ_Q);
          tma2d(sbase + k * SZ_Q, &P.x[qr >> 5], full0 + 8 * k, 64 * k, ((qr >> 2) & 7) * kSq + rank * 128);
          tma3d(sbase + k * SZ_Q + 16384, &P.wq[qr >> 5], full0 + 8 * k, 0, 64 * k, 3 * (4 * ((op0 >> 2) & 7) + (qr & 3)));
        }
      }
      asm volatile("prefetch.tensormap [%0];" ::"l"(rank ? &P.v[blk] : &P.k[blk]) : "memory");
    }
  } else if (threadIdx.x == 0) {
#pragma unroll
    for (int i = EARLY; i < 2 * NBAR + 10 + MAX_PARK; i++) mbar_init(full0 + 8 * i, i < NBAR ? 1 : i < 2 * NBAR ? 16 : i == 2 * NBAR ? 8 : 1);
    asm volatile("fence.mbarrier_init.release.cluster;" ::: "memory");
  }
  __syncwarp();
  asm volatile("barrier.cluster.arrive.relaxed.aligned;\nbarrier.cluster.wait.aligned;" ::: "memory");

  if (wg == 2) {
    asm volatile("setmaxnreg.dec.sync.aligned.u32 24;");
    if (wid == 8) {
      Cursor tail{0, 0};
      int head = 0, sh = 0;
      uint32_t cur = 0, used = 0;
      uint64_t fifo = 0;
      uint32_t dst, bar, oready = oready0;
      uint64_t pol;
      asm volatile("createpolicy.fractional.L2::evict_first.b64 %0, 1.0;" : "=l"(pol));
      const uint64_t pol_o = make_policy(P.dbg & 1), pol_p = make_policy(!(P.dbg & 4));
      const CUtensorMap* kv_map = rank ? &P.v[blk] : &P.k[blk];
      auto acquire = [&](uint32_t bytes) {
        uint32_t fp = bytes >> 12;
        if (cur + fp > (RING >> 12)) { fp += (RING >> 12) - cur; cur = 0; }
        used += fp;
        while (used > (RING >> 12) || sh == 5 * NBAR) {
          mbar_wait(empty0 + 8 * tail.bi, tail.ph);
          tail.next();
          used -= (uint32_t)fifo & 31;
          fifo >>= 5;
          sh -= 5;
        }
        fifo |= (uint64_t)fp << sh;
        sh += 5;
        dst = sbase + (cur << 12);
        bar = full0 + 8 * head;
        cur += bytes >> 12;
        if (++head == NBAR) head = 0;
      };
      for (int pc = 0;; pc++) {
        const uint32_t op = prog[pc];
        const int type = op & 3, a = (op >> 2) & 7;
        if (type == OP_END) break;
        if (type == OP_Q) {
          const int qr = q_role(op);
#pragma unroll 1
          for (int k = 0; k < 10; k++) {
            acquire(SZ_Q);
            if ((pc > 0 || k >= EARLY) && elect()) {
              mbar_expect(bar, SZ_Q);
              tma2d(dst, &P.x[qr >> 5], bar, 64 * k, ((qr >> 2) & 7) * kSq + rank * 128);
              if ((k & 1) == rank) tma3d_mc(dst + 16384, &P.wq[qr >> 5], bar, 0, 64 * k, 3 * (4 * a + (qr & 3)));
            }
          }
        } else if (type == OP_A) {
          const uint32_t nop = prog[pc + 1];
          auto kv = [&](int isv, int wave, int j) {
            const int row0 = ((team & 7) * kH + 4 * wave + nt) * kSk;
            acquire(SZ_KV);
            if (elect()) {
              mbar_expect(bar, SZ_KV);
              if (isv == (int)rank) tma4d_mc_hint(dst, kv_map, bar, row0 / 8 + 8 * j, pol);
            }
          };
#pragma unroll 1
          for (int t = (op & F_PARK) ? 1 : 0; t < 31; t++) {
            const int isv = t == 0 ? 0 : (~t & 1);
            kv(isv, a, isv ? (t - 1) >> 1 : (t + 1) >> 1);
          }
          if ((nop & 3) == OP_A) {
            mbar_wait((nop & F_HELP) ? hready0 + 8 * ((nop >> 10) & 3) : fenced, 0);
            asm volatile("fence.proxy.async.global;" ::: "memory");
#pragma unroll 1
            for (int i = 0; i < 2; i++) {
              acquire(SZ_PARK);
              if (elect()) {
                mbar_expect(bar, SZ_PARK);
                bulk_load_hint(dst, &g_park[((role * 2 + rank) * MAX_PARK + ((nop >> 10) & 3)) * 3072 + i * 1536], SZ_PARK, bar, pol_p);
              }
            }
            kv(0, (nop >> 2) & 7, 0);
          }
          kv(1, a, 15);
        } else {
          const int b = (op >> 5) & 15, ro = o_role(op);
#pragma unroll 1
          for (int i = 0; i < b - a; i++) {
            const int w = o_wave(a, b, i, (P.dbg >> 4) & 7);
            mbar_wait(oready, 0);
            oready += 8;
            asm volatile("fence.proxy.async.global;" ::: "memory");
#pragma unroll 1
            for (int k = 12 * w; k < 12 * w + 12; k++) {
              acquire(SZ_O);
              if (elect()) {
                mbar_expect(bar, SZ_O);
                tma5d_mc(dst + 16384 + rank * 10240, &P.wo[ro >> 5], bar, 8 * k + 4 * rank, 5 * (ro & 3));
                bulk_load_hint(dst, &g_o[(((ro >> 2) * 2 + rank) * 96 + k - 12 * (w - P.slot[w])) * 1024], 16384, bar, pol_o);
              }
            }
          }
          if (op & F_LD) {
            if (op & F_PARK) {
              mbar_wait(hready0 + 8 * (MAX_PARK - 1), 0);
              asm volatile("fence.proxy.async.global;" ::: "memory");
            }
#pragma unroll 1
            for (int i = 0; i < 2; i++) {
              acquire(SZ_PART);
              if (elect()) {
                mbar_expect(bar, SZ_PART);
                bulk_load_hint(dst, &g_part[(role * 2 + rank) * 5120 + i * 2560], SZ_PART, bar, pol_p);
              }
            }
          }
        }
      }
    } else if (threadIdx.x == 288) {
      uint32_t ph = 0;
      bool first = true;
      for (int pc = 0;; pc++) {
        const uint32_t op = prog[pc];
        if ((op & 3) == OP_END) break;
        if ((op & 3) != OP_A && !helper) continue;
        mbar_wait_slow<400>(odone, ph);
        ph ^= 1;
        unsigned int* flag = !helper ? &g_done[(team * 2 + rank) * 8 + ((op >> 2) & 7)]
                             : (op & 3) == OP_Q ? &g_help[(q_role(op) * 2 + rank) * MAX_PARK + ((op >> 10) & 3)]
                                                : &g_help[(o_role(op) * 2 + rank) * MAX_PARK + MAX_PARK - 1];
        asm volatile("red.release.gpu.global.add.u32 [%0], 1;" ::"l"(flag) : "memory");
        if (first) mbar_arrive(fenced);
        first = false;
      }
    } else if (threadIdx.x == 320) {
      uint32_t oready = oready0;
      for (int pc = 0;; pc++) {
        const uint32_t op = prog[pc];
        if ((op & 3) == OP_END) break;
        if ((op & 3) == OP_O) {
          const int a = (op >> 2) & 7, b = (op >> 5) & 15;
          for (int i = 0; i < b - a; i++) {
            const int ci = ((o_role(op) >> 2) * 2 + rank) * 8 + o_wave(a, b, i, (P.dbg >> 4) & 7);
            wait_count(&g_done[ci], 4);
            mbar_arrive(oready);
            oready += 8;
            if (atomicAdd(&g_seen[ci], 1u) == 3u) { g_seen[ci] = 0; g_done[ci] = 0; }
          }
        }
        if ((op & 3) != OP_Q && (op & F_HELP) && (op & F_PARK)) {
          unsigned int* flag = &g_help[(role * 2 + rank) * MAX_PARK + ((op >> 10) & 3)];
          wait_count(flag, 1);
          mbar_arrive(hready0 + 8 * ((op >> 10) & 3));
          *flag = 0;
        }
      }
    }
    __syncwarp();
    asm volatile("barrier.cluster.arrive.relaxed;\nbarrier.cluster.wait;" ::: "memory");
  } else {
    asm volatile("setmaxnreg.inc.sync.aligned.u32 240;");
    const int lane = threadIdx.x & 31, warp = wid & 3;
    uint32_t empty_rem;
    asm volatile("mapa.shared::cluster.u32 %0, %1, %2;" : "=r"(empty_rem) : "r"(empty0), "r"(lane & 1));
    auto release = [&](int slot) { mbar_arrive_cluster_if(lane < 2, empty_rem + 8 * slot); };
    Cursor r{0, 0};
    const uint32_t ring16 = (sbase & 0x3FFFF) >> 4;
    uint32_t cur = ring16;
    bool rdy0 = false, rdy1 = false;
    auto probe1 = [&]() { rdy0 = mbar_test(full0 + 8 * r.bi, r.ph); };
    auto probe2 = [&]() {
      Cursor n = r;
      rdy0 = mbar_test(full0 + 8 * n.bi, n.ph);
      n.next();
      rdy1 = mbar_test(full0 + 8 * n.bi, n.ph);
    };
    auto take = [&](bool rdy, uint32_t bytes, uint32_t& addr) {
      const int bi = r.bi;
      if (!__all_sync(0xffffffffu, rdy)) mbar_wait(full0 + 8 * r.bi, r.ph);
      r.next();
      if (cur > ring16 + ((RING - bytes) >> 4)) cur = ring16;
      addr = cur;
      cur += bytes >> 4;
      return bi;
    };
    uint32_t keep = 0;
    const int row = wg * 64 + warp * 16 + (lane >> 2);
    const int img0 = row * 4 + ((lane & 3) ^ ((row >> 1) & 3));
    uint4* pend = nullptr;
    uint64_t spol;
    int pc = 0;
    uint32_t op = prog[0];
    auto enter = [&]() {
      r.bi = (op >> 15) & 15; r.ph = (op >> 19) & 1; cur = ring16 + (((op >> 20) & 63) << 8);
      spol = make_policy(!(op & F_SOON));
    };
    auto drain = [&](uint32_t (&t)[48], uint32_t c) {
      if (!(op & (3u << 26)) || c >= 6) return;
#pragma unroll
      for (int i = 0; i < 6; i++)
        stg2_if(c == i, pend + i * 512, t[8 * i], t[8 * i + 1], t[8 * i + 2], t[8 * i + 3],
                t[8 * i + 4], t[8 * i + 5], t[8 * i + 6], t[8 * i + 7], spol);
      if ((op & (1u << 26)) && c == 5) {
        __syncwarp();
        mbar_arrive_if(lane == 0, odone);
      }
    };
    float s[32], o[96], c[80];
    uint32_t q[48], pa[16], pb[16];
    float mc0, mc1, l0, l1;
    bool gen;
    auto expo = [&](float (&s)[32], uint32_t (&pout)[16], float& b0, float& b1, bool sub) {
#pragma unroll
      for (int i = 0; i < 8; i++) {
        const float e1 = ex2(sub ? s[4 * i + 1] - mc0 : s[4 * i + 1]), e0 = ex2(sub ? s[4 * i] - mc0 : s[4 * i]);
        const float e3 = ex2(sub ? s[4 * i + 3] - mc1 : s[4 * i + 3]), e2 = ex2(sub ? s[4 * i + 2] - mc1 : s[4 * i + 2]);
        pout[2 * i] = pack_bf16(e0, e1);
        b0 = i ? b0 + fadd(e1, e0) : fadd(e1, e0);
        pout[2 * i + 1] = pack_bf16(e2, e3);
        b1 = i ? b1 + fadd(e3, e2) : fadd(e3, e2);
      }
    };
    auto rowmax = [&](float (&s)[32], float& m0, float& m1) {
      m0 = fmaxf(s[0], s[1]); m1 = fmaxf(s[2], s[3]);
#pragma unroll
      for (int i = 1; i < 8; i++) { m0 = fmaxf(m0, fmaxf(s[4 * i], s[4 * i + 1])); m1 = fmaxf(m1, fmaxf(s[4 * i + 2], s[4 * i + 3])); }
      m0 = fmaxf(m0, __shfl_xor_sync(0xffffffffu, m0, 1)); m1 = fmaxf(m1, __shfl_xor_sync(0xffffffffu, m1, 1));
      m0 = fmaxf(m0, __shfl_xor_sync(0xffffffffu, m0, 2)); m1 = fmaxf(m1, __shfl_xor_sync(0xffffffffu, m1, 2));
    };
    auto first = [&](float (&s)[32]) {
      mc0 = 0.f; mc1 = 0.f;
      expo(s, pa, l0, l1, false);
      gen = __any_sync(0xffffffffu, !(fmaxf(l0, l1) <= kSumLimit && fminf(l0, l1) >= 1.0f / kSumLimit));
      if (gen) {
        rowmax(s, mc0, mc1);
        expo(s, pa, l0, l1, true);
      }
    };
    auto soft = [&](uint32_t (&pout)[16]) {
      float b0, b1;
      if (!gen) {
        expo(s, pout, b0, b1, false);
        gen = __any_sync(0xffffffffu, !(fmaxf(b0, b1) <= kSumLimit));
      }
      if (gen) {
        float m0, m1;
        rowmax(s, m0, m1);
        if (__any_sync(0xffffffffu, !(m0 <= mc0 + kMaxLag && m1 <= mc1 + kMaxLag))) {
          m0 = fmaxf(mc0, m0); m1 = fmaxf(mc1, m1);
          const float a0 = ex2(mc0 - m0), a1 = ex2(mc1 - m1);
          mc0 = m0; mc1 = m1;
          l0 *= a0; l1 *= a1;
          wg_wait<0>();
          fence_regs(o);
#pragma unroll
          for (int i = 0; i < 24; i++) { o[4 * i] *= a0; o[4 * i + 1] *= a0; o[4 * i + 2] *= a1; o[4 * i + 3] *= a1; }
        }
        expo(s, pout, b0, b1, true);
      }
      l0 += b0; l1 += b1;
    };
    auto qk = [&](float (&s)[32], uint32_t ak, int k0, int k1) {
#pragma unroll
      for (int kk = k0; kk < k1; kk++)
        wgmma_rs_n64<0>(s, q[4 * kk], q[4 * kk + 1], q[4 * kk + 2], q[4 * kk + 3], mk_desc(ak + (kk >> 2) * KV_CH + (kk & 3) * 2, 16, KV_SBO, 1), kk != 0);
      wg_commit();
    };
    auto pv = [&](uint32_t (&pin)[16], uint32_t av, int acc) {
#pragma unroll
      for (int kk = 0; kk < 4; kk++)
        wgmma_rs_n192<1>(o, pin[4 * kk], pin[4 * kk + 1], pin[4 * kk + 2], pin[4 * kk + 3], mk_desc(av + kk * (KV_SBO / 8), KV_CH * 16, KV_SBO, 1), acc || (kk != 0));
      wg_commit();
    };
    auto xw = [&](uint32_t ad, int acc) {
      wg_fence();
#pragma unroll
      for (int kk = 0; kk < 4; kk++)
        wgmma_ss_n192<1>(o, mk_desc(ad + wg * 512 + kk * 2, 16, 1024, 1), mk_desc(ad + 1024 + kk * 128, 8192, 1024, 1), acc || kk != 0);
      wg_commit();
    };
    auto ow = [&](int acc, int prev) {
      uint32_t ad;
      const int bi = take(rdy0, SZ_O, ad);
      const uint32_t da = ad + wg * 256, db = ad + 1024;
      wg_fence();
      wgmma_ss_n160<1>(c, mk_desc(da, 16, 512, 2), mk_desc(db, 2048, 512, 2), acc);
      wgmma_ss_n160<1>(c, mk_desc(da + 2, 16, 512, 2), mk_desc(db + 64, 2048, 512, 2), 1);
      wg_commit();
      if (acc) { wg_wait<1>(); release(prev); }
      wgmma_ss_n160<1>(c, mk_desc(da + 512, 16, 512, 2), mk_desc(db + 640, 2048, 512, 2), 1);
      wgmma_ss_n160<1>(c, mk_desc(da + 514, 16, 512, 2), mk_desc(db + 704, 2048, 512, 2), 1);
      wg_commit();
      return bi;
    };
    auto o_run = [&](uint32_t (&t)[48], int bi) {
      const int nk = 12 * (((op >> 5) & 15) - ((op >> 2) & 7));
#pragma unroll 1
      for (int k = 0; k < 6; k++) {
        drain(t, k);
        probe1();
        wg_wait<1>();
        bi = ow(1, bi);
      }
#pragma unroll 1
      for (int k = 7; k < nk; k++) {
        probe1();
        wg_wait<1>();
        bi = ow(1, bi);
      }
      probe1();
      return bi;
    };
    auto st_part = [&](int i) {
      stg2_if(true, pend + i * 512, __float_as_uint(c[8 * i]), __float_as_uint(c[8 * i + 1]), __float_as_uint(c[8 * i + 2]), __float_as_uint(c[8 * i + 3]),
              __float_as_uint(c[8 * i + 4]), __float_as_uint(c[8 * i + 5]), __float_as_uint(c[8 * i + 6]), __float_as_uint(c[8 * i + 7]), spol);
    };
#pragma unroll
    for (int i = 0; i < 48; i++) q[i] = 0;
    enter();

    if ((op & 3) == OP_Q) {
      uint32_t ad;
      int bi0 = take(false, SZ_Q, ad), k = 0, lag = 0;
      xw(ad, 0);
      for (;;) {
#pragma unroll 1
        for (;;) {
          drain(q, k - lag);
          probe1();
          wg_wait<0>();
          release(bi0);
          bi0 = take(rdy0, SZ_Q, ad);
          if (++k == 8) break;
          xw(ad, 1);
        }
        if (wg) bar_sync(2, 256);
        xw(ad, 1);
        const int bi9 = take(false, SZ_Q, ad);
        xw(ad, 1);
        if (!wg) asm volatile("bar.arrive 2, 256;" ::: "memory");
        k = 0; lag = 0;
        uint32_t nop = prog[++pc];
        if (op & F_PARK) {
          pend = &g_park[((q_role(op) * 2 + rank) * MAX_PARK + ((op >> 10) & 3)) * 3072 + img0];
          op = nop;
          enter();
          wg_wait<1>();
          release(bi0);
          probe1();
          wg_wait<0>();
          fence_regs(o);
          release(bi9);
#pragma unroll
          for (int i = 0; i < 48; i++) q[i] = pack_bf16(o[2 * i] * kScaleLog2, o[2 * i + 1] * kScaleLog2);
          if ((op & 3) != OP_Q) break;
          fence_regs(q);
          bi0 = take(rdy0, SZ_Q, ad);
          xw(ad, 0);
          continue;
        }
        int wave = (op >> 2) & 7, sk1;
        uint32_t ak1;
        {
          wg_wait<1>();
          release(bi0);
          probe2();
          wg_wait<0>();
          fence_regs(o);
          release(bi9);
          float s0[32];
#pragma unroll
          for (int i = 0; i < 48; i++) q[i] = pack_bf16(o[2 * i] * kScaleLog2, o[2 * i + 1] * kScaleLog2);
          fence_regs(q);
          const int sk0 = take(rdy0, SZ_KV, ad);
          wg_fence();
          qk(s0, ad, 0, 12);
          sk1 = take(rdy1, SZ_KV, ak1);
          wg_fence();
          qk(s, ak1, 0, S1A);
          probe1();
          wg_wait<1>();
          fence_regs(s0);
          release(sk0);
          first(s0);
        }
        float i0, i1;
        auto sums = [&]() {
          l0 += __shfl_xor_sync(0xffffffffu, l0, 1); l1 += __shfl_xor_sync(0xffffffffu, l1, 1);
          l0 += __shfl_xor_sync(0xffffffffu, l0, 2); l1 += __shfl_xor_sync(0xffffffffu, l1, 2);
          i0 = rcp(l0); i1 = rcp(l1);
          asm volatile("" : "+f"(i0), "+f"(i1));
        };
        auto target = [&]() {
          pend = &g_o[((team * 2 + rank) * 96 + 3 * (4 * P.slot[wave] + nt)) * 1024 + img0];
          asm volatile("" : "+l"(pend));
        };
        for (;;) {
          nop = prog[++pc];
          {
            uint32_t av;
            const int sv = take(rdy0, SZ_KV, av);
            wg_fence();
            qk(s, ak1, S1A, 12);
            pv(pa, av, 0);
            probe2();
            wg_wait<1>();
            fence_regs(s);
            release(sk1);
            soft(pb);
            wg_wait<0>();
            fence_regs(o);
            release(sv);
          }
          auto step = [&](uint32_t (&pin)[16], uint32_t (&pout)[16]) {
            uint32_t ak, av;
            const int sk = take(rdy0, SZ_KV, ak), sv = take(rdy1, SZ_KV, av);
            wg_fence();
            qk(s, ak, 0, 12);
            pv(pin, av, 1);
            probe2();
            wg_wait<1>();
            fence_regs(s);
            release(sk);
            soft(pout);
            wg_wait<0>();
            fence_regs(o);
            release(sv);
          };
#pragma unroll 1
          for (int jj = 0; jj < 7; jj++) {
            step(pb, pa);
            step(pa, pb);
          }
          if ((nop & 3) != OP_A) break;
          uint32_t ak, av;
          {
            const int b0 = take(rdy0, SZ_PARK, ak), b1 = take(rdy1, SZ_PARK, av);
            const uint32_t ad0 = ak, ad1 = av;
            probe2();
#pragma unroll
            for (int i = 0; i < 12; i++)
              lds128(sbase + ((i < 6 ? ad0 : ad1) - ring16 + img0) * 16 + ((i % 6) >> 1) * 8192 + (i & 1) * 512, q[4 * i], q[4 * i + 1], q[4 * i + 2], q[4 * i + 3]);
            release(b0); release(b1);
          }
          const int sk0 = take(rdy0, SZ_KV, ak), sv = take(rdy1, SZ_KV, av);
          wg_fence();
          qk(s, ak, 0, 8);
          sched_fence(keep);
          sums();
          sched_fence(keep);
          qk(s, ak, 8, 12);
          pv(pb, av, 1);
          probe2();
          spol = make_policy(!(nop & F_SOON));
          wg_wait<1>();
          fence_regs(s);
          release(sk0);
          first(s);
          sk1 = take(rdy0, SZ_KV, ak1);
          rdy0 = rdy1;
          wg_wait<0>();
          target();
          fence_regs(o);
          release(sv);
          uint32_t t[48];
#pragma unroll
          for (int j = 0; j < 6; j++) {
#pragma unroll
            for (int i = 0; i < 4; i++) {
              t[8 * j + i] = pack_bf16(o[16 * j + 4 * i] * i0, o[16 * j + 4 * i + 1] * i0);
              t[8 * j + i + 4] = pack_bf16(o[16 * j + 4 * i + 2] * i1, o[16 * j + 4 * i + 3] * i1);
            }
            stg2_if(true, pend + j * 512, t[8 * j], t[8 * j + 1], t[8 * j + 2], t[8 * j + 3], t[8 * j + 4], t[8 * j + 5], t[8 * j + 6], t[8 * j + 7], spol);
            if (j == UC0) { wg_fence(); qk(s, ak1, 0, 4); }
            if (j == UC1) { wg_fence(); qk(s, ak1, 4, S1A); }
            sched_fence(keep);
          }
          if (P.zero) {
#pragma unroll
            for (int j = 0; j < 5; j++)
              stg2_if(true, pend, t[8 * j], t[8 * j + 1], t[8 * j + 2], t[8 * j + 3], t[8 * j + 4], t[8 * j + 5], t[8 * j + 6], t[8 * j + 7], spol);
          }
          __syncwarp();
          mbar_arrive_if(lane == 0, odone);
          wave = (nop >> 2) & 7;
        }
        const int sv = take(rdy0, SZ_KV, ad);
        wg_fence();
        pv(pb, ad, 1);
        sums();
        target();
        op = nop;
        enter();
        rdy0 = rdy1;
        auto convert = [&](uint32_t (&t)[48], float (&u)[96]) {
#pragma unroll
          for (int i = 0; i < 24; i++) {
            t[8 * (i >> 2) + (i & 3)] = pack_bf16(u[4 * i], u[4 * i + 1]);
            t[8 * (i >> 2) + (i & 3) + 4] = pack_bf16(u[4 * i + 2], u[4 * i + 3]);
          }
        };
        if ((op & 3) != OP_O) {
          if ((op & 3) == OP_Q) bi0 = take(rdy0, SZ_Q, ad);
          wg_wait<0>();
          fence_regs(o);
          release(sv);
          float u[96];
#pragma unroll
          for (int i = 0; i < 96; i++) u[i] = o[i] * (i & 2 ? i1 : i0);
          if ((op & 3) != OP_Q) { convert(q, u); break; }
          fence_regs(u);
          xw(ad, 0);
          sched_fence(keep);
          fence_regs(u);
          convert(q, u);
          continue;
        }
        int bi = ow(0, 0);
        wg_wait<2>();
        fence_regs(o);
        release(sv);
        {
          uint32_t t[48];
#pragma unroll
          for (int i = 0; i < 96; i++) o[i] *= i & 2 ? i1 : i0;
          convert(t, o);
          bi = o_run(t, bi);
        }
        nop = prog[++pc];
        if (op & F_LD) {
          uint32_t t[80], ad0, ad1;
          const int b0 = take(rdy0, SZ_PART, ad0), b1 = take(false, SZ_PART, ad1);
          rdy0 = false;
#pragma unroll
          for (int i = 0; i < 20; i++)
            lds128(sbase + ((i < 10 ? ad0 : ad1) - ring16 + img0) * 16 + ((i % 10) >> 1) * 8192 + (i & 1) * 512, t[4 * i], t[4 * i + 1], t[4 * i + 2], t[4 * i + 3]);
          fence_regs(t);
          wg_wait<0>();
          fence_regs(c);
          release(b0); release(b1);
#pragma unroll
          for (int i = 0; i < 80; i++) c[i] += __uint_as_float(t[i]);
        }
        if (!(op & F_ST)) {
          wg_wait<0>();
          fence_regs(c);
          goto finish;
        }
        op = nop;
        enter();
        bi0 = take(rdy0, SZ_Q, ad);
        xw(ad, 0);
        pend = &g_part[(role * 2 + rank) * 5120 + img0];
        probe1();
        wg_wait<1>();
        fence_regs(c);
        release(bi);
        st_part(6); st_part(7);
        wg_wait<0>();
        release(bi0);
        bi0 = take(rdy0, SZ_Q, ad);
        xw(ad, 1);
        st_part(8); st_part(9);
#pragma unroll
        for (int i = 0; i < 48; i++) q[i] = __float_as_uint(c[i]);
        k = 1; lag = 2;
      }
    }
    rdy0 = false;
    {
      uint32_t t[48];
#pragma unroll
      for (int i = 0; i < 48; i++) t[i] = q[i] ^ P.zero;
      while ((op & 3) == OP_O) {
        const int bi = o_run(t, ow(0, 0));
        wg_wait<0>();
        fence_regs(c);
        pc++;
        if (!(op & F_ST)) goto finish;
        release(bi);
        pend = &g_part[(o_role(op) * 2 + rank) * 5120 + img0];
#pragma unroll
        for (int i = 6; i < 10; i++) st_part(i);
#pragma unroll
        for (int i = 0; i < 48; i++) t[i] = __float_as_uint(c[i]) ^ P.zero;
        op = prog[pc];
        enter();
      }
      for (int i = 0; i < 6; i++) drain(t, i);
    }
    asm volatile("barrier.cluster.arrive.relaxed;" ::: "memory");
    if (false) {
    finish:
      asm volatile("barrier.cluster.arrive.relaxed;" ::: "memory");
      bar_sync(1, 256);
      const uint32_t wstage = sbase + (wg * 4 + warp) * 5120;
      const uint32_t sa = wstage + (lane & 15) * 64;
#pragma unroll
      for (int i = 0; i < 10; i++) {
        const int u = (i & 1) * 2 + (lane >> 4);
        stsm4(sa + (i >> 1) * 1024 + ((u ^ ((lane >> 1) & 3)) << 4), pack_bf16(c[8 * i], c[8 * i + 1]), pack_bf16(c[8 * i + 2], c[8 * i + 3]),
              pack_bf16(c[8 * i + 4], c[8 * i + 5]), pack_bf16(c[8 * i + 6], c[8 * i + 7]));
      }
      asm volatile("fence.proxy.async.shared::cta;" ::: "memory");
      __syncwarp();
      if (lane == 0) {
        tma3d_store(&P.out, wstage, 0, (team & 7) * kSq + rank * 128 + wg * 64 + warp * 16, blk * 20 + nt * 5);
        asm volatile("cp.async.bulk.commit_group;\ncp.async.bulk.wait_group.read 0;" ::: "memory");
      }
      __syncwarp();
    }
    if (P.dbg == 0xffffffffu) g_seen[0] = keep;
    asm volatile("barrier.cluster.wait;" ::: "memory");
  }
}

typedef CUresult (*EncodeFn)(CUtensorMap*, CUtensorMapDataType, cuuint32_t, void*, const cuuint64_t*, const cuuint64_t*,
                             const cuuint32_t*, const cuuint32_t*, CUtensorMapInterleave, CUtensorMapSwizzle,
                             CUtensorMapL2promotion, CUtensorMapFloatOOBfill);

void encode(EncodeFn fn, CUtensorMap* m, const void* ptr, int rank, const cuuint64_t* dims, const cuuint64_t* strides,
            const cuuint32_t* box, CUtensorMapSwizzle swz) {
  const cuuint32_t es[5] = {1, 1, 1, 1, 1};
  CUresult r = fn(m, CU_TENSOR_MAP_DATA_TYPE_BFLOAT16, rank, const_cast<void*>(ptr), dims, strides, box, es,
                  CU_TENSOR_MAP_INTERLEAVE_NONE, swz, CU_TENSOR_MAP_L2_PROMOTION_L2_128B, CU_TENSOR_MAP_FLOAT_OOB_FILL_NONE);
  if (r != CUDA_SUCCESS) fprintf(stderr, "cuTensorMapEncodeTiled failed: %d\n", (int)r);
}

void annotate(uint32_t* ops, int n, bool helper) {
  uint32_t items = 0, cur = 0, pend = 0;
  auto item = [&](uint32_t bytes, int count) {
    for (int i = 0; i < count; i++) { if (cur + bytes > RING) cur = 0; cur += bytes; items++; }
  };
  for (int i = 0; i <= n; i++) {
    const uint32_t op = ops[i];
    ops[i] |= (items % NBAR) << 15 | ((items / NBAR) & 1) << 19 | (cur >> 12) << 20 | pend << 26;
    if ((op & 3) == OP_Q) { item(SZ_Q, 10); pend = (op & F_PARK) ? (helper ? 1 : 2) : 0; }
    if ((op & 3) == OP_A) {
      item(SZ_KV, (op & F_PARK) ? 30 : 31);
      if ((ops[i + 1] & 3) == OP_A) { item(SZ_PARK, 2); item(SZ_KV, 1); }
      item(SZ_KV, 1);
      pend = 1;
    }
    if ((op & 3) == OP_O) {
      item(SZ_O, 12 * (((op >> 5) & 15) - ((op >> 2) & 7)));
      if (op & F_LD) item(SZ_PART, 2);
      pend = (op & F_LAZY) ? (helper ? 1 : 2) : 0;
    }
  }
}

void compile_programs(const char* const* text, bool helpers, Params& P) {
  struct Req { int when, team, wave, slot; } req[N_TEAM * MAX_PARK];
  int n_req = 0;
  for (int t = 0; t < N_TEAM; t++) {
    uint32_t* ops = P.ops[t];
    int n = 0, flags[8] = {0, 0, 0, 0, 0, 0, 0, 0}, n_park = 0, last_o = -1, when = 0, given = 0;
    for (const char* s = text[t]; *s; s++) {
      const int a = s[1] - '0';
      if (*s == 'Q' || (*s == 'H' && !helpers)) { ops[n++] = OP_Q | a << 2; when += 10; }
      else if (*s == 'P') { flags[a] = F_PARK | n_park++ << 10; ops[n++] = OP_Q | a << 2 | flags[a]; when += 10; }
      else if (*s == 'H') { req[n_req++] = {when, t, a, n_park}; flags[a] = F_PARK | F_HELP | n_park++ << 10; }
      else if (*s == 'A') { ops[n++] = OP_A | a << 2 | flags[a]; when += 32; }
      else if (*s == 'G') { given = a; if (helpers) req[n_req++] = {1000, t, 0, -a}; }
      else if (*s == 'O') {
        ops[n] = OP_O | a << 2 | (s[2] - '0') << 5;
        if (given) ops[n] = helpers ? ops[n] | F_LD | F_PARK | (MAX_PARK - 1) << 10 : ops[n] & ~(7u << 2);
        if (last_o >= 0) { ops[last_o] |= F_ST; ops[n] |= F_LD; }
        last_o = n++;
        when += 10 * (s[2] - s[1]);
      }
    }
    for (int i = 0; i + 1 < n; i++)
      if ((ops[i] & 3) == OP_O && (ops[i] & F_ST) && (ops[i + 1] & 3) == OP_Q) ops[i] |= F_LAZY;
    for (int i = n; i < MAX_OPS; i++) ops[i] = OP_END;
    annotate(ops, n, false);
    for (int i = 0; i < n; i++) {
      if ((ops[i] & 3) != OP_A && (P.dbg & 8)) ops[i + 1] |= F_SOON;
      if ((ops[i] & 3) != OP_A) continue;
      const int w = (ops[i] >> 2) & 7;
      int dist = 0;
      for (int j = i + 1; j < n; j++) {
        const int a = (ops[j] >> 2) & 7, b = (ops[j] >> 5) & 15;
        if ((ops[j] & 3) == OP_O && w < b) {
          for (int k = 0; k < b - a && o_wave(a, b, k, (P.dbg >> 4) & 7) != w; k++) dist += 10;
          break;
        }
        dist += (ops[j] & 3) == OP_Q ? 10 : (ops[j] & 3) == OP_A ? 32 : 10 * (b - a);
      }
      if (dist <= (int)((P.dbg >> 8) & 255)) ops[i + 1] |= F_SOON;
    }
  }
  for (int i = 1; i < n_req; i++)
    for (int j = i; j > 0 && req[j].when < req[j - 1].when; j--) { Req r = req[j]; req[j] = req[j - 1]; req[j - 1] = r; }
  for (int h = 0; h < N_HELP; h++) {
    uint32_t* ops = P.ops[N_TEAM + 2 * h];
    int n = 0;
    for (int i = 0; i < n_req; i++)
      for (int m = h; m < 4; m += N_HELP) {
        const uint32_t ro = 4 * req[i].team + m;
        ops[n++] = req[i].slot >= 0 ? OP_Q | req[i].wave << 2 | req[i].team << 5 | F_PARK | req[i].slot << 10 | m << 12
                                    : OP_O | -req[i].slot << 5 | F_ST | F_LAZY | F_SOON | (ro & 7) << 9 | (ro >> 3) << 29;
      }
    for (int i = n; i < 2 * MAX_OPS; i++) ops[i] = OP_END | F_SOON;
    annotate(ops, n, true);
  }
  for (int i = 0; i < 32; i++) P.first[i] = i < N_TEAM ? P.ops[i][0] : i < N_TEAM + N_HELP ? P.ops[2 * i - N_TEAM][0] : 0;
}

const char* const kPrograms[N_TEAM] = {
  "Q0A0Q1A1H2A2O03Q3A3Q4A4Q5A5Q6A6Q7A7O38",
  "Q0A0Q1A1Q2A2H3A3Q4A4O03Q5A5Q6A6Q7A7O38",
  "Q0A0H1A1Q2A2Q3A3O04Q4A4Q5A5Q6A6Q7A7O48",
  "Q0A0Q1A1Q2A2Q3A3O02Q4A4Q5A5Q6A6H7A7O28",
  "Q0A0Q1A1Q2A2O03Q3A3Q4A4Q5A5Q6A6H7A7O38",
  "Q0A0Q1A1Q2A2Q3A3Q4A4O05Q5A5Q6A6H7A7O58",
  "Q0A0Q1A1Q2A2Q3A3Q4A4O05Q5A5Q6A6H7A7O58",
  "Q0A0Q1A1Q2A2O03Q3A3Q4A4H5A5Q6A6Q7A7O38",
  "P7Q0A0Q1A1O01Q2A2H3A3Q4A4Q5A5Q6A6A7O18",
  "P3P5Q0A0Q1A1Q2A2A3Q4A4A5H6A6Q7A7O08",
  "P7Q0A0Q1A1Q2A2Q3A3H4A4Q5A5Q6A6A7O08",
  "P3P7Q0A0Q1A1H2A2A3Q4A4Q5A5Q6A6A7O08",
  "Q0A0Q1A1Q2A2O01Q3A3Q4A4H5A5Q6A6Q7A7O18",
  "P3Q0A0Q1A1Q2A2A3Q4A4Q5A5Q6A6Q7A7G1O18",
  "P6Q0A0Q1A1Q2A2Q3A3Q4A4Q5A5A6Q7A7G1O18",
  "P2P6Q0A0Q1A1A2Q3A3H4A4Q5A5A6Q7A7O08",
};

const char* const* bench_programs() {
  return kPrograms;
}

}

extern "C" void kernel_launch(void* const* d_in, const int* in_sizes, int n_in, void* d_out, int out_size) {
  (void)in_sizes; (void)n_in; (void)out_size;
  static EncodeFn fn = nullptr;
  static int n_clusters = 0;
  if (!fn) {
    cudaDriverEntryPointQueryResult qr;
    void* f = nullptr;
    cudaGetDriverEntryPoint("cuTensorMapEncodeTiled", &f, cudaEnableDefault, &qr);
    fn = (EncodeFn)f;
    cudaFuncSetAttribute(fused_kernel, cudaFuncAttributeMaxDynamicSharedMemorySize, SMEM_BYTES);
    cudaLaunchConfig_t cfg = {};
    cfg.gridDim = dim3(132); cfg.blockDim = dim3(384); cfg.dynamicSmemBytes = SMEM_BYTES;
    cudaLaunchAttribute at[1];
    at[0].id = cudaLaunchAttributeClusterDimension; at[0].val.clusterDim.x = 2; at[0].val.clusterDim.y = 1; at[0].val.clusterDim.z = 1;
    cfg.attrs = at; cfg.numAttrs = 1;
    if (cudaOccupancyMaxActiveClusters(&n_clusters, fused_kernel, &cfg) != cudaSuccess || n_clusters < 1) n_clusters = 1;
    (void)cudaGetLastError();
  }
  Params P;
  const CUtensorMapSwizzle S128 = CU_TENSOR_MAP_SWIZZLE_128B, S64 = CU_TENSOR_MAP_SWIZZLE_64B;
  for (int blk = 0; blk < 2; blk++) {
    void* const* in = d_in + 5 * blk;
    { const cuuint64_t d[] = {kD, kB * kSq}, s[] = {kD * 2}; const cuuint32_t b[] = {64, 128};
      encode(fn, &P.x[blk], in[0], 2, d, s, b, S128); }
    { const cuuint64_t d[] = {64, 8, 3, (cuuint64_t)kB * kH * kSk / 8}, s[] = {kDh * 2, 128, 8 * kDh * 2}; const cuuint32_t b[] = {64, 8, 3, 8};
      encode(fn, &P.k[blk], in[1], 4, d, s, b, S128);
      encode(fn, &P.v[blk], in[2], 4, d, s, b, S128); }
    { const cuuint64_t d[] = {64, kD, kHD / 64}, s[] = {kHD * 2, 128}; const cuuint32_t b[] = {64, 64, 3};
      encode(fn, &P.wq[blk], in[3], 3, d, s, b, S128); }
    { const cuuint64_t d[] = {32, 2, kHD / 8, 4, kD / 32}, s[] = {kD * 2, 8 * kD * 2, 2 * kD * 2, 64}; const cuuint32_t b[] = {32, 2, 4, 4, 5};
      encode(fn, &P.wo[blk], in[4], 5, d, s, b, S64); }
  }
  { const cuuint64_t d[] = {32, kB * kSq, 2 * kD / 32}, s[] = {2 * kD * 2, 64}; const cuuint32_t b[] = {32, 16, 5};
    encode(fn, &P.out, d_out, 3, d, s, b, S64); }

  P.zero = 0;
  P.dbg = 0x5030;
  for (int w = 0; w < 8; w++) P.slot[w] = (P.dbg >> 16) & 15 ? w % ((P.dbg >> 16) & 15) : w;
  if (n_clusters >= N_CL) {
    const bool helpers = n_clusters >= N_CL + N_HELP;
    compile_programs(bench_programs(), helpers, P);
    fused_kernel<<<2 * (N_CL + (helpers ? N_HELP : 0)), 384, SMEM_BYTES>>>(P);
  } else {
    for (int phase = 0; phase < 2; phase++) {
      const char* text[N_TEAM];
      for (int t = 0; t < N_TEAM; t++) text[t] = phase ? "O08" : "Q0A0Q1A1Q2A2Q3A3Q4A4Q5A5Q6A6Q7A7";
      compile_programs(text, false, P);
      fused_kernel<<<2 * N_CL, 384, SMEM_BYTES>>>(P);
    }
  }
}
```

```cpp
#include <cuda_runtime.h>
#include <cuda_bf16.h>
#include <cuda.h>
#include <stdint.h>
#include <stdio.h>

namespace {

constexpr int kB = 8, kSq = 256, kD = 640, kH = 32, kSk = 1024, kDh = 192;
constexpr int kHD = kH * kDh;
#define S1A 8
#define UC0 2
#define UC1 5
#define RING_KB 224
constexpr uint32_t RING = RING_KB * 1024;
constexpr uint32_t SZ_KV = 24576;
constexpr uint32_t SZ_Q = 16384 + 24576;
constexpr uint32_t SZ_O = 16384 + 20480;
constexpr uint32_t SZ_PARK = 24576;
constexpr uint32_t SZ_PART = 40960;
constexpr int NBAR = 10;
constexpr int KV_TRANSIT = 4;
constexpr int EARLY = 3;
constexpr uint32_t KV_CH = 64, KV_SBO = 3072;
constexpr int SMEM_BYTES = RING + 512 + 1024;
constexpr int N_TEAM = 16, N_CL = 64, N_HELP = 2, MAX_OPS = 24, MAX_PARK = 4;
enum { OP_END = 0, OP_Q = 1, OP_A = 2, OP_O = 3, F_PARK = 1 << 9, F_LD = 1 << 12, F_ST = 1 << 13, F_LAZY = 1 << 14, F_HELP = 1 << 12, F_SOON = 1 << 28 };

struct alignas(64) Params {
  uint32_t first[32];
  CUtensorMap x[2], wq[2], k[2], v[2], wo[2], out;
  uint32_t ops[N_TEAM + 2 * N_HELP][MAX_OPS];
  uint32_t zero;
  uint32_t slot[8];
  uint32_t dbg;
};

__device__ uint4 g_o[N_TEAM * 2 * 96 * 1024];
__device__ uint4 g_part[N_CL * 2 * 5 * 1024];
__device__ unsigned int g_done[N_TEAM * 2 * 8];
__device__ unsigned int g_help[N_CL * 2 * MAX_PARK];
__device__ unsigned int g_seen[N_TEAM * 2 * 8];

template <int TB, int TA = 0>
__device__ __forceinline__ void wgmma_ss_n64(float (&d)[32], uint64_t da, uint64_t db, int scale_d) {
  asm volatile("{\n.reg .pred p;\nsetp.ne.b32 p, %34, 0;\n"
    "wgmma.mma_async.sync.aligned.m64n64k16.f32.bf16.bf16 {%0, %1, %2, %3, %4, %5, %6, %7, %8, %9, %10, %11, %12, %13, %14, %15, %16, %17, %18, %19, %20, %21, %22, %23, %24, %25, %26, %27, %28, %29, %30, %31}, %32, %33, p, 1, 1, %35, %36;\n}\n"
    : "+f"(d[0]), "+f"(d[1]), "+f"(d[2]), "+f"(d[3]), "+f"(d[4]), "+f"(d[5]), "+f"(d[6]), "+f"(d[7]), "+f"(d[8]), "+f"(d[9]), "+f"(d[10]), "+f"(d[11]), "+f"(d[12]), "+f"(d[13]), "+f"(d[14]), "+f"(d[15]), "+f"(d[16]), "+f"(d[17]), "+f"(d[18]), "+f"(d[19]), "+f"(d[20]), "+f"(d[21]), "+f"(d[22]), "+f"(d[23]), "+f"(d[24]), "+f"(d[25]), "+f"(d[26]), "+f"(d[27]), "+f"(d[28]), "+f"(d[29]), "+f"(d[30]), "+f"(d[31])
    : "l"(da), "l"(db), "r"(scale_d), "n"(TA), "n"(TB));
}
template <int TB>
__device__ __forceinline__ void wgmma_rs_n64(float (&d)[32], uint32_t a0, uint32_t a1, uint32_t a2, uint32_t a3, uint64_t db, int scale_d) {
  asm volatile("{\n.reg .pred p;\nsetp.ne.b32 p, %37, 0;\n"
    "wgmma.mma_async.sync.aligned.m64n64k16.f32.bf16.bf16 {%0, %1, %2, %3, %4, %5, %6, %7, %8, %9, %10, %11, %12, %13, %14, %15, %16, %17, %18, %19, %20, %21, %22, %23, %24, %25, %26, %27, %28, %29, %30, %31}, {%32, %33, %34, %35}, %36, p, 1, 1, %38;\n}\n"
    : "+f"(d[0]), "+f"(d[1]), "+f"(d[2]), "+f"(d[3]), "+f"(d[4]), "+f"(d[5]), "+f"(d[6]), "+f"(d[7]), "+f"(d[8]), "+f"(d[9]), "+f"(d[10]), "+f"(d[11]), "+f"(d[12]), "+f"(d[13]), "+f"(d[14]), "+f"(d[15]), "+f"(d[16]), "+f"(d[17]), "+f"(d[18]), "+f"(d[19]), "+f"(d[20]), "+f"(d[21]), "+f"(d[22]), "+f"(d[23]), "+f"(d[24]), "+f"(d[25]), "+f"(d[26]), "+f"(d[27]), "+f"(d[28]), "+f"(d[29]), "+f"(d[30]), "+f"(d[31])
    : "r"(a0), "r"(a1), "r"(a2), "r"(a3), "l"(db), "r"(scale_d), "n"(TB));
}
template <int TB, int TA = 0>
__device__ __forceinline__ void wgmma_ss_n160(float (&d)[80], uint64_t da, uint64_t db, int scale_d) {
  asm volatile("{\n.reg .pred p;\nsetp.ne.b32 p, %82, 0;\n"
    "wgmma.mma_async.sync.aligned.m64n160k16.f32.bf16.bf16 {%0, %1, %2, %3, %4, %5, %6, %7, %8, %9, %10, %11, %12, %13, %14, %15, %16, %17, %18, %19, %20, %21, %22, %23, %24, %25, %26, %27, %28, %29, %30, %31, %32, %33, %34, %35, %36, %37, %38, %39, %40, %41, %42, %43, %44, %45, %46, %47, %48, %49, %50, %51, %52, %53, %54, %55, %56, %57, %58, %59, %60, %61, %62, %63, %64, %65, %66, %67, %68, %69, %70, %71, %72, %73, %74, %75, %76, %77, %78, %79}, %80, %81, p, 1, 1, %83, %84;\n}\n"
    : "+f"(d[0]), "+f"(d[1]), "+f"(d[2]), "+f"(d[3]), "+f"(d[4]), "+f"(d[5]), "+f"(d[6]), "+f"(d[7]), "+f"(d[8]), "+f"(d[9]), "+f"(d[10]), "+f"(d[11]), "+f"(d[12]), "+f"(d[13]), "+f"(d[14]), "+f"(d[15]), "+f"(d[16]), "+f"(d[17]), "+f"(d[18]), "+f"(d[19]), "+f"(d[20]), "+f"(d[21]), "+f"(d[22]), "+f"(d[23]), "+f"(d[24]), "+f"(d[25]), "+f"(d[26]), "+f"(d[27]), "+f"(d[28]), "+f"(d[29]), "+f"(d[30]), "+f"(d[31]), "+f"(d[32]), "+f"(d[33]), "+f"(d[34]), "+f"(d[35]), "+f"(d[36]), "+f"(d[37]), "+f"(d[38]), "+f"(d[39]), "+f"(d[40]), "+f"(d[41]), "+f"(d[42]), "+f"(d[43]), "+f"(d[44]), "+f"(d[45]), "+f"(d[46]), "+f"(d[47]), "+f"(d[48]), "+f"(d[49]), "+f"(d[50]), "+f"(d[51]), "+f"(d[52]), "+f"(d[53]), "+f"(d[54]), "+f"(d[55]), "+f"(d[56]), "+f"(d[57]), "+f"(d[58]), "+f"(d[59]), "+f"(d[60]), "+f"(d[61]), "+f"(d[62]), "+f"(d[63]), "+f"(d[64]), "+f"(d[65]), "+f"(d[66]), "+f"(d[67]), "+f"(d[68]), "+f"(d[69]), "+f"(d[70]), "+f"(d[71]), "+f"(d[72]), "+f"(d[73]), "+f"(d[74]), "+f"(d[75]), "+f"(d[76]), "+f"(d[77]), "+f"(d[78]), "+f"(d[79])
    : "l"(da), "l"(db), "r"(scale_d), "n"(TA), "n"(TB));
}
template <int TB>
__device__ __forceinline__ void wgmma_rs_n160(float (&d)[80], uint32_t a0, uint32_t a1, uint32_t a2, uint32_t a3, uint64_t db, int scale_d) {
  asm volatile("{\n.reg .pred p;\nsetp.ne.b32 p, %85, 0;\n"
    "wgmma.mma_async.sync.aligned.m64n160k16.f32.bf16.bf16 {%0, %1, %2, %3, %4, %5, %6, %7, %8, %9, %10, %11, %12, %13, %14, %15, %16, %17, %18, %19, %20, %21, %22, %23, %24, %25, %26, %27, %28, %29, %30, %31, %32, %33, %34, %35, %36, %37, %38, %39, %40, %41, %42, %43, %44, %45, %46, %47, %48, %49, %50, %51, %52, %53, %54, %55, %56, %57, %58, %59, %60, %61, %62, %63, %64, %65, %66, %67, %68, %69, %70, %71, %72, %73, %74, %75, %76, %77, %78, %79}, {%80, %81, %82, %83}, %84, p, 1, 1, %86;\n}\n"
    : "+f"(d[0]), "+f"(d[1]), "+f"(d[2]), "+f"(d[3]), "+f"(d[4]), "+f"(d[5]), "+f"(d[6]), "+f"(d[7]), "+f"(d[8]), "+f"(d[9]), "+f"(d[10]), "+f"(d[11]), "+f"(d[12]), "+f"(d[13]), "+f"(d[14]), "+f"(d[15]), "+f"(d[16]), "+f"(d[17]), "+f"(d[18]), "+f"(d[19]), "+f"(d[20]), "+f"(d[21]), "+f"(d[22]), "+f"(d[23]), "+f"(d[24]), "+f"(d[25]), "+f"(d[26]), "+f"(d[27]), "+f"(d[28]), "+f"(d[29]), "+f"(d[30]), "+f"(d[31]), "+f"(d[32]), "+f"(d[33]), "+f"(d[34]), "+f"(d[35]), "+f"(d[36]), "+f"(d[37]), "+f"(d[38]), "+f"(d[39]), "+f"(d[40]), "+f"(d[41]), "+f"(d[42]), "+f"(d[43]), "+f"(d[44]), "+f"(d[45]), "+f"(d[46]), "+f"(d[47]), "+f"(d[48]), "+f"(d[49]), "+f"(d[50]), "+f"(d[51]), "+f"(d[52]), "+f"(d[53]), "+f"(d[54]), "+f"(d[55]), "+f"(d[56]), "+f"(d[57]), "+f"(d[58]), "+f"(d[59]), "+f"(d[60]), "+f"(d[61]), "+f"(d[62]), "+f"(d[63]), "+f"(d[64]), "+f"(d[65]), "+f"(d[66]), "+f"(d[67]), "+f"(d[68]), "+f"(d[69]), "+f"(d[70]), "+f"(d[71]), "+f"(d[72]), "+f"(d[73]), "+f"(d[74]), "+f"(d[75]), "+f"(d[76]), "+f"(d[77]), "+f"(d[78]), "+f"(d[79])
    : "r"(a0), "r"(a1), "r"(a2), "r"(a3), "l"(db), "r"(scale_d), "n"(TB));
}
template <int TB, int TA = 0>
__device__ __forceinline__ void wgmma_ss_n192(float (&d)[96], uint64_t da, uint64_t db, int scale_d) {
  asm volatile("{\n.reg .pred p;\nsetp.ne.b32 p, %98, 0;\n"
    "wgmma.mma_async.sync.aligned.m64n192k16.f32.bf16.bf16 {%0, %1, %2, %3, %4, %5, %6, %7, %8, %9, %10, %11, %12, %13, %14, %15, %16, %17, %18, %19, %20, %21, %22, %23, %24, %25, %26, %27, %28, %29, %30, %31, %32, %33, %34, %35, %36, %37, %38, %39, %40, %41, %42, %43, %44, %45, %46, %47, %48, %49, %50, %51, %52, %53, %54, %55, %56, %57, %58, %59, %60, %61, %62, %63, %64, %65, %66, %67, %68, %69, %70, %71, %72, %73, %74, %75, %76, %77, %78, %79, %80, %81, %82, %83, %84, %85, %86, %87, %88, %89, %90, %91, %92, %93, %94, %95}, %96, %97, p, 1, 1, %99, %100;\n}\n"
    : "+f"(d[0]), "+f"(d[1]), "+f"(d[2]), "+f"(d[3]), "+f"(d[4]), "+f"(d[5]), "+f"(d[6]), "+f"(d[7]), "+f"(d[8]), "+f"(d[9]), "+f"(d[10]), "+f"(d[11]), "+f"(d[12]), "+f"(d[13]), "+f"(d[14]), "+f"(d[15]), "+f"(d[16]), "+f"(d[17]), "+f"(d[18]), "+f"(d[19]), "+f"(d[20]), "+f"(d[21]), "+f"(d[22]), "+f"(d[23]), "+f"(d[24]), "+f"(d[25]), "+f"(d[26]), "+f"(d[27]), "+f"(d[28]), "+f"(d[29]), "+f"(d[30]), "+f"(d[31]), "+f"(d[32]), "+f"(d[33]), "+f"(d[34]), "+f"(d[35]), "+f"(d[36]), "+f"(d[37]), "+f"(d[38]), "+f"(d[39]), "+f"(d[40]), "+f"(d[41]), "+f"(d[42]), "+f"(d[43]), "+f"(d[44]), "+f"(d[45]), "+f"(d[46]), "+f"(d[47]), "+f"(d[48]), "+f"(d[49]), "+f"(d[50]), "+f"(d[51]), "+f"(d[52]), "+f"(d[53]), "+f"(d[54]), "+f"(d[55]), "+f"(d[56]), "+f"(d[57]), "+f"(d[58]), "+f"(d[59]), "+f"(d[60]), "+f"(d[61]), "+f"(d[62]), "+f"(d[63]), "+f"(d[64]), "+f"(d[65]), "+f"(d[66]), "+f"(d[67]), "+f"(d[68]), "+f"(d[69]), "+f"(d[70]), "+f"(d[71]), "+f"(d[72]), "+f"(d[73]), "+f"(d[74]), "+f"(d[75]), "+f"(d[76]), "+f"(d[77]), "+f"(d[78]), "+f"(d[79]), "+f"(d[80]), "+f"(d[81]), "+f"(d[82]), "+f"(d[83]), "+f"(d[84]), "+f"(d[85]), "+f"(d[86]), "+f"(d[87]), "+f"(d[88]), "+f"(d[89]), "+f"(d[90]), "+f"(d[91]), "+f"(d[92]), "+f"(d[93]), "+f"(d[94]), "+f"(d[95])
    : "l"(da), "l"(db), "r"(scale_d), "n"(TA), "n"(TB));
}
template <int TB>
__device__ __forceinline__ void wgmma_rs_n192(float (&d)[96], uint32_t a0, uint32_t a1, uint32_t a2, uint32_t a3, uint64_t db, int scale_d) {
  asm volatile("{\n.reg .pred p;\nsetp.ne.b32 p, %101, 0;\n"
    "wgmma.mma_async.sync.aligned.m64n192k16.f32.bf16.bf16 {%0, %1, %2, %3, %4, %5, %6, %7, %8, %9, %10, %11, %12, %13, %14, %15, %16, %17, %18, %19, %20, %21, %22, %23, %24, %25, %26, %27, %28, %29, %30, %31, %32, %33, %34, %35, %36, %37, %38, %39, %40, %41, %42, %43, %44, %45, %46, %47, %48, %49, %50, %51, %52, %53, %54, %55, %56, %57, %58, %59, %60, %61, %62, %63, %64, %65, %66, %67, %68, %69, %70, %71, %72, %73, %74, %75, %76, %77, %78, %79, %80, %81, %82, %83, %84, %85, %86, %87, %88, %89, %90, %91, %92, %93, %94, %95}, {%96, %97, %98, %99}, %100, p, 1, 1, %102;\n}\n"
    : "+f"(d[0]), "+f"(d[1]), "+f"(d[2]), "+f"(d[3]), "+f"(d[4]), "+f"(d[5]), "+f"(d[6]), "+f"(d[7]), "+f"(d[8]), "+f"(d[9]), "+f"(d[10]), "+f"(d[11]), "+f"(d[12]), "+f"(d[13]), "+f"(d[14]), "+f"(d[15]), "+f"(d[16]), "+f"(d[17]), "+f"(d[18]), "+f"(d[19]), "+f"(d[20]), "+f"(d[21]), "+f"(d[22]), "+f"(d[23]), "+f"(d[24]), "+f"(d[25]), "+f"(d[26]), "+f"(d[27]), "+f"(d[28]), "+f"(d[29]), "+f"(d[30]), "+f"(d[31]), "+f"(d[32]), "+f"(d[33]), "+f"(d[34]), "+f"(d[35]), "+f"(d[36]), "+f"(d[37]), "+f"(d[38]), "+f"(d[39]), "+f"(d[40]), "+f"(d[41]), "+f"(d[42]), "+f"(d[43]), "+f"(d[44]), "+f"(d[45]), "+f"(d[46]), "+f"(d[47]), "+f"(d[48]), "+f"(d[49]), "+f"(d[50]), "+f"(d[51]), "+f"(d[52]), "+f"(d[53]), "+f"(d[54]), "+f"(d[55]), "+f"(d[56]), "+f"(d[57]), "+f"(d[58]), "+f"(d[59]), "+f"(d[60]), "+f"(d[61]), "+f"(d[62]), "+f"(d[63]), "+f"(d[64]), "+f"(d[65]), "+f"(d[66]), "+f"(d[67]), "+f"(d[68]), "+f"(d[69]), "+f"(d[70]), "+f"(d[71]), "+f"(d[72]), "+f"(d[73]), "+f"(d[74]), "+f"(d[75]), "+f"(d[76]), "+f"(d[77]), "+f"(d[78]), "+f"(d[79]), "+f"(d[80]), "+f"(d[81]), "+f"(d[82]), "+f"(d[83]), "+f"(d[84]), "+f"(d[85]), "+f"(d[86]), "+f"(d[87]), "+f"(d[88]), "+f"(d[89]), "+f"(d[90]), "+f"(d[91]), "+f"(d[92]), "+f"(d[93]), "+f"(d[94]), "+f"(d[95])
    : "r"(a0), "r"(a1), "r"(a2), "r"(a3), "l"(db), "r"(scale_d), "n"(TB));
}

__device__ __forceinline__ uint32_t smem_u32(const void* p) { return (uint32_t)__cvta_generic_to_shared(p); }
__device__ __forceinline__ void wg_fence() { asm volatile("wgmma.fence.sync.aligned;" ::: "memory"); }
__device__ __forceinline__ void wg_commit() { asm volatile("wgmma.commit_group.sync.aligned;" ::: "memory"); }
template <int N> __device__ __forceinline__ void wg_wait() { asm volatile("wgmma.wait_group.sync.aligned %0;" ::"n"(N) : "memory"); }
__device__ __forceinline__ void sched_fence(uint32_t& keep) {
  asm volatile("{\n.reg .u32 c;\nmov.u32 c, %%clock;\nxor.b32 %0, %0, c;\n}\n" : "+r"(keep)::"memory");
}
template <int N> __device__ __forceinline__ void fence_regs(float (&r)[N]) {
#pragma unroll
  for (int i = 0; i < N; i++) asm volatile("" : "+f"(r[i])::"memory");
}
template <int N> __device__ __forceinline__ void fence_regs(uint32_t (&r)[N]) {
#pragma unroll
  for (int i = 0; i < N; i++) asm volatile("" : "+r"(r[i])::"memory");
}
__device__ __forceinline__ uint64_t mk_desc(uint32_t a16, uint32_t lbo, uint32_t sbo, uint32_t swz) {
  uint64_t d;
  asm("mov.b64 %0, {%1, %2};" : "=l"(d) : "r"(a16 + ((lbo >> 4) << 16)), "r"((sbo >> 4) | (swz << 30)));
  return d;
}
__device__ __forceinline__ void mbar_init(uint32_t bar, uint32_t cnt) {
  asm volatile("mbarrier.init.shared::cta.b64 [%0], %1;" ::"r"(bar), "r"(cnt) : "memory");
}
__device__ __forceinline__ void mbar_expect(uint32_t bar, uint32_t tx) {
  asm volatile("mbarrier.arrive.expect_tx.shared::cta.b64 _, [%0], %1;" ::"r"(bar), "r"(tx) : "memory");
}
__device__ __forceinline__ bool mbar_test(uint32_t bar, uint32_t ph) {
  uint32_t ok;
  asm volatile("{\n.reg .pred p;\nmbarrier.test_wait.parity.shared::cta.b64 p, [%1], %2;\nselp.u32 %0, 1, 0, p;\n}\n"
               : "=r"(ok) : "r"(bar), "r"(ph) : "memory");
  return ok;
}
__device__ __forceinline__ void mbar_wait(uint32_t bar, uint32_t ph) {
  asm volatile("{\n.reg .pred p;\n.reg .u32 n;\n"
               "mbarrier.try_wait.parity.shared::cta.b64 p, [%0], %1;\n@p bra DONE;\n"
               "mov.u32 n, 0;\n"
               "LOOP:\nmbarrier.try_wait.parity.shared::cta.b64 p, [%0], %1;\n@p bra DONE;\n"
               "add.u32 n, n, 1;\nsetp.lt.u32 p, n, 0x1000000;\n@p bra LOOP;\ntrap;\n"
               "DONE:\n}\n" ::"r"(bar), "r"(ph) : "memory");
}
template <int NS> __device__ __forceinline__ void mbar_wait_slow(uint32_t bar, uint32_t ph) {
  asm volatile("{\n.reg .pred p;\n.reg .u32 n;\nmov.u32 n, 0;\n"
               "LOOP:\nmbarrier.test_wait.parity.shared::cta.b64 p, [%0], %1;\n@p bra DONE;\n"
               "nanosleep.u32 %2;\nadd.u32 n, n, 1;\nsetp.lt.u32 p, n, 0x400000;\n@p bra LOOP;\ntrap;\n"
               "DONE:\n}\n" ::"r"(bar), "r"(ph), "n"(NS) : "memory");
}
__device__ __forceinline__ void mbar_arrive_cluster_if(bool on, uint32_t addr) {
  asm volatile("{\n.reg .pred p;\nsetp.ne.b32 p, %1, 0;\n@p mbarrier.arrive.shared::cluster.b64 _, [%0];\n}\n" ::"r"(addr), "r"((int)on) : "memory");
}
__device__ __forceinline__ void mbar_arrive_if(bool on, uint32_t addr) {
  asm volatile("{\n.reg .pred p;\nsetp.ne.b32 p, %1, 0;\n@p mbarrier.arrive.shared::cta.b64 _, [%0];\n}\n" ::"r"(addr), "r"((int)on) : "memory");
}
__device__ __forceinline__ void tma2d(uint32_t dst, const CUtensorMap* m, uint32_t bar, int c0, int c1) {
  asm volatile("cp.async.bulk.tensor.2d.shared::cluster.global.mbarrier::complete_tx::bytes [%0], [%1, {%3, %4}], [%2];"
               ::"r"(dst), "l"(m), "r"(bar), "r"(c0), "r"(c1) : "memory");
}
__device__ __forceinline__ void tma3d(uint32_t dst, const CUtensorMap* m, uint32_t bar, int c0, int c1, int c2) {
  asm volatile("cp.async.bulk.tensor.3d.shared::cluster.global.mbarrier::complete_tx::bytes [%0], [%1, {%3, %4, %5}], [%2];"
               ::"r"(dst), "l"(m), "r"(bar), "r"(c0), "r"(c1), "r"(c2) : "memory");
}
__device__ __forceinline__ void tma3d_mc(uint32_t dst, const CUtensorMap* m, uint32_t bar, int c0, int c1, int c2) {
  asm volatile("cp.async.bulk.tensor.3d.shared::cluster.global.mbarrier::complete_tx::bytes.multicast::cluster"
               " [%0], [%1, {%3, %4, %5}], [%2], %6;"
               ::"r"(dst), "l"(m), "r"(bar), "r"(c0), "r"(c1), "r"(c2), "h"((uint16_t)3) : "memory");
}
__device__ __forceinline__ void tma3d_store(const CUtensorMap* m, uint32_t src, int c0, int c1, int c2) {
  asm volatile("cp.async.bulk.tensor.3d.global.shared::cta.bulk_group [%0, {%2, %3, %4}], [%1];"
               ::"l"(m), "r"(src), "r"(c0), "r"(c1), "r"(c2) : "memory");
}
__device__ __forceinline__ void bar_sync(int id, int n) { asm volatile("bar.sync %0, %1;" ::"r"(id), "r"(n) : "memory"); }
__device__ __forceinline__ uint32_t pack_bf16(float lo, float hi) {
  uint32_t r;
  asm("cvt.rn.bf16x2.f32 %0, %1, %2;" : "=r"(r) : "f"(hi), "f"(lo));
  return r;
}
__device__ __forceinline__ float ex2(float x) {
  float y;
  asm("ex2.approx.ftz.f32 %0, %1;" : "=f"(y) : "f"(x));
  return y;
}
__device__ __forceinline__ float fadd(float a, float b) {
  float y;
  asm("add.f32 %0, %1, %2;" : "=f"(y) : "f"(a), "f"(b));
  return y;
}
__device__ __forceinline__ float rcp(float x) {
  float y;
  asm("rcp.approx.ftz.f32 %0, %1;" : "=f"(y) : "f"(x));
  return y;
}
__device__ __forceinline__ void stsm4(uint32_t addr, uint32_t a, uint32_t b, uint32_t c, uint32_t d) {
  asm volatile("stmatrix.sync.aligned.m8n8.x4.shared.b16 [%0], {%1, %2, %3, %4};" ::"r"(addr), "r"(a), "r"(b), "r"(c), "r"(d) : "memory");
}

__device__ __forceinline__ void tma4d_mc_hint(uint32_t dst, const CUtensorMap* m, uint32_t bar, int c3, uint64_t pol) {
  asm volatile("cp.async.bulk.tensor.4d.shared::cluster.global.mbarrier::complete_tx::bytes.multicast::cluster.L2::cache_hint"
               " [%0], [%1, {%3, %3, %3, %4}], [%2], %5, %6;"
               ::"r"(dst), "l"(m), "r"(bar), "r"(0), "r"(c3), "h"((uint16_t)3), "l"(pol) : "memory");
}
__device__ __forceinline__ void tma5d_mc(uint32_t dst, const CUtensorMap* m, uint32_t bar, int c2, int c4) {
  asm volatile("cp.async.bulk.tensor.5d.shared::cluster.global.mbarrier::complete_tx::bytes.multicast::cluster"
               " [%0], [%1, {%3, %3, %4, %3, %5}], [%2], %6;"
               ::"r"(dst), "l"(m), "r"(bar), "r"(0), "r"(c2), "r"(c4), "h"((uint16_t)3) : "memory");
}
__device__ __forceinline__ void bulk_load_hint(uint32_t dst, const void* src, uint32_t bytes, uint32_t bar, uint64_t pol) {
  asm volatile("cp.async.bulk.shared::cluster.global.mbarrier::complete_tx::bytes.L2::cache_hint [%0], [%1], %2, [%3], %4;"
               ::"r"(dst), "l"(src), "r"(bytes), "r"(bar), "l"(pol) : "memory");
}
__device__ __forceinline__ void stg128_hint(void* p, uint32_t a, uint32_t b, uint32_t c, uint32_t d, uint64_t pol) {
  asm volatile("st.global.L2::cache_hint.v4.b32 [%0], {%1, %2, %3, %4}, %5;" ::"l"(p), "r"(a), "r"(b), "r"(c), "r"(d), "l"(pol) : "memory");
}
__device__ __forceinline__ void stg2_if(bool on, void* p, uint32_t a, uint32_t b, uint32_t c, uint32_t d, uint32_t e, uint32_t f,
                                        uint32_t g, uint32_t h, uint64_t pol) {
  asm volatile("{\n.reg .pred p;\nsetp.ne.b32 p, %10, 0;\n"
               "@p st.global.L2::cache_hint.v4.b32 [%0], {%1, %2, %3, %4}, %9;\n"
               "@p st.global.L2::cache_hint.v4.b32 [%0 + 512], {%5, %6, %7, %8}, %9;\n}\n"
               ::"l"(p), "r"(a), "r"(b), "r"(c), "r"(d), "r"(e), "r"(f), "r"(g), "r"(h), "l"(pol), "r"((int)on) : "memory");
}
__device__ __forceinline__ uint64_t make_policy(bool first) {
  uint64_t pf, pn;
  asm("createpolicy.fractional.L2::evict_first.b64 %0, 1.0;" : "=l"(pf));
  asm("createpolicy.fractional.L2::evict_normal.b64 %0, 1.0;" : "=l"(pn));
  return first ? pf : pn;
}
__device__ __forceinline__ bool elect() {
  uint32_t ok;
  asm volatile("{\n.reg .pred p;\nelect.sync _|p, 0xffffffff;\nselp.u32 %0, 1, 0, p;\n}\n" : "=r"(ok));
  return ok;
}
__device__ __forceinline__ void mbar_arrive(uint32_t bar) {
  asm volatile("mbarrier.arrive.shared::cta.b64 _, [%0];" ::"r"(bar) : "memory");
}
__device__ __forceinline__ void stg128(void* p, uint32_t a, uint32_t b, uint32_t c, uint32_t d) {
  asm volatile("st.global.v4.b32 [%0], {%1, %2, %3, %4};" ::"l"(p), "r"(a), "r"(b), "r"(c), "r"(d) : "memory");
}
__device__ __forceinline__ void lds128(uint32_t p, uint32_t& a, uint32_t& b, uint32_t& c, uint32_t& d) {
  asm volatile("ld.shared.v4.b32 {%0, %1, %2, %3}, [%4];" : "=r"(a), "=r"(b), "=r"(c), "=r"(d) : "r"(p) : "memory");
}
__device__ __forceinline__ void wait_count(const unsigned int* p, uint32_t target) {
  asm volatile("{\n.reg .pred p;\n.reg .u32 n, v;\nmov.u32 n, 0;\n"
               "LOOP:\nld.acquire.gpu.global.u32 v, [%0];\nsetp.ge.u32 p, v, %1;\n@p bra DONE;\n"
               "nanosleep.u32 %2;\nadd.u32 n, n, 1;\nsetp.lt.u32 p, n, 0x400000;\n@p bra LOOP;\ntrap;\n"
               "DONE:\n}\n" ::"l"(p), "r"(target), "n"(200) : "memory");
}

__host__ __device__ __forceinline__ int o_wave(int a, int b, int i, int lag) {
  if (lag == 0) return a + i;
  const int p = lag < b - a - 1 ? lag : b - a - 1;
  return i < p ? b - 2 - i : i == p ? b - 1 : b - 1 - i;
}

struct Cursor {
  int bi;
  uint32_t ph;
  __device__ __forceinline__ void next() {
    if (++bi == NBAR) { bi = 0; ph ^= 1; }
  }
};

constexpr float kScaleLog2 = 0.07216878364870322f * 1.4426950408889634f;
constexpr float kSumLimit = 1048576.0f;
constexpr float kMaxLag = 8.0f;

__global__ void __cluster_dims__(2, 1, 1) __launch_bounds__(384, 1)
fused_kernel(const __grid_constant__ Params P) {
  extern __shared__ uint8_t smem_raw[];
  const uint32_t sbase = (smem_u32(smem_raw) + 1023) & ~1023u;
  const uint32_t full0 = sbase + RING, empty0 = full0 + 8 * NBAR, odone = empty0 + 8 * NBAR, oready0 = odone + 8;
  const uint32_t fenced = oready0 + 64, hready0 = fenced + 8;
  const uint32_t rank = blockIdx.x & 1;
  const int role = blockIdx.x >> 1;
  const bool helper = role >= N_CL;
  const int team = helper ? 0 : role >> 2, nt = role & 3, blk = team >> 3;
  const uint32_t* prog = P.ops[helper ? N_TEAM + 2 * (role - N_CL) : team];
  auto q_role = [&](uint32_t op) { return helper ? (int)(((op >> 3) & 60) | ((op >> 12) & 3)) : role; };
  auto o_role = [&](uint32_t op) { return helper ? (int)(((op >> 26) & 56) | ((op >> 9) & 7)) : role; };
  const int wid = __shfl_sync(0xffffffffu, (int)(threadIdx.x >> 5), 0);
  const int wg = wid >> 2;

  const uint32_t op0 = P.first[helper ? N_TEAM + role - N_CL : team];
  if (__builtin_expect(wid == 8, 1)) {
    if (elect()) {
#pragma unroll
      for (int k = 0; k < EARLY; k++) mbar_init(full0 + 8 * k, 1);
      asm volatile("fence.mbarrier_init.release.cluster;" ::: "memory");
      if ((op0 & 3) == OP_Q) {
        const int qr = q_role(op0);
#pragma unroll
        for (int k = 0; k < EARLY; k++) {
          mbar_expect(full0 + 8 * k, SZ_Q);
          tma2d(sbase + k * SZ_Q, &P.x[qr >> 5], full0 + 8 * k, 64 * k, ((qr >> 2) & 7) * kSq + rank * 128);
          tma3d(sbase + k * SZ_Q + 16384, &P.wq[qr >> 5], full0 + 8 * k, 0, 64 * k, 3 * (4 * ((op0 >> 2) & 7) + (qr & 3)));
        }
      }
      asm volatile("prefetch.tensormap [%0];" ::"l"(rank ? &P.v[blk] : &P.k[blk]) : "memory");
    }
  } else if (threadIdx.x == 0) {
#pragma unroll
    for (int i = EARLY; i < 2 * NBAR + 10 + MAX_PARK; i++) mbar_init(full0 + 8 * i, i < NBAR ? 1 : i < 2 * NBAR ? 16 : i == 2 * NBAR ? 8 : 1);
    asm volatile("fence.mbarrier_init.release.cluster;" ::: "memory");
  }
  __syncwarp();
  asm volatile("barrier.cluster.arrive.relaxed.aligned;\nbarrier.cluster.wait.aligned;" ::: "memory");

  if (wg == 2) {
    asm volatile("setmaxnreg.dec.sync.aligned.u32 24;");
    if (wid == 8) {
      Cursor tail{0, 0};
      int head = 0, sh = 0;
      uint32_t hph = 0;
      uint32_t cur = 0, used = 0;
      uint64_t fifo = 0;
      uint32_t dst, bar, oready = oready0;
      uint64_t pol;
      asm volatile("createpolicy.fractional.L2::evict_first.b64 %0, 1.0;" : "=l"(pol));
      const uint64_t pol_o = make_policy(P.dbg & 1), pol_p = make_policy(!(P.dbg & 4));
      const CUtensorMap* kv_map = rank ? &P.v[blk] : &P.k[blk];
      auto acquire = [&](uint32_t bytes) {
        uint32_t fp = bytes >> 12;
        if (cur + fp > (RING >> 12)) { fp += (RING >> 12) - cur; cur = 0; }
        used += fp;
        while (used > (RING >> 12) || sh == 5 * NBAR) {
          mbar_wait(empty0 + 8 * tail.bi, tail.ph);
          tail.next();
          used -= (uint32_t)fifo & 31;
          fifo >>= 5;
          sh -= 5;
        }
        fifo |= (uint64_t)fp << sh;
        sh += 5;
        dst = sbase + (cur << 12);
        bar = full0 + 8 * head;
        cur += bytes >> 12;
        if (++head == NBAR) { head = 0; hph ^= 1; }
      };
      for (int pc = 0;; pc++) {
        const uint32_t op = prog[pc];
        const int type = op & 3, a = (op >> 2) & 7;
        if (type == OP_END) break;
        if (type == OP_Q) {
          const int qr = q_role(op);
#pragma unroll 1
          for (int k = 0; k < 10; k++) {
            acquire(SZ_Q);
            if ((pc > 0 || k >= EARLY) && elect()) {
              mbar_expect(bar, SZ_Q);
              tma2d(dst, &P.x[qr >> 5], bar, 64 * k, ((qr >> 2) & 7) * kSq + rank * 128);
              if ((k & 1) == rank) tma3d_mc(dst + 16384, &P.wq[qr >> 5], bar, 0, 64 * k, 3 * (4 * a + (qr & 3)));
            }
          }
        } else if (type == OP_A) {
          const uint32_t nop = prog[pc + 1];
          auto kv = [&](int isv, int wave, int j) {
            const int row0 = ((team & 7) * kH + 4 * wave + nt) * kSk;
            acquire(SZ_KV);
            if (isv == (int)rank) {
              const int j = head - 1 - KV_TRANSIT;
              mbar_wait(full0 + 8 * (j < 0 ? j + NBAR : j), j < 0 ? hph ^ 1 : hph);
            }
            if (elect()) {
              mbar_expect(bar, SZ_KV);
              if (isv == (int)rank) tma4d_mc_hint(dst, kv_map, bar, row0 / 8 + 8 * j, pol);
            }
          };
#pragma unroll 1
          for (int t = (op & F_PARK) ? 1 : 0; t < 31; t++) {
            const int isv = t == 0 ? 0 : (~t & 1);
            kv(isv, a, isv ? (t - 1) >> 1 : (t + 1) >> 1);
          }
          if ((nop & 3) == OP_A) {
            mbar_wait((nop & F_HELP) ? hready0 + 8 * ((nop >> 10) & 3) : fenced, 0);
            asm volatile("fence.proxy.async.global;" ::: "memory");
#pragma unroll 1
            for (int i = 0; i < 2; i++) {
              acquire(SZ_PARK);
              if (elect()) {
                mbar_expect(bar, SZ_PARK);
                bulk_load_hint(dst, &g_o[((team * 2 + rank) * 96 + 3 * (4 * ((nop >> 2) & 7) + nt)) * 1024 + i * 1536], SZ_PARK, bar, pol_p);
              }
            }
            kv(0, (nop >> 2) & 7, 0);
          }
          kv(1, a, 15);
        } else {
          const int b = (op >> 5) & 15, ro = o_role(op);
#pragma unroll 1
          for (int i = 0; i < b - a; i++) {
            const int w = o_wave(a, b, i, (P.dbg >> 4) & 7);
            mbar_wait(oready, 0);
            oready += 8;
            asm volatile("fence.proxy.async.global;" ::: "memory");
#pragma unroll 1
            for (int k = 12 * w; k < 12 * w + 12; k++) {
              acquire(SZ_O);
              if (elect()) {
                mbar_expect(bar, SZ_O);
                tma5d_mc(dst + 16384 + rank * 10240, &P.wo[ro >> 5], bar, 8 * k + 4 * rank, 5 * (ro & 3));
                bulk_load_hint(dst, &g_o[(((ro >> 2) * 2 + rank) * 96 + k - 12 * (w - P.slot[w])) * 1024], 16384, bar, pol_o);
              }
            }
          }
          if (op & F_LD) {
            if (op & F_PARK) {
              mbar_wait(hready0 + 8 * (MAX_PARK - 1), 0);
              asm volatile("fence.proxy.async.global;" ::: "memory");
            }
#pragma unroll 1
            for (int i = 0; i < 2; i++) {
              acquire(SZ_PART);
              if (elect()) {
                mbar_expect(bar, SZ_PART);
                bulk_load_hint(dst, &g_part[(role * 2 + rank) * 5120 + i * 2560], SZ_PART, bar, pol_p);
              }
            }
          }
        }
      }
    } else if (threadIdx.x == 288) {
      uint32_t ph = 0;
      bool first = true;
      for (int pc = 0;; pc++) {
        const uint32_t op = prog[pc];
        if ((op & 3) == OP_END) break;
        if ((op & 3) != OP_A && !helper) continue;
        mbar_wait_slow<400>(odone, ph);
        ph ^= 1;
        unsigned int* flag = !helper ? &g_done[(team * 2 + rank) * 8 + ((op >> 2) & 7)]
                             : (op & 3) == OP_Q ? &g_help[(q_role(op) * 2 + rank) * MAX_PARK + ((op >> 10) & 3)]
                                                : &g_help[(o_role(op) * 2 + rank) * MAX_PARK + MAX_PARK - 1];
        asm volatile("red.release.gpu.global.add.u32 [%0], 1;" ::"l"(flag) : "memory");
        if (first) mbar_arrive(fenced);
        first = false;
      }
    } else if (threadIdx.x == 320) {
      uint32_t oready = oready0;
      for (int pc = 0;; pc++) {
        const uint32_t op = prog[pc];
        if ((op & 3) == OP_END) break;
        if ((op & 3) == OP_O) {
          const int a = (op >> 2) & 7, b = (op >> 5) & 15;
          for (int i = 0; i < b - a; i++) {
            const int ci = ((o_role(op) >> 2) * 2 + rank) * 8 + o_wave(a, b, i, (P.dbg >> 4) & 7);
            wait_count(&g_done[ci], 4);
            mbar_arrive(oready);
            oready += 8;
            if (atomicAdd(&g_seen[ci], 1u) == 3u) { g_seen[ci] = 0; g_done[ci] = 0; }
          }
        }
        if ((op & 3) != OP_Q && (op & F_HELP) && (op & F_PARK)) {
          unsigned int* flag = &g_help[(role * 2 + rank) * MAX_PARK + ((op >> 10) & 3)];
          wait_count(flag, 1);
          mbar_arrive(hready0 + 8 * ((op >> 10) & 3));
          *flag = 0;
        }
      }
    }
    __syncwarp();
    asm volatile("barrier.cluster.arrive.relaxed;\nbarrier.cluster.wait;" ::: "memory");
  } else {
    asm volatile("setmaxnreg.inc.sync.aligned.u32 240;");
    const int lane = threadIdx.x & 31, warp = wid & 3;
    uint32_t empty_rem;
    asm volatile("mapa.shared::cluster.u32 %0, %1, %2;" : "=r"(empty_rem) : "r"(empty0), "r"(lane & 1));
    auto release = [&](int slot) { mbar_arrive_cluster_if(lane < 2, empty_rem + 8 * slot); };
    Cursor r{0, 0};
    const uint32_t ring16 = (sbase & 0x3FFFF) >> 4;
    uint32_t cur = ring16;
    bool rdy0 = false, rdy1 = false;
    auto probe1 = [&]() { rdy0 = mbar_test(full0 + 8 * r.bi, r.ph); };
    auto probe2 = [&]() {
      Cursor n = r;
      rdy0 = mbar_test(full0 + 8 * n.bi, n.ph);
      n.next();
      rdy1 = mbar_test(full0 + 8 * n.bi, n.ph);
    };
    auto take = [&](bool rdy, uint32_t bytes, uint32_t& addr) {
      const int bi = r.bi;
      if (!__all_sync(0xffffffffu, rdy)) mbar_wait(full0 + 8 * r.bi, r.ph);
      r.next();
      if (cur > ring16 + ((RING - bytes) >> 4)) cur = ring16;
      addr = cur;
      cur += bytes >> 4;
      return bi;
    };
    uint32_t keep = 0;
    const int row = wg * 64 + warp * 16 + (lane >> 2);
    const int img0 = row * 4 + ((lane & 3) ^ ((row >> 1) & 3));
    uint4* pend = nullptr;
    uint64_t spol;
    int pc = 0;
    uint32_t op = prog[0];
    auto enter = [&]() {
      r.bi = (op >> 15) & 15; r.ph = (op >> 19) & 1; cur = ring16 + (((op >> 20) & 63) << 8);
      spol = make_policy(!(op & F_SOON));
    };
    auto drain = [&](uint32_t (&t)[48], uint32_t c) {
      if (!(op & (3u << 26)) || c >= 6) return;
#pragma unroll
      for (int i = 0; i < 6; i++)
        stg2_if(c == i, pend + i * 512, t[8 * i], t[8 * i + 1], t[8 * i + 2], t[8 * i + 3],
                t[8 * i + 4], t[8 * i + 5], t[8 * i + 6], t[8 * i + 7], spol);
      if ((op & (1u << 26)) && c == 5) {
        __syncwarp();
        mbar_arrive_if(lane == 0, odone);
      }
    };
    float s[32], o[96], c[80];
    uint32_t q[48], pa[16], pb[16];
    float mc0, mc1, l0, l1;
    bool gen;
    auto expo = [&](float (&s)[32], uint32_t (&pout)[16], float& b0, float& b1, bool sub) {
#pragma unroll
      for (int i = 0; i < 8; i++) {
        const float e1 = ex2(sub ? s[4 * i + 1] - mc0 : s[4 * i + 1]), e0 = ex2(sub ? s[4 * i] - mc0 : s[4 * i]);
        const float e3 = ex2(sub ? s[4 * i + 3] - mc1 : s[4 * i + 3]), e2 = ex2(sub ? s[4 * i + 2] - mc1 : s[4 * i + 2]);
        pout[2 * i] = pack_bf16(e0, e1);
        b0 = i ? b0 + fadd(e1, e0) : fadd(e1, e0);
        pout[2 * i + 1] = pack_bf16(e2, e3);
        b1 = i ? b1 + fadd(e3, e2) : fadd(e3, e2);
      }
    };
    auto rowmax = [&](float (&s)[32], float& m0, float& m1) {
      m0 = fmaxf(s[0], s[1]); m1 = fmaxf(s[2], s[3]);
#pragma unroll
      for (int i = 1; i < 8; i++) { m0 = fmaxf(m0, fmaxf(s[4 * i], s[4 * i + 1])); m1 = fmaxf(m1, fmaxf(s[4 * i + 2], s[4 * i + 3])); }
      m0 = fmaxf(m0, __shfl_xor_sync(0xffffffffu, m0, 1)); m1 = fmaxf(m1, __shfl_xor_sync(0xffffffffu, m1, 1));
      m0 = fmaxf(m0, __shfl_xor_sync(0xffffffffu, m0, 2)); m1 = fmaxf(m1, __shfl_xor_sync(0xffffffffu, m1, 2));
    };
    auto first = [&](float (&s)[32]) {
      mc0 = 0.f; mc1 = 0.f;
      expo(s, pa, l0, l1, false);
      gen = __any_sync(0xffffffffu, !(fmaxf(l0, l1) <= kSumLimit && fminf(l0, l1) >= 1.0f / kSumLimit));
      if (gen) {
        rowmax(s, mc0, mc1);
        expo(s, pa, l0, l1, true);
      }
    };
    auto soft = [&](uint32_t (&pout)[16]) {
      float b0, b1;
      if (!gen) {
        expo(s, pout, b0, b1, false);
        gen = __any_sync(0xffffffffu, !(fmaxf(b0, b1) <= kSumLimit));
      }
      if (gen) {
        float m0, m1;
        rowmax(s, m0, m1);
        if (__any_sync(0xffffffffu, !(m0 <= mc0 + kMaxLag && m1 <= mc1 + kMaxLag))) {
          m0 = fmaxf(mc0, m0); m1 = fmaxf(mc1, m1);
          const float a0 = ex2(mc0 - m0), a1 = ex2(mc1 - m1);
          mc0 = m0; mc1 = m1;
          l0 *= a0; l1 *= a1;
          wg_wait<0>();
          fence_regs(o);
#pragma unroll
          for (int i = 0; i < 24; i++) { o[4 * i] *= a0; o[4 * i + 1] *= a0; o[4 * i + 2] *= a1; o[4 * i + 3] *= a1; }
        }
        expo(s, pout, b0, b1, true);
      }
      l0 += b0; l1 += b1;
    };
    auto qk = [&](float (&s)[32], uint32_t ak, int k0, int k1) {
#pragma unroll
      for (int kk = k0; kk < k1; kk++)
        wgmma_rs_n64<0>(s, q[4 * kk], q[4 * kk + 1], q[4 * kk + 2], q[4 * kk + 3], mk_desc(ak + (kk >> 2) * KV_CH + (kk & 3) * 2, 16, KV_SBO, 1), kk != 0);
      wg_commit();
    };
    auto pv = [&](uint32_t (&pin)[16], uint32_t av, int acc) {
#pragma unroll
      for (int kk = 0; kk < 4; kk++)
        wgmma_rs_n192<1>(o, pin[4 * kk], pin[4 * kk + 1], pin[4 * kk + 2], pin[4 * kk + 3], mk_desc(av + kk * (KV_SBO / 8), KV_CH * 16, KV_SBO, 1), acc || (kk != 0));
      wg_commit();
    };
    auto xw = [&](uint32_t ad, int acc) {
      wg_fence();
#pragma unroll
      for (int kk = 0; kk < 4; kk++)
        wgmma_ss_n192<1>(o, mk_desc(ad + wg * 512 + kk * 2, 16, 1024, 1), mk_desc(ad + 1024 + kk * 128, 8192, 1024, 1), acc || kk != 0);
      wg_commit();
    };
    auto ow = [&](int acc, int prev) {
      uint32_t ad;
      const int bi = take(rdy0, SZ_O, ad);
      const uint32_t da = ad + wg * 256, db = ad + 1024;
      wg_fence();
      wgmma_ss_n160<1>(c, mk_desc(da, 16, 512, 2), mk_desc(db, 2048, 512, 2), acc);
      wgmma_ss_n160<1>(c, mk_desc(da + 2, 16, 512, 2), mk_desc(db + 64, 2048, 512, 2), 1);
      wg_commit();
      if (acc) { wg_wait<1>(); release(prev); }
      wgmma_ss_n160<1>(c, mk_desc(da + 512, 16, 512, 2), mk_desc(db + 640, 2048, 512, 2), 1);
      wgmma_ss_n160<1>(c, mk_desc(da + 514, 16, 512, 2), mk_desc(db + 704, 2048, 512, 2), 1);
      wg_commit();
      return bi;
    };
    auto o_run = [&](uint32_t (&t)[48], int bi) {
      const int nk = 12 * (((op >> 5) & 15) - ((op >> 2) & 7));
#pragma unroll 1
      for (int k = 0; k < 6; k++) {
        drain(t, k);
        probe1();
        wg_wait<1>();
        bi = ow(1, bi);
      }
#pragma unroll 1
      for (int k = 7; k < nk; k++) {
        probe1();
        wg_wait<1>();
        bi = ow(1, bi);
      }
      probe1();
      return bi;
    };
    auto st_part = [&](int i) {
      stg2_if(true, pend + i * 512, __float_as_uint(c[8 * i]), __float_as_uint(c[8 * i + 1]), __float_as_uint(c[8 * i + 2]), __float_as_uint(c[8 * i + 3]),
              __float_as_uint(c[8 * i + 4]), __float_as_uint(c[8 * i + 5]), __float_as_uint(c[8 * i + 6]), __float_as_uint(c[8 * i + 7]), spol);
    };
#pragma unroll
    for (int i = 0; i < 48; i++) q[i] = 0;
    enter();

    if ((op & 3) == OP_Q) {
      uint32_t ad;
      int bi0 = take(false, SZ_Q, ad), k = 0, lag = 0;
      xw(ad, 0);
      for (;;) {
#pragma unroll 1
        for (;;) {
          drain(q, k - lag);
          probe1();
          wg_wait<0>();
          release(bi0);
          bi0 = take(rdy0, SZ_Q, ad);
          if (++k == 8) break;
          xw(ad, 1);
        }
        if (wg) bar_sync(2, 256);
        xw(ad, 1);
        const int bi9 = take(false, SZ_Q, ad);
        xw(ad, 1);
        if (!wg) asm volatile("bar.arrive 2, 256;" ::: "memory");
        k = 0; lag = 0;
        uint32_t nop = prog[++pc];
        if (op & F_PARK) {
          pend = &g_o[(((q_role(op) >> 2) * 2 + rank) * 96 + 3 * (4 * ((op >> 2) & 7) + (q_role(op) & 3))) * 1024 + img0];
          op = nop;
          enter();
          wg_wait<1>();
          release(bi0);
          probe1();
          wg_wait<0>();
          fence_regs(o);
          release(bi9);
#pragma unroll
          for (int i = 0; i < 48; i++) q[i] = pack_bf16(o[2 * i] * kScaleLog2, o[2 * i + 1] * kScaleLog2);
          if ((op & 3) != OP_Q) break;
          fence_regs(q);
          bi0 = take(rdy0, SZ_Q, ad);
          xw(ad, 0);
          continue;
        }
        int wave = (op >> 2) & 7, sk1;
        uint32_t ak1;
        {
          wg_wait<1>();
          release(bi0);
          probe2();
          wg_wait<0>();
          fence_regs(o);
          release(bi9);
          float s0[32];
#pragma unroll
          for (int i = 0; i < 48; i++) q[i] = pack_bf16(o[2 * i] * kScaleLog2, o[2 * i + 1] * kScaleLog2);
          fence_regs(q);
          const int sk0 = take(rdy0, SZ_KV, ad);
          wg_fence();
          qk(s0, ad, 0, 12);
          sk1 = take(rdy1, SZ_KV, ak1);
          wg_fence();
          qk(s, ak1, 0, S1A);
          probe1();
          wg_wait<1>();
          fence_regs(s0);
          release(sk0);
          first(s0);
        }
        float i0, i1;
        auto sums = [&]() {
          l0 += __shfl_xor_sync(0xffffffffu, l0, 1); l1 += __shfl_xor_sync(0xffffffffu, l1, 1);
          l0 += __shfl_xor_sync(0xffffffffu, l0, 2); l1 += __shfl_xor_sync(0xffffffffu, l1, 2);
          i0 = rcp(l0); i1 = rcp(l1);
          asm volatile("" : "+f"(i0), "+f"(i1));
        };
        auto target = [&]() {
          pend = &g_o[((team * 2 + rank) * 96 + 3 * (4 * P.slot[wave] + nt)) * 1024 + img0];
          asm volatile("" : "+l"(pend));
        };
        for (;;) {
          nop = prog[++pc];
          {
            uint32_t av;
            const int sv = take(rdy0, SZ_KV, av);
            wg_fence();
            qk(s, ak1, S1A, 12);
            pv(pa, av, 0);
            probe2();
            wg_wait<1>();
            fence_regs(s);
            release(sk1);
            soft(pb);
            wg_wait<0>();
            fence_regs(o);
            release(sv);
          }
          auto step = [&](uint32_t (&pin)[16], uint32_t (&pout)[16]) {
            uint32_t ak, av;
            const int sk = take(rdy0, SZ_KV, ak), sv = take(rdy1, SZ_KV, av);
            wg_fence();
            qk(s, ak, 0, 12);
            pv(pin, av, 1);
            probe2();
            wg_wait<1>();
            fence_regs(s);
            release(sk);
            soft(pout);
            wg_wait<0>();
            fence_regs(o);
            release(sv);
          };
#pragma unroll 1
          for (int jj = 0; jj < 7; jj++) {
            step(pb, pa);
            step(pa, pb);
          }
          if ((nop & 3) != OP_A) break;
          uint32_t ak, av;
          {
            const int b0 = take(rdy0, SZ_PARK, ak), b1 = take(rdy1, SZ_PARK, av);
            const uint32_t ad0 = ak, ad1 = av;
            probe2();
#pragma unroll
            for (int i = 0; i < 12; i++)
              lds128(sbase + ((i < 6 ? ad0 : ad1) - ring16 + img0) * 16 + ((i % 6) >> 1) * 8192 + (i & 1) * 512, q[4 * i], q[4 * i + 1], q[4 * i + 2], q[4 * i + 3]);
            release(b0); release(b1);
          }
          const int sk0 = take(rdy0, SZ_KV, ak), sv = take(rdy1, SZ_KV, av);
          wg_fence();
          qk(s, ak, 0, 8);
          sched_fence(keep);
          sums();
          sched_fence(keep);
          qk(s, ak, 8, 12);
          pv(pb, av, 1);
          probe2();
          spol = make_policy(!(nop & F_SOON));
          wg_wait<1>();
          fence_regs(s);
          release(sk0);
          first(s);
          sk1 = take(rdy0, SZ_KV, ak1);
          rdy0 = rdy1;
          wg_wait<0>();
          target();
          fence_regs(o);
          release(sv);
          uint32_t t[48];
#pragma unroll
          for (int j = 0; j < 6; j++) {
#pragma unroll
            for (int i = 0; i < 4; i++) {
              t[8 * j + i] = pack_bf16(o[16 * j + 4 * i] * i0, o[16 * j + 4 * i + 1] * i0);
              t[8 * j + i + 4] = pack_bf16(o[16 * j + 4 * i + 2] * i1, o[16 * j + 4 * i + 3] * i1);
            }
            stg2_if(true, pend + j * 512, t[8 * j], t[8 * j + 1], t[8 * j + 2], t[8 * j + 3], t[8 * j + 4], t[8 * j + 5], t[8 * j + 6], t[8 * j + 7], spol);
            if (j == UC0) { wg_fence(); qk(s, ak1, 0, 4); }
            if (j == UC1) { wg_fence(); qk(s, ak1, 4, S1A); }
            sched_fence(keep);
          }
          if (P.zero) {
#pragma unroll
            for (int j = 0; j < 5; j++)
              stg2_if(true, pend, t[8 * j], t[8 * j + 1], t[8 * j + 2], t[8 * j + 3], t[8 * j + 4], t[8 * j + 5], t[8 * j + 6], t[8 * j + 7], spol);
          }
          __syncwarp();
          mbar_arrive_if(lane == 0, odone);
          wave = (nop >> 2) & 7;
        }
        const int sv = take(rdy0, SZ_KV, ad);
        wg_fence();
        pv(pb, ad, 1);
        sums();
        target();
        op = nop;
        enter();
        rdy0 = rdy1;
        auto convert = [&](uint32_t (&t)[48], float (&u)[96]) {
#pragma unroll
          for (int i = 0; i < 24; i++) {
            t[8 * (i >> 2) + (i & 3)] = pack_bf16(u[4 * i], u[4 * i + 1]);
            t[8 * (i >> 2) + (i & 3) + 4] = pack_bf16(u[4 * i + 2], u[4 * i + 3]);
          }
        };
        if ((op & 3) != OP_O) {
          if ((op & 3) == OP_Q) bi0 = take(rdy0, SZ_Q, ad);
          wg_wait<0>();
          fence_regs(o);
          release(sv);
          float u[96];
#pragma unroll
          for (int i = 0; i < 96; i++) u[i] = o[i] * (i & 2 ? i1 : i0);
          if ((op & 3) != OP_Q) { convert(q, u); break; }
          fence_regs(u);
          xw(ad, 0);
          sched_fence(keep);
          fence_regs(u);
          convert(q, u);
          continue;
        }
        int bi = ow(0, 0);
        wg_wait<2>();
        fence_regs(o);
        release(sv);
        {
          uint32_t t[48];
#pragma unroll
          for (int i = 0; i < 96; i++) o[i] *= i & 2 ? i1 : i0;
          convert(t, o);
          bi = o_run(t, bi);
        }
        nop = prog[++pc];
        if (op & F_LD) {
          uint32_t t[80], ad0, ad1;
          const int b0 = take(rdy0, SZ_PART, ad0), b1 = take(false, SZ_PART, ad1);
          rdy0 = false;
#pragma unroll
          for (int i = 0; i < 20; i++)
            lds128(sbase + ((i < 10 ? ad0 : ad1) - ring16 + img0) * 16 + ((i % 10) >> 1) * 8192 + (i & 1) * 512, t[4 * i], t[4 * i + 1], t[4 * i + 2], t[4 * i + 3]);
          fence_regs(t);
          wg_wait<0>();
          fence_regs(c);
          release(b0); release(b1);
#pragma unroll
          for (int i = 0; i < 80; i++) c[i] += __uint_as_float(t[i]);
        }
        if (!(op & F_ST)) {
          wg_wait<0>();
          fence_regs(c);
          goto finish;
        }
        op = nop;
        enter();
        bi0 = take(rdy0, SZ_Q, ad);
        xw(ad, 0);
        pend = &g_part[(role * 2 + rank) * 5120 + img0];
        probe1();
        wg_wait<1>();
        fence_regs(c);
        release(bi);
        st_part(6); st_part(7);
        wg_wait<0>();
        release(bi0);
        bi0 = take(rdy0, SZ_Q, ad);
        xw(ad, 1);
        st_part(8); st_part(9);
#pragma unroll
        for (int i = 0; i < 48; i++) q[i] = __float_as_uint(c[i]);
        k = 1; lag = 2;
      }
    }
    rdy0 = false;
    {
      uint32_t t[48];
#pragma unroll
      for (int i = 0; i < 48; i++) t[i] = q[i] ^ P.zero;
      while ((op & 3) == OP_O) {
        const int bi = o_run(t, ow(0, 0));
        wg_wait<0>();
        fence_regs(c);
        pc++;
        if (!(op & F_ST)) goto finish;
        release(bi);
        pend = &g_part[(o_role(op) * 2 + rank) * 5120 + img0];
#pragma unroll
        for (int i = 6; i < 10; i++) st_part(i);
#pragma unroll
        for (int i = 0; i < 48; i++) t[i] = __float_as_uint(c[i]) ^ P.zero;
        op = prog[pc];
        enter();
      }
      for (int i = 0; i < 6; i++) drain(t, i);
    }
    asm volatile("barrier.cluster.arrive.relaxed;" ::: "memory");
    if (false) {
    finish:
      asm volatile("barrier.cluster.arrive.relaxed;" ::: "memory");
      bar_sync(1, 256);
      const uint32_t wstage = sbase + (wg * 4 + warp) * 5120;
      const uint32_t sa = wstage + (lane & 15) * 64;
#pragma unroll
      for (int i = 0; i < 10; i++) {
        const int u = (i & 1) * 2 + (lane >> 4);
        stsm4(sa + (i >> 1) * 1024 + ((u ^ ((lane >> 1) & 3)) << 4), pack_bf16(c[8 * i], c[8 * i + 1]), pack_bf16(c[8 * i + 2], c[8 * i + 3]),
              pack_bf16(c[8 * i + 4], c[8 * i + 5]), pack_bf16(c[8 * i + 6], c[8 * i + 7]));
      }
      asm volatile("fence.proxy.async.shared::cta;" ::: "memory");
      __syncwarp();
      if (lane == 0) {
        tma3d_store(&P.out, wstage, 0, (team & 7) * kSq + rank * 128 + wg * 64 + warp * 16, blk * 20 + nt * 5);
        asm volatile("cp.async.bulk.commit_group;\ncp.async.bulk.wait_group.read 0;" ::: "memory");
      }
      __syncwarp();
    }
    if (P.dbg == 0xffffffffu) g_seen[0] = keep;
    asm volatile("barrier.cluster.wait;" ::: "memory");
  }
}

typedef CUresult (*EncodeFn)(CUtensorMap*, CUtensorMapDataType, cuuint32_t, void*, const cuuint64_t*, const cuuint64_t*,
                             const cuuint32_t*, const cuuint32_t*, CUtensorMapInterleave, CUtensorMapSwizzle,
                             CUtensorMapL2promotion, CUtensorMapFloatOOBfill);

void encode(EncodeFn fn, CUtensorMap* m, const void* ptr, int rank, const cuuint64_t* dims, const cuuint64_t* strides,
            const cuuint32_t* box, CUtensorMapSwizzle swz) {
  const cuuint32_t es[5] = {1, 1, 1, 1, 1};
  CUresult r = fn(m, CU_TENSOR_MAP_DATA_TYPE_BFLOAT16, rank, const_cast<void*>(ptr), dims, strides, box, es,
                  CU_TENSOR_MAP_INTERLEAVE_NONE, swz, CU_TENSOR_MAP_L2_PROMOTION_L2_128B, CU_TENSOR_MAP_FLOAT_OOB_FILL_NONE);
  if (r != CUDA_SUCCESS) fprintf(stderr, "cuTensorMapEncodeTiled failed: %d\n", (int)r);
}

void annotate(uint32_t* ops, int n, bool helper) {
  uint32_t items = 0, cur = 0, pend = 0;
  auto item = [&](uint32_t bytes, int count) {
    for (int i = 0; i < count; i++) { if (cur + bytes > RING) cur = 0; cur += bytes; items++; }
  };
  for (int i = 0; i <= n; i++) {
    const uint32_t op = ops[i];
    ops[i] |= (items % NBAR) << 15 | ((items / NBAR) & 1) << 19 | (cur >> 12) << 20 | pend << 26;
    if ((op & 3) == OP_Q) { item(SZ_Q, 10); pend = (op & F_PARK) ? (helper ? 1 : 2) : 0; }
    if ((op & 3) == OP_A) {
      item(SZ_KV, (op & F_PARK) ? 30 : 31);
      if ((ops[i + 1] & 3) == OP_A) { item(SZ_PARK, 2); item(SZ_KV, 1); }
      item(SZ_KV, 1);
      pend = 1;
    }
    if ((op & 3) == OP_O) {
      item(SZ_O, 12 * (((op >> 5) & 15) - ((op >> 2) & 7)));
      if (op & F_LD) item(SZ_PART, 2);
      pend = (op & F_LAZY) ? (helper ? 1 : 2) : 0;
    }
  }
}

void compile_programs(const char* const* text, bool helpers, Params& P) {
  struct Req { int when, team, wave, slot; } req[N_TEAM * MAX_PARK];
  int n_req = 0;
  for (int t = 0; t < N_TEAM; t++) {
    uint32_t* ops = P.ops[t];
    int n = 0, flags[8] = {0, 0, 0, 0, 0, 0, 0, 0}, n_park = 0, last_o = -1, when = 0, given = 0;
    for (const char* s = text[t]; *s; s++) {
      const int a = s[1] - '0';
      if (*s == 'Q' || (*s == 'H' && !helpers)) { ops[n++] = OP_Q | a << 2; when += 10; }
      else if (*s == 'P') { flags[a] = F_PARK | n_park++ << 10; ops[n++] = OP_Q | a << 2 | flags[a]; when += 10; }
      else if (*s == 'H') { req[n_req++] = {when, t, a, n_park}; flags[a] = F_PARK | F_HELP | n_park++ << 10; }
      else if (*s == 'A') { ops[n++] = OP_A | a << 2 | flags[a]; when += 32; }
      else if (*s == 'G') { given = a; if (helpers) req[n_req++] = {1000, t, 0, -a}; }
      else if (*s == 'O') {
        ops[n] = OP_O | a << 2 | (s[2] - '0') << 5;
        if (given) ops[n] = helpers ? ops[n] | F_LD | F_PARK | (MAX_PARK - 1) << 10 : ops[n] & ~(7u << 2);
        if (last_o >= 0) { ops[last_o] |= F_ST; ops[n] |= F_LD; }
        last_o = n++;
        when += 10 * (s[2] - s[1]);
      }
    }
    for (int i = 0; i + 1 < n; i++)
      if ((ops[i] & 3) == OP_O && (ops[i] & F_ST) && (ops[i + 1] & 3) == OP_Q) ops[i] |= F_LAZY;
    for (int i = n; i < MAX_OPS; i++) ops[i] = OP_END;
    annotate(ops, n, false);
    for (int i = 0; i < n; i++) {
      if ((ops[i] & 3) != OP_A && (P.dbg & 8)) ops[i + 1] |= F_SOON;
      if ((ops[i] & 3) != OP_A) continue;
      const int w = (ops[i] >> 2) & 7;
      int dist = 0;
      for (int j = i + 1; j < n; j++) {
        const int a = (ops[j] >> 2) & 7, b = (ops[j] >> 5) & 15;
        if ((ops[j] & 3) == OP_O && w < b) {
          for (int k = 0; k < b - a && o_wave(a, b, k, (P.dbg >> 4) & 7) != w; k++) dist += 10;
          break;
        }
        dist += (ops[j] & 3) == OP_Q ? 10 : (ops[j] & 3) == OP_A ? 32 : 10 * (b - a);
      }
      if (dist <= (int)((P.dbg >> 8) & 255)) ops[i + 1] |= F_SOON;
    }
  }
  for (int i = 1; i < n_req; i++)
    for (int j = i; j > 0 && req[j].when < req[j - 1].when; j--) { Req r = req[j]; req[j] = req[j - 1]; req[j - 1] = r; }
  for (int h = 0; h < N_HELP; h++) {
    uint32_t* ops = P.ops[N_TEAM + 2 * h];
    int n = 0;
    for (int i = 0; i < n_req; i++)
      for (int m = h; m < 4; m += N_HELP) {
        const uint32_t ro = 4 * req[i].team + m;
        ops[n++] = req[i].slot >= 0 ? OP_Q | req[i].wave << 2 | req[i].team << 5 | F_PARK | req[i].slot << 10 | m << 12
                                    : OP_O | -req[i].slot << 5 | F_ST | F_LAZY | F_SOON | (ro & 7) << 9 | (ro >> 3) << 29;
      }
    for (int i = n; i < 2 * MAX_OPS; i++) ops[i] = OP_END | F_SOON;
    annotate(ops, n, true);
  }
  for (int i = 0; i < 32; i++) P.first[i] = i < N_TEAM ? P.ops[i][0] : i < N_TEAM + N_HELP ? P.ops[2 * i - N_TEAM][0] : 0;
}

const char* const kPrograms[N_TEAM] = {
  "Q0A0Q1A1H2A2O03Q3A3Q4A4Q5A5Q6A6Q7A7O38",
  "Q0A0Q1A1Q2A2H3A3Q4A4O03Q5A5Q6A6Q7A7O38",
  "Q0A0H1A1Q2A2Q3A3O04Q4A4Q5A5Q6A6Q7A7O48",
  "Q0A0Q1A1Q2A2Q3A3O02Q4A4Q5A5Q6A6H7A7O28",
  "Q0A0Q1A1Q2A2O03Q3A3Q4A4Q5A5Q6A6H7A7O38",
  "Q0A0Q1A1Q2A2Q3A3Q4A4O05Q5A5Q6A6H7A7O58",
  "Q0A0Q1A1Q2A2Q3A3Q4A4O05Q5A5Q6A6H7A7O58",
  "Q0A0Q1A1Q2A2O03Q3A3Q4A4H5A5Q6A6Q7A7O38",
  "P7Q0A0Q1A1O01Q2A2H3A3Q4A4Q5A5Q6A6A7O18",
  "P3P5Q0A0Q1A1Q2A2A3Q4A4A5H6A6Q7A7O08",
  "P7Q0A0Q1A1Q2A2Q3A3H4A4Q5A5Q6A6A7O08",
  "P3P7Q0A0Q1A1H2A2A3Q4A4Q5A5Q6A6A7O08",
  "Q0A0Q1A1Q2A2O01Q3A3Q4A4H5A5Q6A6Q7A7O18",
  "P3Q0A0Q1A1Q2A2A3Q4A4Q5A5Q6A6Q7A7G1O18",
  "P6Q0A0Q1A1Q2A2Q3A3Q4A4Q5A5A6Q7A7G1O18",
  "P2P6Q0A0Q1A1A2Q3A3H4A4Q5A5A6Q7A7O08",
};

const char* const* bench_programs() {
  return kPrograms;
}

}

extern "C" void kernel_launch(void* const* d_in, const int* in_sizes, int n_in, void* d_out, int out_size) {
  (void)in_sizes; (void)n_in; (void)out_size;
  static EncodeFn fn = nullptr;
  static int n_clusters = 0;
  if (!fn) {
    cudaDriverEntryPointQueryResult qr;
    void* f = nullptr;
    cudaGetDriverEntryPoint("cuTensorMapEncodeTiled", &f, cudaEnableDefault, &qr);
    fn = (EncodeFn)f;
    cudaFuncSetAttribute(fused_kernel, cudaFuncAttributeMaxDynamicSharedMemorySize, SMEM_BYTES);
    cudaLaunchConfig_t cfg = {};
    cfg.gridDim = dim3(132); cfg.blockDim = dim3(384); cfg.dynamicSmemBytes = SMEM_BYTES;
    cudaLaunchAttribute at[1];
    at[0].id = cudaLaunchAttributeClusterDimension; at[0].val.clusterDim.x = 2; at[0].val.clusterDim.y = 1; at[0].val.clusterDim.z = 1;
    cfg.attrs = at; cfg.numAttrs = 1;
    if (cudaOccupancyMaxActiveClusters(&n_clusters, fused_kernel, &cfg) != cudaSuccess || n_clusters < 1) n_clusters = 1;
    (void)cudaGetLastError();
  }
  Params P;
  const CUtensorMapSwizzle S128 = CU_TENSOR_MAP_SWIZZLE_128B, S64 = CU_TENSOR_MAP_SWIZZLE_64B;
  for (int blk = 0; blk < 2; blk++) {
    void* const* in = d_in + 5 * blk;
    { const cuuint64_t d[] = {kD, kB * kSq}, s[] = {kD * 2}; const cuuint32_t b[] = {64, 128};
      encode(fn, &P.x[blk], in[0], 2, d, s, b, S128); }
    { const cuuint64_t d[] = {64, 8, 3, (cuuint64_t)kB * kH * kSk / 8}, s[] = {kDh * 2, 128, 8 * kDh * 2}; const cuuint32_t b[] = {64, 8, 3, 8};
      encode(fn, &P.k[blk], in[1], 4, d, s, b, S128);
      encode(fn, &P.v[blk], in[2], 4, d, s, b, S128); }
    { const cuuint64_t d[] = {64, kD, kHD / 64}, s[] = {kHD * 2, 128}; const cuuint32_t b[] = {64, 64, 3};
      encode(fn, &P.wq[blk], in[3], 3, d, s, b, S128); }
    { const cuuint64_t d[] = {32, 2, kHD / 8, 4, kD / 32}, s[] = {kD * 2, 8 * kD * 2, 2 * kD * 2, 64}; const cuuint32_t b[] = {32, 2, 4, 4, 5};
      encode(fn, &P.wo[blk], in[4], 5, d, s, b, S64); }
  }
  { const cuuint64_t d[] = {32, kB * kSq, 2 * kD / 32}, s[] = {2 * kD * 2, 64}; const cuuint32_t b[] = {32, 16, 5};
    encode(fn, &P.out, d_out, 3, d, s, b, S64); }

  P.zero = 0;
  P.dbg = 0x5030;
  for (int w = 0; w < 8; w++) P.slot[w] = (P.dbg >> 16) & 15 ? w % ((P.dbg >> 16) & 15) : w;
  if (n_clusters >= N_CL) {
    const bool helpers = n_clusters >= N_CL + N_HELP;
    compile_programs(bench_programs(), helpers, P);
    fused_kernel<<<2 * (N_CL + (helpers ? N_HELP : 0)), 384, SMEM_BYTES>>>(P);
  } else {
    for (int phase = 0; phase < 2; phase++) {
      const char* text[N_TEAM];
      for (int t = 0; t < N_TEAM; t++) text[t] = phase ? "O08" : "Q0A0Q1A1Q2A2Q3A3Q4A4Q5A5Q6A6Q7A7";
      compile_programs(text, false, P);
      fused_kernel<<<2 * N_CL, 384, SMEM_BYTES>>>(P);
    }
  }
}
```

```cpp
#include <cuda_runtime.h>
#include <cuda_bf16.h>
#include <cuda.h>
#include <stdint.h>
#include <stdio.h>

namespace {

constexpr int kB = 8, kSq = 256, kD = 640, kH = 32, kSk = 1024, kDh = 192;
constexpr int kHD = kH * kDh;
#define S1A 8
#define UC0 2
#define UC1 5
#define RING_KB 224
constexpr uint32_t RING = RING_KB * 1024;
constexpr uint32_t SZ_KV = 24576;
constexpr uint32_t SZ_Q = 16384 + 24576;
constexpr uint32_t SZ_O = 16384 + 20480;
constexpr uint32_t SZ_PARK = 24576;
constexpr uint32_t SZ_PART = 16384;
constexpr int NBAR = 10;
constexpr int KV_TRANSIT = 4;
constexpr int EARLY = 3;
constexpr uint32_t KV_CH = 64, KV_SBO = 3072;
constexpr int SMEM_BYTES = RING + 512 + 1024;
constexpr int N_TEAM = 16, N_CL = 64, N_HELP = 2, MAX_OPS = 24, MAX_PARK = 4;
enum { OP_END = 0, OP_Q = 1, OP_A = 2, OP_O = 3, F_PARK = 1 << 9, F_LD = 1 << 12, F_ST = 1 << 13, F_LAZY = 1 << 14, F_HELP = 1 << 12, F_SOON = 1 << 28 };

struct alignas(64) Params {
  uint32_t first[32];
  CUtensorMap x[2], wq[2], k[2], v[2], wo[2], out;
  uint32_t ops[N_TEAM + 2 * N_HELP][MAX_OPS];
  uint32_t zero;
  uint32_t slot[8];
  uint32_t dbg;
};

__device__ uint4 g_o[N_TEAM * 2 * 96 * 1024];
__device__ uint4 g_part[N_CL * 2 * 5 * 1024];
__device__ unsigned int g_done[N_TEAM * 2 * 8];
__device__ unsigned int g_help[N_CL * 2 * MAX_PARK];
__device__ unsigned int g_seen[N_TEAM * 2 * 8];

template <int TB, int TA = 0>
__device__ __forceinline__ void wgmma_ss_n64(float (&d)[32], uint64_t da, uint64_t db, int scale_d) {
  asm volatile("{\n.reg .pred p;\nsetp.ne.b32 p, %34, 0;\n"
    "wgmma.mma_async.sync.aligned.m64n64k16.f32.bf16.bf16 {%0, %1, %2, %3, %4, %5, %6, %7, %8, %9, %10, %11, %12, %13, %14, %15, %16, %17, %18, %19, %20, %21, %22, %23, %24, %25, %26, %27, %28, %29, %30, %31}, %32, %33, p, 1, 1, %35, %36;\n}\n"
    : "+f"(d[0]), "+f"(d[1]), "+f"(d[2]), "+f"(d[3]), "+f"(d[4]), "+f"(d[5]), "+f"(d[6]), "+f"(d[7]), "+f"(d[8]), "+f"(d[9]), "+f"(d[10]), "+f"(d[11]), "+f"(d[12]), "+f"(d[13]), "+f"(d[14]), "+f"(d[15]), "+f"(d[16]), "+f"(d[17]), "+f"(d[18]), "+f"(d[19]), "+f"(d[20]), "+f"(d[21]), "+f"(d[22]), "+f"(d[23]), "+f"(d[24]), "+f"(d[25]), "+f"(d[26]), "+f"(d[27]), "+f"(d[28]), "+f"(d[29]), "+f"(d[30]), "+f"(d[31])
    : "l"(da), "l"(db), "r"(scale_d), "n"(TA), "n"(TB));
}
template <int TB>
__device__ __forceinline__ void wgmma_rs_n64(float (&d)[32], uint32_t a0, uint32_t a1, uint32_t a2, uint32_t a3, uint64_t db, int scale_d) {
  asm volatile("{\n.reg .pred p;\nsetp.ne.b32 p, %37, 0;\n"
    "wgmma.mma_async.sync.aligned.m64n64k16.f32.bf16.bf16 {%0, %1, %2, %3, %4, %5, %6, %7, %8, %9, %10, %11, %12, %13, %14, %15, %16, %17, %18, %19, %20, %21, %22, %23, %24, %25, %26, %27, %28, %29, %30, %31}, {%32, %33, %34, %35}, %36, p, 1, 1, %38;\n}\n"
    : "+f"(d[0]), "+f"(d[1]), "+f"(d[2]), "+f"(d[3]), "+f"(d[4]), "+f"(d[5]), "+f"(d[6]), "+f"(d[7]), "+f"(d[8]), "+f"(d[9]), "+f"(d[10]), "+f"(d[11]), "+f"(d[12]), "+f"(d[13]), "+f"(d[14]), "+f"(d[15]), "+f"(d[16]), "+f"(d[17]), "+f"(d[18]), "+f"(d[19]), "+f"(d[20]), "+f"(d[21]), "+f"(d[22]), "+f"(d[23]), "+f"(d[24]), "+f"(d[25]), "+f"(d[26]), "+f"(d[27]), "+f"(d[28]), "+f"(d[29]), "+f"(d[30]), "+f"(d[31])
    : "r"(a0), "r"(a1), "r"(a2), "r"(a3), "l"(db), "r"(scale_d), "n"(TB));
}
template <int TB, int TA = 0>
__device__ __forceinline__ void wgmma_ss_n160(float (&d)[80], uint64_t da, uint64_t db, int scale_d) {
  asm volatile("{\n.reg .pred p;\nsetp.ne.b32 p, %82, 0;\n"
    "wgmma.mma_async.sync.aligned.m64n160k16.f32.bf16.bf16 {%0, %1, %2, %3, %4, %5, %6, %7, %8, %9, %10, %11, %12, %13, %14, %15, %16, %17, %18, %19, %20, %21, %22, %23, %24, %25, %26, %27, %28, %29, %30, %31, %32, %33, %34, %35, %36, %37, %38, %39, %40, %41, %42, %43, %44, %45, %46, %47, %48, %49, %50, %51, %52, %53, %54, %55, %56, %57, %58, %59, %60, %61, %62, %63, %64, %65, %66, %67, %68, %69, %70, %71, %72, %73, %74, %75, %76, %77, %78, %79}, %80, %81, p, 1, 1, %83, %84;\n}\n"
    : "+f"(d[0]), "+f"(d[1]), "+f"(d[2]), "+f"(d[3]), "+f"(d[4]), "+f"(d[5]), "+f"(d[6]), "+f"(d[7]), "+f"(d[8]), "+f"(d[9]), "+f"(d[10]), "+f"(d[11]), "+f"(d[12]), "+f"(d[13]), "+f"(d[14]), "+f"(d[15]), "+f"(d[16]), "+f"(d[17]), "+f"(d[18]), "+f"(d[19]), "+f"(d[20]), "+f"(d[21]), "+f"(d[22]), "+f"(d[23]), "+f"(d[24]), "+f"(d[25]), "+f"(d[26]), "+f"(d[27]), "+f"(d[28]), "+f"(d[29]), "+f"(d[30]), "+f"(d[31]), "+f"(d[32]), "+f"(d[33]), "+f"(d[34]), "+f"(d[35]), "+f"(d[36]), "+f"(d[37]), "+f"(d[38]), "+f"(d[39]), "+f"(d[40]), "+f"(d[41]), "+f"(d[42]), "+f"(d[43]), "+f"(d[44]), "+f"(d[45]), "+f"(d[46]), "+f"(d[47]), "+f"(d[48]), "+f"(d[49]), "+f"(d[50]), "+f"(d[51]), "+f"(d[52]), "+f"(d[53]), "+f"(d[54]), "+f"(d[55]), "+f"(d[56]), "+f"(d[57]), "+f"(d[58]), "+f"(d[59]), "+f"(d[60]), "+f"(d[61]), "+f"(d[62]), "+f"(d[63]), "+f"(d[64]), "+f"(d[65]), "+f"(d[66]), "+f"(d[67]), "+f"(d[68]), "+f"(d[69]), "+f"(d[70]), "+f"(d[71]), "+f"(d[72]), "+f"(d[73]), "+f"(d[74]), "+f"(d[75]), "+f"(d[76]), "+f"(d[77]), "+f"(d[78]), "+f"(d[79])
    : "l"(da), "l"(db), "r"(scale_d), "n"(TA), "n"(TB));
}
template <int TB>
__device__ __forceinline__ void wgmma_rs_n160(float (&d)[80], uint32_t a0, uint32_t a1, uint32_t a2, uint32_t a3, uint64_t db, int scale_d) {
  asm volatile("{\n.reg .pred p;\nsetp.ne.b32 p, %85, 0;\n"
    "wgmma.mma_async.sync.aligned.m64n160k16.f32.bf16.bf16 {%0, %1, %2, %3, %4, %5, %6, %7, %8, %9, %10, %11, %12, %13, %14, %15, %16, %17, %18, %19, %20, %21, %22, %23, %24, %25, %26, %27, %28, %29, %30, %31, %32, %33, %34, %35, %36, %37, %38, %39, %40, %41, %42, %43, %44, %45, %46, %47, %48, %49, %50, %51, %52, %53, %54, %55, %56, %57, %58, %59, %60, %61, %62, %63, %64, %65, %66, %67, %68, %69, %70, %71, %72, %73, %74, %75, %76, %77, %78, %79}, {%80, %81, %82, %83}, %84, p, 1, 1, %86;\n}\n"
    : "+f"(d[0]), "+f"(d[1]), "+f"(d[2]), "+f"(d[3]), "+f"(d[4]), "+f"(d[5]), "+f"(d[6]), "+f"(d[7]), "+f"(d[8]), "+f"(d[9]), "+f"(d[10]), "+f"(d[11]), "+f"(d[12]), "+f"(d[13]), "+f"(d[14]), "+f"(d[15]), "+f"(d[16]), "+f"(d[17]), "+f"(d[18]), "+f"(d[19]), "+f"(d[20]), "+f"(d[21]), "+f"(d[22]), "+f"(d[23]), "+f"(d[24]), "+f"(d[25]), "+f"(d[26]), "+f"(d[27]), "+f"(d[28]), "+f"(d[29]), "+f"(d[30]), "+f"(d[31]), "+f"(d[32]), "+f"(d[33]), "+f"(d[34]), "+f"(d[35]), "+f"(d[36]), "+f"(d[37]), "+f"(d[38]), "+f"(d[39]), "+f"(d[40]), "+f"(d[41]), "+f"(d[42]), "+f"(d[43]), "+f"(d[44]), "+f"(d[45]), "+f"(d[46]), "+f"(d[47]), "+f"(d[48]), "+f"(d[49]), "+f"(d[50]), "+f"(d[51]), "+f"(d[52]), "+f"(d[53]), "+f"(d[54]), "+f"(d[55]), "+f"(d[56]), "+f"(d[57]), "+f"(d[58]), "+f"(d[59]), "+f"(d[60]), "+f"(d[61]), "+f"(d[62]), "+f"(d[63]), "+f"(d[64]), "+f"(d[65]), "+f"(d[66]), "+f"(d[67]), "+f"(d[68]), "+f"(d[69]), "+f"(d[70]), "+f"(d[71]), "+f"(d[72]), "+f"(d[73]), "+f"(d[74]), "+f"(d[75]), "+f"(d[76]), "+f"(d[77]), "+f"(d[78]), "+f"(d[79])
    : "r"(a0), "r"(a1), "r"(a2), "r"(a3), "l"(db), "r"(scale_d), "n"(TB));
}
template <int TB, int TA = 0>
__device__ __forceinline__ void wgmma_ss_n192(float (&d)[96], uint64_t da, uint64_t db, int scale_d) {
  asm volatile("{\n.reg .pred p;\nsetp.ne.b32 p, %98, 0;\n"
    "wgmma.mma_async.sync.aligned.m64n192k16.f32.bf16.bf16 {%0, %1, %2, %3, %4, %5, %6, %7, %8, %9, %10, %11, %12, %13, %14, %15, %16, %17, %18, %19, %20, %21, %22, %23, %24, %25, %26, %27, %28, %29, %30, %31, %32, %33, %34, %35, %36, %37, %38, %39, %40, %41, %42, %43, %44, %45, %46, %47, %48, %49, %50, %51, %52, %53, %54, %55, %56, %57, %58, %59, %60, %61, %62, %63, %64, %65, %66, %67, %68, %69, %70, %71, %72, %73, %74, %75, %76, %77, %78, %79, %80, %81, %82, %83, %84, %85, %86, %87, %88, %89, %90, %91, %92, %93, %94, %95}, %96, %97, p, 1, 1, %99, %100;\n}\n"
    : "+f"(d[0]), "+f"(d[1]), "+f"(d[2]), "+f"(d[3]), "+f"(d[4]), "+f"(d[5]), "+f"(d[6]), "+f"(d[7]), "+f"(d[8]), "+f"(d[9]), "+f"(d[10]), "+f"(d[11]), "+f"(d[12]), "+f"(d[13]), "+f"(d[14]), "+f"(d[15]), "+f"(d[16]), "+f"(d[17]), "+f"(d[18]), "+f"(d[19]), "+f"(d[20]), "+f"(d[21]), "+f"(d[22]), "+f"(d[23]), "+f"(d[24]), "+f"(d[25]), "+f"(d[26]), "+f"(d[27]), "+f"(d[28]), "+f"(d[29]), "+f"(d[30]), "+f"(d[31]), "+f"(d[32]), "+f"(d[33]), "+f"(d[34]), "+f"(d[35]), "+f"(d[36]), "+f"(d[37]), "+f"(d[38]), "+f"(d[39]), "+f"(d[40]), "+f"(d[41]), "+f"(d[42]), "+f"(d[43]), "+f"(d[44]), "+f"(d[45]), "+f"(d[46]), "+f"(d[47]), "+f"(d[48]), "+f"(d[49]), "+f"(d[50]), "+f"(d[51]), "+f"(d[52]), "+f"(d[53]), "+f"(d[54]), "+f"(d[55]), "+f"(d[56]), "+f"(d[57]), "+f"(d[58]), "+f"(d[59]), "+f"(d[60]), "+f"(d[61]), "+f"(d[62]), "+f"(d[63]), "+f"(d[64]), "+f"(d[65]), "+f"(d[66]), "+f"(d[67]), "+f"(d[68]), "+f"(d[69]), "+f"(d[70]), "+f"(d[71]), "+f"(d[72]), "+f"(d[73]), "+f"(d[74]), "+f"(d[75]), "+f"(d[76]), "+f"(d[77]), "+f"(d[78]), "+f"(d[79]), "+f"(d[80]), "+f"(d[81]), "+f"(d[82]), "+f"(d[83]), "+f"(d[84]), "+f"(d[85]), "+f"(d[86]), "+f"(d[87]), "+f"(d[88]), "+f"(d[89]), "+f"(d[90]), "+f"(d[91]), "+f"(d[92]), "+f"(d[93]), "+f"(d[94]), "+f"(d[95])
    : "l"(da), "l"(db), "r"(scale_d), "n"(TA), "n"(TB));
}
template <int TB>
__device__ __forceinline__ void wgmma_rs_n192(float (&d)[96], uint32_t a0, uint32_t a1, uint32_t a2, uint32_t a3, uint64_t db, int scale_d) {
  asm volatile("{\n.reg .pred p;\nsetp.ne.b32 p, %101, 0;\n"
    "wgmma.mma_async.sync.aligned.m64n192k16.f32.bf16.bf16 {%0, %1, %2, %3, %4, %5, %6, %7, %8, %9, %10, %11, %12, %13, %14, %15, %16, %17, %18, %19, %20, %21, %22, %23, %24, %25, %26, %27, %28, %29, %30, %31, %32, %33, %34, %35, %36, %37, %38, %39, %40, %41, %42, %43, %44, %45, %46, %47, %48, %49, %50, %51, %52, %53, %54, %55, %56, %57, %58, %59, %60, %61, %62, %63, %64, %65, %66, %67, %68, %69, %70, %71, %72, %73, %74, %75, %76, %77, %78, %79, %80, %81, %82, %83, %84, %85, %86, %87, %88, %89, %90, %91, %92, %93, %94, %95}, {%96, %97, %98, %99}, %100, p, 1, 1, %102;\n}\n"
    : "+f"(d[0]), "+f"(d[1]), "+f"(d[2]), "+f"(d[3]), "+f"(d[4]), "+f"(d[5]), "+f"(d[6]), "+f"(d[7]), "+f"(d[8]), "+f"(d[9]), "+f"(d[10]), "+f"(d[11]), "+f"(d[12]), "+f"(d[13]), "+f"(d[14]), "+f"(d[15]), "+f"(d[16]), "+f"(d[17]), "+f"(d[18]), "+f"(d[19]), "+f"(d[20]), "+f"(d[21]), "+f"(d[22]), "+f"(d[23]), "+f"(d[24]), "+f"(d[25]), "+f"(d[26]), "+f"(d[27]), "+f"(d[28]), "+f"(d[29]), "+f"(d[30]), "+f"(d[31]), "+f"(d[32]), "+f"(d[33]), "+f"(d[34]), "+f"(d[35]), "+f"(d[36]), "+f"(d[37]), "+f"(d[38]), "+f"(d[39]), "+f"(d[40]), "+f"(d[41]), "+f"(d[42]), "+f"(d[43]), "+f"(d[44]), "+f"(d[45]), "+f"(d[46]), "+f"(d[47]), "+f"(d[48]), "+f"(d[49]), "+f"(d[50]), "+f"(d[51]), "+f"(d[52]), "+f"(d[53]), "+f"(d[54]), "+f"(d[55]), "+f"(d[56]), "+f"(d[57]), "+f"(d[58]), "+f"(d[59]), "+f"(d[60]), "+f"(d[61]), "+f"(d[62]), "+f"(d[63]), "+f"(d[64]), "+f"(d[65]), "+f"(d[66]), "+f"(d[67]), "+f"(d[68]), "+f"(d[69]), "+f"(d[70]), "+f"(d[71]), "+f"(d[72]), "+f"(d[73]), "+f"(d[74]), "+f"(d[75]), "+f"(d[76]), "+f"(d[77]), "+f"(d[78]), "+f"(d[79]), "+f"(d[80]), "+f"(d[81]), "+f"(d[82]), "+f"(d[83]), "+f"(d[84]), "+f"(d[85]), "+f"(d[86]), "+f"(d[87]), "+f"(d[88]), "+f"(d[89]), "+f"(d[90]), "+f"(d[91]), "+f"(d[92]), "+f"(d[93]), "+f"(d[94]), "+f"(d[95])
    : "r"(a0), "r"(a1), "r"(a2), "r"(a3), "l"(db), "r"(scale_d), "n"(TB));
}

__device__ __forceinline__ uint32_t smem_u32(const void* p) { return (uint32_t)__cvta_generic_to_shared(p); }
__device__ __forceinline__ void wg_fence() { asm volatile("wgmma.fence.sync.aligned;" ::: "memory"); }
__device__ __forceinline__ void wg_commit() { asm volatile("wgmma.commit_group.sync.aligned;" ::: "memory"); }
template <int N> __device__ __forceinline__ void wg_wait() { asm volatile("wgmma.wait_group.sync.aligned %0;" ::"n"(N) : "memory"); }
__device__ __forceinline__ void sched_fence(int& keep, uint32_t zero) {
  asm volatile("{\n.reg .u32 c;\nmov.u32 c, %%clock;\nand.b32 c, c, %1;\nxor.b32 %0, %0, c;\n}\n" : "+r"(keep) : "r"(zero) : "memory");
}
template <int N> __device__ __forceinline__ void fence_regs(float (&r)[N]) {
#pragma unroll
  for (int i = 0; i < N; i++) asm volatile("" : "+f"(r[i])::"memory");
}
template <int N> __device__ __forceinline__ void fence_regs(uint32_t (&r)[N]) {
#pragma unroll
  for (int i = 0; i < N; i++) asm volatile("" : "+r"(r[i])::"memory");
}
__device__ __forceinline__ uint64_t mk_desc(uint32_t a16, uint32_t lbo, uint32_t sbo, uint32_t swz) {
  uint64_t d;
  asm("mov.b64 %0, {%1, %2};" : "=l"(d) : "r"(a16 + ((lbo >> 4) << 16)), "r"((sbo >> 4) | (swz << 30)));
  return d;
}
__device__ __forceinline__ void mbar_init(uint32_t bar, uint32_t cnt) {
  asm volatile("mbarrier.init.shared::cta.b64 [%0], %1;" ::"r"(bar), "r"(cnt) : "memory");
}
__device__ __forceinline__ void mbar_expect(uint32_t bar, uint32_t tx) {
  asm volatile("mbarrier.arrive.expect_tx.shared::cta.b64 _, [%0], %1;" ::"r"(bar), "r"(tx) : "memory");
}
__device__ __forceinline__ bool mbar_test(uint32_t bar, uint32_t ph) {
  uint32_t ok;
  asm volatile("{\n.reg .pred p;\nmbarrier.test_wait.parity.shared::cta.b64 p, [%1], %2;\nselp.u32 %0, 1, 0, p;\n}\n"
               : "=r"(ok) : "r"(bar), "r"(ph) : "memory");
  return ok;
}
__device__ __forceinline__ void mbar_wait(uint32_t bar, uint32_t ph) {
  asm volatile("{\n.reg .pred p;\n.reg .u32 n;\n"
               "mbarrier.try_wait.parity.shared::cta.b64 p, [%0], %1;\n@p bra DONE;\n"
               "mov.u32 n, 0;\n"
               "LOOP:\nmbarrier.try_wait.parity.shared::cta.b64 p, [%0], %1;\n@p bra DONE;\n"
               "add.u32 n, n, 1;\nsetp.lt.u32 p, n, 0x1000000;\n@p bra LOOP;\ntrap;\n"
               "DONE:\n}\n" ::"r"(bar), "r"(ph) : "memory");
}
template <int NS> __device__ __forceinline__ void mbar_wait_slow(uint32_t bar, uint32_t ph) {
  asm volatile("{\n.reg .pred p;\n.reg .u32 n;\nmov.u32 n, 0;\n"
               "LOOP:\nmbarrier.test_wait.parity.shared::cta.b64 p, [%0], %1;\n@p bra DONE;\n"
               "nanosleep.u32 %2;\nadd.u32 n, n, 1;\nsetp.lt.u32 p, n, 0x400000;\n@p bra LOOP;\ntrap;\n"
               "DONE:\n}\n" ::"r"(bar), "r"(ph), "n"(NS) : "memory");
}
__device__ __forceinline__ void mbar_arrive_cluster_if(bool on, uint32_t addr) {
  asm volatile("{\n.reg .pred p;\nsetp.ne.b32 p, %1, 0;\n@p mbarrier.arrive.shared::cluster.b64 _, [%0];\n}\n" ::"r"(addr), "r"((int)on) : "memory");
}
__device__ __forceinline__ void mbar_arrive_if(bool on, uint32_t addr) {
  asm volatile("{\n.reg .pred p;\nsetp.ne.b32 p, %1, 0;\n@p mbarrier.arrive.shared::cta.b64 _, [%0];\n}\n" ::"r"(addr), "r"((int)on) : "memory");
}
__device__ __forceinline__ void tma2d(uint32_t dst, const CUtensorMap* m, uint32_t bar, int c0, int c1) {
  asm volatile("cp.async.bulk.tensor.2d.shared::cluster.global.mbarrier::complete_tx::bytes [%0], [%1, {%3, %4}], [%2];"
               ::"r"(dst), "l"(m), "r"(bar), "r"(c0), "r"(c1) : "memory");
}
__device__ __forceinline__ void tma3d(uint32_t dst, const CUtensorMap* m, uint32_t bar, int c0, int c1, int c2) {
  asm volatile("cp.async.bulk.tensor.3d.shared::cluster.global.mbarrier::complete_tx::bytes [%0], [%1, {%3, %4, %5}], [%2];"
               ::"r"(dst), "l"(m), "r"(bar), "r"(c0), "r"(c1), "r"(c2) : "memory");
}
__device__ __forceinline__ void tma3d_mc(uint32_t dst, const CUtensorMap* m, uint32_t bar, int c0, int c1, int c2) {
  asm volatile("cp.async.bulk.tensor.3d.shared::cluster.global.mbarrier::complete_tx::bytes.multicast::cluster"
               " [%0], [%1, {%3, %4, %5}], [%2], %6;"
               ::"r"(dst), "l"(m), "r"(bar), "r"(c0), "r"(c1), "r"(c2), "h"((uint16_t)3) : "memory");
}
__device__ __forceinline__ void tma3d_store(const CUtensorMap* m, uint32_t src, int c0, int c1, int c2) {
  asm volatile("cp.async.bulk.tensor.3d.global.shared::cta.bulk_group [%0, {%2, %3, %4}], [%1];"
               ::"l"(m), "r"(src), "r"(c0), "r"(c1), "r"(c2) : "memory");
}
__device__ __forceinline__ void bar_sync(int id, int n) { asm volatile("bar.sync %0, %1;" ::"r"(id), "r"(n) : "memory"); }
__device__ __forceinline__ uint32_t pack_bf16(float lo, float hi) {
  uint32_t r;
  asm("cvt.rn.bf16x2.f32 %0, %1, %2;" : "=r"(r) : "f"(hi), "f"(lo));
  return r;
}
__device__ __forceinline__ float ex2(float x) {
  float y;
  asm("ex2.approx.ftz.f32 %0, %1;" : "=f"(y) : "f"(x));
  return y;
}
__device__ __forceinline__ float fadd(float a, float b) {
  float y;
  asm("add.f32 %0, %1, %2;" : "=f"(y) : "f"(a), "f"(b));
  return y;
}
__device__ __forceinline__ float rcp(float x) {
  float y;
  asm("rcp.approx.ftz.f32 %0, %1;" : "=f"(y) : "f"(x));
  return y;
}
__device__ __forceinline__ void stsm4(uint32_t addr, uint32_t a, uint32_t b, uint32_t c, uint32_t d) {
  asm volatile("stmatrix.sync.aligned.m8n8.x4.shared.b16 [%0], {%1, %2, %3, %4};" ::"r"(addr), "r"(a), "r"(b), "r"(c), "r"(d) : "memory");
}

__device__ __forceinline__ void tma4d_mc_hint(uint32_t dst, const CUtensorMap* m, uint32_t bar, int c3, uint64_t pol) {
  asm volatile("cp.async.bulk.tensor.4d.shared::cluster.global.mbarrier::complete_tx::bytes.multicast::cluster.L2::cache_hint"
               " [%0], [%1, {%3, %3, %3, %4}], [%2], %5, %6;"
               ::"r"(dst), "l"(m), "r"(bar), "r"(0), "r"(c3), "h"((uint16_t)3), "l"(pol) : "memory");
}
__device__ __forceinline__ void tma5d_mc(uint32_t dst, const CUtensorMap* m, uint32_t bar, int c2, int c4) {
  asm volatile("cp.async.bulk.tensor.5d.shared::cluster.global.mbarrier::complete_tx::bytes.multicast::cluster"
               " [%0], [%1, {%3, %3, %4, %3, %5}], [%2], %6;"
               ::"r"(dst), "l"(m), "r"(bar), "r"(0), "r"(c2), "r"(c4), "h"((uint16_t)3) : "memory");
}
__device__ __forceinline__ void bulk_load_hint(uint32_t dst, const void* src, uint32_t bytes, uint32_t bar, uint64_t pol) {
  asm volatile("cp.async.bulk.shared::cluster.global.mbarrier::complete_tx::bytes.L2::cache_hint [%0], [%1], %2, [%3], %4;"
               ::"r"(dst), "l"(src), "r"(bytes), "r"(bar), "l"(pol) : "memory");
}
__device__ __forceinline__ void stg128_hint(void* p, uint32_t a, uint32_t b, uint32_t c, uint32_t d, uint64_t pol) {
  asm volatile("st.global.L2::cache_hint.v4.b32 [%0], {%1, %2, %3, %4}, %5;" ::"l"(p), "r"(a), "r"(b), "r"(c), "r"(d), "l"(pol) : "memory");
}
__device__ __forceinline__ void stg2_if(bool on, void* p, uint32_t a, uint32_t b, uint32_t c, uint32_t d, uint32_t e, uint32_t f,
                                        uint32_t g, uint32_t h, uint64_t pol) {
  asm volatile("{\n.reg .pred p;\nsetp.ne.b32 p, %10, 0;\n"
               "@p st.global.L2::cache_hint.v4.b32 [%0], {%1, %2, %3, %4}, %9;\n"
               "@p st.global.L2::cache_hint.v4.b32 [%0 + 512], {%5, %6, %7, %8}, %9;\n}\n"
               ::"l"(p), "r"(a), "r"(b), "r"(c), "r"(d), "r"(e), "r"(f), "r"(g), "r"(h), "l"(pol), "r"((int)on) : "memory");
}
__device__ __forceinline__ uint64_t make_policy(bool first) {
  uint64_t pf, pn;
  asm("createpolicy.fractional.L2::evict_first.b64 %0, 1.0;" : "=l"(pf));
  asm("createpolicy.fractional.L2::evict_normal.b64 %0, 1.0;" : "=l"(pn));
  return first ? pf : pn;
}
__device__ __forceinline__ bool elect() {
  uint32_t ok;
  asm volatile("{\n.reg .pred p;\nelect.sync _|p, 0xffffffff;\nselp.u32 %0, 1, 0, p;\n}\n" : "=r"(ok));
  return ok;
}
__device__ __forceinline__ void mbar_arrive(uint32_t bar) {
  asm volatile("mbarrier.arrive.shared::cta.b64 _, [%0];" ::"r"(bar) : "memory");
}
__device__ __forceinline__ void stg128(void* p, uint32_t a, uint32_t b, uint32_t c, uint32_t d) {
  asm volatile("st.global.v4.b32 [%0], {%1, %2, %3, %4};" ::"l"(p), "r"(a), "r"(b), "r"(c), "r"(d) : "memory");
}
__device__ __forceinline__ void lds128(uint32_t p, uint32_t& a, uint32_t& b, uint32_t& c, uint32_t& d) {
  asm volatile("ld.shared.v4.b32 {%0, %1, %2, %3}, [%4];" : "=r"(a), "=r"(b), "=r"(c), "=r"(d) : "r"(p) : "memory");
}
__device__ __forceinline__ void wait_count(const unsigned int* p, uint32_t target) {
  asm volatile("{\n.reg .pred p;\n.reg .u32 n, v;\nmov.u32 n, 0;\n"
               "LOOP:\nld.acquire.gpu.global.u32 v, [%0];\nsetp.ge.u32 p, v, %1;\n@p bra DONE;\n"
               "nanosleep.u32 %2;\nadd.u32 n, n, 1;\nsetp.lt.u32 p, n, 0x400000;\n@p bra LOOP;\ntrap;\n"
               "DONE:\n}\n" ::"l"(p), "r"(target), "n"(200) : "memory");
}

__host__ __device__ __forceinline__ int o_wave(int a, int b, int i, int lag) {
  if (lag == 0) return a + i;
  const int p = lag < b - a - 1 ? lag : b - a - 1;
  return i < p ? b - 2 - i : i == p ? b - 1 : b - 1 - i;
}

struct Cursor {
  int bi;
  uint32_t ph;
  __device__ __forceinline__ void next() {
    if (++bi == NBAR) { bi = 0; ph ^= 1; }
  }
};

constexpr float kScaleLog2 = 0.07216878364870322f * 1.4426950408889634f;
constexpr float kSumLimit = 1048576.0f;
constexpr float kMaxLag = 8.0f;

__global__ void __cluster_dims__(2, 1, 1) __launch_bounds__(384, 1)
fused_kernel(const __grid_constant__ Params P) {
  extern __shared__ uint8_t smem_raw[];
  const uint32_t sbase = (smem_u32(smem_raw) + 1023) & ~1023u;
  const uint32_t full0 = sbase + RING, empty0 = full0 + 8 * NBAR, odone = empty0 + 8 * NBAR, oready0 = odone + 8;
  const uint32_t fenced = oready0 + 64, hready0 = fenced + 8;
  const uint32_t rank = blockIdx.x & 1;
  const int role = blockIdx.x >> 1;
  const bool helper = role >= N_CL;
  const int team = helper ? 0 : role >> 2, nt = role & 3, blk = team >> 3;
  const uint32_t* prog = P.ops[helper ? N_TEAM + 2 * (role - N_CL) : team];
  auto q_role = [&](uint32_t op) { return helper ? (int)(((op >> 3) & 60) | ((op >> 12) & 3)) : role; };
  auto o_role = [&](uint32_t op) { return helper ? (int)(((op >> 26) & 56) | ((op >> 9) & 7)) : role; };
  const int wid = __shfl_sync(0xffffffffu, (int)(threadIdx.x >> 5), 0);
  const int wg = wid >> 2;

  const uint32_t op0 = P.first[helper ? N_TEAM + role - N_CL : team];
  if (__builtin_expect(wid == 8, 1)) {
    if (elect()) {
#pragma unroll
      for (int k = 0; k < EARLY; k++) mbar_init(full0 + 8 * k, 1);
      asm volatile("fence.mbarrier_init.release.cluster;" ::: "memory");
      if ((op0 & 3) == OP_Q) {
        const int qr = q_role(op0);
#pragma unroll
        for (int k = 0; k < EARLY; k++) {
          mbar_expect(full0 + 8 * k, SZ_Q);
          tma2d(sbase + k * SZ_Q, &P.x[qr >> 5], full0 + 8 * k, 64 * k, ((qr >> 2) & 7) * kSq + rank * 128);
          tma3d(sbase + k * SZ_Q + 16384, &P.wq[qr >> 5], full0 + 8 * k, 0, 64 * k, 3 * (4 * ((op0 >> 2) & 7) + (qr & 3)));
        }
      }
      asm volatile("prefetch.tensormap [%0];" ::"l"(rank ? &P.v[blk] : &P.k[blk]) : "memory");
    }
  } else if (threadIdx.x == 0) {
#pragma unroll
    for (int i = EARLY; i < 2 * NBAR + 10 + MAX_PARK; i++) mbar_init(full0 + 8 * i, i < NBAR ? 1 : i <= 2 * NBAR ? 16 : 1);
    asm volatile("fence.mbarrier_init.release.cluster;" ::: "memory");
  }
  __syncwarp();
  asm volatile("barrier.cluster.arrive.relaxed.aligned;\nbarrier.cluster.wait.aligned;" ::: "memory");

  if (wg == 2) {
    asm volatile("setmaxnreg.dec.sync.aligned.u32 24;");
    if (wid == 8) {
      Cursor tail{0, 0};
      int head = 0, sh = 0;
      uint32_t hph = 0;
      uint32_t cur = 0, used = 0;
      uint64_t fifo = 0;
      uint32_t dst, bar, oready = oready0;
      uint64_t pol;
      asm volatile("createpolicy.fractional.L2::evict_first.b64 %0, 1.0;" : "=l"(pol));
      const uint64_t pol_o = make_policy(P.dbg & 1), pol_p = make_policy(!(P.dbg & 4));
      const CUtensorMap* kv_map = rank ? &P.v[blk] : &P.k[blk];
      auto acquire = [&](uint32_t bytes) {
        uint32_t fp = bytes >> 12;
        if (cur + fp > (RING >> 12)) { fp += (RING >> 12) - cur; cur = 0; }
        used += fp;
        while (used > (RING >> 12) || sh == 5 * NBAR) {
          mbar_wait(empty0 + 8 * tail.bi, tail.ph);
          tail.next();
          used -= (uint32_t)fifo & 31;
          fifo >>= 5;
          sh -= 5;
        }
        fifo |= (uint64_t)fp << sh;
        sh += 5;
        dst = sbase + (cur << 12);
        bar = full0 + 8 * head;
        cur += bytes >> 12;
        if (++head == NBAR) { head = 0; hph ^= 1; }
      };
      for (int pc = 0;; pc++) {
        const uint32_t op = prog[pc];
        const int type = op & 3, a = (op >> 2) & 7;
        if (type == OP_END) break;
        if (type == OP_Q) {
          const int qr = q_role(op);
#pragma unroll 1
          for (int k = 0; k < 10; k++) {
            acquire(SZ_Q);
            if ((pc > 0 || k >= EARLY) && elect()) {
              mbar_expect(bar, SZ_Q);
              tma2d(dst, &P.x[qr >> 5], bar, 64 * k, ((qr >> 2) & 7) * kSq + rank * 128);
              if ((k & 1) == rank) tma3d_mc(dst + 16384, &P.wq[qr >> 5], bar, 0, 64 * k, 3 * (4 * a + (qr & 3)));
            }
          }
        } else if (type == OP_A) {
          const uint32_t nop = prog[pc + 1];
          auto kv = [&](int isv, int wave, int j) {
            const int row0 = ((team & 7) * kH + 4 * wave + nt) * kSk;
            acquire(SZ_KV);
            if (isv == (int)rank) {
              const int j = head - 1 - KV_TRANSIT;
              mbar_wait(full0 + 8 * (j < 0 ? j + NBAR : j), j < 0 ? hph ^ 1 : hph);
            }
            if (elect()) {
              mbar_expect(bar, SZ_KV);
              if (isv == (int)rank) tma4d_mc_hint(dst, kv_map, bar, row0 / 8 + 8 * j, pol);
            }
          };
#pragma unroll 1
          for (int t = (op & F_PARK) ? 1 : 0; t < 31; t++) {
            const int isv = t == 0 ? 0 : (~t & 1);
            kv(isv, a, isv ? (t - 1) >> 1 : (t + 1) >> 1);
          }
          if ((nop & 3) == OP_A) {
            mbar_wait((nop & F_HELP) ? hready0 + 8 * ((nop >> 10) & 3) : fenced, 0);
            asm volatile("fence.proxy.async.global;" ::: "memory");
#pragma unroll 1
            for (int i = 0; i < 2; i++) {
              acquire(SZ_PARK);
              if (elect()) {
                mbar_expect(bar, SZ_PARK);
                bulk_load_hint(dst, &g_o[((team * 2 + rank) * 96 + 3 * (4 * ((nop >> 2) & 7) + nt)) * 1024 + i * 1536], SZ_PARK, bar, pol_p);
              }
            }
            kv(0, (nop >> 2) & 7, 0);
          }
          kv(1, a, 15);
        } else {
          const int b = (op >> 5) & 15, ro = o_role(op);
#pragma unroll 1
          for (int i = 0; i < b - a; i++) {
            const int w = o_wave(a, b, i, (P.dbg >> 4) & 7);
            mbar_wait(oready, 0);
            oready += 8;
            asm volatile("fence.proxy.async.global;" ::: "memory");
#pragma unroll 1
            for (int k = 12 * w; k < 12 * w + 12; k++) {
              acquire(SZ_O);
              if (elect()) {
                mbar_expect(bar, SZ_O);
                tma5d_mc(dst + 16384 + rank * 10240, &P.wo[ro >> 5], bar, 8 * k + 4 * rank, 5 * (ro & 3));
                bulk_load_hint(dst, &g_o[(((ro >> 2) * 2 + rank) * 96 + k - 12 * (w - P.slot[w])) * 1024], 16384, bar, pol_o);
              }
            }
          }
          if (op & F_LD) {
            if (op & F_PARK) {
              mbar_wait(hready0 + 8 * (MAX_PARK - 1), 0);
              asm volatile("fence.proxy.async.global;" ::: "memory");
            }
#pragma unroll 1
            for (int i = 0; i < 5; i++) {
              acquire(SZ_PART);
              if (elect()) {
                mbar_expect(bar, SZ_PART);
                bulk_load_hint(dst, &g_part[(role * 2 + rank) * 5120 + i * 1024], SZ_PART, bar, pol_p);
              }
            }
          }
        }
      }
    } else if (threadIdx.x == 288) {
      uint32_t ph = 0;
      bool first = true;
      for (int pc = 0;; pc++) {
        const uint32_t op = prog[pc];
        if ((op & 3) == OP_END) break;
        if ((op & 3) != OP_A && !helper) continue;
        mbar_wait_slow<400>(odone, ph);
        ph ^= 1;
        unsigned int* flag = !helper ? &g_done[(team * 2 + rank) * 8 + ((op >> 2) & 7)]
                             : (op & 3) == OP_Q ? &g_help[(q_role(op) * 2 + rank) * MAX_PARK + ((op >> 10) & 3)]
                                                : &g_help[(o_role(op) * 2 + rank) * MAX_PARK + MAX_PARK - 1];
        asm volatile("red.release.gpu.global.add.u32 [%0], 1;" ::"l"(flag) : "memory");
        if (first) mbar_arrive(fenced);
        first = false;
      }
    } else if (threadIdx.x == 320) {
      uint32_t oready = oready0;
      for (int pc = 0;; pc++) {
        const uint32_t op = prog[pc];
        if ((op & 3) == OP_END) break;
        if ((op & 3) == OP_O) {
          const int a = (op >> 2) & 7, b = (op >> 5) & 15;
          for (int i = 0; i < b - a; i++) {
            const int ci = ((o_role(op) >> 2) * 2 + rank) * 8 + o_wave(a, b, i, (P.dbg >> 4) & 7);
            wait_count(&g_done[ci], 4);
            mbar_arrive(oready);
            oready += 8;
            if (atomicAdd(&g_seen[ci], 1u) == 3u) { g_seen[ci] = 0; g_done[ci] = 0; }
          }
        }
        if ((op & 3) != OP_Q && (op & F_HELP) && (op & F_PARK)) {
          unsigned int* flag = &g_help[(role * 2 + rank) * MAX_PARK + ((op >> 10) & 3)];
          wait_count(flag, 1);
          mbar_arrive(hready0 + 8 * ((op >> 10) & 3));
          *flag = 0;
        }
      }
    }
    __syncwarp();
    asm volatile("barrier.cluster.arrive.relaxed;\nbarrier.cluster.wait;" ::: "memory");
  } else {
    asm volatile("setmaxnreg.inc.sync.aligned.u32 240;");
    const int lane = threadIdx.x & 31, warp = wid & 3;
    uint32_t empty_rem;
    asm volatile("mapa.shared::cluster.u32 %0, %1, %2;" : "=r"(empty_rem) : "r"(empty0), "r"(lane & 1));
    auto release = [&](int slot) { mbar_arrive_cluster_if(lane < 2, empty_rem + 8 * slot); };
    Cursor r{0, 0};
    const uint32_t ring16 = (sbase & 0x3FFFF) >> 4;
    uint32_t cur = ring16;
    bool rdy0 = false, rdy1 = false;
    auto probe1 = [&]() { rdy0 = mbar_test(full0 + 8 * r.bi, r.ph); };
    auto probe2 = [&]() {
      Cursor n = r;
      rdy0 = mbar_test(full0 + 8 * n.bi, n.ph);
      n.next();
      rdy1 = mbar_test(full0 + 8 * n.bi, n.ph);
    };
    auto take = [&](bool rdy, uint32_t bytes, uint32_t& addr) {
      const int bi = r.bi;
      if (!__all_sync(0xffffffffu, rdy)) mbar_wait(full0 + 8 * r.bi, r.ph);
      r.next();
      if (cur > ring16 + ((RING - bytes) >> 4)) cur = ring16;
      addr = cur;
      cur += bytes >> 4;
      return bi;
    };
    const int row = wg * 64 + warp * 16 + (lane >> 2);
    int img0 = row * 4 + ((lane & 3) ^ ((row >> 1) & 3));
    uint4* pend = nullptr;
    uint64_t spol;
    int pc = 0;
    uint32_t op = prog[0];
    auto enter = [&]() {
      r.bi = (op >> 15) & 15; r.ph = (op >> 19) & 1; cur = ring16 + (((op >> 20) & 63) << 8);
      spol = make_policy(!(op & F_SOON));
    };
    auto drain = [&](uint32_t (&t)[48], uint32_t c) {
      if (!(op & (3u << 26)) || c >= 6) return;
#pragma unroll
      for (int i = 0; i < 6; i++)
        stg2_if(c == i, pend + i * 512, t[8 * i], t[8 * i + 1], t[8 * i + 2], t[8 * i + 3],
                t[8 * i + 4], t[8 * i + 5], t[8 * i + 6], t[8 * i + 7], spol);
      if ((op & (1u << 26)) && c == 5) {
        __syncwarp();
        mbar_arrive_if(lane < 2, odone);
      }
    };
    float s[32], o[96], c[80];
    uint32_t q[48], pa[16], pb[16];
    float mc0, mc1, l0, l1;
    bool gen;
    auto expo = [&](float (&s)[32], uint32_t (&pout)[16], float& b0, float& b1, bool sub) {
#pragma unroll
      for (int i = 0; i < 8; i++) {
        const float e1 = ex2(sub ? s[4 * i + 1] - mc0 : s[4 * i + 1]), e0 = ex2(sub ? s[4 * i] - mc0 : s[4 * i]);
        const float e3 = ex2(sub ? s[4 * i + 3] - mc1 : s[4 * i + 3]), e2 = ex2(sub ? s[4 * i + 2] - mc1 : s[4 * i + 2]);
        pout[2 * i] = pack_bf16(e0, e1);
        b0 = i ? b0 + fadd(e1, e0) : fadd(e1, e0);
        pout[2 * i + 1] = pack_bf16(e2, e3);
        b1 = i ? b1 + fadd(e3, e2) : fadd(e3, e2);
      }
    };
    auto rowmax = [&](float (&s)[32], float& m0, float& m1) {
      m0 = fmaxf(s[0], s[1]); m1 = fmaxf(s[2], s[3]);
#pragma unroll
      for (int i = 1; i < 8; i++) { m0 = fmaxf(m0, fmaxf(s[4 * i], s[4 * i + 1])); m1 = fmaxf(m1, fmaxf(s[4 * i + 2], s[4 * i + 3])); }
      m0 = fmaxf(m0, __shfl_xor_sync(0xffffffffu, m0, 1)); m1 = fmaxf(m1, __shfl_xor_sync(0xffffffffu, m1, 1));
      m0 = fmaxf(m0, __shfl_xor_sync(0xffffffffu, m0, 2)); m1 = fmaxf(m1, __shfl_xor_sync(0xffffffffu, m1, 2));
    };
    auto first = [&](float (&s)[32]) {
      mc0 = 0.f; mc1 = 0.f;
      expo(s, pa, l0, l1, false);
      gen = __any_sync(0xffffffffu, !(fmaxf(l0, l1) <= kSumLimit && fminf(l0, l1) >= 1.0f / kSumLimit));
      if (gen) {
        rowmax(s, mc0, mc1);
        expo(s, pa, l0, l1, true);
      }
    };
    auto soft = [&](uint32_t (&pout)[16]) {
      float b0, b1;
      if (!gen) {
        expo(s, pout, b0, b1, false);
        gen = __any_sync(0xffffffffu, !(fmaxf(b0, b1) <= kSumLimit));
      }
      if (gen) {
        float m0, m1;
        rowmax(s, m0, m1);
        if (__any_sync(0xffffffffu, !(m0 <= mc0 + kMaxLag && m1 <= mc1 + kMaxLag))) {
          m0 = fmaxf(mc0, m0); m1 = fmaxf(mc1, m1);
          const float a0 = ex2(mc0 - m0), a1 = ex2(mc1 - m1);
          mc0 = m0; mc1 = m1;
          l0 *= a0; l1 *= a1;
          wg_wait<0>();
          fence_regs(o);
#pragma unroll
          for (int i = 0; i < 24; i++) { o[4 * i] *= a0; o[4 * i + 1] *= a0; o[4 * i + 2] *= a1; o[4 * i + 3] *= a1; }
        }
        expo(s, pout, b0, b1, true);
      }
      l0 += b0; l1 += b1;
    };
    auto qk = [&](float (&s)[32], uint32_t ak, int k0, int k1) {
#pragma unroll
      for (int kk = k0; kk < k1; kk++)
        wgmma_rs_n64<0>(s, q[4 * kk], q[4 * kk + 1], q[4 * kk + 2], q[4 * kk + 3], mk_desc(ak + (kk >> 2) * KV_CH + (kk & 3) * 2, 16, KV_SBO, 1), kk != 0);
      wg_commit();
    };
    auto pv = [&](uint32_t (&pin)[16], uint32_t av, int acc) {
#pragma unroll
      for (int kk = 0; kk < 4; kk++)
        wgmma_rs_n192<1>(o, pin[4 * kk], pin[4 * kk + 1], pin[4 * kk + 2], pin[4 * kk + 3], mk_desc(av + kk * (KV_SBO / 8), KV_CH * 16, KV_SBO, 1), acc || (kk != 0));
      wg_commit();
    };
    auto xw = [&](uint32_t ad, int acc) {
      wg_fence();
#pragma unroll
      for (int kk = 0; kk < 4; kk++)
        wgmma_ss_n192<1>(o, mk_desc(ad + wg * 512 + kk * 2, 16, 1024, 1), mk_desc(ad + 1024 + kk * 128, 8192, 1024, 1), acc || kk != 0);
      wg_commit();
    };
    auto ow = [&](int acc, int prev) {
      uint32_t ad;
      const int bi = take(rdy0, SZ_O, ad);
      const uint32_t da = ad + wg * 256, db = ad + 1024;
      wg_fence();
      wgmma_ss_n160<1>(c, mk_desc(da, 16, 512, 2), mk_desc(db, 2048, 512, 2), acc);
      wgmma_ss_n160<1>(c, mk_desc(da + 2, 16, 512, 2), mk_desc(db + 64, 2048, 512, 2), 1);
      wg_commit();
      if (acc) { wg_wait<1>(); release(prev); }
      wgmma_ss_n160<1>(c, mk_desc(da + 512, 16, 512, 2), mk_desc(db + 640, 2048, 512, 2), 1);
      wgmma_ss_n160<1>(c, mk_desc(da + 514, 16, 512, 2), mk_desc(db + 704, 2048, 512, 2), 1);
      wg_commit();
      return bi;
    };
    auto o_run = [&](uint32_t (&t)[48], int bi) {
      const int nk = 12 * (((op >> 5) & 15) - ((op >> 2) & 7));
#pragma unroll 1
      for (int k = 0; k < 6; k++) {
        drain(t, k);
        probe1();
        wg_wait<1>();
        bi = ow(1, bi);
      }
#pragma unroll 1
      for (int k = 7; k < nk; k++) {
        probe1();
        wg_wait<1>();
        bi = ow(1, bi);
      }
      probe1();
      return bi;
    };
    auto st_part = [&](int i) {
      stg2_if(true, pend + i * 512, __float_as_uint(c[8 * i]), __float_as_uint(c[8 * i + 1]), __float_as_uint(c[8 * i + 2]), __float_as_uint(c[8 * i + 3]),
              __float_as_uint(c[8 * i + 4]), __float_as_uint(c[8 * i + 5]), __float_as_uint(c[8 * i + 6]), __float_as_uint(c[8 * i + 7]), spol);
    };
#pragma unroll
    for (int i = 0; i < 48; i++) q[i] = 0;
    enter();

    if ((op & 3) == OP_Q) {
      uint32_t ad;
      int bi0 = take(false, SZ_Q, ad), k = 0, lag = 0;
      xw(ad, 0);
      for (;;) {
#pragma unroll 1
        for (;;) {
          drain(q, k - lag);
          probe1();
          wg_wait<0>();
          release(bi0);
          bi0 = take(rdy0, SZ_Q, ad);
          if (++k == 8) break;
          xw(ad, 1);
        }
        if (wg) bar_sync(2, 256);
        xw(ad, 1);
        const int bi9 = take(false, SZ_Q, ad);
        xw(ad, 1);
        if (!wg) asm volatile("bar.arrive 2, 256;" ::: "memory");
        k = 0; lag = 0;
        uint32_t nop = prog[++pc];
        if (op & F_PARK) {
          pend = &g_o[(((q_role(op) >> 2) * 2 + rank) * 96 + 3 * (4 * ((op >> 2) & 7) + (q_role(op) & 3))) * 1024 + img0];
          op = nop;
          enter();
          wg_wait<1>();
          release(bi0);
          probe1();
          wg_wait<0>();
          fence_regs(o);
          release(bi9);
#pragma unroll
          for (int i = 0; i < 48; i++) q[i] = pack_bf16(o[2 * i] * kScaleLog2, o[2 * i + 1] * kScaleLog2);
          if ((op & 3) != OP_Q) break;
          fence_regs(q);
          bi0 = take(rdy0, SZ_Q, ad);
          xw(ad, 0);
          continue;
        }
        int wave = (op >> 2) & 7, sk1;
        uint32_t ak1;
        {
          wg_wait<1>();
          release(bi0);
          probe2();
          wg_wait<0>();
          fence_regs(o);
          release(bi9);
          float s0[32];
#pragma unroll
          for (int i = 0; i < 48; i++) q[i] = pack_bf16(o[2 * i] * kScaleLog2, o[2 * i + 1] * kScaleLog2);
          fence_regs(q);
          const int sk0 = take(rdy0, SZ_KV, ad);
          wg_fence();
          qk(s0, ad, 0, 12);
          sk1 = take(rdy1, SZ_KV, ak1);
          wg_fence();
          qk(s, ak1, 0, S1A);
          probe1();
          wg_wait<1>();
          fence_regs(s0);
          release(sk0);
          first(s0);
        }
        float i0, i1;
        auto sums = [&]() {
          l0 += __shfl_xor_sync(0xffffffffu, l0, 1); l1 += __shfl_xor_sync(0xffffffffu, l1, 1);
          l0 += __shfl_xor_sync(0xffffffffu, l0, 2); l1 += __shfl_xor_sync(0xffffffffu, l1, 2);
          i0 = rcp(l0); i1 = rcp(l1);
          asm volatile("" : "+f"(i0), "+f"(i1));
        };
        auto target = [&]() {
          pend = &g_o[((team * 2 + rank) * 96 + 3 * (4 * P.slot[wave] + nt)) * 1024 + img0];
          asm volatile("" : "+l"(pend));
        };
        for (;;) {
          nop = prog[++pc];
          {
            uint32_t av;
            const int sv = take(rdy0, SZ_KV, av);
            wg_fence();
            qk(s, ak1, S1A, 12);
            pv(pa, av, 0);
            probe2();
            wg_wait<1>();
            fence_regs(s);
            release(sk1);
            soft(pb);
            wg_wait<0>();
            fence_regs(o);
            release(sv);
          }
          auto step = [&](uint32_t (&pin)[16], uint32_t (&pout)[16]) {
            uint32_t ak, av;
            const int sk = take(rdy0, SZ_KV, ak), sv = take(rdy1, SZ_KV, av);
            wg_fence();
            qk(s, ak, 0, 12);
            pv(pin, av, 1);
            probe2();
            wg_wait<1>();
            fence_regs(s);
            release(sk);
            soft(pout);
            wg_wait<0>();
            fence_regs(o);
            release(sv);
          };
#pragma unroll 1
          for (int jj = 0; jj < 7; jj++) {
            step(pb, pa);
            step(pa, pb);
          }
          if ((nop & 3) != OP_A) break;
          uint32_t ak, av;
          {
            const int b0 = take(rdy0, SZ_PARK, ak), b1 = take(rdy1, SZ_PARK, av);
            const uint32_t ad0 = ak, ad1 = av;
            probe2();
#pragma unroll
            for (int i = 0; i < 12; i++)
              lds128(sbase + ((i < 6 ? ad0 : ad1) - ring16 + img0) * 16 + ((i % 6) >> 1) * 8192 + (i & 1) * 512, q[4 * i], q[4 * i + 1], q[4 * i + 2], q[4 * i + 3]);
            release(b0); release(b1);
          }
          const int sk0 = take(rdy0, SZ_KV, ak), sv = take(rdy1, SZ_KV, av);
          wg_fence();
          qk(s, ak, 0, 8);
          sched_fence(img0, P.zero);
          sums();
          sched_fence(img0, P.zero);
          qk(s, ak, 8, 12);
          pv(pb, av, 1);
          probe2();
          spol = make_policy(!(nop & F_SOON));
          wg_wait<1>();
          fence_regs(s);
          release(sk0);
          first(s);
          sk1 = take(rdy0, SZ_KV, ak1);
          rdy0 = rdy1;
          wg_wait<0>();
          target();
          fence_regs(o);
          release(sv);
          uint32_t t[48];
#pragma unroll
          for (int j = 0; j < 6; j++) {
#pragma unroll
            for (int i = 0; i < 4; i++) {
              t[8 * j + i] = pack_bf16(o[16 * j + 4 * i] * i0, o[16 * j + 4 * i + 1] * i0);
              t[8 * j + i + 4] = pack_bf16(o[16 * j + 4 * i + 2] * i1, o[16 * j + 4 * i + 3] * i1);
            }
            stg2_if(true, pend + j * 512, t[8 * j], t[8 * j + 1], t[8 * j + 2], t[8 * j + 3], t[8 * j + 4], t[8 * j + 5], t[8 * j + 6], t[8 * j + 7], spol);
            if (j == UC0) { wg_fence(); qk(s, ak1, 0, 4); }
            if (j == UC1) { wg_fence(); qk(s, ak1, 4, S1A); }
            sched_fence(img0, P.zero);
          }
          if (P.zero) {
#pragma unroll
            for (int j = 0; j < 5; j++)
              stg2_if(true, pend, t[8 * j], t[8 * j + 1], t[8 * j + 2], t[8 * j + 3], t[8 * j + 4], t[8 * j + 5], t[8 * j + 6], t[8 * j + 7], spol);
          }
          __syncwarp();
          mbar_arrive_if(lane < 2, odone);
          wave = (nop >> 2) & 7;
        }
        const int sv = take(rdy0, SZ_KV, ad);
        wg_fence();
        pv(pb, ad, 1);
        sums();
        target();
        op = nop;
        enter();
        rdy0 = rdy1;
        auto convert = [&](uint32_t (&t)[48], float (&u)[96]) {
#pragma unroll
          for (int i = 0; i < 24; i++) {
            t[8 * (i >> 2) + (i & 3)] = pack_bf16(u[4 * i], u[4 * i + 1]);
            t[8 * (i >> 2) + (i & 3) + 4] = pack_bf16(u[4 * i + 2], u[4 * i + 3]);
          }
        };
        if ((op & 3) != OP_O) {
          if ((op & 3) == OP_Q) bi0 = take(rdy0, SZ_Q, ad);
          wg_wait<0>();
          fence_regs(o);
          release(sv);
          float u[96];
#pragma unroll
          for (int i = 0; i < 96; i++) u[i] = o[i] * (i & 2 ? i1 : i0);
          if ((op & 3) != OP_Q) { convert(q, u); break; }
          fence_regs(u);
          xw(ad, 0);
          sched_fence(img0, P.zero);
          fence_regs(u);
          convert(q, u);
          continue;
        }
        int bi = ow(0, 0);
        wg_wait<2>();
        fence_regs(o);
        release(sv);
#pragma unroll
        for (int j = 0; j < 6; j++) {
          uint32_t t[8];
#pragma unroll
          for (int i = 0; i < 4; i++) {
            t[i] = pack_bf16(o[16 * j + 4 * i] * i0, o[16 * j + 4 * i + 1] * i0);
            t[i + 4] = pack_bf16(o[16 * j + 4 * i + 2] * i1, o[16 * j + 4 * i + 3] * i1);
          }
          stg2_if(true, pend + j * 512, t[0], t[1], t[2], t[3], t[4], t[5], t[6], t[7], spol);
          if (j == 5) {
            __syncwarp();
            mbar_arrive_if(lane < 2, odone);
          }
          probe1();
          wg_wait<1>();
          bi = ow(1, bi);
          fence_regs(o);
        }
        {
          const int nk = 12 * (((op >> 5) & 15) - ((op >> 2) & 7));
#pragma unroll 1
          for (int k = 7; k < nk; k++) {
            probe1();
            wg_wait<1>();
            bi = ow(1, bi);
          }
          probe1();
        }
        nop = prog[++pc];
        if (op & F_LD) {
          uint32_t t[80];
#pragma unroll
          for (int j = 0; j < 5; j++) {
            const int b = take(rdy0, SZ_PART, ad);
            probe1();
#pragma unroll
            for (int i = 4 * j; i < 4 * j + 4; i++)
              lds128(sbase + (ad - ring16 + img0) * 16 + ((i >> 1) & 1) * 8192 + (i & 1) * 512, t[4 * i], t[4 * i + 1], t[4 * i + 2], t[4 * i + 3]);
            release(b);
          }
          wg_wait<0>();
          fence_regs(c);
#pragma unroll
          for (int i = 0; i < 80; i++) c[i] += __uint_as_float(t[i]);
        }
        if (!(op & F_ST)) {
          wg_wait<0>();
          fence_regs(c);
          goto finish;
        }
        op = nop;
        enter();
        bi0 = take(rdy0, SZ_Q, ad);
        xw(ad, 0);
        pend = &g_part[(role * 2 + rank) * 5120 + img0];
        probe1();
        wg_wait<1>();
        fence_regs(c);
        release(bi);
        st_part(6); st_part(7);
        wg_wait<0>();
        release(bi0);
        bi0 = take(rdy0, SZ_Q, ad);
        xw(ad, 1);
        st_part(8); st_part(9);
#pragma unroll
        for (int i = 0; i < 48; i++) q[i] = __float_as_uint(c[i]);
        k = 1; lag = 2;
      }
    }
    rdy0 = false;
    {
      uint32_t t[48];
#pragma unroll
      for (int i = 0; i < 48; i++) t[i] = q[i] ^ P.zero;
      while ((op & 3) == OP_O) {
        const int bi = o_run(t, ow(0, 0));
        wg_wait<0>();
        fence_regs(c);
        pc++;
        if (!(op & F_ST)) goto finish;
        release(bi);
        pend = &g_part[(o_role(op) * 2 + rank) * 5120 + img0];
#pragma unroll
        for (int i = 6; i < 10; i++) st_part(i);
#pragma unroll
        for (int i = 0; i < 48; i++) t[i] = __float_as_uint(c[i]) ^ P.zero;
        op = prog[pc];
        enter();
      }
      for (int i = 0; i < 6; i++) drain(t, i);
    }
    asm volatile("barrier.cluster.arrive.relaxed;" ::: "memory");
    if (false) {
    finish:
      asm volatile("barrier.cluster.arrive.relaxed;" ::: "memory");
      bar_sync(1, 256);
      const uint32_t wstage = sbase + (wg * 4 + warp) * 5120;
      const uint32_t sa = wstage + (lane & 15) * 64;
#pragma unroll
      for (int i = 0; i < 10; i++) {
        const int u = (i & 1) * 2 + (lane >> 4);
        stsm4(sa + (i >> 1) * 1024 + ((u ^ ((lane >> 1) & 3)) << 4), pack_bf16(c[8 * i], c[8 * i + 1]), pack_bf16(c[8 * i + 2], c[8 * i + 3]),
              pack_bf16(c[8 * i + 4], c[8 * i + 5]), pack_bf16(c[8 * i + 6], c[8 * i + 7]));
      }
      asm volatile("fence.proxy.async.shared::cta;" ::: "memory");
      __syncwarp();
      if (lane == 0) {
        tma3d_store(&P.out, wstage, 0, (team & 7) * kSq + rank * 128 + wg * 64 + warp * 16, blk * 20 + nt * 5);
        asm volatile("cp.async.bulk.commit_group;\ncp.async.bulk.wait_group.read 0;" ::: "memory");
      }
      __syncwarp();
    }
    asm volatile("barrier.cluster.wait;" ::: "memory");
  }
}

typedef CUresult (*EncodeFn)(CUtensorMap*, CUtensorMapDataType, cuuint32_t, void*, const cuuint64_t*, const cuuint64_t*,
                             const cuuint32_t*, const cuuint32_t*, CUtensorMapInterleave, CUtensorMapSwizzle,
                             CUtensorMapL2promotion, CUtensorMapFloatOOBfill);

void encode(EncodeFn fn, CUtensorMap* m, const void* ptr, int rank, const cuuint64_t* dims, const cuuint64_t* strides,
            const cuuint32_t* box, CUtensorMapSwizzle swz) {
  const cuuint32_t es[5] = {1, 1, 1, 1, 1};
  CUresult r = fn(m, CU_TENSOR_MAP_DATA_TYPE_BFLOAT16, rank, const_cast<void*>(ptr), dims, strides, box, es,
                  CU_TENSOR_MAP_INTERLEAVE_NONE, swz, CU_TENSOR_MAP_L2_PROMOTION_L2_128B, CU_TENSOR_MAP_FLOAT_OOB_FILL_NONE);
  if (r != CUDA_SUCCESS) fprintf(stderr, "cuTensorMapEncodeTiled failed: %d\n", (int)r);
}

void annotate(uint32_t* ops, int n, bool helper) {
  uint32_t items = 0, cur = 0, pend = 0;
  auto item = [&](uint32_t bytes, int count) {
    for (int i = 0; i < count; i++) { if (cur + bytes > RING) cur = 0; cur += bytes; items++; }
  };
  for (int i = 0; i <= n; i++) {
    const uint32_t op = ops[i];
    ops[i] |= (items % NBAR) << 15 | ((items / NBAR) & 1) << 19 | (cur >> 12) << 20 | pend << 26;
    if ((op & 3) == OP_Q) { item(SZ_Q, 10); pend = (op & F_PARK) ? (helper ? 1 : 2) : 0; }
    if ((op & 3) == OP_A) {
      item(SZ_KV, (op & F_PARK) ? 30 : 31);
      if ((ops[i + 1] & 3) == OP_A) { item(SZ_PARK, 2); item(SZ_KV, 1); }
      item(SZ_KV, 1);
      pend = 1;
    }
    if ((op & 3) == OP_O) {
      item(SZ_O, 12 * (((op >> 5) & 15) - ((op >> 2) & 7)));
      if (op & F_LD) item(SZ_PART, 5);
      pend = (op & F_LAZY) ? (helper ? 1 : 2) : 0;
    }
  }
}

void compile_programs(const char* const* text, bool helpers, Params& P) {
  struct Req { int when, team, wave, slot; } req[N_TEAM * MAX_PARK];
  int n_req = 0;
  for (int t = 0; t < N_TEAM; t++) {
    uint32_t* ops = P.ops[t];
    int n = 0, flags[8] = {0, 0, 0, 0, 0, 0, 0, 0}, n_park = 0, last_o = -1, when = 0, given = 0;
    for (const char* s = text[t]; *s; s++) {
      const int a = s[1] - '0';
      if (*s == 'Q' || (*s == 'H' && !helpers)) { ops[n++] = OP_Q | a << 2; when += 10; }
      else if (*s == 'P') { flags[a] = F_PARK | n_park++ << 10; ops[n++] = OP_Q | a << 2 | flags[a]; when += 10; }
      else if (*s == 'H') { req[n_req++] = {when, t, a, n_park}; flags[a] = F_PARK | F_HELP | n_park++ << 10; }
      else if (*s == 'A') { ops[n++] = OP_A | a << 2 | flags[a]; when += 32; }
      else if (*s == 'G') { given = a; if (helpers) req[n_req++] = {1000, t, 0, -a}; }
      else if (*s == 'O') {
        ops[n] = OP_O | a << 2 | (s[2] - '0') << 5;
        if (given) ops[n] = helpers ? ops[n] | F_LD | F_PARK | (MAX_PARK - 1) << 10 : ops[n] & ~(7u << 2);
        if (last_o >= 0) { ops[last_o] |= F_ST; ops[n] |= F_LD; }
        last_o = n++;
        when += 10 * (s[2] - s[1]);
      }
    }
    for (int i = 0; i + 1 < n; i++)
      if ((ops[i] & 3) == OP_O && (ops[i] & F_ST) && (ops[i + 1] & 3) == OP_Q) ops[i] |= F_LAZY;
    for (int i = n; i < MAX_OPS; i++) ops[i] = OP_END;
    annotate(ops, n, false);
    for (int i = 0; i < n; i++) {
      if ((ops[i] & 3) != OP_A && (P.dbg & 8)) ops[i + 1] |= F_SOON;
      if ((ops[i] & 3) != OP_A) continue;
      const int w = (ops[i] >> 2) & 7;
      int dist = 0;
      for (int j = i + 1; j < n; j++) {
        const int a = (ops[j] >> 2) & 7, b = (ops[j] >> 5) & 15;
        if ((ops[j] & 3) == OP_O && w < b) {
          for (int k = 0; k < b - a && o_wave(a, b, k, (P.dbg >> 4) & 7) != w; k++) dist += 10;
          break;
        }
        dist += (ops[j] & 3) == OP_Q ? 10 : (ops[j] & 3) == OP_A ? 32 : 10 * (b - a);
      }
      if (dist <= (int)((P.dbg >> 8) & 255)) ops[i + 1] |= F_SOON;
    }
  }
  for (int i = 1; i < n_req; i++)
    for (int j = i; j > 0 && req[j].when < req[j - 1].when; j--) { Req r = req[j]; req[j] = req[j - 1]; req[j - 1] = r; }
  for (int h = 0; h < N_HELP; h++) {
    uint32_t* ops = P.ops[N_TEAM + 2 * h];
    int n = 0;
    for (int i = 0; i < n_req; i++)
      for (int m = h; m < 4; m += N_HELP) {
        const uint32_t ro = 4 * req[i].team + m;
        ops[n++] = req[i].slot >= 0 ? OP_Q | req[i].wave << 2 | req[i].team << 5 | F_PARK | req[i].slot << 10 | m << 12
                                    : OP_O | -req[i].slot << 5 | F_ST | F_LAZY | F_SOON | (ro & 7) << 9 | (ro >> 3) << 29;
      }
    for (int i = n; i < 2 * MAX_OPS; i++) ops[i] = OP_END | F_SOON;
    annotate(ops, n, true);
  }
  for (int i = 0; i < 32; i++) P.first[i] = i < N_TEAM ? P.ops[i][0] : i < N_TEAM + N_HELP ? P.ops[2 * i - N_TEAM][0] : 0;
}

const char* const kPrograms[N_TEAM] = {
  "Q0A0Q1A1H2A2O03Q3A3Q4A4Q5A5Q6A6Q7A7O38",
  "Q0A0Q1A1Q2A2H3A3Q4A4O03Q5A5Q6A6Q7A7O38",
  "Q0A0H1A1Q2A2Q3A3O04Q4A4Q5A5Q6A6Q7A7O48",
  "Q0A0Q1A1Q2A2Q3A3O02Q4A4Q5A5Q6A6H7A7O28",
  "Q0A0Q1A1Q2A2O03Q3A3Q4A4Q5A5Q6A6H7A7O38",
  "Q0A0Q1A1Q2A2Q3A3Q4A4O05Q5A5Q6A6H7A7O58",
  "Q0A0Q1A1Q2A2Q3A3Q4A4O05Q5A5Q6A6H7A7O58",
  "Q0A0Q1A1Q2A2O03Q3A3Q4A4H5A5Q6A6Q7A7O38",
  "P7Q0A0Q1A1O01Q2A2H3A3Q4A4Q5A5Q6A6A7O18",
  "P3P5Q0A0Q1A1Q2A2A3Q4A4A5H6A6Q7A7O08",
  "P7Q0A0Q1A1Q2A2Q3A3H4A4Q5A5Q6A6A7O08",
  "P3P7Q0A0Q1A1H2A2A3Q4A4Q5A5Q6A6A7O08",
  "Q0A0Q1A1Q2A2O01Q3A3Q4A4H5A5Q6A6Q7A7O18",
  "P3Q0A0Q1A1Q2A2A3Q4A4Q5A5Q6A6Q7A7G1O18",
  "P6Q0A0Q1A1Q2A2Q3A3Q4A4Q5A5A6Q7A7G1O18",
  "P2P6Q0A0Q1A1A2Q3A3H4A4Q5A5A6Q7A7O08",
};

const char* const* bench_programs() {
  return kPrograms;
}

}

extern "C" void kernel_launch(void* const* d_in, const int* in_sizes, int n_in, void* d_out, int out_size) {
  (void)in_sizes; (void)n_in; (void)out_size;
  static EncodeFn fn = nullptr;
  static int n_clusters = 0;
  if (!fn) {
    cudaDriverEntryPointQueryResult qr;
    void* f = nullptr;
    cudaGetDriverEntryPoint("cuTensorMapEncodeTiled", &f, cudaEnableDefault, &qr);
    fn = (EncodeFn)f;
    cudaFuncSetAttribute(fused_kernel, cudaFuncAttributeMaxDynamicSharedMemorySize, SMEM_BYTES);
    cudaLaunchConfig_t cfg = {};
    cfg.gridDim = dim3(132); cfg.blockDim = dim3(384); cfg.dynamicSmemBytes = SMEM_BYTES;
    cudaLaunchAttribute at[1];
    at[0].id = cudaLaunchAttributeClusterDimension; at[0].val.clusterDim.x = 2; at[0].val.clusterDim.y = 1; at[0].val.clusterDim.z = 1;
    cfg.attrs = at; cfg.numAttrs = 1;
    if (cudaOccupancyMaxActiveClusters(&n_clusters, fused_kernel, &cfg) != cudaSuccess || n_clusters < 1) n_clusters = 1;
    (void)cudaGetLastError();
  }
  Params P;
  const CUtensorMapSwizzle S128 = CU_TENSOR_MAP_SWIZZLE_128B, S64 = CU_TENSOR_MAP_SWIZZLE_64B;
  for (int blk = 0; blk < 2; blk++) {
    void* const* in = d_in + 5 * blk;
    { const cuuint64_t d[] = {kD, kB * kSq}, s[] = {kD * 2}; const cuuint32_t b[] = {64, 128};
      encode(fn, &P.x[blk], in[0], 2, d, s, b, S128); }
    { const cuuint64_t d[] = {64, 8, 3, (cuuint64_t)kB * kH * kSk / 8}, s[] = {kDh * 2, 128, 8 * kDh * 2}; const cuuint32_t b[] = {64, 8, 3, 8};
      encode(fn, &P.k[blk], in[1], 4, d, s, b, S128);
      encode(fn, &P.v[blk], in[2], 4, d, s, b, S128); }
    { const cuuint64_t d[] = {64, kD, kHD / 64}, s[] = {kHD * 2, 128}; const cuuint32_t b[] = {64, 64, 3};
      encode(fn, &P.wq[blk], in[3], 3, d, s, b, S128); }
    { const cuuint64_t d[] = {32, 2, kHD / 8, 4, kD / 32}, s[] = {kD * 2, 8 * kD * 2, 2 * kD * 2, 64}; const cuuint32_t b[] = {32, 2, 4, 4, 5};
      encode(fn, &P.wo[blk], in[4], 5, d, s, b, S64); }
  }
  { const cuuint64_t d[] = {32, kB * kSq, 2 * kD / 32}, s[] = {2 * kD * 2, 64}; const cuuint32_t b[] = {32, 16, 5};
    encode(fn, &P.out, d_out, 3, d, s, b, S64); }

  P.zero = 0;
  P.dbg = 0x5030;
  for (int w = 0; w < 8; w++) P.slot[w] = (P.dbg >> 16) & 15 ? w % ((P.dbg >> 16) & 15) : w;
  if (n_clusters >= N_CL) {
    const bool helpers = n_clusters >= N_CL + N_HELP;
    compile_programs(bench_programs(), helpers, P);
    fused_kernel<<<2 * (N_CL + (helpers ? N_HELP : 0)), 384, SMEM_BYTES>>>(P);
  } else {
    for (int phase = 0; phase < 2; phase++) {
      const char* text[N_TEAM];
      for (int t = 0; t < N_TEAM; t++) text[t] = phase ? "O08" : "Q0A0Q1A1Q2A2Q3A3Q4A4Q5A5Q6A6Q7A7";
      compile_programs(text, false, P);
      fused_kernel<<<2 * N_CL, 384, SMEM_BYTES>>>(P);
    }
  }
}
```

```cpp
#include <cuda_runtime.h>
#include <cuda_bf16.h>
#include <cuda.h>
#include <stdint.h>
#include <stdio.h>

namespace {

constexpr int kB = 8, kSq = 256, kD = 640, kH = 32, kSk = 1024, kDh = 192;
constexpr int kHD = kH * kDh;
#define S1A 7
#define UC0 3
#define UC1 4
#define RING_KB 224
constexpr uint32_t RING = RING_KB * 1024;
constexpr uint32_t SZ_KV = 24576;
constexpr uint32_t SZ_WQ = 24576, SZ_WO = 20480, SZ_A = 16384;
constexpr uint32_t SZ_PARK = 24576;
constexpr uint32_t SZ_PART = 16384;
constexpr int NBAR = 10;
#define KVT 4
constexpr int KV_TRANSIT = KVT;
#define EARLY_N 3
constexpr int EARLY = EARLY_N;
constexpr uint32_t KV_CH = 64, KV_SBO = 3072;
constexpr int SMEM_BYTES = RING + 512 + 1024;
constexpr int N_TEAM = 16, N_CL = 64, N_HELP = 2, MAX_OPS = 24, MAX_PARK = 4;
enum { OP_END = 0, OP_Q = 1, OP_A = 2, OP_O = 3, F_PARK = 1 << 9, F_LD = 1 << 12, F_ST = 1 << 13, F_LAZY = 1 << 14, F_HELP = 1 << 12, F_SOON = 1 << 28 };

struct alignas(64) Params {
  uint32_t first[32];
  CUtensorMap x[2], wq[2], k[2], v[2], wo[2], out;
  uint32_t ops[N_TEAM + 2 * N_HELP][MAX_OPS];
  uint32_t zero;
  uint32_t slot[8];
  uint32_t dbg;
};

__device__ uint4 g_o[N_TEAM * 2 * 96 * 1024];
__device__ uint4 g_part[N_CL * 2 * 5 * 1024];
__device__ unsigned int g_done[N_TEAM * 2 * 8];
__device__ unsigned int g_help[N_CL * 2 * MAX_PARK];
__device__ unsigned int g_seen[N_TEAM * 2 * 8];

template <int TB, int TA = 0>
__device__ __forceinline__ void wgmma_ss_n64(float (&d)[32], uint64_t da, uint64_t db, int scale_d) {
  asm volatile("{\n.reg .pred p;\nsetp.ne.b32 p, %34, 0;\n"
    "wgmma.mma_async.sync.aligned.m64n64k16.f32.bf16.bf16 {%0, %1, %2, %3, %4, %5, %6, %7, %8, %9, %10, %11, %12, %13, %14, %15, %16, %17, %18, %19, %20, %21, %22, %23, %24, %25, %26, %27, %28, %29, %30, %31}, %32, %33, p, 1, 1, %35, %36;\n}\n"
    : "+f"(d[0]), "+f"(d[1]), "+f"(d[2]), "+f"(d[3]), "+f"(d[4]), "+f"(d[5]), "+f"(d[6]), "+f"(d[7]), "+f"(d[8]), "+f"(d[9]), "+f"(d[10]), "+f"(d[11]), "+f"(d[12]), "+f"(d[13]), "+f"(d[14]), "+f"(d[15]), "+f"(d[16]), "+f"(d[17]), "+f"(d[18]), "+f"(d[19]), "+f"(d[20]), "+f"(d[21]), "+f"(d[22]), "+f"(d[23]), "+f"(d[24]), "+f"(d[25]), "+f"(d[26]), "+f"(d[27]), "+f"(d[28]), "+f"(d[29]), "+f"(d[30]), "+f"(d[31])
    : "l"(da), "l"(db), "r"(scale_d), "n"(TA), "n"(TB));
}
template <int TB>
__device__ __forceinline__ void wgmma_rs_n64(float (&d)[32], uint32_t a0, uint32_t a1, uint32_t a2, uint32_t a3, uint64_t db, int scale_d) {
  asm volatile("{\n.reg .pred p;\nsetp.ne.b32 p, %37, 0;\n"
    "wgmma.mma_async.sync.aligned.m64n64k16.f32.bf16.bf16 {%0, %1, %2, %3, %4, %5, %6, %7, %8, %9, %10, %11, %12, %13, %14, %15, %16, %17, %18, %19, %20, %21, %22, %23, %24, %25, %26, %27, %28, %29, %30, %31}, {%32, %33, %34, %35}, %36, p, 1, 1, %38;\n}\n"
    : "+f"(d[0]), "+f"(d[1]), "+f"(d[2]), "+f"(d[3]), "+f"(d[4]), "+f"(d[5]), "+f"(d[6]), "+f"(d[7]), "+f"(d[8]), "+f"(d[9]), "+f"(d[10]), "+f"(d[11]), "+f"(d[12]), "+f"(d[13]), "+f"(d[14]), "+f"(d[15]), "+f"(d[16]), "+f"(d[17]), "+f"(d[18]), "+f"(d[19]), "+f"(d[20]), "+f"(d[21]), "+f"(d[22]), "+f"(d[23]), "+f"(d[24]), "+f"(d[25]), "+f"(d[26]), "+f"(d[27]), "+f"(d[28]), "+f"(d[29]), "+f"(d[30]), "+f"(d[31])
    : "r"(a0), "r"(a1), "r"(a2), "r"(a3), "l"(db), "r"(scale_d), "n"(TB));
}
template <int TB, int TA = 0>
__device__ __forceinline__ void wgmma_ss_n160(float (&d)[80], uint64_t da, uint64_t db, int scale_d) {
  asm volatile("{\n.reg .pred p;\nsetp.ne.b32 p, %82, 0;\n"
    "wgmma.mma_async.sync.aligned.m64n160k16.f32.bf16.bf16 {%0, %1, %2, %3, %4, %5, %6, %7, %8, %9, %10, %11, %12, %13, %14, %15, %16, %17, %18, %19, %20, %21, %22, %23, %24, %25, %26, %27, %28, %29, %30, %31, %32, %33, %34, %35, %36, %37, %38, %39, %40, %41, %42, %43, %44, %45, %46, %47, %48, %49, %50, %51, %52, %53, %54, %55, %56, %57, %58, %59, %60, %61, %62, %63, %64, %65, %66, %67, %68, %69, %70, %71, %72, %73, %74, %75, %76, %77, %78, %79}, %80, %81, p, 1, 1, %83, %84;\n}\n"
    : "+f"(d[0]), "+f"(d[1]), "+f"(d[2]), "+f"(d[3]), "+f"(d[4]), "+f"(d[5]), "+f"(d[6]), "+f"(d[7]), "+f"(d[8]), "+f"(d[9]), "+f"(d[10]), "+f"(d[11]), "+f"(d[12]), "+f"(d[13]), "+f"(d[14]), "+f"(d[15]), "+f"(d[16]), "+f"(d[17]), "+f"(d[18]), "+f"(d[19]), "+f"(d[20]), "+f"(d[21]), "+f"(d[22]), "+f"(d[23]), "+f"(d[24]), "+f"(d[25]), "+f"(d[26]), "+f"(d[27]), "+f"(d[28]), "+f"(d[29]), "+f"(d[30]), "+f"(d[31]), "+f"(d[32]), "+f"(d[33]), "+f"(d[34]), "+f"(d[35]), "+f"(d[36]), "+f"(d[37]), "+f"(d[38]), "+f"(d[39]), "+f"(d[40]), "+f"(d[41]), "+f"(d[42]), "+f"(d[43]), "+f"(d[44]), "+f"(d[45]), "+f"(d[46]), "+f"(d[47]), "+f"(d[48]), "+f"(d[49]), "+f"(d[50]), "+f"(d[51]), "+f"(d[52]), "+f"(d[53]), "+f"(d[54]), "+f"(d[55]), "+f"(d[56]), "+f"(d[57]), "+f"(d[58]), "+f"(d[59]), "+f"(d[60]), "+f"(d[61]), "+f"(d[62]), "+f"(d[63]), "+f"(d[64]), "+f"(d[65]), "+f"(d[66]), "+f"(d[67]), "+f"(d[68]), "+f"(d[69]), "+f"(d[70]), "+f"(d[71]), "+f"(d[72]), "+f"(d[73]), "+f"(d[74]), "+f"(d[75]), "+f"(d[76]), "+f"(d[77]), "+f"(d[78]), "+f"(d[79])
    : "l"(da), "l"(db), "r"(scale_d), "n"(TA), "n"(TB));
}
template <int TB>
__device__ __forceinline__ void wgmma_rs_n160(float (&d)[80], uint32_t a0, uint32_t a1, uint32_t a2, uint32_t a3, uint64_t db, int scale_d) {
  asm volatile("{\n.reg .pred p;\nsetp.ne.b32 p, %85, 0;\n"
    "wgmma.mma_async.sync.aligned.m64n160k16.f32.bf16.bf16 {%0, %1, %2, %3, %4, %5, %6, %7, %8, %9, %10, %11, %12, %13, %14, %15, %16, %17, %18, %19, %20, %21, %22, %23, %24, %25, %26, %27, %28, %29, %30, %31, %32, %33, %34, %35, %36, %37, %38, %39, %40, %41, %42, %43, %44, %45, %46, %47, %48, %49, %50, %51, %52, %53, %54, %55, %56, %57, %58, %59, %60, %61, %62, %63, %64, %65, %66, %67, %68, %69, %70, %71, %72, %73, %74, %75, %76, %77, %78, %79}, {%80, %81, %82, %83}, %84, p, 1, 1, %86;\n}\n"
    : "+f"(d[0]), "+f"(d[1]), "+f"(d[2]), "+f"(d[3]), "+f"(d[4]), "+f"(d[5]), "+f"(d[6]), "+f"(d[7]), "+f"(d[8]), "+f"(d[9]), "+f"(d[10]), "+f"(d[11]), "+f"(d[12]), "+f"(d[13]), "+f"(d[14]), "+f"(d[15]), "+f"(d[16]), "+f"(d[17]), "+f"(d[18]), "+f"(d[19]), "+f"(d[20]), "+f"(d[21]), "+f"(d[22]), "+f"(d[23]), "+f"(d[24]), "+f"(d[25]), "+f"(d[26]), "+f"(d[27]), "+f"(d[28]), "+f"(d[29]), "+f"(d[30]), "+f"(d[31]), "+f"(d[32]), "+f"(d[33]), "+f"(d[34]), "+f"(d[35]), "+f"(d[36]), "+f"(d[37]), "+f"(d[38]), "+f"(d[39]), "+f"(d[40]), "+f"(d[41]), "+f"(d[42]), "+f"(d[43]), "+f"(d[44]), "+f"(d[45]), "+f"(d[46]), "+f"(d[47]), "+f"(d[48]), "+f"(d[49]), "+f"(d[50]), "+f"(d[51]), "+f"(d[52]), "+f"(d[53]), "+f"(d[54]), "+f"(d[55]), "+f"(d[56]), "+f"(d[57]), "+f"(d[58]), "+f"(d[59]), "+f"(d[60]), "+f"(d[61]), "+f"(d[62]), "+f"(d[63]), "+f"(d[64]), "+f"(d[65]), "+f"(d[66]), "+f"(d[67]), "+f"(d[68]), "+f"(d[69]), "+f"(d[70]), "+f"(d[71]), "+f"(d[72]), "+f"(d[73]), "+f"(d[74]), "+f"(d[75]), "+f"(d[76]), "+f"(d[77]), "+f"(d[78]), "+f"(d[79])
    : "r"(a0), "r"(a1), "r"(a2), "r"(a3), "l"(db), "r"(scale_d), "n"(TB));
}
template <int TB, int TA = 0>
__device__ __forceinline__ void wgmma_ss_n192(float (&d)[96], uint64_t da, uint64_t db, int scale_d) {
  asm volatile("{\n.reg .pred p;\nsetp.ne.b32 p, %98, 0;\n"
    "wgmma.mma_async.sync.aligned.m64n192k16.f32.bf16.bf16 {%0, %1, %2, %3, %4, %5, %6, %7, %8, %9, %10, %11, %12, %13, %14, %15, %16, %17, %18, %19, %20, %21, %22, %23, %24, %25, %26, %27, %28, %29, %30, %31, %32, %33, %34, %35, %36, %37, %38, %39, %40, %41, %42, %43, %44, %45, %46, %47, %48, %49, %50, %51, %52, %53, %54, %55, %56, %57, %58, %59, %60, %61, %62, %63, %64, %65, %66, %67, %68, %69, %70, %71, %72, %73, %74, %75, %76, %77, %78, %79, %80, %81, %82, %83, %84, %85, %86, %87, %88, %89, %90, %91, %92, %93, %94, %95}, %96, %97, p, 1, 1, %99, %100;\n}\n"
    : "+f"(d[0]), "+f"(d[1]), "+f"(d[2]), "+f"(d[3]), "+f"(d[4]), "+f"(d[5]), "+f"(d[6]), "+f"(d[7]), "+f"(d[8]), "+f"(d[9]), "+f"(d[10]), "+f"(d[11]), "+f"(d[12]), "+f"(d[13]), "+f"(d[14]), "+f"(d[15]), "+f"(d[16]), "+f"(d[17]), "+f"(d[18]), "+f"(d[19]), "+f"(d[20]), "+f"(d[21]), "+f"(d[22]), "+f"(d[23]), "+f"(d[24]), "+f"(d[25]), "+f"(d[26]), "+f"(d[27]), "+f"(d[28]), "+f"(d[29]), "+f"(d[30]), "+f"(d[31]), "+f"(d[32]), "+f"(d[33]), "+f"(d[34]), "+f"(d[35]), "+f"(d[36]), "+f"(d[37]), "+f"(d[38]), "+f"(d[39]), "+f"(d[40]), "+f"(d[41]), "+f"(d[42]), "+f"(d[43]), "+f"(d[44]), "+f"(d[45]), "+f"(d[46]), "+f"(d[47]), "+f"(d[48]), "+f"(d[49]), "+f"(d[50]), "+f"(d[51]), "+f"(d[52]), "+f"(d[53]), "+f"(d[54]), "+f"(d[55]), "+f"(d[56]), "+f"(d[57]), "+f"(d[58]), "+f"(d[59]), "+f"(d[60]), "+f"(d[61]), "+f"(d[62]), "+f"(d[63]), "+f"(d[64]), "+f"(d[65]), "+f"(d[66]), "+f"(d[67]), "+f"(d[68]), "+f"(d[69]), "+f"(d[70]), "+f"(d[71]), "+f"(d[72]), "+f"(d[73]), "+f"(d[74]), "+f"(d[75]), "+f"(d[76]), "+f"(d[77]), "+f"(d[78]), "+f"(d[79]), "+f"(d[80]), "+f"(d[81]), "+f"(d[82]), "+f"(d[83]), "+f"(d[84]), "+f"(d[85]), "+f"(d[86]), "+f"(d[87]), "+f"(d[88]), "+f"(d[89]), "+f"(d[90]), "+f"(d[91]), "+f"(d[92]), "+f"(d[93]), "+f"(d[94]), "+f"(d[95])
    : "l"(da), "l"(db), "r"(scale_d), "n"(TA), "n"(TB));
}
template <int TB>
__device__ __forceinline__ void wgmma_rs_n192(float (&d)[96], uint32_t a0, uint32_t a1, uint32_t a2, uint32_t a3, uint64_t db, int scale_d) {
  asm volatile("{\n.reg .pred p;\nsetp.ne.b32 p, %101, 0;\n"
    "wgmma.mma_async.sync.aligned.m64n192k16.f32.bf16.bf16 {%0, %1, %2, %3, %4, %5, %6, %7, %8, %9, %10, %11, %12, %13, %14, %15, %16, %17, %18, %19, %20, %21, %22, %23, %24, %25, %26, %27, %28, %29, %30, %31, %32, %33, %34, %35, %36, %37, %38, %39, %40, %41, %42, %43, %44, %45, %46, %47, %48, %49, %50, %51, %52, %53, %54, %55, %56, %57, %58, %59, %60, %61, %62, %63, %64, %65, %66, %67, %68, %69, %70, %71, %72, %73, %74, %75, %76, %77, %78, %79, %80, %81, %82, %83, %84, %85, %86, %87, %88, %89, %90, %91, %92, %93, %94, %95}, {%96, %97, %98, %99}, %100, p, 1, 1, %102;\n}\n"
    : "+f"(d[0]), "+f"(d[1]), "+f"(d[2]), "+f"(d[3]), "+f"(d[4]), "+f"(d[5]), "+f"(d[6]), "+f"(d[7]), "+f"(d[8]), "+f"(d[9]), "+f"(d[10]), "+f"(d[11]), "+f"(d[12]), "+f"(d[13]), "+f"(d[14]), "+f"(d[15]), "+f"(d[16]), "+f"(d[17]), "+f"(d[18]), "+f"(d[19]), "+f"(d[20]), "+f"(d[21]), "+f"(d[22]), "+f"(d[23]), "+f"(d[24]), "+f"(d[25]), "+f"(d[26]), "+f"(d[27]), "+f"(d[28]), "+f"(d[29]), "+f"(d[30]), "+f"(d[31]), "+f"(d[32]), "+f"(d[33]), "+f"(d[34]), "+f"(d[35]), "+f"(d[36]), "+f"(d[37]), "+f"(d[38]), "+f"(d[39]), "+f"(d[40]), "+f"(d[41]), "+f"(d[42]), "+f"(d[43]), "+f"(d[44]), "+f"(d[45]), "+f"(d[46]), "+f"(d[47]), "+f"(d[48]), "+f"(d[49]), "+f"(d[50]), "+f"(d[51]), "+f"(d[52]), "+f"(d[53]), "+f"(d[54]), "+f"(d[55]), "+f"(d[56]), "+f"(d[57]), "+f"(d[58]), "+f"(d[59]), "+f"(d[60]), "+f"(d[61]), "+f"(d[62]), "+f"(d[63]), "+f"(d[64]), "+f"(d[65]), "+f"(d[66]), "+f"(d[67]), "+f"(d[68]), "+f"(d[69]), "+f"(d[70]), "+f"(d[71]), "+f"(d[72]), "+f"(d[73]), "+f"(d[74]), "+f"(d[75]), "+f"(d[76]), "+f"(d[77]), "+f"(d[78]), "+f"(d[79]), "+f"(d[80]), "+f"(d[81]), "+f"(d[82]), "+f"(d[83]), "+f"(d[84]), "+f"(d[85]), "+f"(d[86]), "+f"(d[87]), "+f"(d[88]), "+f"(d[89]), "+f"(d[90]), "+f"(d[91]), "+f"(d[92]), "+f"(d[93]), "+f"(d[94]), "+f"(d[95])
    : "r"(a0), "r"(a1), "r"(a2), "r"(a3), "l"(db), "r"(scale_d), "n"(TB));
}

__device__ __forceinline__ uint32_t smem_u32(const void* p) { return (uint32_t)__cvta_generic_to_shared(p); }
__device__ __forceinline__ void wg_fence() { asm volatile("wgmma.fence.sync.aligned;" ::: "memory"); }
__device__ __forceinline__ void wg_commit() { asm volatile("wgmma.commit_group.sync.aligned;" ::: "memory"); }
template <int N> __device__ __forceinline__ void wg_wait() { asm volatile("wgmma.wait_group.sync.aligned %0;" ::"n"(N) : "memory"); }
__device__ __forceinline__ void sched_fence(int& keep, uint32_t zero) {
  asm volatile("{\n.reg .u32 c;\nmov.u32 c, %%clock;\nand.b32 c, c, %1;\nxor.b32 %0, %0, c;\n}\n" : "+r"(keep) : "r"(zero) : "memory");
}
template <int N> __device__ __forceinline__ void fence_regs(float (&r)[N]) {
#pragma unroll
  for (int i = 0; i < N; i++) asm volatile("" : "+f"(r[i])::"memory");
}
template <int N> __device__ __forceinline__ void fence_regs(uint32_t (&r)[N]) {
#pragma unroll
  for (int i = 0; i < N; i++) asm volatile("" : "+r"(r[i])::"memory");
}
__device__ __forceinline__ uint64_t mk_desc(uint32_t a16, uint32_t lbo, uint32_t sbo, uint32_t swz) {
  uint64_t d;
  asm("mov.b64 %0, {%1, %2};" : "=l"(d) : "r"(a16 + ((lbo >> 4) << 16)), "r"((sbo >> 4) | (swz << 30)));
  return d;
}
__device__ __forceinline__ void mbar_init(uint32_t bar, uint32_t cnt) {
  asm volatile("mbarrier.init.shared::cta.b64 [%0], %1;" ::"r"(bar), "r"(cnt) : "memory");
}
__device__ __forceinline__ void mbar_expect(uint32_t bar, uint32_t tx) {
  asm volatile("mbarrier.arrive.expect_tx.shared::cta.b64 _, [%0], %1;" ::"r"(bar), "r"(tx) : "memory");
}
__device__ __forceinline__ bool mbar_test(uint32_t bar, uint32_t ph) {
  uint32_t ok;
  asm volatile("{\n.reg .pred p;\nmbarrier.test_wait.parity.shared::cta.b64 p, [%1], %2;\nselp.u32 %0, 1, 0, p;\n}\n"
               : "=r"(ok) : "r"(bar), "r"(ph) : "memory");
  return ok;
}
__device__ __forceinline__ void mbar_wait(uint32_t bar, uint32_t ph) {
  asm volatile("{\n.reg .pred p;\n.reg .u32 n;\n"
               "mbarrier.try_wait.parity.shared::cta.b64 p, [%0], %1;\n@p bra DONE;\n"
               "mov.u32 n, 0;\n"
               "LOOP:\nmbarrier.try_wait.parity.shared::cta.b64 p, [%0], %1;\n@p bra DONE;\n"
               "add.u32 n, n, 1;\nsetp.lt.u32 p, n, 0x1000000;\n@p bra LOOP;\ntrap;\n"
               "DONE:\n}\n" ::"r"(bar), "r"(ph) : "memory");
}
template <int NS> __device__ __forceinline__ void mbar_wait_slow(uint32_t bar, uint32_t ph) {
  asm volatile("{\n.reg .pred p;\n.reg .u32 n;\nmov.u32 n, 0;\n"
               "LOOP:\nmbarrier.test_wait.parity.shared::cta.b64 p, [%0], %1;\n@p bra DONE;\n"
               "nanosleep.u32 %2;\nadd.u32 n, n, 1;\nsetp.lt.u32 p, n, 0x400000;\n@p bra LOOP;\ntrap;\n"
               "DONE:\n}\n" ::"r"(bar), "r"(ph), "n"(NS) : "memory");
}
__device__ __forceinline__ void mbar_arrive_cluster_if(bool on, uint32_t addr) {
  asm volatile("{\n.reg .pred p;\nsetp.ne.b32 p, %1, 0;\n@p mbarrier.arrive.shared::cluster.b64 _, [%0];\n}\n" ::"r"(addr), "r"((int)on) : "memory");
}
__device__ __forceinline__ void mbar_arrive_if(bool on, uint32_t addr) {
  asm volatile("{\n.reg .pred p;\nsetp.ne.b32 p, %1, 0;\n@p mbarrier.arrive.shared::cta.b64 _, [%0];\n}\n" ::"r"(addr), "r"((int)on) : "memory");
}
__device__ __forceinline__ void tma2d(uint32_t dst, const CUtensorMap* m, uint32_t bar, int c0, int c1) {
  asm volatile("cp.async.bulk.tensor.2d.shared::cluster.global.mbarrier::complete_tx::bytes [%0], [%1, {%3, %4}], [%2];"
               ::"r"(dst), "l"(m), "r"(bar), "r"(c0), "r"(c1) : "memory");
}
__device__ __forceinline__ void tma3d(uint32_t dst, const CUtensorMap* m, uint32_t bar, int c0, int c1, int c2) {
  asm volatile("cp.async.bulk.tensor.3d.shared::cluster.global.mbarrier::complete_tx::bytes [%0], [%1, {%3, %4, %5}], [%2];"
               ::"r"(dst), "l"(m), "r"(bar), "r"(c0), "r"(c1), "r"(c2) : "memory");
}
__device__ __forceinline__ void tma3d_mc(uint32_t dst, const CUtensorMap* m, uint32_t bar, int c0, int c1, int c2) {
  asm volatile("cp.async.bulk.tensor.3d.shared::cluster.global.mbarrier::complete_tx::bytes.multicast::cluster"
               " [%0], [%1, {%3, %4, %5}], [%2], %6;"
               ::"r"(dst), "l"(m), "r"(bar), "r"(c0), "r"(c1), "r"(c2), "h"((uint16_t)3) : "memory");
}
__device__ __forceinline__ void tma3d_store(const CUtensorMap* m, uint32_t src, int c0, int c1, int c2) {
  asm volatile("cp.async.bulk.tensor.3d.global.shared::cta.bulk_group [%0, {%2, %3, %4}], [%1];"
               ::"l"(m), "r"(src), "r"(c0), "r"(c1), "r"(c2) : "memory");
}
__device__ __forceinline__ void bar_sync(int id, int n) { asm volatile("bar.sync %0, %1;" ::"r"(id), "r"(n) : "memory"); }
__device__ __forceinline__ uint32_t pack_bf16(float lo, float hi) {
  uint32_t r;
  asm("cvt.rn.bf16x2.f32 %0, %1, %2;" : "=r"(r) : "f"(hi), "f"(lo));
  return r;
}
__device__ __forceinline__ float ex2(float x) {
  float y;
  asm("ex2.approx.ftz.f32 %0, %1;" : "=f"(y) : "f"(x));
  return y;
}
__device__ __forceinline__ float fadd(float a, float b) {
  float y;
  asm("add.f32 %0, %1, %2;" : "=f"(y) : "f"(a), "f"(b));
  return y;
}
__device__ __forceinline__ float rcp(float x) {
  float y;
  asm("rcp.approx.ftz.f32 %0, %1;" : "=f"(y) : "f"(x));
  return y;
}
__device__ __forceinline__ void stsm4(uint32_t addr, uint32_t a, uint32_t b, uint32_t c, uint32_t d) {
  asm volatile("stmatrix.sync.aligned.m8n8.x4.shared.b16 [%0], {%1, %2, %3, %4};" ::"r"(addr), "r"(a), "r"(b), "r"(c), "r"(d) : "memory");
}

__device__ __forceinline__ void tma4d_mc_hint(uint32_t dst, const CUtensorMap* m, uint32_t bar, int c3, uint64_t pol) {
  asm volatile("cp.async.bulk.tensor.4d.shared::cluster.global.mbarrier::complete_tx::bytes.multicast::cluster.L2::cache_hint"
               " [%0], [%1, {%3, %3, %3, %4}], [%2], %5, %6;"
               ::"r"(dst), "l"(m), "r"(bar), "r"(0), "r"(c3), "h"((uint16_t)3), "l"(pol) : "memory");
}
__device__ __forceinline__ void tma5d_mc(uint32_t dst, const CUtensorMap* m, uint32_t bar, int c2, int c4) {
  asm volatile("cp.async.bulk.tensor.5d.shared::cluster.global.mbarrier::complete_tx::bytes.multicast::cluster"
               " [%0], [%1, {%3, %3, %4, %3, %5}], [%2], %6;"
               ::"r"(dst), "l"(m), "r"(bar), "r"(0), "r"(c2), "r"(c4), "h"((uint16_t)3) : "memory");
}
__device__ __forceinline__ void bulk_load_hint(uint32_t dst, const void* src, uint32_t bytes, uint32_t bar, uint64_t pol) {
  asm volatile("cp.async.bulk.shared::cluster.global.mbarrier::complete_tx::bytes.L2::cache_hint [%0], [%1], %2, [%3], %4;"
               ::"r"(dst), "l"(src), "r"(bytes), "r"(bar), "l"(pol) : "memory");
}
__device__ __forceinline__ void stg128_hint(void* p, uint32_t a, uint32_t b, uint32_t c, uint32_t d, uint64_t pol) {
  asm volatile("st.global.L2::cache_hint.v4.b32 [%0], {%1, %2, %3, %4}, %5;" ::"l"(p), "r"(a), "r"(b), "r"(c), "r"(d), "l"(pol) : "memory");
}
__device__ __forceinline__ void stg2_if(bool on, void* p, uint32_t a, uint32_t b, uint32_t c, uint32_t d, uint32_t e, uint32_t f,
                                        uint32_t g, uint32_t h, uint64_t pol) {
  asm volatile("{\n.reg .pred p;\nsetp.ne.b32 p, %10, 0;\n"
               "@p st.global.L2::cache_hint.v4.b32 [%0], {%1, %2, %3, %4}, %9;\n"
               "@p st.global.L2::cache_hint.v4.b32 [%0 + 512], {%5, %6, %7, %8}, %9;\n}\n"
               ::"l"(p), "r"(a), "r"(b), "r"(c), "r"(d), "r"(e), "r"(f), "r"(g), "r"(h), "l"(pol), "r"((int)on) : "memory");
}
__device__ __forceinline__ uint64_t make_policy(bool first) {
  uint64_t pf, pn;
  asm("createpolicy.fractional.L2::evict_first.b64 %0, 1.0;" : "=l"(pf));
  asm("createpolicy.fractional.L2::evict_normal.b64 %0, 1.0;" : "=l"(pn));
  return first ? pf : pn;
}
__device__ __forceinline__ bool elect() {
  uint32_t ok;
  asm volatile("{\n.reg .pred p;\nelect.sync _|p, 0xffffffff;\nselp.u32 %0, 1, 0, p;\n}\n" : "=r"(ok));
  return ok;
}
__device__ __forceinline__ void mbar_arrive(uint32_t bar) {
  asm volatile("mbarrier.arrive.shared::cta.b64 _, [%0];" ::"r"(bar) : "memory");
}
__device__ __forceinline__ void stg128(void* p, uint32_t a, uint32_t b, uint32_t c, uint32_t d) {
  asm volatile("st.global.v4.b32 [%0], {%1, %2, %3, %4};" ::"l"(p), "r"(a), "r"(b), "r"(c), "r"(d) : "memory");
}
__device__ __forceinline__ void lds128(uint32_t p, uint32_t& a, uint32_t& b, uint32_t& c, uint32_t& d) {
  asm volatile("ld.shared.v4.b32 {%0, %1, %2, %3}, [%4];" : "=r"(a), "=r"(b), "=r"(c), "=r"(d) : "r"(p) : "memory");
}
__device__ __forceinline__ void wait_count(const unsigned int* p, uint32_t target) {
  asm volatile("{\n.reg .pred p;\n.reg .u32 n, v;\nmov.u32 n, 0;\n"
               "LOOP:\nld.acquire.gpu.global.u32 v, [%0];\nsetp.ge.u32 p, v, %1;\n@p bra DONE;\n"
               "nanosleep.u32 %2;\nadd.u32 n, n, 1;\nsetp.lt.u32 p, n, 0x400000;\n@p bra LOOP;\ntrap;\n"
               "DONE:\n}\n" ::"l"(p), "r"(target), "n"(200) : "memory");
}

__host__ __device__ __forceinline__ int o_wave(int a, int b, int i, int lag) {
  if (lag == 0) return a + i;
  const int p = lag < b - a - 1 ? lag : b - a - 1;
  return i < p ? b - 2 - i : i == p ? b - 1 : b - 1 - i;
}

struct Cursor {
  int bi;
  uint32_t ph;
  __device__ __forceinline__ void next() {
    if (++bi == NBAR) { bi = 0; ph ^= 1; }
  }
};

constexpr float kScaleLog2 = 0.07216878364870322f * 1.4426950408889634f;
constexpr float kSumLimit = 1048576.0f;
constexpr float kMaxLag = 8.0f;

__global__ void __cluster_dims__(2, 1, 1) __launch_bounds__(384, 1)
fused_kernel(const __grid_constant__ Params P) {
  extern __shared__ uint8_t smem_raw[];
  const uint32_t sbase = (smem_u32(smem_raw) + 1023) & ~1023u;
  const uint32_t full0 = sbase + RING, empty0 = full0 + 8 * NBAR, odone = empty0 + 8 * NBAR, oready0 = odone + 8;
  const uint32_t fenced = oready0 + 64, hready0 = fenced + 8;
  const uint32_t rank = blockIdx.x & 1;
  const int role = blockIdx.x >> 1;
  const bool helper = role >= N_CL;
  const int team = helper ? 0 : role >> 2, nt = role & 3, blk = team >> 3;
  const uint32_t* prog = P.ops[helper ? N_TEAM + 2 * (role - N_CL) : team];
  auto q_role = [&](uint32_t op) { return helper ? (int)(((op >> 3) & 60) | ((op >> 12) & 3)) : role; };
  auto o_role = [&](uint32_t op) { return helper ? (int)(((op >> 26) & 56) | ((op >> 9) & 7)) : role; };
  const int wid = __shfl_sync(0xffffffffu, (int)(threadIdx.x >> 5), 0);
  const int wg = wid >> 2;

  const uint32_t op0 = P.first[helper ? N_TEAM + role - N_CL : team];
  if (__builtin_expect(wid == 8, 1)) {
    if (elect()) {
#pragma unroll
      for (int k = 0; k < EARLY; k++) mbar_init(full0 + 8 * k, 1);
      asm volatile("fence.mbarrier_init.release.cluster;" ::: "memory");
      if ((op0 & 3) == OP_Q) {
        const int qr = q_role(op0);
#pragma unroll
        for (int k = 0; k < EARLY; k++) {
          mbar_expect(full0 + 8 * k, SZ_WQ + SZ_A);
          tma2d(sbase + k * (SZ_WQ + SZ_A) + SZ_WQ, &P.x[qr >> 5], full0 + 8 * k, 64 * k, ((qr >> 2) & 7) * kSq + rank * 128);
          tma3d(sbase + k * (SZ_WQ + SZ_A), &P.wq[qr >> 5], full0 + 8 * k, 0, 64 * k, 3 * (4 * ((op0 >> 2) & 7) + (qr & 3)));
        }
      }
      asm volatile("prefetch.tensormap [%0];" ::"l"(rank ? &P.v[blk] : &P.k[blk]) : "memory");
    }
  } else if (threadIdx.x == 0) {
#pragma unroll
    for (int i = EARLY; i < 2 * NBAR + 10 + MAX_PARK; i++) mbar_init(full0 + 8 * i, i < NBAR ? 1 : i <= 2 * NBAR ? 16 : 1);
    asm volatile("fence.mbarrier_init.release.cluster;" ::: "memory");
  }
  __syncwarp();
  asm volatile("barrier.cluster.arrive.relaxed.aligned;\nbarrier.cluster.wait.aligned;" ::: "memory");

  if (wg == 2) {
    asm volatile("setmaxnreg.dec.sync.aligned.u32 24;");
    if (wid == 8) {
      Cursor tail{0, 0};
      int head = 0, sh = 0;
      uint32_t hph = 0;
      uint32_t cur = 0, used = 0;
      uint64_t fifo = 0;
      uint32_t dst, bar, oready = oready0;
      uint64_t pol;
      asm volatile("createpolicy.fractional.L2::evict_first.b64 %0, 1.0;" : "=l"(pol));
      const uint64_t pol_o = make_policy(P.dbg & 1), pol_p = make_policy(!(P.dbg & 4));
      const CUtensorMap* kv_map = rank ? &P.v[blk] : &P.k[blk];
      auto acquire = [&](uint32_t bytes, int part = 0) {
        uint32_t fp = bytes >> 12;
        if (cur + fp > (RING >> 12)) { fp += (RING >> 12) - cur; cur = 0; }
        used += fp;
        bool more = false;
        uint32_t wbar, wph;
        while (used > (RING >> 12) || (part != 2 && sh == 5 * NBAR)) {
          if (more) mbar_wait(wbar, wph);
          more = true;
          wbar = empty0 + 8 * tail.bi; wph = tail.ph;
          tail.next();
          used -= (uint32_t)fifo & 31;
          fifo >>= 5;
          sh -= 5;
        }
        fifo += (uint64_t)fp << sh;
        dst = sbase + (cur << 12);
        bar = full0 + 8 * head;
        cur += bytes >> 12;
        if (part != 1) {
          sh += 5;
          if (++head == NBAR) { head = 0; hph ^= 1; }
        }
        if (more) mbar_wait(wbar, wph);
      };
      for (int pc = 0;; pc++) {
        const uint32_t op = prog[pc];
        const int type = op & 3, a = (op >> 2) & 7;
        if (type == OP_END) break;
        if (type == OP_Q) {
          const int qr = q_role(op);
#pragma unroll 1
          for (int k = 0; k < 10; k++) {
            acquire(SZ_WQ, 1);
            if ((pc > 0 || k >= EARLY) && (k & 1) == rank && elect()) tma3d_mc(dst, &P.wq[qr >> 5], bar, 0, 64 * k, 3 * (4 * a + (qr & 3)));
            acquire(SZ_A, 2);
            if ((pc > 0 || k >= EARLY) && elect()) {
              tma2d(dst, &P.x[qr >> 5], bar, 64 * k, ((qr >> 2) & 7) * kSq + rank * 128);
              mbar_expect(bar, SZ_WQ + SZ_A);
            }
          }
        } else if (type == OP_A) {
          const uint32_t nop = prog[pc + 1];
          auto kv = [&](int isv, int wave, int j) {
            const int row0 = ((team & 7) * kH + 4 * wave + nt) * kSk;
            acquire(SZ_KV);
            if (isv == (int)rank) {
              const int j = head - 1 - KV_TRANSIT;
              mbar_wait(full0 + 8 * (j < 0 ? j + NBAR : j), j < 0 ? hph ^ 1 : hph);
            }
            if (elect()) {
              if (isv == (int)rank) tma4d_mc_hint(dst, kv_map, bar, row0 / 8 + 8 * j, pol);
              mbar_expect(bar, SZ_KV);
            }
          };
#pragma unroll 1
          for (int t = (op & F_PARK) ? 1 : 0; t < 31; t++) {
            const int isv = t == 0 ? 0 : (~t & 1);
            kv(isv, a, isv ? (t - 1) >> 1 : (t + 1) >> 1);
          }
          if ((nop & 3) == OP_A) {
            mbar_wait((nop & F_HELP) ? hready0 + 8 * ((nop >> 10) & 3) : fenced, 0);
            asm volatile("fence.proxy.async.global;" ::: "memory");
#pragma unroll 1
            for (int i = 0; i < 2; i++) {
              acquire(SZ_PARK);
              if (elect()) {
                mbar_expect(bar, SZ_PARK);
                bulk_load_hint(dst, &g_o[((team * 2 + rank) * 96 + 3 * (4 * ((nop >> 2) & 7) + nt)) * 1024 + i * 1536], SZ_PARK, bar, pol_p);
              }
            }
            kv(0, (nop >> 2) & 7, 0);
          }
          kv(1, a, 15);
        } else {
          const int b = (op >> 5) & 15, ro = o_role(op);
#pragma unroll 1
          for (int i = 0; i < b - a; i++) {
            const int w = o_wave(a, b, i, (P.dbg >> 4) & 7);
            mbar_wait(oready, 0);
            oready += 8;
            asm volatile("fence.proxy.async.global;" ::: "memory");
#pragma unroll 1
            for (int k = 12 * w; k < 12 * w + 12; k++) {
              acquire(SZ_WO, 1);
              if (elect()) tma5d_mc(dst + rank * 10240, &P.wo[ro >> 5], bar, 8 * k + 4 * rank, 5 * (ro & 3));
              acquire(SZ_A, 2);
              if (elect()) {
                bulk_load_hint(dst, &g_o[(((ro >> 2) * 2 + rank) * 96 + k - 12 * (w - P.slot[w])) * 1024], SZ_A, bar, pol_o);
                mbar_expect(bar, SZ_WO + SZ_A);
              }
            }
          }
          if (op & F_LD) {
            if (op & F_PARK) {
              mbar_wait(hready0 + 8 * (MAX_PARK - 1), 0);
              asm volatile("fence.proxy.async.global;" ::: "memory");
            }
#pragma unroll 1
            for (int i = 0; i < 5; i++) {
              acquire(SZ_PART);
              if (elect()) {
                mbar_expect(bar, SZ_PART);
                bulk_load_hint(dst, &g_part[(role * 2 + rank) * 5120 + i * 1024], SZ_PART, bar, pol_p);
              }
            }
          }
        }
      }
    } else if (threadIdx.x == 288) {
      uint32_t ph = 0;
      bool first = true;
      for (int pc = 0;; pc++) {
        const uint32_t op = prog[pc];
        if ((op & 3) == OP_END) break;
        if ((op & 3) != OP_A && !helper) continue;
        mbar_wait_slow<400>(odone, ph);
        ph ^= 1;
        unsigned int* flag = !helper ? &g_done[(team * 2 + rank) * 8 + ((op >> 2) & 7)]
                             : (op & 3) == OP_Q ? &g_help[(q_role(op) * 2 + rank) * MAX_PARK + ((op >> 10) & 3)]
                                                : &g_help[(o_role(op) * 2 + rank) * MAX_PARK + MAX_PARK - 1];
        asm volatile("red.release.gpu.global.add.u32 [%0], 1;" ::"l"(flag) : "memory");
        if (first) mbar_arrive(fenced);
        first = false;
      }
    } else if (threadIdx.x == 320) {
      uint32_t oready = oready0;
      for (int pc = 0;; pc++) {
        const uint32_t op = prog[pc];
        if ((op & 3) == OP_END) break;
        if ((op & 3) == OP_O) {
          const int a = (op >> 2) & 7, b = (op >> 5) & 15;
          for (int i = 0; i < b - a; i++) {
            const int ci = ((o_role(op) >> 2) * 2 + rank) * 8 + o_wave(a, b, i, (P.dbg >> 4) & 7);
            wait_count(&g_done[ci], 4);
            mbar_arrive(oready);
            oready += 8;
            if (atomicAdd(&g_seen[ci], 1u) == 3u) { g_seen[ci] = 0; g_done[ci] = 0; }
          }
        }
        if ((op & 3) != OP_Q && (op & F_HELP) && (op & F_PARK)) {
          unsigned int* flag = &g_help[(role * 2 + rank) * MAX_PARK + ((op >> 10) & 3)];
          wait_count(flag, 1);
          mbar_arrive(hready0 + 8 * ((op >> 10) & 3));
          *flag = 0;
        }
      }
    }
    __syncwarp();
    asm volatile("barrier.cluster.arrive.relaxed;\nbarrier.cluster.wait;" ::: "memory");
  } else {
    asm volatile("setmaxnreg.inc.sync.aligned.u32 240;");
    const int lane = threadIdx.x & 31, warp = wid & 3;
    uint32_t empty_rem;
    asm volatile("mapa.shared::cluster.u32 %0, %1, %2;" : "=r"(empty_rem) : "r"(empty0), "r"(lane & 1));
    auto release = [&](int slot) { mbar_arrive_cluster_if(lane < 2, empty_rem + 8 * slot); };
    Cursor r{0, 0};
    const uint32_t ring16 = (sbase & 0x3FFFF) >> 4;
    uint32_t cur = ring16;
    bool rdy0 = false, rdy1 = false;
    auto probe1 = [&]() { rdy0 = mbar_test(full0 + 8 * r.bi, r.ph); };
    auto probe2 = [&]() {
      Cursor n = r;
      rdy0 = mbar_test(full0 + 8 * n.bi, n.ph);
      n.next();
      rdy1 = mbar_test(full0 + 8 * n.bi, n.ph);
    };
    auto take = [&](bool rdy, uint32_t bytes, uint32_t& addr) {
      const int bi = r.bi;
      if (!__all_sync(0xffffffffu, rdy)) mbar_wait(full0 + 8 * r.bi, r.ph);
      r.next();
      if (cur > ring16 + ((RING - bytes) >> 4)) cur = ring16;
      addr = cur;
      cur += bytes >> 4;
      return bi;
    };
    auto second = [&](uint32_t bytes) {
      if (cur > ring16 + ((RING - bytes) >> 4)) cur = ring16;
      cur += bytes >> 4;
      return cur - (bytes >> 4);
    };
    const int row = wg * 64 + warp * 16 + (lane >> 2);
    int img0 = row * 4 + ((lane & 3) ^ ((row >> 1) & 3));
    uint4* pend = nullptr;
    uint64_t spol;
    int pc = 0;
    uint32_t op = prog[0];
    auto enter = [&]() {
      r.bi = (op >> 15) & 15; r.ph = (op >> 19) & 1; cur = ring16 + (((op >> 20) & 63) << 8);
      spol = make_policy(!(op & F_SOON));
    };
    auto drain = [&](uint32_t (&t)[48], uint32_t c) {
      if (!(op & (3u << 26)) || c >= 6) return;
#pragma unroll
      for (int i = 0; i < 6; i++)
        stg2_if(c == i, pend + i * 512, t[8 * i], t[8 * i + 1], t[8 * i + 2], t[8 * i + 3],
                t[8 * i + 4], t[8 * i + 5], t[8 * i + 6], t[8 * i + 7], spol);
      if ((op & (1u << 26)) && c == 5) {
        __syncwarp();
        mbar_arrive_if(lane < 2, odone);
      }
    };
    float s[32], o[96], c[80];
    uint32_t q[48], pa[16], pb[16];
    float mc0, mc1, l0, l1;
    bool gen;
    auto expo = [&](float (&s)[32], uint32_t (&pout)[16], float& b0, float& b1, bool sub) {
#pragma unroll
      for (int i = 0; i < 8; i++) {
        const float e1 = ex2(sub ? s[4 * i + 1] - mc0 : s[4 * i + 1]), e0 = ex2(sub ? s[4 * i] - mc0 : s[4 * i]);
        const float e3 = ex2(sub ? s[4 * i + 3] - mc1 : s[4 * i + 3]), e2 = ex2(sub ? s[4 * i + 2] - mc1 : s[4 * i + 2]);
        pout[2 * i] = pack_bf16(e0, e1);
        b0 = i ? b0 + fadd(e1, e0) : fadd(e1, e0);
        pout[2 * i + 1] = pack_bf16(e2, e3);
        b1 = i ? b1 + fadd(e3, e2) : fadd(e3, e2);
      }
    };
    auto rowmax = [&](float (&s)[32], float& m0, float& m1) {
      m0 = fmaxf(s[0], s[1]); m1 = fmaxf(s[2], s[3]);
#pragma unroll
      for (int i = 1; i < 8; i++) { m0 = fmaxf(m0, fmaxf(s[4 * i], s[4 * i + 1])); m1 = fmaxf(m1, fmaxf(s[4 * i + 2], s[4 * i + 3])); }
      m0 = fmaxf(m0, __shfl_xor_sync(0xffffffffu, m0, 1)); m1 = fmaxf(m1, __shfl_xor_sync(0xffffffffu, m1, 1));
      m0 = fmaxf(m0, __shfl_xor_sync(0xffffffffu, m0, 2)); m1 = fmaxf(m1, __shfl_xor_sync(0xffffffffu, m1, 2));
    };
    auto first = [&](float (&s)[32]) {
      mc0 = 0.f; mc1 = 0.f;
      expo(s, pa, l0, l1, false);
      gen = __any_sync(0xffffffffu, !(fmaxf(l0, l1) <= kSumLimit && fminf(l0, l1) >= 1.0f / kSumLimit));
      if (gen) {
        rowmax(s, mc0, mc1);
        expo(s, pa, l0, l1, true);
      }
    };
    auto soft = [&](uint32_t (&pout)[16]) {
      float b0, b1;
      if (!gen) {
        expo(s, pout, b0, b1, false);
        gen = __any_sync(0xffffffffu, !(fmaxf(b0, b1) <= kSumLimit));
      }
      if (gen) {
        float m0, m1;
        rowmax(s, m0, m1);
        if (__any_sync(0xffffffffu, !(m0 <= mc0 + kMaxLag && m1 <= mc1 + kMaxLag))) {
          m0 = fmaxf(mc0, m0); m1 = fmaxf(mc1, m1);
          const float a0 = ex2(mc0 - m0), a1 = ex2(mc1 - m1);
          mc0 = m0; mc1 = m1;
          l0 *= a0; l1 *= a1;
          wg_wait<0>();
          fence_regs(o);
#pragma unroll
          for (int i = 0; i < 24; i++) { o[4 * i] *= a0; o[4 * i + 1] *= a0; o[4 * i + 2] *= a1; o[4 * i + 3] *= a1; }
        }
        expo(s, pout, b0, b1, true);
      }
      l0 += b0; l1 += b1;
    };
    auto qk = [&](float (&s)[32], uint32_t ak, int k0, int k1) {
#pragma unroll
      for (int kk = k0; kk < k1; kk++)
        wgmma_rs_n64<0>(s, q[4 * kk], q[4 * kk + 1], q[4 * kk + 2], q[4 * kk + 3], mk_desc(ak + (kk >> 2) * KV_CH + (kk & 3) * 2, 16, KV_SBO, 1), kk != 0);
      wg_commit();
    };
    auto pv = [&](uint32_t (&pin)[16], uint32_t av, int acc) {
#pragma unroll
      for (int kk = 0; kk < 4; kk++)
        wgmma_rs_n192<1>(o, pin[4 * kk], pin[4 * kk + 1], pin[4 * kk + 2], pin[4 * kk + 3], mk_desc(av + kk * (KV_SBO / 8), KV_CH * 16, KV_SBO, 1), acc || (kk != 0));
      wg_commit();
    };
    auto xw = [&](uint32_t ad, int acc) {
      const uint32_t da = second(SZ_A) + wg * 512;
      wg_fence();
#pragma unroll
      for (int kk = 0; kk < 4; kk++)
        wgmma_ss_n192<1>(o, mk_desc(da + kk * 2, 16, 1024, 1), mk_desc(ad + kk * 128, 8192, 1024, 1), acc || kk != 0);
      wg_commit();
    };
    auto ow = [&](int acc, int prev) {
      uint32_t db;
      const int bi = take(rdy0, SZ_WO, db);
      const uint32_t da = second(SZ_A) + wg * 256;
      wg_fence();
      wgmma_ss_n160<1>(c, mk_desc(da, 16, 512, 2), mk_desc(db, 2048, 512, 2), acc);
      wgmma_ss_n160<1>(c, mk_desc(da + 2, 16, 512, 2), mk_desc(db + 64, 2048, 512, 2), 1);
      wg_commit();
      if (acc) { wg_wait<1>(); release(prev); }
      wgmma_ss_n160<1>(c, mk_desc(da + 512, 16, 512, 2), mk_desc(db + 640, 2048, 512, 2), 1);
      wgmma_ss_n160<1>(c, mk_desc(da + 514, 16, 512, 2), mk_desc(db + 704, 2048, 512, 2), 1);
      wg_commit();
      return bi;
    };
    auto o_run = [&](uint32_t (&t)[48], int bi) {
      const int nk = 12 * (((op >> 5) & 15) - ((op >> 2) & 7));
#pragma unroll 1
      for (int k = 0; k < 6; k++) {
        drain(t, k);
        probe1();
        wg_wait<1>();
        bi = ow(1, bi);
      }
#pragma unroll 1
      for (int k = 7; k < nk; k++) {
        probe1();
        wg_wait<1>();
        bi = ow(1, bi);
      }
      probe1();
      return bi;
    };
    auto st_part = [&](int i) {
      stg2_if(true, pend + i * 512, __float_as_uint(c[8 * i]), __float_as_uint(c[8 * i + 1]), __float_as_uint(c[8 * i + 2]), __float_as_uint(c[8 * i + 3]),
              __float_as_uint(c[8 * i + 4]), __float_as_uint(c[8 * i + 5]), __float_as_uint(c[8 * i + 6]), __float_as_uint(c[8 * i + 7]), spol);
    };
#pragma unroll
    for (int i = 0; i < 48; i++) q[i] = 0;
    enter();

    if ((op & 3) == OP_Q) {
      uint32_t ad;
      int bi0 = take(false, SZ_WQ, ad), k = 0, lag = 0;
      xw(ad, 0);
      for (;;) {
#pragma unroll 1
        for (;;) {
          drain(q, k - lag);
          probe1();
          wg_wait<0>();
          release(bi0);
          bi0 = take(rdy0, SZ_WQ, ad);
          if (++k == 8) break;
          xw(ad, 1);
        }
        if (wg) bar_sync(2, 256);
        xw(ad, 1);
        const int bi9 = take(false, SZ_WQ, ad);
        xw(ad, 1);
        if (!wg) asm volatile("bar.arrive 2, 256;" ::: "memory");
        k = 0; lag = 0;
        uint32_t nop = prog[++pc];
        if (op & F_PARK) {
          pend = &g_o[(((q_role(op) >> 2) * 2 + rank) * 96 + 3 * (4 * ((op >> 2) & 7) + (q_role(op) & 3))) * 1024 + img0];
          op = nop;
          enter();
          wg_wait<1>();
          release(bi0);
          probe1();
          wg_wait<0>();
          fence_regs(o);
          release(bi9);
#pragma unroll
          for (int i = 0; i < 48; i++) q[i] = pack_bf16(o[2 * i] * kScaleLog2, o[2 * i + 1] * kScaleLog2);
          if ((op & 3) != OP_Q) break;
          fence_regs(q);
          bi0 = take(rdy0, SZ_WQ, ad);
          xw(ad, 0);
          continue;
        }
        int wave = (op >> 2) & 7, sk1;
        uint32_t ak1;
        {
          wg_wait<1>();
          release(bi0);
          probe2();
          wg_wait<0>();
          fence_regs(o);
          release(bi9);
          float s0[32];
#pragma unroll
          for (int i = 0; i < 48; i++) q[i] = pack_bf16(o[2 * i] * kScaleLog2, o[2 * i + 1] * kScaleLog2);
          fence_regs(q);
          const int sk0 = take(rdy0, SZ_KV, ad);
          wg_fence();
          qk(s0, ad, 0, 12);
          sk1 = take(rdy1, SZ_KV, ak1);
          wg_fence();
          qk(s, ak1, 0, S1A);
          probe1();
          wg_wait<1>();
          fence_regs(s0);
          release(sk0);
          first(s0);
        }
        float i0, i1;
        auto sums = [&]() {
          l0 += __shfl_xor_sync(0xffffffffu, l0, 1); l1 += __shfl_xor_sync(0xffffffffu, l1, 1);
          l0 += __shfl_xor_sync(0xffffffffu, l0, 2); l1 += __shfl_xor_sync(0xffffffffu, l1, 2);
          i0 = rcp(l0); i1 = rcp(l1);
          asm volatile("" : "+f"(i0), "+f"(i1));
        };
        auto target = [&]() {
          pend = &g_o[((team * 2 + rank) * 96 + 3 * (4 * P.slot[wave] + nt)) * 1024 + img0];
          asm volatile("" : "+l"(pend));
        };
        for (;;) {
          nop = prog[++pc];
          {
            uint32_t av;
            const int sv = take(rdy0, SZ_KV, av);
            wg_fence();
            qk(s, ak1, S1A, 12);
            pv(pa, av, 0);
            probe2();
            wg_wait<1>();
            fence_regs(s);
            release(sk1);
            soft(pb);
            wg_wait<0>();
            fence_regs(o);
            release(sv);
          }
          auto step = [&](uint32_t (&pin)[16], uint32_t (&pout)[16]) {
            uint32_t ak, av;
            const int sk = take(rdy0, SZ_KV, ak), sv = take(rdy1, SZ_KV, av);
            wg_fence();
            qk(s, ak, 0, 12);
            pv(pin, av, 1);
            probe2();
            wg_wait<1>();
            fence_regs(s);
            release(sk);
            soft(pout);
            wg_wait<0>();
            fence_regs(o);
            release(sv);
          };
#pragma unroll 1
          for (int jj = 0; jj < 7; jj++) {
            step(pb, pa);
            step(pa, pb);
          }
          if ((nop & 3) != OP_A) break;
          uint32_t ak, av;
          {
            const int b0 = take(rdy0, SZ_PARK, ak), b1 = take(rdy1, SZ_PARK, av);
            const uint32_t ad0 = ak, ad1 = av;
            probe2();
#pragma unroll
            for (int i = 0; i < 12; i++)
              lds128(sbase + ((i < 6 ? ad0 : ad1) - ring16 + img0) * 16 + ((i % 6) >> 1) * 8192 + (i & 1) * 512, q[4 * i], q[4 * i + 1], q[4 * i + 2], q[4 * i + 3]);
            release(b0); release(b1);
          }
          const int sk0 = take(rdy0, SZ_KV, ak), sv = take(rdy1, SZ_KV, av);
          wg_fence();
          qk(s, ak, 0, 8);
          sched_fence(img0, P.zero);
          sums();
          sched_fence(img0, P.zero);
          qk(s, ak, 8, 12);
          pv(pb, av, 1);
          probe2();
          spol = make_policy(!(nop & F_SOON));
          wg_wait<1>();
          fence_regs(s);
          release(sk0);
          first(s);
          sk1 = take(rdy0, SZ_KV, ak1);
          rdy0 = rdy1;
          wg_wait<0>();
          target();
          fence_regs(o);
          release(sv);
          uint32_t t[48];
#pragma unroll
          for (int j = 0; j < 6; j++) {
#pragma unroll
            for (int i = 0; i < 4; i++) {
              t[8 * j + i] = pack_bf16(o[16 * j + 4 * i] * i0, o[16 * j + 4 * i + 1] * i0);
              t[8 * j + i + 4] = pack_bf16(o[16 * j + 4 * i + 2] * i1, o[16 * j + 4 * i + 3] * i1);
            }
            stg2_if(true, pend + j * 512, t[8 * j], t[8 * j + 1], t[8 * j + 2], t[8 * j + 3], t[8 * j + 4], t[8 * j + 5], t[8 * j + 6], t[8 * j + 7], spol);
            if (j == UC0) { wg_fence(); qk(s, ak1, 0, 4); }
            if (j == UC1) { wg_fence(); qk(s, ak1, 4, S1A); }
            sched_fence(img0, P.zero);
          }
          if (P.zero) {
#pragma unroll
            for (int j = 0; j < 5; j++)
              stg2_if(true, pend, t[8 * j], t[8 * j + 1], t[8 * j + 2], t[8 * j + 3], t[8 * j + 4], t[8 * j + 5], t[8 * j + 6], t[8 * j + 7], spol);
          }
          __syncwarp();
          mbar_arrive_if(lane < 2, odone);
          wave = (nop >> 2) & 7;
        }
        const int sv = take(rdy0, SZ_KV, ad);
        wg_fence();
        pv(pb, ad, 1);
        sums();
        target();
        op = nop;
        enter();
        rdy0 = rdy1;
        auto convert = [&](uint32_t (&t)[48], float (&u)[96]) {
#pragma unroll
          for (int i = 0; i < 24; i++) {
            t[8 * (i >> 2) + (i & 3)] = pack_bf16(u[4 * i], u[4 * i + 1]);
            t[8 * (i >> 2) + (i & 3) + 4] = pack_bf16(u[4 * i + 2], u[4 * i + 3]);
          }
        };
        if ((op & 3) != OP_O) {
          if ((op & 3) == OP_Q) bi0 = take(rdy0, SZ_WQ, ad);
          wg_wait<0>();
          fence_regs(o);
          release(sv);
          float u[96];
#pragma unroll
          for (int i = 0; i < 96; i++) u[i] = o[i] * (i & 2 ? i1 : i0);
          if ((op & 3) != OP_Q) { convert(q, u); break; }
          fence_regs(u);
          xw(ad, 0);
          sched_fence(img0, P.zero);
          fence_regs(u);
          convert(q, u);
          continue;
        }
        int bi = ow(0, 0);
        wg_wait<2>();
        fence_regs(o);
        release(sv);
#pragma unroll
        for (int j = 0; j < 6; j++) {
          uint32_t t[8];
#pragma unroll
          for (int i = 0; i < 4; i++) {
            t[i] = pack_bf16(o[16 * j + 4 * i] * i0, o[16 * j + 4 * i + 1] * i0);
            t[i + 4] = pack_bf16(o[16 * j + 4 * i + 2] * i1, o[16 * j + 4 * i + 3] * i1);
          }
          stg2_if(true, pend + j * 512, t[0], t[1], t[2], t[3], t[4], t[5], t[6], t[7], spol);
          if (j == 5) {
            __syncwarp();
            mbar_arrive_if(lane < 2, odone);
          }
          probe1();
          wg_wait<1>();
          bi = ow(1, bi);
          fence_regs(o);
        }
        {
          const int nk = 12 * (((op >> 5) & 15) - ((op >> 2) & 7));
#pragma unroll 1
          for (int k = 7; k < nk; k++) {
            probe1();
            wg_wait<1>();
            bi = ow(1, bi);
          }
          probe1();
        }
        nop = prog[++pc];
        if (op & F_LD) {
          uint32_t t[80];
#pragma unroll
          for (int j = 0; j < 5; j++) {
            const int b = take(rdy0, SZ_PART, ad);
            probe1();
#pragma unroll
            for (int i = 4 * j; i < 4 * j + 4; i++)
              lds128(sbase + (ad - ring16 + img0) * 16 + ((i >> 1) & 1) * 8192 + (i & 1) * 512, t[4 * i], t[4 * i + 1], t[4 * i + 2], t[4 * i + 3]);
            release(b);
          }
          wg_wait<0>();
          fence_regs(c);
#pragma unroll
          for (int i = 0; i < 80; i++) c[i] += __uint_as_float(t[i]);
        }
        if (!(op & F_ST)) {
          wg_wait<0>();
          fence_regs(c);
          goto finish;
        }
        op = nop;
        enter();
        bi0 = take(rdy0, SZ_WQ, ad);
        xw(ad, 0);
        pend = &g_part[(role * 2 + rank) * 5120 + img0];
        probe1();
        wg_wait<1>();
        fence_regs(c);
        release(bi);
        st_part(6); st_part(7);
        wg_wait<0>();
        release(bi0);
        bi0 = take(rdy0, SZ_WQ, ad);
        xw(ad, 1);
        st_part(8); st_part(9);
#pragma unroll
        for (int i = 0; i < 48; i++) q[i] = __float_as_uint(c[i]);
        k = 1; lag = 2;
      }
    }
    rdy0 = false;
    {
      uint32_t t[48];
#pragma unroll
      for (int i = 0; i < 48; i++) t[i] = q[i] ^ P.zero;
      while ((op & 3) == OP_O) {
        const int bi = o_run(t, ow(0, 0));
        wg_wait<0>();
        fence_regs(c);
        pc++;
        if (!(op & F_ST)) goto finish;
        release(bi);
        pend = &g_part[(o_role(op) * 2 + rank) * 5120 + img0];
#pragma unroll
        for (int i = 6; i < 10; i++) st_part(i);
#pragma unroll
        for (int i = 0; i < 48; i++) t[i] = __float_as_uint(c[i]) ^ P.zero;
        op = prog[pc];
        enter();
      }
      for (int i = 0; i < 6; i++) drain(t, i);
    }
    asm volatile("barrier.cluster.arrive.relaxed;" ::: "memory");
    if (false) {
    finish:
      asm volatile("barrier.cluster.arrive.relaxed;" ::: "memory");
      bar_sync(1, 256);
      const uint32_t wstage = sbase + (wg * 4 + warp) * 5120;
      const uint32_t sa = wstage + (lane & 15) * 64;
#pragma unroll
      for (int i = 0; i < 10; i++) {
        const int u = (i & 1) * 2 + (lane >> 4);
        stsm4(sa + (i >> 1) * 1024 + ((u ^ ((lane >> 1) & 3)) << 4), pack_bf16(c[8 * i], c[8 * i + 1]), pack_bf16(c[8 * i + 2], c[8 * i + 3]),
              pack_bf16(c[8 * i + 4], c[8 * i + 5]), pack_bf16(c[8 * i + 6], c[8 * i + 7]));
      }
      asm volatile("fence.proxy.async.shared::cta;" ::: "memory");
      __syncwarp();
      if (lane == 0) {
        tma3d_store(&P.out, wstage, 0, (team & 7) * kSq + rank * 128 + wg * 64 + warp * 16, blk * 20 + nt * 5);
        asm volatile("cp.async.bulk.commit_group;\ncp.async.bulk.wait_group.read 0;" ::: "memory");
      }
      __syncwarp();
    }
    asm volatile("barrier.cluster.wait;" ::: "memory");
  }
}

typedef CUresult (*EncodeFn)(CUtensorMap*, CUtensorMapDataType, cuuint32_t, void*, const cuuint64_t*, const cuuint64_t*,
                             const cuuint32_t*, const cuuint32_t*, CUtensorMapInterleave, CUtensorMapSwizzle,
                             CUtensorMapL2promotion, CUtensorMapFloatOOBfill);

void encode(EncodeFn fn, CUtensorMap* m, const void* ptr, int rank, const cuuint64_t* dims, const cuuint64_t* strides,
            const cuuint32_t* box, CUtensorMapSwizzle swz) {
  const cuuint32_t es[5] = {1, 1, 1, 1, 1};
  CUresult r = fn(m, CU_TENSOR_MAP_DATA_TYPE_BFLOAT16, rank, const_cast<void*>(ptr), dims, strides, box, es,
                  CU_TENSOR_MAP_INTERLEAVE_NONE, swz, CU_TENSOR_MAP_L2_PROMOTION_L2_128B, CU_TENSOR_MAP_FLOAT_OOB_FILL_NONE);
  if (r != CUDA_SUCCESS) fprintf(stderr, "cuTensorMapEncodeTiled failed: %d\n", (int)r);
}

void annotate(uint32_t* ops, int n, bool helper) {
  uint32_t items = 0, cur = 0, pend = 0;
  auto item = [&](uint32_t bytes, int count, uint32_t bytes2 = 0) {
    for (int i = 0; i < count; i++) {
      if (cur + bytes > RING) cur = 0;
      cur += bytes;
      if (cur + bytes2 > RING) cur = 0;
      cur += bytes2;
      items++;
    }
  };
  for (int i = 0; i <= n; i++) {
    const uint32_t op = ops[i];
    ops[i] |= (items % NBAR) << 15 | ((items / NBAR) & 1) << 19 | (cur >> 12) << 20 | pend << 26;
    if ((op & 3) == OP_Q) { item(SZ_WQ, 10, SZ_A); pend = (op & F_PARK) ? (helper ? 1 : 2) : 0; }
    if ((op & 3) == OP_A) {
      item(SZ_KV, (op & F_PARK) ? 30 : 31);
      if ((ops[i + 1] & 3) == OP_A) { item(SZ_PARK, 2); item(SZ_KV, 1); }
      item(SZ_KV, 1);
      pend = 1;
    }
    if ((op & 3) == OP_O) {
      item(SZ_WO, 12 * (((op >> 5) & 15) - ((op >> 2) & 7)), SZ_A);
      if (op & F_LD) item(SZ_PART, 5);
      pend = (op & F_LAZY) ? (helper ? 1 : 2) : 0;
    }
  }
}

void compile_programs(const char* const* text, bool helpers, Params& P) {
  struct Req { int when, team, wave, slot; } req[N_TEAM * MAX_PARK];
  int n_req = 0;
  for (int t = 0; t < N_TEAM; t++) {
    uint32_t* ops = P.ops[t];
    int n = 0, flags[8] = {0, 0, 0, 0, 0, 0, 0, 0}, n_park = 0, last_o = -1, when = 0, given = 0;
    for (const char* s = text[t]; *s; s++) {
      const int a = s[1] - '0';
      if (*s == 'Q' || (*s == 'H' && !helpers)) { ops[n++] = OP_Q | a << 2; when += 10; }
      else if (*s == 'P') { flags[a] = F_PARK | n_park++ << 10; ops[n++] = OP_Q | a << 2 | flags[a]; when += 10; }
      else if (*s == 'H') { req[n_req++] = {when, t, a, n_park}; flags[a] = F_PARK | F_HELP | n_park++ << 10; }
      else if (*s == 'A') { ops[n++] = OP_A | a << 2 | flags[a]; when += 32; }
      else if (*s == 'G') { given = a; if (helpers) req[n_req++] = {1000, t, 0, -a}; }
      else if (*s == 'O') {
        ops[n] = OP_O | a << 2 | (s[2] - '0') << 5;
        if (given) ops[n] = helpers ? ops[n] | F_LD | F_PARK | (MAX_PARK - 1) << 10 : ops[n] & ~(7u << 2);
        if (last_o >= 0) { ops[last_o] |= F_ST; ops[n] |= F_LD; }
        last_o = n++;
        when += 10 * (s[2] - s[1]);
      }
    }
    for (int i = 0; i + 1 < n; i++)
      if ((ops[i] & 3) == OP_O && (ops[i] & F_ST) && (ops[i + 1] & 3) == OP_Q) ops[i] |= F_LAZY;
    for (int i = n; i < MAX_OPS; i++) ops[i] = OP_END;
    annotate(ops, n, false);
    for (int i = 0; i < n; i++) {
      if ((ops[i] & 3) != OP_A && (P.dbg & 8)) ops[i + 1] |= F_SOON;
      if ((ops[i] & 3) != OP_A) continue;
      const int w = (ops[i] >> 2) & 7;
      int dist = 0;
      for (int j = i + 1; j < n; j++) {
        const int a = (ops[j] >> 2) & 7, b = (ops[j] >> 5) & 15;
        if ((ops[j] & 3) == OP_O && w < b) {
          for (int k = 0; k < b - a && o_wave(a, b, k, (P.dbg >> 4) & 7) != w; k++) dist += 10;
          break;
        }
        dist += (ops[j] & 3) == OP_Q ? 10 : (ops[j] & 3) == OP_A ? 32 : 10 * (b - a);
      }
      if (dist <= (int)((P.dbg >> 8) & 255)) ops[i + 1] |= F_SOON;
    }
  }
  for (int i = 1; i < n_req; i++)
    for (int j = i; j > 0 && req[j].when < req[j - 1].when; j--) { Req r = req[j]; req[j] = req[j - 1]; req[j - 1] = r; }
  for (int h = 0; h < N_HELP; h++) {
    uint32_t* ops = P.ops[N_TEAM + 2 * h];
    int n = 0;
    for (int i = 0; i < n_req; i++)
      for (int m = h; m < 4; m += N_HELP) {
        const uint32_t ro = 4 * req[i].team + m;
        ops[n++] = req[i].slot >= 0 ? OP_Q | req[i].wave << 2 | req[i].team << 5 | F_PARK | req[i].slot << 10 | m << 12
                                    : OP_O | -req[i].slot << 5 | F_ST | F_LAZY | F_SOON | (ro & 7) << 9 | (ro >> 3) << 29;
      }
    for (int i = n; i < 2 * MAX_OPS; i++) ops[i] = OP_END | F_SOON;
    annotate(ops, n, true);
  }
  for (int i = 0; i < 32; i++) P.first[i] = i < N_TEAM ? P.ops[i][0] : i < N_TEAM + N_HELP ? P.ops[2 * i - N_TEAM][0] : 0;
}

const char* const kPrograms[N_TEAM] = {
  "Q0A0Q1A1H2A2O03Q3A3Q4A4Q5A5Q6A6Q7A7O38",
  "Q0A0Q1A1Q2A2H3A3Q4A4O03Q5A5Q6A6Q7A7O38",
  "Q0A0H1A1Q2A2Q3A3O04Q4A4Q5A5Q6A6Q7A7O48",
  "Q0A0Q1A1Q2A2Q3A3O02Q4A4Q5A5Q6A6H7A7O28",
  "Q0A0Q1A1Q2A2O03Q3A3Q4A4Q5A5Q6A6H7A7O38",
  "Q0A0Q1A1Q2A2Q3A3Q4A4O05Q5A5Q6A6H7A7O58",
  "Q0A0Q1A1Q2A2Q3A3Q4A4O05Q5A5Q6A6H7A7O58",
  "Q0A0Q1A1Q2A2O03Q3A3Q4A4H5A5Q6A6Q7A7O38",
  "P7Q0A0Q1A1O01Q2A2H3A3Q4A4Q5A5Q6A6A7O18",
  "P3P5Q0A0Q1A1Q2A2A3Q4A4A5H6A6Q7A7O08",
  "P7Q0A0Q1A1Q2A2Q3A3H4A4Q5A5Q6A6A7O08",
  "P3P7Q0A0Q1A1H2A2A3Q4A4Q5A5Q6A6A7O08",
  "Q0A0Q1A1Q2A2O01Q3A3Q4A4H5A5Q6A6Q7A7O18",
  "P3Q0A0Q1A1Q2A2A3Q4A4Q5A5Q6A6Q7A7G1O18",
  "P6Q0A0Q1A1Q2A2Q3A3Q4A4Q5A5A6Q7A7G1O18",
  "P2P6Q0A0Q1A1A2Q3A3H4A4Q5A5A6Q7A7O08",
};

const char* const* bench_programs() {
  return kPrograms;
}

}

extern "C" void kernel_launch(void* const* d_in, const int* in_sizes, int n_in, void* d_out, int out_size) {
  (void)in_sizes; (void)n_in; (void)out_size;
  static EncodeFn fn = nullptr;
  static int n_clusters = 0;
  if (!fn) {
    cudaDriverEntryPointQueryResult qr;
    void* f = nullptr;
    cudaGetDriverEntryPoint("cuTensorMapEncodeTiled", &f, cudaEnableDefault, &qr);
    fn = (EncodeFn)f;
    cudaFuncSetAttribute(fused_kernel, cudaFuncAttributeMaxDynamicSharedMemorySize, SMEM_BYTES);
    cudaLaunchConfig_t cfg = {};
    cfg.gridDim = dim3(132); cfg.blockDim = dim3(384); cfg.dynamicSmemBytes = SMEM_BYTES;
    cudaLaunchAttribute at[1];
    at[0].id = cudaLaunchAttributeClusterDimension; at[0].val.clusterDim.x = 2; at[0].val.clusterDim.y = 1; at[0].val.clusterDim.z = 1;
    cfg.attrs = at; cfg.numAttrs = 1;
    if (cudaOccupancyMaxActiveClusters(&n_clusters, fused_kernel, &cfg) != cudaSuccess || n_clusters < 1) n_clusters = 1;
    (void)cudaGetLastError();
  }
  Params P;
  const CUtensorMapSwizzle S128 = CU_TENSOR_MAP_SWIZZLE_128B, S64 = CU_TENSOR_MAP_SWIZZLE_64B;
  for (int blk = 0; blk < 2; blk++) {
    void* const* in = d_in + 5 * blk;
    { const cuuint64_t d[] = {kD, kB * kSq}, s[] = {kD * 2}; const cuuint32_t b[] = {64, 128};
      encode(fn, &P.x[blk], in[0], 2, d, s, b, S128); }
    { const cuuint64_t d[] = {64, 8, 3, (cuuint64_t)kB * kH * kSk / 8}, s[] = {kDh * 2, 128, 8 * kDh * 2}; const cuuint32_t b[] = {64, 8, 3, 8};
      encode(fn, &P.k[blk], in[1], 4, d, s, b, S128);
      encode(fn, &P.v[blk], in[2], 4, d, s, b, S128); }
    { const cuuint64_t d[] = {64, kD, kHD / 64}, s[] = {kHD * 2, 128}; const cuuint32_t b[] = {64, 64, 3};
      encode(fn, &P.wq[blk], in[3], 3, d, s, b, S128); }
    { const cuuint64_t d[] = {32, 2, kHD / 8, 4, kD / 32}, s[] = {kD * 2, 8 * kD * 2, 2 * kD * 2, 64}; const cuuint32_t b[] = {32, 2, 4, 4, 5};
      encode(fn, &P.wo[blk], in[4], 5, d, s, b, S64); }
  }
  { const cuuint64_t d[] = {32, kB * kSq, 2 * kD / 32}, s[] = {2 * kD * 2, 64}; const cuuint32_t b[] = {32, 16, 5};
    encode(fn, &P.out, d_out, 3, d, s, b, S64); }

  P.zero = 0;
  P.dbg = 0x5030;
  for (int w = 0; w < 8; w++) P.slot[w] = (P.dbg >> 16) & 15 ? w % ((P.dbg >> 16) & 15) : w;
  if (n_clusters >= N_CL) {
    const bool helpers = n_clusters >= N_CL + N_HELP;
    compile_programs(bench_programs(), helpers, P);
    fused_kernel<<<2 * (N_CL + (helpers ? N_HELP : 0)), 384, SMEM_BYTES>>>(P);
  } else {
    for (int phase = 0; phase < 2; phase++) {
      const char* text[N_TEAM];
      for (int t = 0; t < N_TEAM; t++) text[t] = phase ? "O08" : "Q0A0Q1A1Q2A2Q3A3Q4A4Q5A5Q6A6Q7A7";
      compile_programs(text, false, P);
      fused_kernel<<<2 * N_CL, 384, SMEM_BYTES>>>(P);
    }
  }
}
```

```cpp
#include <cuda_runtime.h>
#include <cuda_bf16.h>
#include <cuda.h>
#include <stdint.h>
#include <stdio.h>

namespace {

constexpr int kB = 8, kSq = 256, kD = 640, kH = 32, kSk = 1024, kDh = 192;
constexpr int kHD = kH * kDh;
#define S1A 7
#define UC0 3
#define UC1 4
#define RING_KB 224
constexpr uint32_t RING = RING_KB * 1024;
constexpr uint32_t SZ_KV = 24576;
constexpr uint32_t SZ_WQ = 24576, SZ_WO = 20480, SZ_A = 16384;
constexpr uint32_t SZ_PARK = 24576;
constexpr uint32_t SZ_PART = 16384;
constexpr int NBAR = 10;
#define KVT 4
constexpr int KV_TRANSIT = KVT;
#define EARLY_N 3
constexpr int EARLY = EARLY_N;
constexpr uint32_t KV_CH = 64, KV_SBO = 3072;
constexpr int SMEM_BYTES = RING + 512 + 1024;
constexpr int N_TEAM = 16, N_CL = 64, N_HELP = 2, MAX_OPS = 24, MAX_PARK = 4;
enum { OP_END = 0, OP_Q = 1, OP_A = 2, OP_O = 3, F_PARK = 1 << 9, F_LD = 1 << 12, F_ST = 1 << 13, F_LAZY = 1 << 14, F_HELP = 1 << 12, F_SOON = 1 << 28 };

struct alignas(64) Params {
  uint32_t first[32];
  CUtensorMap x[2], wq[2], k[2], v[2], wo[2], out;
  uint32_t ops[N_TEAM + 2 * N_HELP][MAX_OPS];
  uint32_t zero;
  uint32_t slot[8];
  uint32_t dbg;
};

__device__ uint4 g_o[N_TEAM * 2 * 96 * 1024];
__device__ uint4 g_part[N_CL * 2 * 5 * 1024];
__device__ unsigned int g_done[N_TEAM * 2 * 8];
__device__ unsigned int g_help[N_CL * 2 * MAX_PARK];
__device__ unsigned int g_seen[N_TEAM * 2 * 8];

template <int TB, int TA = 0>
__device__ __forceinline__ void wgmma_ss_n64(float (&d)[32], uint64_t da, uint64_t db, int scale_d) {
  asm volatile("{\n.reg .pred p;\nsetp.ne.b32 p, %34, 0;\n"
    "wgmma.mma_async.sync.aligned.m64n64k16.f32.bf16.bf16 {%0, %1, %2, %3, %4, %5, %6, %7, %8, %9, %10, %11, %12, %13, %14, %15, %16, %17, %18, %19, %20, %21, %22, %23, %24, %25, %26, %27, %28, %29, %30, %31}, %32, %33, p, 1, 1, %35, %36;\n}\n"
    : "+f"(d[0]), "+f"(d[1]), "+f"(d[2]), "+f"(d[3]), "+f"(d[4]), "+f"(d[5]), "+f"(d[6]), "+f"(d[7]), "+f"(d[8]), "+f"(d[9]), "+f"(d[10]), "+f"(d[11]), "+f"(d[12]), "+f"(d[13]), "+f"(d[14]), "+f"(d[15]), "+f"(d[16]), "+f"(d[17]), "+f"(d[18]), "+f"(d[19]), "+f"(d[20]), "+f"(d[21]), "+f"(d[22]), "+f"(d[23]), "+f"(d[24]), "+f"(d[25]), "+f"(d[26]), "+f"(d[27]), "+f"(d[28]), "+f"(d[29]), "+f"(d[30]), "+f"(d[31])
    : "l"(da), "l"(db), "r"(scale_d), "n"(TA), "n"(TB));
}
template <int TB>
__device__ __forceinline__ void wgmma_rs_n64(float (&d)[32], uint32_t a0, uint32_t a1, uint32_t a2, uint32_t a3, uint64_t db, int scale_d) {
  asm volatile("{\n.reg .pred p;\nsetp.ne.b32 p, %37, 0;\n"
    "wgmma.mma_async.sync.aligned.m64n64k16.f32.bf16.bf16 {%0, %1, %2, %3, %4, %5, %6, %7, %8, %9, %10, %11, %12, %13, %14, %15, %16, %17, %18, %19, %20, %21, %22, %23, %24, %25, %26, %27, %28, %29, %30, %31}, {%32, %33, %34, %35}, %36, p, 1, 1, %38;\n}\n"
    : "+f"(d[0]), "+f"(d[1]), "+f"(d[2]), "+f"(d[3]), "+f"(d[4]), "+f"(d[5]), "+f"(d[6]), "+f"(d[7]), "+f"(d[8]), "+f"(d[9]), "+f"(d[10]), "+f"(d[11]), "+f"(d[12]), "+f"(d[13]), "+f"(d[14]), "+f"(d[15]), "+f"(d[16]), "+f"(d[17]), "+f"(d[18]), "+f"(d[19]), "+f"(d[20]), "+f"(d[21]), "+f"(d[22]), "+f"(d[23]), "+f"(d[24]), "+f"(d[25]), "+f"(d[26]), "+f"(d[27]), "+f"(d[28]), "+f"(d[29]), "+f"(d[30]), "+f"(d[31])
    : "r"(a0), "r"(a1), "r"(a2), "r"(a3), "l"(db), "r"(scale_d), "n"(TB));
}
template <int TB, int TA = 0>
__device__ __forceinline__ void wgmma_ss_n160(float (&d)[80], uint64_t da, uint64_t db, int scale_d) {
  asm volatile("{\n.reg .pred p;\nsetp.ne.b32 p, %82, 0;\n"
    "wgmma.mma_async.sync.aligned.m64n160k16.f32.bf16.bf16 {%0, %1, %2, %3, %4, %5, %6, %7, %8, %9, %10, %11, %12, %13, %14, %15, %16, %17, %18, %19, %20, %21, %22, %23, %24, %25, %26, %27, %28, %29, %30, %31, %32, %33, %34, %35, %36, %37, %38, %39, %40, %41, %42, %43, %44, %45, %46, %47, %48, %49, %50, %51, %52, %53, %54, %55, %56, %57, %58, %59, %60, %61, %62, %63, %64, %65, %66, %67, %68, %69, %70, %71, %72, %73, %74, %75, %76, %77, %78, %79}, %80, %81, p, 1, 1, %83, %84;\n}\n"
    : "+f"(d[0]), "+f"(d[1]), "+f"(d[2]), "+f"(d[3]), "+f"(d[4]), "+f"(d[5]), "+f"(d[6]), "+f"(d[7]), "+f"(d[8]), "+f"(d[9]), "+f"(d[10]), "+f"(d[11]), "+f"(d[12]), "+f"(d[13]), "+f"(d[14]), "+f"(d[15]), "+f"(d[16]), "+f"(d[17]), "+f"(d[18]), "+f"(d[19]), "+f"(d[20]), "+f"(d[21]), "+f"(d[22]), "+f"(d[23]), "+f"(d[24]), "+f"(d[25]), "+f"(d[26]), "+f"(d[27]), "+f"(d[28]), "+f"(d[29]), "+f"(d[30]), "+f"(d[31]), "+f"(d[32]), "+f"(d[33]), "+f"(d[34]), "+f"(d[35]), "+f"(d[36]), "+f"(d[37]), "+f"(d[38]), "+f"(d[39]), "+f"(d[40]), "+f"(d[41]), "+f"(d[42]), "+f"(d[43]), "+f"(d[44]), "+f"(d[45]), "+f"(d[46]), "+f"(d[47]), "+f"(d[48]), "+f"(d[49]), "+f"(d[50]), "+f"(d[51]), "+f"(d[52]), "+f"(d[53]), "+f"(d[54]), "+f"(d[55]), "+f"(d[56]), "+f"(d[57]), "+f"(d[58]), "+f"(d[59]), "+f"(d[60]), "+f"(d[61]), "+f"(d[62]), "+f"(d[63]), "+f"(d[64]), "+f"(d[65]), "+f"(d[66]), "+f"(d[67]), "+f"(d[68]), "+f"(d[69]), "+f"(d[70]), "+f"(d[71]), "+f"(d[72]), "+f"(d[73]), "+f"(d[74]), "+f"(d[75]), "+f"(d[76]), "+f"(d[77]), "+f"(d[78]), "+f"(d[79])
    : "l"(da), "l"(db), "r"(scale_d), "n"(TA), "n"(TB));
}
template <int TB>
__device__ __forceinline__ void wgmma_rs_n160(float (&d)[80], uint32_t a0, uint32_t a1, uint32_t a2, uint32_t a3, uint64_t db, int scale_d) {
  asm volatile("{\n.reg .pred p;\nsetp.ne.b32 p, %85, 0;\n"
    "wgmma.mma_async.sync.aligned.m64n160k16.f32.bf16.bf16 {%0, %1, %2, %3, %4, %5, %6, %7, %8, %9, %10, %11, %12, %13, %14, %15, %16, %17, %18, %19, %20, %21, %22, %23, %24, %25, %26, %27, %28, %29, %30, %31, %32, %33, %34, %35, %36, %37, %38, %39, %40, %41, %42, %43, %44, %45, %46, %47, %48, %49, %50, %51, %52, %53, %54, %55, %56, %57, %58, %59, %60, %61, %62, %63, %64, %65, %66, %67, %68, %69, %70, %71, %72, %73, %74, %75, %76, %77, %78, %79}, {%80, %81, %82, %83}, %84, p, 1, 1, %86;\n}\n"
    : "+f"(d[0]), "+f"(d[1]), "+f"(d[2]), "+f"(d[3]), "+f"(d[4]), "+f"(d[5]), "+f"(d[6]), "+f"(d[7]), "+f"(d[8]), "+f"(d[9]), "+f"(d[10]), "+f"(d[11]), "+f"(d[12]), "+f"(d[13]), "+f"(d[14]), "+f"(d[15]), "+f"(d[16]), "+f"(d[17]), "+f"(d[18]), "+f"(d[19]), "+f"(d[20]), "+f"(d[21]), "+f"(d[22]), "+f"(d[23]), "+f"(d[24]), "+f"(d[25]), "+f"(d[26]), "+f"(d[27]), "+f"(d[28]), "+f"(d[29]), "+f"(d[30]), "+f"(d[31]), "+f"(d[32]), "+f"(d[33]), "+f"(d[34]), "+f"(d[35]), "+f"(d[36]), "+f"(d[37]), "+f"(d[38]), "+f"(d[39]), "+f"(d[40]), "+f"(d[41]), "+f"(d[42]), "+f"(d[43]), "+f"(d[44]), "+f"(d[45]), "+f"(d[46]), "+f"(d[47]), "+f"(d[48]), "+f"(d[49]), "+f"(d[50]), "+f"(d[51]), "+f"(d[52]), "+f"(d[53]), "+f"(d[54]), "+f"(d[55]), "+f"(d[56]), "+f"(d[57]), "+f"(d[58]), "+f"(d[59]), "+f"(d[60]), "+f"(d[61]), "+f"(d[62]), "+f"(d[63]), "+f"(d[64]), "+f"(d[65]), "+f"(d[66]), "+f"(d[67]), "+f"(d[68]), "+f"(d[69]), "+f"(d[70]), "+f"(d[71]), "+f"(d[72]), "+f"(d[73]), "+f"(d[74]), "+f"(d[75]), "+f"(d[76]), "+f"(d[77]), "+f"(d[78]), "+f"(d[79])
    : "r"(a0), "r"(a1), "r"(a2), "r"(a3), "l"(db), "r"(scale_d), "n"(TB));
}
template <int TB, int TA = 0>
__device__ __forceinline__ void wgmma_ss_n192(float (&d)[96], uint64_t da, uint64_t db, int scale_d) {
  asm volatile("{\n.reg .pred p;\nsetp.ne.b32 p, %98, 0;\n"
    "wgmma.mma_async.sync.aligned.m64n192k16.f32.bf16.bf16 {%0, %1, %2, %3, %4, %5, %6, %7, %8, %9, %10, %11, %12, %13, %14, %15, %16, %17, %18, %19, %20, %21, %22, %23, %24, %25, %26, %27, %28, %29, %30, %31, %32, %33, %34, %35, %36, %37, %38, %39, %40, %41, %42, %43, %44, %45, %46, %47, %48, %49, %50, %51, %52, %53, %54, %55, %56, %57, %58, %59, %60, %61, %62, %63, %64, %65, %66, %67, %68, %69, %70, %71, %72, %73, %74, %75, %76, %77, %78, %79, %80, %81, %82, %83, %84, %85, %86, %87, %88, %89, %90, %91, %92, %93, %94, %95}, %96, %97, p, 1, 1, %99, %100;\n}\n"
    : "+f"(d[0]), "+f"(d[1]), "+f"(d[2]), "+f"(d[3]), "+f"(d[4]), "+f"(d[5]), "+f"(d[6]), "+f"(d[7]), "+f"(d[8]), "+f"(d[9]), "+f"(d[10]), "+f"(d[11]), "+f"(d[12]), "+f"(d[13]), "+f"(d[14]), "+f"(d[15]), "+f"(d[16]), "+f"(d[17]), "+f"(d[18]), "+f"(d[19]), "+f"(d[20]), "+f"(d[21]), "+f"(d[22]), "+f"(d[23]), "+f"(d[24]), "+f"(d[25]), "+f"(d[26]), "+f"(d[27]), "+f"(d[28]), "+f"(d[29]), "+f"(d[30]), "+f"(d[31]), "+f"(d[32]), "+f"(d[33]), "+f"(d[34]), "+f"(d[35]), "+f"(d[36]), "+f"(d[37]), "+f"(d[38]), "+f"(d[39]), "+f"(d[40]), "+f"(d[41]), "+f"(d[42]), "+f"(d[43]), "+f"(d[44]), "+f"(d[45]), "+f"(d[46]), "+f"(d[47]), "+f"(d[48]), "+f"(d[49]), "+f"(d[50]), "+f"(d[51]), "+f"(d[52]), "+f"(d[53]), "+f"(d[54]), "+f"(d[55]), "+f"(d[56]), "+f"(d[57]), "+f"(d[58]), "+f"(d[59]), "+f"(d[60]), "+f"(d[61]), "+f"(d[62]), "+f"(d[63]), "+f"(d[64]), "+f"(d[65]), "+f"(d[66]), "+f"(d[67]), "+f"(d[68]), "+f"(d[69]), "+f"(d[70]), "+f"(d[71]), "+f"(d[72]), "+f"(d[73]), "+f"(d[74]), "+f"(d[75]), "+f"(d[76]), "+f"(d[77]), "+f"(d[78]), "+f"(d[79]), "+f"(d[80]), "+f"(d[81]), "+f"(d[82]), "+f"(d[83]), "+f"(d[84]), "+f"(d[85]), "+f"(d[86]), "+f"(d[87]), "+f"(d[88]), "+f"(d[89]), "+f"(d[90]), "+f"(d[91]), "+f"(d[92]), "+f"(d[93]), "+f"(d[94]), "+f"(d[95])
    : "l"(da), "l"(db), "r"(scale_d), "n"(TA), "n"(TB));
}
template <int TB>
__device__ __forceinline__ void wgmma_rs_n192(float (&d)[96], uint32_t a0, uint32_t a1, uint32_t a2, uint32_t a3, uint64_t db, int scale_d) {
  asm volatile("{\n.reg .pred p;\nsetp.ne.b32 p, %101, 0;\n"
    "wgmma.mma_async.sync.aligned.m64n192k16.f32.bf16.bf16 {%0, %1, %2, %3, %4, %5, %6, %7, %8, %9, %10, %11, %12, %13, %14, %15, %16, %17, %18, %19, %20, %21, %22, %23, %24, %25, %26, %27, %28, %29, %30, %31, %32, %33, %34, %35, %36, %37, %38, %39, %40, %41, %42, %43, %44, %45, %46, %47, %48, %49, %50, %51, %52, %53, %54, %55, %56, %57, %58, %59, %60, %61, %62, %63, %64, %65, %66, %67, %68, %69, %70, %71, %72, %73, %74, %75, %76, %77, %78, %79, %80, %81, %82, %83, %84, %85, %86, %87, %88, %89, %90, %91, %92, %93, %94, %95}, {%96, %97, %98, %99}, %100, p, 1, 1, %102;\n}\n"
    : "+f"(d[0]), "+f"(d[1]), "+f"(d[2]), "+f"(d[3]), "+f"(d[4]), "+f"(d[5]), "+f"(d[6]), "+f"(d[7]), "+f"(d[8]), "+f"(d[9]), "+f"(d[10]), "+f"(d[11]), "+f"(d[12]), "+f"(d[13]), "+f"(d[14]), "+f"(d[15]), "+f"(d[16]), "+f"(d[17]), "+f"(d[18]), "+f"(d[19]), "+f"(d[20]), "+f"(d[21]), "+f"(d[22]), "+f"(d[23]), "+f"(d[24]), "+f"(d[25]), "+f"(d[26]), "+f"(d[27]), "+f"(d[28]), "+f"(d[29]), "+f"(d[30]), "+f"(d[31]), "+f"(d[32]), "+f"(d[33]), "+f"(d[34]), "+f"(d[35]), "+f"(d[36]), "+f"(d[37]), "+f"(d[38]), "+f"(d[39]), "+f"(d[40]), "+f"(d[41]), "+f"(d[42]), "+f"(d[43]), "+f"(d[44]), "+f"(d[45]), "+f"(d[46]), "+f"(d[47]), "+f"(d[48]), "+f"(d[49]), "+f"(d[50]), "+f"(d[51]), "+f"(d[52]), "+f"(d[53]), "+f"(d[54]), "+f"(d[55]), "+f"(d[56]), "+f"(d[57]), "+f"(d[58]), "+f"(d[59]), "+f"(d[60]), "+f"(d[61]), "+f"(d[62]), "+f"(d[63]), "+f"(d[64]), "+f"(d[65]), "+f"(d[66]), "+f"(d[67]), "+f"(d[68]), "+f"(d[69]), "+f"(d[70]), "+f"(d[71]), "+f"(d[72]), "+f"(d[73]), "+f"(d[74]), "+f"(d[75]), "+f"(d[76]), "+f"(d[77]), "+f"(d[78]), "+f"(d[79]), "+f"(d[80]), "+f"(d[81]), "+f"(d[82]), "+f"(d[83]), "+f"(d[84]), "+f"(d[85]), "+f"(d[86]), "+f"(d[87]), "+f"(d[88]), "+f"(d[89]), "+f"(d[90]), "+f"(d[91]), "+f"(d[92]), "+f"(d[93]), "+f"(d[94]), "+f"(d[95])
    : "r"(a0), "r"(a1), "r"(a2), "r"(a3), "l"(db), "r"(scale_d), "n"(TB));
}

__device__ __forceinline__ uint32_t smem_u32(const void* p) { return (uint32_t)__cvta_generic_to_shared(p); }
__device__ __forceinline__ void wg_fence() { asm volatile("wgmma.fence.sync.aligned;" ::: "memory"); }
__device__ __forceinline__ void wg_commit() { asm volatile("wgmma.commit_group.sync.aligned;" ::: "memory"); }
template <int N> __device__ __forceinline__ void wg_wait() { asm volatile("wgmma.wait_group.sync.aligned %0;" ::"n"(N) : "memory"); }
__device__ __forceinline__ void sched_fence(int& keep, uint32_t zero) {
  asm volatile("{\n.reg .u32 c;\nmov.u32 c, %%clock;\nand.b32 c, c, %1;\nxor.b32 %0, %0, c;\n}\n" : "+r"(keep) : "r"(zero) : "memory");
}
template <int N> __device__ __forceinline__ void fence_regs(float (&r)[N]) {
#pragma unroll
  for (int i = 0; i < N; i++) asm volatile("" : "+f"(r[i])::"memory");
}
template <int N> __device__ __forceinline__ void fence_regs(uint32_t (&r)[N]) {
#pragma unroll
  for (int i = 0; i < N; i++) asm volatile("" : "+r"(r[i])::"memory");
}
__device__ __forceinline__ uint64_t mk_desc(uint32_t a16, uint32_t lbo, uint32_t sbo, uint32_t swz) {
  uint64_t d;
  asm("mov.b64 %0, {%1, %2};" : "=l"(d) : "r"(a16 + ((lbo >> 4) << 16)), "r"((sbo >> 4) | (swz << 30)));
  return d;
}
__device__ __forceinline__ void mbar_init(uint32_t bar, uint32_t cnt) {
  asm volatile("mbarrier.init.shared::cta.b64 [%0], %1;" ::"r"(bar), "r"(cnt) : "memory");
}
__device__ __forceinline__ void mbar_expect(uint32_t bar, uint32_t tx) {
  asm volatile("mbarrier.arrive.expect_tx.shared::cta.b64 _, [%0], %1;" ::"r"(bar), "r"(tx) : "memory");
}
__device__ __forceinline__ bool mbar_test(uint32_t bar, uint32_t ph) {
  uint32_t ok;
  asm volatile("{\n.reg .pred p;\nmbarrier.test_wait.parity.shared::cta.b64 p, [%1], %2;\nselp.u32 %0, 1, 0, p;\n}\n"
               : "=r"(ok) : "r"(bar), "r"(ph) : "memory");
  return ok;
}
__device__ __forceinline__ void mbar_wait(uint32_t bar, uint32_t ph) {
  asm volatile("{\n.reg .pred p;\n.reg .u32 n;\nmov.u32 n, 0;\n"
               "LOOP:\nadd.u32 n, n, 1;\nmbarrier.try_wait.parity.shared::cta.b64 p, [%0], %1;\n@p bra DONE;\n"
               "setp.lt.u32 p, n, 0x1000000;\n@p bra LOOP;\ntrap;\n"
               "DONE:\n}\n" ::"r"(bar), "r"(ph) : "memory");
}
template <int NS> __device__ __forceinline__ void mbar_wait_slow(uint32_t bar, uint32_t ph) {
  asm volatile("{\n.reg .pred p;\n.reg .u32 n;\nmov.u32 n, 0;\n"
               "LOOP:\nmbarrier.test_wait.parity.shared::cta.b64 p, [%0], %1;\n@p bra DONE;\n"
               "nanosleep.u32 %2;\nadd.u32 n, n, 1;\nsetp.lt.u32 p, n, 0x400000;\n@p bra LOOP;\ntrap;\n"
               "DONE:\n}\n" ::"r"(bar), "r"(ph), "n"(NS) : "memory");
}
__device__ __forceinline__ void mbar_arrive_cluster_if(bool on, uint32_t addr) {
  asm volatile("{\n.reg .pred p;\nsetp.ne.b32 p, %1, 0;\n@p mbarrier.arrive.shared::cluster.b64 _, [%0];\n}\n" ::"r"(addr), "r"((int)on) : "memory");
}
__device__ __forceinline__ void mbar_arrive_if(bool on, uint32_t addr) {
  asm volatile("{\n.reg .pred p;\nsetp.ne.b32 p, %1, 0;\n@p mbarrier.arrive.shared::cta.b64 _, [%0];\n}\n" ::"r"(addr), "r"((int)on) : "memory");
}
__device__ __forceinline__ void tma2d(uint32_t dst, const CUtensorMap* m, uint32_t bar, int c0, int c1) {
  asm volatile("cp.async.bulk.tensor.2d.shared::cluster.global.mbarrier::complete_tx::bytes [%0], [%1, {%3, %4}], [%2];"
               ::"r"(dst), "l"(m), "r"(bar), "r"(c0), "r"(c1) : "memory");
}
__device__ __forceinline__ void tma3d(uint32_t dst, const CUtensorMap* m, uint32_t bar, int c0, int c1, int c2) {
  asm volatile("cp.async.bulk.tensor.3d.shared::cluster.global.mbarrier::complete_tx::bytes [%0], [%1, {%3, %4, %5}], [%2];"
               ::"r"(dst), "l"(m), "r"(bar), "r"(c0), "r"(c1), "r"(c2) : "memory");
}
__device__ __forceinline__ void tma3d_mc(uint32_t dst, const CUtensorMap* m, uint32_t bar, int c0, int c1, int c2) {
  asm volatile("cp.async.bulk.tensor.3d.shared::cluster.global.mbarrier::complete_tx::bytes.multicast::cluster"
               " [%0], [%1, {%3, %4, %5}], [%2], %6;"
               ::"r"(dst), "l"(m), "r"(bar), "r"(c0), "r"(c1), "r"(c2), "h"((uint16_t)3) : "memory");
}
__device__ __forceinline__ void tma3d_store(const CUtensorMap* m, uint32_t src, int c0, int c1, int c2) {
  asm volatile("cp.async.bulk.tensor.3d.global.shared::cta.bulk_group [%0, {%2, %3, %4}], [%1];"
               ::"l"(m), "r"(src), "r"(c0), "r"(c1), "r"(c2) : "memory");
}
__device__ __forceinline__ void bar_sync(int id, int n) { asm volatile("bar.sync %0, %1;" ::"r"(id), "r"(n) : "memory"); }
__device__ __forceinline__ uint32_t pack_bf16(float lo, float hi) {
  uint32_t r;
  asm("cvt.rn.bf16x2.f32 %0, %1, %2;" : "=r"(r) : "f"(hi), "f"(lo));
  return r;
}
__device__ __forceinline__ float ex2(float x) {
  float y;
  asm("ex2.approx.ftz.f32 %0, %1;" : "=f"(y) : "f"(x));
  return y;
}
__device__ __forceinline__ float fadd(float a, float b) {
  float y;
  asm("add.f32 %0, %1, %2;" : "=f"(y) : "f"(a), "f"(b));
  return y;
}
__device__ __forceinline__ float rcp(float x) {
  float y;
  asm("rcp.approx.ftz.f32 %0, %1;" : "=f"(y) : "f"(x));
  return y;
}
__device__ __forceinline__ void stsm4(uint32_t addr, uint32_t a, uint32_t b, uint32_t c, uint32_t d) {
  asm volatile("stmatrix.sync.aligned.m8n8.x4.shared.b16 [%0], {%1, %2, %3, %4};" ::"r"(addr), "r"(a), "r"(b), "r"(c), "r"(d) : "memory");
}

__device__ __forceinline__ void tma4d_mc_hint(uint32_t dst, const CUtensorMap* m, uint32_t bar, int c3, uint64_t pol) {
  asm volatile("cp.async.bulk.tensor.4d.shared::cluster.global.mbarrier::complete_tx::bytes.multicast::cluster.L2::cache_hint"
               " [%0], [%1, {%3, %3, %3, %4}], [%2], %5, %6;"
               ::"r"(dst), "l"(m), "r"(bar), "r"(0), "r"(c3), "h"((uint16_t)3), "l"(pol) : "memory");
}
__device__ __forceinline__ void tma5d_mc(uint32_t dst, const CUtensorMap* m, uint32_t bar, int c2, int c4) {
  asm volatile("cp.async.bulk.tensor.5d.shared::cluster.global.mbarrier::complete_tx::bytes.multicast::cluster"
               " [%0], [%1, {%3, %3, %4, %3, %5}], [%2], %6;"
               ::"r"(dst), "l"(m), "r"(bar), "r"(0), "r"(c2), "r"(c4), "h"((uint16_t)3) : "memory");
}
__device__ __forceinline__ void bulk_load_hint(uint32_t dst, const void* src, uint32_t bytes, uint32_t bar, uint64_t pol) {
  asm volatile("cp.async.bulk.shared::cluster.global.mbarrier::complete_tx::bytes.L2::cache_hint [%0], [%1], %2, [%3], %4;"
               ::"r"(dst), "l"(src), "r"(bytes), "r"(bar), "l"(pol) : "memory");
}
__device__ __forceinline__ void stg128_hint(void* p, uint32_t a, uint32_t b, uint32_t c, uint32_t d, uint64_t pol) {
  asm volatile("st.global.L2::cache_hint.v4.b32 [%0], {%1, %2, %3, %4}, %5;" ::"l"(p), "r"(a), "r"(b), "r"(c), "r"(d), "l"(pol) : "memory");
}
__device__ __forceinline__ void stg2_if(bool on, void* p, uint32_t a, uint32_t b, uint32_t c, uint32_t d, uint32_t e, uint32_t f,
                                        uint32_t g, uint32_t h, uint64_t pol) {
  asm volatile("{\n.reg .pred p;\nsetp.ne.b32 p, %10, 0;\n"
               "@p st.global.L2::cache_hint.v4.b32 [%0], {%1, %2, %3, %4}, %9;\n"
               "@p st.global.L2::cache_hint.v4.b32 [%0 + 512], {%5, %6, %7, %8}, %9;\n}\n"
               ::"l"(p), "r"(a), "r"(b), "r"(c), "r"(d), "r"(e), "r"(f), "r"(g), "r"(h), "l"(pol), "r"((int)on) : "memory");
}
__device__ __forceinline__ uint64_t make_policy(bool first) {
  uint64_t pf, pn;
  asm("createpolicy.fractional.L2::evict_first.b64 %0, 1.0;" : "=l"(pf));
  asm("createpolicy.fractional.L2::evict_normal.b64 %0, 1.0;" : "=l"(pn));
  return first ? pf : pn;
}
__device__ __forceinline__ bool elect() {
  uint32_t ok;
  asm volatile("{\n.reg .pred p;\nelect.sync _|p, 0xffffffff;\nselp.u32 %0, 1, 0, p;\n}\n" : "=r"(ok));
  return ok;
}
__device__ __forceinline__ void mbar_arrive(uint32_t bar) {
  asm volatile("mbarrier.arrive.shared::cta.b64 _, [%0];" ::"r"(bar) : "memory");
}
__device__ __forceinline__ void stg128(void* p, uint32_t a, uint32_t b, uint32_t c, uint32_t d) {
  asm volatile("st.global.v4.b32 [%0], {%1, %2, %3, %4};" ::"l"(p), "r"(a), "r"(b), "r"(c), "r"(d) : "memory");
}
__device__ __forceinline__ void lds128(uint32_t p, uint32_t& a, uint32_t& b, uint32_t& c, uint32_t& d) {
  asm volatile("ld.shared.v4.b32 {%0, %1, %2, %3}, [%4];" : "=r"(a), "=r"(b), "=r"(c), "=r"(d) : "r"(p) : "memory");
}
__device__ __forceinline__ void wait_count(const unsigned int* p, uint32_t target) {
  asm volatile("{\n.reg .pred p;\n.reg .u32 n, v;\nmov.u32 n, 0;\n"
               "LOOP:\nld.acquire.gpu.global.u32 v, [%0];\nsetp.ge.u32 p, v, %1;\n@p bra DONE;\n"
               "nanosleep.u32 %2;\nadd.u32 n, n, 1;\nsetp.lt.u32 p, n, 0x400000;\n@p bra LOOP;\ntrap;\n"
               "DONE:\n}\n" ::"l"(p), "r"(target), "n"(200) : "memory");
}

__host__ __device__ __forceinline__ int o_wave(int a, int b, int i, int lag) {
  if (lag == 0) return a + i;
  const int p = lag < b - a - 1 ? lag : b - a - 1;
  return i < p ? b - 2 - i : i == p ? b - 1 : b - 1 - i;
}

struct Cursor {
  int bi;
  uint32_t ph;
  __device__ __forceinline__ void next() {
    if (++bi == NBAR) { bi = 0; ph ^= 1; }
  }
};

constexpr float kScaleLog2 = 0.07216878364870322f * 1.4426950408889634f;
constexpr float kSumLimit = 1048576.0f;
constexpr float kMaxLag = 8.0f;

__global__ void __cluster_dims__(2, 1, 1) __launch_bounds__(384, 1)
fused_kernel(const __grid_constant__ Params P) {
  extern __shared__ uint8_t smem_raw[];
  const uint32_t sbase = (smem_u32(smem_raw) + 1023) & ~1023u;
  const uint32_t full0 = sbase + RING, empty0 = full0 + 8 * NBAR, odone = empty0 + 8 * NBAR, oready0 = odone + 8;
  const uint32_t fenced = oready0 + 64, hready0 = fenced + 8;
  const uint32_t rank = blockIdx.x & 1;
  const int role = blockIdx.x >> 1;
  const bool helper = role >= N_CL;
  const int team = helper ? 0 : role >> 2, nt = role & 3, blk = team >> 3;
  const uint32_t* prog = P.ops[helper ? N_TEAM + 2 * (role - N_CL) : team];
  auto q_role = [&](uint32_t op) { return helper ? (int)(((op >> 3) & 60) | ((op >> 12) & 3)) : role; };
  auto o_role = [&](uint32_t op) { return helper ? (int)(((op >> 26) & 56) | ((op >> 9) & 7)) : role; };
  const int wid = __shfl_sync(0xffffffffu, (int)(threadIdx.x >> 5), 0);
  const int wg = wid >> 2;

  const uint32_t op0 = P.first[helper ? N_TEAM + role - N_CL : team];
  if (__builtin_expect(wid == 8, 1)) {
    if (elect()) {
#pragma unroll
      for (int k = 0; k < EARLY; k++) mbar_init(full0 + 8 * k, 1);
      asm volatile("fence.mbarrier_init.release.cluster;" ::: "memory");
      if ((op0 & 3) == OP_Q) {
        const int qr = q_role(op0);
#pragma unroll
        for (int k = 0; k < EARLY; k++) {
          mbar_expect(full0 + 8 * k, SZ_WQ + SZ_A);
          tma2d(sbase + k * (SZ_WQ + SZ_A) + SZ_WQ, &P.x[qr >> 5], full0 + 8 * k, 64 * k, ((qr >> 2) & 7) * kSq + rank * 128);
          tma3d(sbase + k * (SZ_WQ + SZ_A), &P.wq[qr >> 5], full0 + 8 * k, 0, 64 * k, 3 * (4 * ((op0 >> 2) & 7) + (qr & 3)));
        }
      }
      asm volatile("prefetch.tensormap [%0];" ::"l"(rank ? &P.v[blk] : &P.k[blk]) : "memory");
    }
  } else if (threadIdx.x == 0) {
#pragma unroll
    for (int i = EARLY; i < 2 * NBAR + 10 + MAX_PARK; i++) mbar_init(full0 + 8 * i, i >= NBAR && i <= 2 * NBAR ? 16 : 1);
    asm volatile("fence.mbarrier_init.release.cluster;" ::: "memory");
  }
  __syncwarp();
  asm volatile("barrier.cluster.arrive.relaxed.aligned;\nbarrier.cluster.wait.aligned;" ::: "memory");

  if (wg == 2) {
    asm volatile("setmaxnreg.dec.sync.aligned.u32 24;");
    if (wid == 8) {
      Cursor tail{0, 0};
      int head = 0, sh = 0;
      uint32_t hph = 0;
      uint32_t cur = 0, used = 0;
      uint64_t fifo = 0;
      uint32_t dst, bar, oready = oready0;
      uint64_t pol;
      asm volatile("createpolicy.fractional.L2::evict_first.b64 %0, 1.0;" : "=l"(pol));
      const uint64_t pol_o = make_policy(P.dbg & 1), pol_p = make_policy(!(P.dbg & 4));
      const CUtensorMap* kv_map = rank ? &P.v[blk] : &P.k[blk];
      auto acquire = [&](uint32_t bytes, int part = 0) {
        uint32_t fp = bytes >> 12;
        if (cur + fp > (RING >> 12)) { fp += (RING >> 12) - cur; cur = 0; }
        used += fp;
        bool more = false;
        uint32_t wbar, wph;
        while (used > (RING >> 12) || (part != 2 && sh == 5 * NBAR)) {
          if (more) mbar_wait(wbar, wph);
          more = true;
          wbar = empty0 + 8 * tail.bi; wph = tail.ph;
          tail.next();
          used -= (uint32_t)fifo & 31;
          fifo >>= 5;
          sh -= 5;
        }
        fifo += (uint64_t)fp << sh;
        dst = sbase + (cur << 12);
        bar = full0 + 8 * head;
        cur += bytes >> 12;
        if (part != 1) {
          sh += 5;
          if (++head == NBAR) { head = 0; hph ^= 1; }
        }
        if (more) mbar_wait(wbar, wph);
      };
      auto scratch = [&](const uint4* src, uint32_t bytes, int n) {
        asm volatile("fence.proxy.async.global;" ::: "memory");
#pragma unroll 1
        for (int i = 0; i < n; i++) {
          acquire(bytes);
          if (elect()) {
            bulk_load_hint(dst, src + i * (bytes / 16), bytes, bar, pol_p);
            mbar_expect(bar, bytes);
          }
        }
      };
      for (int pc = 0;; pc++) {
        const uint32_t op = prog[pc];
        const int type = op & 3, a = (op >> 2) & 7;
        if (type == OP_END) break;
        if (type == OP_Q) {
          const int qr = q_role(op);
#pragma unroll 1
          for (int k = 0; k < 10; k++) {
            acquire(SZ_WQ, 1);
            if ((pc > 0 || k >= EARLY) && (k & 1) == rank && elect()) tma3d_mc(dst, &P.wq[qr >> 5], bar, 0, 64 * k, 3 * (4 * a + (qr & 3)));
            acquire(SZ_A, 2);
            if ((pc > 0 || k >= EARLY) && elect()) {
              tma2d(dst, &P.x[qr >> 5], bar, 64 * k, ((qr >> 2) & 7) * kSq + rank * 128);
              mbar_expect(bar, SZ_WQ + SZ_A);
            }
          }
        } else if (type == OP_A) {
          const uint32_t nop = prog[pc + 1];
#pragma unroll 1
          for (int t = (op & F_PARK) ? 1 : 0; t < 33; t++) {
            int wave = a;
            if (t == 31 && (nop & 3) != OP_A) t++;
            if (t == 31) {
              wave = (nop >> 2) & 7;
              mbar_wait((nop & F_HELP) ? hready0 + 8 * ((nop >> 10) & 3) : fenced, 0);
              scratch(&g_o[((team * 2 + rank) * 96 + 3 * (4 * wave + nt)) * 1024], SZ_PARK, 2);
            }
            const int isv = t ? ~t & 1 : 0, j = (isv ? (t - 1) >> 1 : (t + 1) >> 1) & 15;
            const int row0 = ((team & 7) * kH + 4 * wave + nt) * kSk;
            acquire(SZ_KV);
            if (isv == (int)rank && t >= KV_TRANSIT) {
              const int i = head - 1 - KV_TRANSIT;
              mbar_wait(full0 + 8 * (i < 0 ? i + NBAR : i), i < 0 ? hph ^ 1 : hph);
            }
            if (elect()) {
              if (isv == (int)rank) tma4d_mc_hint(dst, kv_map, bar, row0 / 8 + 8 * j, pol);
              mbar_expect(bar, SZ_KV);
            }
          }
        } else {
          const int b = (op >> 5) & 15, ro = o_role(op);
#pragma unroll 1
          for (int i = 0; i < b - a; i++) {
            const int w = o_wave(a, b, i, (P.dbg >> 4) & 7);
            mbar_wait(oready, 0);
            oready += 8;
            asm volatile("fence.proxy.async.global;" ::: "memory");
#pragma unroll 1
            for (int k = 12 * w; k < 12 * w + 12; k++) {
              acquire(SZ_A, 1);
              if (elect()) bulk_load_hint(dst, &g_o[(((ro >> 2) * 2 + rank) * 96 + k - 12 * (w - P.slot[w])) * 1024], SZ_A, bar, pol_o);
              acquire(SZ_WO, 2);
              if (elect()) {
                tma5d_mc(dst + rank * 10240, &P.wo[ro >> 5], bar, 8 * k + 4 * rank, 5 * (ro & 3));
                mbar_expect(bar, SZ_WO + SZ_A);
              }
            }
          }
          if (op & F_LD) {
            if (op & F_PARK) mbar_wait(hready0 + 8 * (MAX_PARK - 1), 0);
            scratch(&g_part[(role * 2 + rank) * 5120], SZ_PART, 5);
          }
        }
      }
    } else if (threadIdx.x == 288) {
      uint32_t ph = 0;
      bool first = true;
      for (int pc = 0;; pc++) {
        const uint32_t op = prog[pc];
        if ((op & 3) == OP_END) break;
        if ((op & 3) != OP_A && !helper) continue;
        mbar_wait_slow<400>(odone, ph);
        ph ^= 1;
        unsigned int* flag = !helper ? &g_done[(team * 2 + rank) * 8 + ((op >> 2) & 7)]
                             : (op & 3) == OP_Q ? &g_help[(q_role(op) * 2 + rank) * MAX_PARK + ((op >> 10) & 3)]
                                                : &g_help[(o_role(op) * 2 + rank) * MAX_PARK + MAX_PARK - 1];
        asm volatile("red.release.gpu.global.add.u32 [%0], 1;" ::"l"(flag) : "memory");
        if (first) mbar_arrive(fenced);
        first = false;
      }
    } else if (threadIdx.x == 320) {
      uint32_t oready = oready0;
      for (int pc = 0;; pc++) {
        const uint32_t op = prog[pc];
        if ((op & 3) == OP_END) break;
        if ((op & 3) == OP_O) {
          const int a = (op >> 2) & 7, b = (op >> 5) & 15;
#pragma unroll 1
          for (int i = 0; i < b - a; i++) {
            const int ci = ((o_role(op) >> 2) * 2 + rank) * 8 + o_wave(a, b, i, (P.dbg >> 4) & 7);
            wait_count(&g_done[ci], 4);
            mbar_arrive(oready);
            oready += 8;
            if (atomicAdd(&g_seen[ci], 1u) == 3u) { g_seen[ci] = 0; g_done[ci] = 0; }
          }
        }
        if ((op & 3) != OP_Q && (op & F_HELP) && (op & F_PARK)) {
          unsigned int* flag = &g_help[(role * 2 + rank) * MAX_PARK + ((op >> 10) & 3)];
          wait_count(flag, 1);
          mbar_arrive(hready0 + 8 * ((op >> 10) & 3));
          *flag = 0;
        }
      }
    }
    __syncwarp();
    asm volatile("barrier.cluster.arrive.relaxed;\nbarrier.cluster.wait;" ::: "memory");
  } else {
    asm volatile("setmaxnreg.inc.sync.aligned.u32 240;");
    const int lane = threadIdx.x & 31, warp = wid & 3;
    uint32_t empty_rem;
    asm volatile("mapa.shared::cluster.u32 %0, %1, %2;" : "=r"(empty_rem) : "r"(empty0), "r"(lane & 1));
    auto release = [&](int slot) { mbar_arrive_cluster_if(lane < 2, empty_rem + 8 * slot); };
    Cursor r{0, 0};
    const uint32_t ring16 = (sbase & 0x3FFFF) >> 4;
    uint32_t cur = ring16;
    bool rdy0 = false, rdy1 = false;
    auto probe1 = [&]() { rdy0 = mbar_test(full0 + 8 * r.bi, r.ph); };
    auto probe2 = [&]() {
      Cursor n = r;
      rdy0 = mbar_test(full0 + 8 * n.bi, n.ph);
      n.next();
      rdy1 = mbar_test(full0 + 8 * n.bi, n.ph);
    };
    auto take = [&](bool rdy, uint32_t bytes, uint32_t& addr) {
      const int bi = r.bi;
      if (!__all_sync(0xffffffffu, rdy)) mbar_wait(full0 + 8 * r.bi, r.ph);
      r.next();
      if (cur > ring16 + ((RING - bytes) >> 4)) cur = ring16;
      addr = cur;
      cur += bytes >> 4;
      return bi;
    };
    auto second = [&](uint32_t bytes) {
      if (cur > ring16 + ((RING - bytes) >> 4)) cur = ring16;
      cur += bytes >> 4;
      return cur - (bytes >> 4);
    };
    const int row = wg * 64 + warp * 16 + (lane >> 2);
    int img0 = row * 4 + ((lane & 3) ^ ((row >> 1) & 3));
    uint4* pend = nullptr;
    uint64_t spol;
    int pc = 0;
    uint32_t op = prog[0];
    auto enter = [&]() {
      r.bi = (op >> 15) & 15; r.ph = (op >> 19) & 1; cur = ring16 + (((op >> 20) & 63) << 8);
      spol = make_policy(!(op & F_SOON));
    };
    auto drain = [&](uint32_t (&t)[48], uint32_t c) {
      if (!(op & (3u << 26)) || c >= 6) return;
#pragma unroll
      for (int i = 0; i < 6; i++)
        stg2_if(c == i, pend + i * 512, t[8 * i], t[8 * i + 1], t[8 * i + 2], t[8 * i + 3],
                t[8 * i + 4], t[8 * i + 5], t[8 * i + 6], t[8 * i + 7], spol);
      if ((op & (1u << 26)) && c == 5) {
        __syncwarp();
        mbar_arrive_if(lane < 2, odone);
      }
    };
    float s[32], o[96], c[80];
    uint32_t q[48], pa[16], pb[16];
    float mc0, mc1, l0, l1;
    bool gen;
    auto soft = [&](float (&s)[32], uint32_t (&pout)[16], bool first) {
      if (first) { gen = false; mc0 = 0.f; mc1 = 0.f; }
      float b0, b1;
      for (;;) {
        if (gen) {
          float m0 = fmaxf(s[0], s[1]), m1 = fmaxf(s[2], s[3]);
#pragma unroll
          for (int i = 1; i < 8; i++) { m0 = fmaxf(m0, fmaxf(s[4 * i], s[4 * i + 1])); m1 = fmaxf(m1, fmaxf(s[4 * i + 2], s[4 * i + 3])); }
          m0 = fmaxf(m0, __shfl_xor_sync(0xffffffffu, m0, 1)); m1 = fmaxf(m1, __shfl_xor_sync(0xffffffffu, m1, 1));
          m0 = fmaxf(m0, __shfl_xor_sync(0xffffffffu, m0, 2)); m1 = fmaxf(m1, __shfl_xor_sync(0xffffffffu, m1, 2));
          if (first) {
            mc0 = m0; mc1 = m1;
          } else if (__any_sync(0xffffffffu, !(m0 <= mc0 + kMaxLag && m1 <= mc1 + kMaxLag))) {
            m0 = fmaxf(mc0, m0); m1 = fmaxf(mc1, m1);
            const float a0 = ex2(mc0 - m0), a1 = ex2(mc1 - m1);
            mc0 = m0; mc1 = m1;
            l0 *= a0; l1 *= a1;
            wg_wait<0>();
            fence_regs(o);
#pragma unroll
            for (int i = 0; i < 96; i++) o[i] *= i & 2 ? a1 : a0;
          }
#pragma unroll
          for (int i = 0; i < 32; i++) s[i] -= i & 2 ? mc1 : mc0;
        }
#pragma unroll
        for (int i = 0; i < 8; i++) {
          const float e1 = ex2(s[4 * i + 1]), e0 = ex2(s[4 * i]), e3 = ex2(s[4 * i + 3]), e2 = ex2(s[4 * i + 2]);
          pout[2 * i] = pack_bf16(e0, e1);
          b0 = i ? b0 + fadd(e1, e0) : fadd(e1, e0);
          pout[2 * i + 1] = pack_bf16(e2, e3);
          b1 = i ? b1 + fadd(e3, e2) : fadd(e3, e2);
        }
        if (!__any_sync(0xffffffffu, !gen && !(fmaxf(b0, b1) <= kSumLimit && (!first || fminf(b0, b1) >= 1.0f / kSumLimit)))) break;
        gen = __any_sync(0xffffffffu, true);
      }
      l0 = first ? b0 : l0 + b0;
      l1 = first ? b1 : l1 + b1;
    };
    auto qk = [&](float (&s)[32], uint32_t ak, int k0, int k1) {
#pragma unroll
      for (int kk = k0; kk < k1; kk++)
        wgmma_rs_n64<0>(s, q[4 * kk], q[4 * kk + 1], q[4 * kk + 2], q[4 * kk + 3], mk_desc(ak + (kk >> 2) * KV_CH + (kk & 3) * 2, 16, KV_SBO, 1), kk != 0);
      wg_commit();
    };
    auto pv = [&](uint32_t (&pin)[16], uint32_t av, int acc) {
#pragma unroll
      for (int kk = 0; kk < 4; kk++)
        wgmma_rs_n192<1>(o, pin[4 * kk], pin[4 * kk + 1], pin[4 * kk + 2], pin[4 * kk + 3], mk_desc(av + kk * (KV_SBO / 8), KV_CH * 16, KV_SBO, 1), acc || (kk != 0));
      wg_commit();
    };
    auto xw = [&](uint32_t ad, int acc) {
      const uint32_t da = second(SZ_A) + wg * 512;
      wg_fence();
#pragma unroll
      for (int kk = 0; kk < 4; kk++)
        wgmma_ss_n192<1>(o, mk_desc(da + kk * 2, 16, 1024, 1), mk_desc(ad + kk * 128, 8192, 1024, 1), acc || kk != 0);
      wg_commit();
    };
    auto ow = [&](int acc, int prev) {
      uint32_t da;
      const int bi = take(rdy0, SZ_A, da);
      const uint32_t db = second(SZ_WO);
      da += wg * 256;
      wg_fence();
      wgmma_ss_n160<1>(c, mk_desc(da, 16, 512, 2), mk_desc(db, 2048, 512, 2), acc);
      wgmma_ss_n160<1>(c, mk_desc(da + 2, 16, 512, 2), mk_desc(db + 64, 2048, 512, 2), 1);
      wg_commit();
      if (acc) { wg_wait<1>(); release(prev); }
      wgmma_ss_n160<1>(c, mk_desc(da + 512, 16, 512, 2), mk_desc(db + 640, 2048, 512, 2), 1);
      wgmma_ss_n160<1>(c, mk_desc(da + 514, 16, 512, 2), mk_desc(db + 704, 2048, 512, 2), 1);
      wg_commit();
      return bi;
    };
    auto st_part = [&](int i) {
      stg2_if(true, pend + i * 512, __float_as_uint(c[8 * i]), __float_as_uint(c[8 * i + 1]), __float_as_uint(c[8 * i + 2]), __float_as_uint(c[8 * i + 3]),
              __float_as_uint(c[8 * i + 4]), __float_as_uint(c[8 * i + 5]), __float_as_uint(c[8 * i + 6]), __float_as_uint(c[8 * i + 7]), spol);
    };
#pragma unroll
    for (int i = 0; i < 48; i++) q[i] = 0;
    enter();

    if ((op & 3) == OP_Q) {
      uint32_t ad;
      int bi0 = take(false, SZ_WQ, ad), k = 0, lag = 0;
      xw(ad, 0);
      for (;;) {
#pragma unroll 1
        for (;;) {
          drain(q, k - lag);
          probe1();
          wg_wait<0>();
          release(bi0);
          bi0 = take(rdy0, SZ_WQ, ad);
          if (++k == 8) break;
          xw(ad, 1);
        }
        if (wg) bar_sync(2, 256);
        xw(ad, 1);
        const int bi9 = take(false, SZ_WQ, ad);
        xw(ad, 1);
        if (!wg) asm volatile("bar.arrive 2, 256;" ::: "memory");
        k = 0; lag = 0;
        uint32_t nop = prog[++pc];
        wg_wait<1>();
        release(bi0);
        probe2();
        wg_wait<0>();
        fence_regs(o);
        release(bi9);
#pragma unroll
        for (int i = 0; i < 48; i++) q[i] = pack_bf16(o[2 * i] * kScaleLog2, o[2 * i + 1] * kScaleLog2);
        fence_regs(q);
        if (op & F_PARK) {
          pend = &g_o[(((q_role(op) >> 2) * 2 + rank) * 96 + 3 * (4 * ((op >> 2) & 7) + (q_role(op) & 3))) * 1024 + img0];
          op = nop;
          enter();
          if ((op & 3) != OP_Q) break;
          bi0 = take(rdy0, SZ_WQ, ad);
          xw(ad, 0);
          continue;
        }
        int wave = (op >> 2) & 7, sk1;
        uint32_t ak1;
        {
          float s0[32];
          const int sk0 = take(rdy0, SZ_KV, ad);
          wg_fence();
          qk(s0, ad, 0, 12);
          sk1 = take(rdy1, SZ_KV, ak1);
          wg_fence();
          qk(s, ak1, 0, S1A);
          probe1();
          wg_wait<1>();
          fence_regs(s0);
          release(sk0);
          soft(s0, pa, true);
        }
        float i0, i1;
        auto sums = [&]() {
          l0 += __shfl_xor_sync(0xffffffffu, l0, 1); l1 += __shfl_xor_sync(0xffffffffu, l1, 1);
          l0 += __shfl_xor_sync(0xffffffffu, l0, 2); l1 += __shfl_xor_sync(0xffffffffu, l1, 2);
          i0 = rcp(l0); i1 = rcp(l1);
          asm volatile("" : "+f"(i0), "+f"(i1));
        };
        auto target = [&]() {
          pend = &g_o[((team * 2 + rank) * 96 + 3 * (4 * P.slot[wave] + nt)) * 1024 + img0];
          asm volatile("" : "+l"(pend));
        };
        for (;;) {
          nop = prog[++pc];
          {
            uint32_t av;
            const int sv = take(rdy0, SZ_KV, av);
            wg_fence();
            qk(s, ak1, S1A, 12);
            pv(pa, av, 0);
            probe2();
            wg_wait<1>();
            fence_regs(s);
            release(sk1);
            soft(s, pb, false);
            wg_wait<0>();
            fence_regs(o);
            release(sv);
          }
          auto step = [&](uint32_t (&pin)[16], uint32_t (&pout)[16]) {
            uint32_t ak, av;
            const int sk = take(rdy0, SZ_KV, ak), sv = take(rdy1, SZ_KV, av);
            wg_fence();
            qk(s, ak, 0, 12);
            pv(pin, av, 1);
            probe2();
            wg_wait<1>();
            fence_regs(s);
            release(sk);
            soft(s, pout, false);
            wg_wait<0>();
            fence_regs(o);
            release(sv);
          };
#pragma unroll 1
          for (int jj = 0; jj < 7; jj++) {
            step(pb, pa);
            step(pa, pb);
          }
          if ((nop & 3) != OP_A) break;
          uint32_t ak, av;
          {
            const int b0 = take(rdy0, SZ_PARK, ak), b1 = take(rdy1, SZ_PARK, av);
            const uint32_t ad0 = ak, ad1 = av;
            probe2();
#pragma unroll
            for (int i = 0; i < 12; i++)
              lds128(sbase + ((i < 6 ? ad0 : ad1) - ring16 + img0) * 16 + ((i % 6) >> 1) * 8192 + (i & 1) * 512, q[4 * i], q[4 * i + 1], q[4 * i + 2], q[4 * i + 3]);
            release(b0); release(b1);
          }
          const int sk0 = take(rdy0, SZ_KV, ak), sv = take(rdy1, SZ_KV, av);
          wg_fence();
          qk(s, ak, 0, 8);
          sched_fence(img0, P.zero);
          sums();
          sched_fence(img0, P.zero);
          qk(s, ak, 8, 12);
          pv(pb, av, 1);
          probe2();
          spol = make_policy(!(nop & F_SOON));
          wg_wait<1>();
          fence_regs(s);
          release(sk0);
          soft(s, pa, true);
          sk1 = take(rdy0, SZ_KV, ak1);
          rdy0 = rdy1;
          wg_wait<0>();
          target();
          fence_regs(o);
          release(sv);
          uint32_t t[48];
#pragma unroll
          for (int j = 0; j < 6; j++) {
#pragma unroll
            for (int i = 0; i < 4; i++) {
              t[8 * j + i] = pack_bf16(o[16 * j + 4 * i] * i0, o[16 * j + 4 * i + 1] * i0);
              t[8 * j + i + 4] = pack_bf16(o[16 * j + 4 * i + 2] * i1, o[16 * j + 4 * i + 3] * i1);
            }
            stg2_if(true, pend + j * 512, t[8 * j], t[8 * j + 1], t[8 * j + 2], t[8 * j + 3], t[8 * j + 4], t[8 * j + 5], t[8 * j + 6], t[8 * j + 7], spol);
            if (j == UC0) { wg_fence(); qk(s, ak1, 0, 4); }
            if (j == UC1) { wg_fence(); qk(s, ak1, 4, S1A); }
            sched_fence(img0, P.zero);
          }
          if (P.zero) {
#pragma unroll
            for (int j = 0; j < 5; j++)
              stg2_if(true, pend, t[8 * j], t[8 * j + 1], t[8 * j + 2], t[8 * j + 3], t[8 * j + 4], t[8 * j + 5], t[8 * j + 6], t[8 * j + 7], spol);
          }
          __syncwarp();
          mbar_arrive_if(lane < 2, odone);
          wave = (nop >> 2) & 7;
        }
        const int sv = take(rdy0, SZ_KV, ad);
        wg_fence();
        pv(pb, ad, 1);
        sums();
        target();
        op = nop;
        enter();
        rdy0 = rdy1;
        auto convert = [&](uint32_t (&t)[48], float (&u)[96]) {
#pragma unroll
          for (int i = 0; i < 24; i++) {
            t[8 * (i >> 2) + (i & 3)] = pack_bf16(u[4 * i], u[4 * i + 1]);
            t[8 * (i >> 2) + (i & 3) + 4] = pack_bf16(u[4 * i + 2], u[4 * i + 3]);
          }
        };
        if ((op & 3) != OP_O) {
          if ((op & 3) == OP_Q) bi0 = take(rdy0, SZ_WQ, ad);
          wg_wait<0>();
          fence_regs(o);
          release(sv);
          float u[96];
#pragma unroll
          for (int i = 0; i < 96; i++) u[i] = o[i] * (i & 2 ? i1 : i0);
          if ((op & 3) != OP_Q) { convert(q, u); break; }
          fence_regs(u);
          xw(ad, 0);
          sched_fence(img0, P.zero);
          fence_regs(u);
          convert(q, u);
          continue;
        }
        int bi = ow(0, 0);
        wg_wait<2>();
        fence_regs(o);
        release(sv);
#pragma unroll
        for (int j = 0; j < 6; j++) {
          uint32_t t[8];
#pragma unroll
          for (int i = 0; i < 4; i++) {
            t[i] = pack_bf16(o[16 * j + 4 * i] * i0, o[16 * j + 4 * i + 1] * i0);
            t[i + 4] = pack_bf16(o[16 * j + 4 * i + 2] * i1, o[16 * j + 4 * i + 3] * i1);
          }
          stg2_if(true, pend + j * 512, t[0], t[1], t[2], t[3], t[4], t[5], t[6], t[7], spol);
          if (j == 5) {
            __syncwarp();
            mbar_arrive_if(lane < 2, odone);
          }
          probe1();
          wg_wait<1>();
          bi = ow(1, bi);
          fence_regs(o);
        }
        {
          const int nk = 12 * (((op >> 5) & 15) - ((op >> 2) & 7));
#pragma unroll 1
          for (int k = 7; k < nk; k++) {
            probe1();
            wg_wait<1>();
            bi = ow(1, bi);
          }
          probe1();
        }
        nop = prog[++pc];
        if (op & F_LD) {
          uint32_t t[80];
#pragma unroll
          for (int j = 0; j < 5; j++) {
            const int b = take(rdy0, SZ_PART, ad);
            probe1();
#pragma unroll
            for (int i = 4 * j; i < 4 * j + 4; i++)
              lds128(sbase + (ad - ring16 + img0) * 16 + ((i >> 1) & 1) * 8192 + (i & 1) * 512, t[4 * i], t[4 * i + 1], t[4 * i + 2], t[4 * i + 3]);
            release(b);
          }
          wg_wait<0>();
          fence_regs(c);
#pragma unroll
          for (int i = 0; i < 80; i++) c[i] += __uint_as_float(t[i]);
        }
        if (!(op & F_ST)) {
          wg_wait<0>();
          fence_regs(c);
          goto finish;
        }
        op = nop;
        enter();
        bi0 = take(rdy0, SZ_WQ, ad);
        xw(ad, 0);
        pend = &g_part[(role * 2 + rank) * 5120 + img0];
        probe1();
        wg_wait<1>();
        fence_regs(c);
        release(bi);
        st_part(0); st_part(1);
        wg_wait<0>();
        release(bi0);
        bi0 = take(rdy0, SZ_WQ, ad);
        xw(ad, 1);
        st_part(2); st_part(3);
#pragma unroll
        for (int i = 0; i < 48; i++) q[i] = __float_as_uint(c[32 + i]);
        pend += 4 * 512;
        k = 1; lag = 2;
      }
    }
    rdy0 = false;
    {
      uint32_t t[48];
#pragma unroll
      for (int i = 0; i < 48; i++) t[i] = q[i] ^ P.zero;
      while ((op & 3) == OP_O) {
        int bi = ow(0, 0);
#pragma unroll 1
        for (int k = 1; k < 12 * (int)(((op >> 5) & 15) - ((op >> 2) & 7)); k++) {
          drain(t, k - 1);
          probe1();
          wg_wait<1>();
          bi = ow(1, bi);
        }
        rdy0 = false;
        wg_wait<0>();
        fence_regs(c);
        pc++;
        if (!(op & F_ST)) goto finish;
        release(bi);
        pend = &g_part[(o_role(op) * 2 + rank) * 5120 + img0];
#pragma unroll
        for (int i = 6; i < 10; i++) st_part(i);
#pragma unroll
        for (int i = 0; i < 48; i++) t[i] = __float_as_uint(c[i]) ^ P.zero;
        op = prog[pc];
        enter();
      }
      for (int i = 0; i < 6; i++) drain(t, i);
    }
    asm volatile("barrier.cluster.arrive.relaxed;" ::: "memory");
    if (false) {
    finish:
      asm volatile("barrier.cluster.arrive.relaxed;" ::: "memory");
      bar_sync(1, 256);
      const uint32_t wstage = sbase + (wg * 4 + warp) * 5120;
      const uint32_t sa = wstage + (lane & 15) * 64;
#pragma unroll
      for (int i = 0; i < 10; i++) {
        const int u = (i & 1) * 2 + (lane >> 4);
        stsm4(sa + (i >> 1) * 1024 + ((u ^ ((lane >> 1) & 3)) << 4), pack_bf16(c[8 * i], c[8 * i + 1]), pack_bf16(c[8 * i + 2], c[8 * i + 3]),
              pack_bf16(c[8 * i + 4], c[8 * i + 5]), pack_bf16(c[8 * i + 6], c[8 * i + 7]));
      }
      asm volatile("fence.proxy.async.shared::cta;" ::: "memory");
      __syncwarp();
      if (lane == 0) {
        tma3d_store(&P.out, wstage, 0, (team & 7) * kSq + rank * 128 + wg * 64 + warp * 16, blk * 20 + nt * 5);
        asm volatile("cp.async.bulk.commit_group;\ncp.async.bulk.wait_group.read 0;" ::: "memory");
      }
      __syncwarp();
    }
    asm volatile("barrier.cluster.wait;" ::: "memory");
  }
}

typedef CUresult (*EncodeFn)(CUtensorMap*, CUtensorMapDataType, cuuint32_t, void*, const cuuint64_t*, const cuuint64_t*,
                             const cuuint32_t*, const cuuint32_t*, CUtensorMapInterleave, CUtensorMapSwizzle,
                             CUtensorMapL2promotion, CUtensorMapFloatOOBfill);

void encode(EncodeFn fn, CUtensorMap* m, const void* ptr, int rank, const cuuint64_t* dims, const cuuint64_t* strides,
            const cuuint32_t* box, CUtensorMapSwizzle swz) {
  const cuuint32_t es[5] = {1, 1, 1, 1, 1};
  CUresult r = fn(m, CU_TENSOR_MAP_DATA_TYPE_BFLOAT16, rank, const_cast<void*>(ptr), dims, strides, box, es,
                  CU_TENSOR_MAP_INTERLEAVE_NONE, swz, CU_TENSOR_MAP_L2_PROMOTION_L2_128B, CU_TENSOR_MAP_FLOAT_OOB_FILL_NONE);
  if (r != CUDA_SUCCESS) fprintf(stderr, "cuTensorMapEncodeTiled failed: %d\n", (int)r);
}

void annotate(uint32_t* ops, int n, bool helper) {
  uint32_t items = 0, cur = 0, pend = 0;
  auto item = [&](uint32_t bytes, int count, uint32_t bytes2 = 0) {
    for (int i = 0; i < count; i++) {
      if (cur + bytes > RING) cur = 0;
      cur += bytes;
      if (cur + bytes2 > RING) cur = 0;
      cur += bytes2;
      items++;
    }
  };
  for (int i = 0; i <= n; i++) {
    const uint32_t op = ops[i];
    ops[i] |= (items % NBAR) << 15 | ((items / NBAR) & 1) << 19 | (cur >> 12) << 20 | pend << 26;
    if ((op & 3) == OP_Q) { item(SZ_WQ, 10, SZ_A); pend = (op & F_PARK) ? (helper ? 1 : 2) : 0; }
    if ((op & 3) == OP_A) {
      item(SZ_KV, (op & F_PARK) ? 30 : 31);
      if ((ops[i + 1] & 3) == OP_A) { item(SZ_PARK, 2); item(SZ_KV, 1); }
      item(SZ_KV, 1);
      pend = 1;
    }
    if ((op & 3) == OP_O) {
      item(SZ_A, 12 * (((op >> 5) & 15) - ((op >> 2) & 7)), SZ_WO);
      if (op & F_LD) item(SZ_PART, 5);
      pend = (op & F_LAZY) ? (helper ? 1 : 2) : 0;
    }
  }
}

void compile_programs(const char* const* text, bool helpers, Params& P) {
  struct Req { int when, team, wave, slot; } req[N_TEAM * MAX_PARK];
  int n_req = 0;
  for (int t = 0; t < N_TEAM; t++) {
    uint32_t* ops = P.ops[t];
    int n = 0, flags[8] = {0, 0, 0, 0, 0, 0, 0, 0}, n_park = 0, last_o = -1, when = 0, given = 0;
    for (const char* s = text[t]; *s; s++) {
      const int a = s[1] - '0';
      if (*s == 'Q' || (*s == 'H' && !helpers)) { ops[n++] = OP_Q | a << 2; when += 10; }
      else if (*s == 'P') { flags[a] = F_PARK | n_park++ << 10; ops[n++] = OP_Q | a << 2 | flags[a]; when += 10; }
      else if (*s == 'H') { req[n_req++] = {when, t, a, n_park}; flags[a] = F_PARK | F_HELP | n_park++ << 10; }
      else if (*s == 'A') { ops[n++] = OP_A | a << 2 | flags[a]; when += 32; }
      else if (*s == 'G') { given = a; if (helpers) req[n_req++] = {1000, t, 0, -a}; }
      else if (*s == 'O') {
        ops[n] = OP_O | a << 2 | (s[2] - '0') << 5;
        if (given) ops[n] = helpers ? ops[n] | F_LD | F_PARK | (MAX_PARK - 1) << 10 : ops[n] & ~(7u << 2);
        if (last_o >= 0) { ops[last_o] |= F_ST; ops[n] |= F_LD; }
        last_o = n++;
        when += 10 * (s[2] - s[1]);
      }
    }
    for (int i = 0; i + 1 < n; i++)
      if ((ops[i] & 3) == OP_O && (ops[i] & F_ST) && (ops[i + 1] & 3) == OP_Q) ops[i] |= F_LAZY;
    for (int i = n; i < MAX_OPS; i++) ops[i] = OP_END;
    annotate(ops, n, false);
    for (int i = 0; i < n; i++) {
      if ((ops[i] & 3) != OP_A && (P.dbg & 8)) ops[i + 1] |= F_SOON;
      if ((ops[i] & 3) != OP_A) continue;
      const int w = (ops[i] >> 2) & 7;
      int dist = 0;
      for (int j = i + 1; j < n; j++) {
        const int a = (ops[j] >> 2) & 7, b = (ops[j] >> 5) & 15;
        if ((ops[j] & 3) == OP_O && w < b) {
          for (int k = 0; k < b - a && o_wave(a, b, k, (P.dbg >> 4) & 7) != w; k++) dist += 10;
          break;
        }
        dist += (ops[j] & 3) == OP_Q ? 10 : (ops[j] & 3) == OP_A ? 32 : 10 * (b - a);
      }
      if (dist <= (int)((P.dbg >> 8) & 255)) ops[i + 1] |= F_SOON;
    }
  }
  for (int i = 1; i < n_req; i++)
    for (int j = i; j > 0 && req[j].when < req[j - 1].when; j--) { Req r = req[j]; req[j] = req[j - 1]; req[j - 1] = r; }
  for (int h = 0; h < N_HELP; h++) {
    uint32_t* ops = P.ops[N_TEAM + 2 * h];
    int n = 0;
    for (int i = 0; i < n_req; i++)
      for (int m = h; m < 4; m += N_HELP) {
        const uint32_t ro = 4 * req[i].team + m;
        ops[n++] = req[i].slot >= 0 ? OP_Q | req[i].wave << 2 | req[i].team << 5 | F_PARK | req[i].slot << 10 | m << 12
                                    : OP_O | -req[i].slot << 5 | F_ST | F_LAZY | F_SOON | (ro & 7) << 9 | (ro >> 3) << 29;
      }
    for (int i = n; i < 2 * MAX_OPS; i++) ops[i] = OP_END | F_SOON;
    annotate(ops, n, true);
  }
  for (int i = 0; i < 32; i++) P.first[i] = i < N_TEAM ? P.ops[i][0] : i < N_TEAM + N_HELP ? P.ops[2 * i - N_TEAM][0] : 0;
}

const char* const kPrograms[N_TEAM] = {
  "Q0A0Q1A1H2A2O03Q3A3Q4A4Q5A5Q6A6Q7A7O38",
  "Q0A0Q1A1Q2A2H3A3Q4A4O03Q5A5Q6A6Q7A7O38",
  "Q0A0H1A1Q2A2Q3A3O04Q4A4Q5A5Q6A6Q7A7O48",
  "Q0A0Q1A1Q2A2Q3A3O02Q4A4Q5A5Q6A6H7A7O28",
  "Q0A0Q1A1Q2A2O03Q3A3Q4A4Q5A5Q6A6H7A7O38",
  "Q0A0Q1A1Q2A2Q3A3Q4A4O05Q5A5Q6A6H7A7O58",
  "Q0A0Q1A1Q2A2Q3A3Q4A4O05Q5A5Q6A6H7A7O58",
  "Q0A0Q1A1Q2A2O03Q3A3Q4A4H5A5Q6A6Q7A7O38",
  "P7Q0A0Q1A1O01Q2A2H3A3Q4A4Q5A5Q6A6A7O18",
  "P3P5Q0A0Q1A1Q2A2A3Q4A4A5H6A6Q7A7O08",
  "P7Q0A0Q1A1Q2A2Q3A3H4A4Q5A5Q6A6A7O08",
  "P3P7Q0A0Q1A1H2A2A3Q4A4Q5A5Q6A6A7O08",
  "Q0A0Q1A1Q2A2O01Q3A3Q4A4H5A5Q6A6Q7A7O18",
  "P3Q0A0Q1A1Q2A2A3Q4A4Q5A5Q6A6Q7A7G1O18",
  "P6Q0A0Q1A1Q2A2Q3A3Q4A4Q5A5A6Q7A7G1O18",
  "P2P6Q0A0Q1A1A2Q3A3H4A4Q5A5A6Q7A7O08",
};

const char* const* bench_programs() {
  return kPrograms;
}

}

extern "C" void kernel_launch(void* const* d_in, const int* in_sizes, int n_in, void* d_out, int out_size) {
  (void)in_sizes; (void)n_in; (void)out_size;
  static EncodeFn fn = nullptr;
  static int n_clusters = 0;
  if (!fn) {
    cudaDriverEntryPointQueryResult qr;
    void* f = nullptr;
    cudaGetDriverEntryPoint("cuTensorMapEncodeTiled", &f, cudaEnableDefault, &qr);
    fn = (EncodeFn)f;
    cudaFuncSetAttribute(fused_kernel, cudaFuncAttributeMaxDynamicSharedMemorySize, SMEM_BYTES);
    cudaLaunchConfig_t cfg = {};
    cfg.gridDim = dim3(132); cfg.blockDim = dim3(384); cfg.dynamicSmemBytes = SMEM_BYTES;
    cudaLaunchAttribute at[1];
    at[0].id = cudaLaunchAttributeClusterDimension; at[0].val.clusterDim.x = 2; at[0].val.clusterDim.y = 1; at[0].val.clusterDim.z = 1;
    cfg.attrs = at; cfg.numAttrs = 1;
    if (cudaOccupancyMaxActiveClusters(&n_clusters, fused_kernel, &cfg) != cudaSuccess || n_clusters < 1) n_clusters = 1;
    (void)cudaGetLastError();
  }
  Params P;
  const CUtensorMapSwizzle S128 = CU_TENSOR_MAP_SWIZZLE_128B, S64 = CU_TENSOR_MAP_SWIZZLE_64B;
  for (int blk = 0; blk < 2; blk++) {
    void* const* in = d_in + 5 * blk;
    { const cuuint64_t d[] = {kD, kB * kSq}, s[] = {kD * 2}; const cuuint32_t b[] = {64, 128};
      encode(fn, &P.x[blk], in[0], 2, d, s, b, S128); }
    { const cuuint64_t d[] = {64, 8, 3, (cuuint64_t)kB * kH * kSk / 8}, s[] = {kDh * 2, 128, 8 * kDh * 2}; const cuuint32_t b[] = {64, 8, 3, 8};
      encode(fn, &P.k[blk], in[1], 4, d, s, b, S128);
      encode(fn, &P.v[blk], in[2], 4, d, s, b, S128); }
    { const cuuint64_t d[] = {64, kD, kHD / 64}, s[] = {kHD * 2, 128}; const cuuint32_t b[] = {64, 64, 3};
      encode(fn, &P.wq[blk], in[3], 3, d, s, b, S128); }
    { const cuuint64_t d[] = {32, 2, kHD / 8, 4, kD / 32}, s[] = {kD * 2, 8 * kD * 2, 2 * kD * 2, 64}; const cuuint32_t b[] = {32, 2, 4, 4, 5};
      encode(fn, &P.wo[blk], in[4], 5, d, s, b, S64); }
  }
  { const cuuint64_t d[] = {32, kB * kSq, 2 * kD / 32}, s[] = {2 * kD * 2, 64}; const cuuint32_t b[] = {32, 16, 5};
    encode(fn, &P.out, d_out, 3, d, s, b, S64); }

  P.zero = 0;
  P.dbg = 0x5030;
  for (int w = 0; w < 8; w++) P.slot[w] = (P.dbg >> 16) & 15 ? w % ((P.dbg >> 16) & 15) : w;
  if (n_clusters >= N_CL) {
    const bool helpers = n_clusters >= N_CL + N_HELP;
    compile_programs(bench_programs(), helpers, P);
    fused_kernel<<<2 * (N_CL + (helpers ? N_HELP : 0)), 384, SMEM_BYTES>>>(P);
  } else {
    for (int phase = 0; phase < 2; phase++) {
      const char* text[N_TEAM];
      for (int t = 0; t < N_TEAM; t++) text[t] = phase ? "O08" : "Q0A0Q1A1Q2A2Q3A3Q4A4Q5A5Q6A6Q7A7";
      compile_programs(text, false, P);
      fused_kernel<<<2 * N_CL, 384, SMEM_BYTES>>>(P);
    }
  }
}
```

```cpp
#include <cuda_runtime.h>
#include <cuda_bf16.h>
#include <cuda.h>
#include <stdint.h>
#include <stdio.h>

namespace {

constexpr int kB = 8, kSq = 256, kD = 640, kH = 32, kSk = 1024, kDh = 192;
constexpr int kHD = kH * kDh;
#define S1A 7
#define UC0 3
#define UC1 4
#define AQS 2
#define RING_KB 224
constexpr uint32_t RING = RING_KB * 1024;
constexpr uint32_t SZ_KV = 24576;
constexpr uint32_t SZ_WQ = 24576, SZ_WO = 20480, SZ_A = 16384;
constexpr uint32_t SZ_PARK = 24576;
constexpr uint32_t SZ_PART = 16384;
constexpr int NBAR = 10;
#define KVT 4
constexpr int KV_TRANSIT = KVT;
#define EARLY_N 3
constexpr int EARLY = EARLY_N;
constexpr uint32_t KV_CH = 64, KV_SBO = 3072;
constexpr int SMEM_BYTES = RING + 512 + 1024;
constexpr int N_TEAM = 16, N_CL = 64, N_HELP = 2, MAX_OPS = 24, MAX_PARK = 4;
enum { OP_END = 0, OP_Q = 1, OP_A = 2, OP_O = 3, F_PARK = 1 << 9, F_LD = 1 << 12, F_ST = 1 << 13, F_LAZY = 1 << 14, F_HELP = 1 << 12, F_SOON = 1 << 28 };

struct alignas(64) Params {
  uint32_t first[32];
  CUtensorMap x[2], wq[2], k[2], v[2], wo[2], out;
  uint32_t ops[N_TEAM + 2 * N_HELP][MAX_OPS];
  uint32_t zero;
  uint32_t slot[8];
  uint32_t dbg;
};

__device__ uint4 g_o[N_TEAM * 2 * 96 * 1024];
__device__ uint4 g_part[N_CL * 2 * 5 * 1024];
__device__ unsigned int g_done[N_TEAM * 2 * 8];
__device__ unsigned int g_help[N_CL * 2 * MAX_PARK];
__device__ unsigned int g_seen[N_TEAM * 2 * 8];

template <int TB, int TA = 0>
__device__ __forceinline__ void wgmma_ss_n64(float (&d)[32], uint64_t da, uint64_t db, int scale_d) {
  asm volatile("{\n.reg .pred p;\nsetp.ne.b32 p, %34, 0;\n"
    "wgmma.mma_async.sync.aligned.m64n64k16.f32.bf16.bf16 {%0, %1, %2, %3, %4, %5, %6, %7, %8, %9, %10, %11, %12, %13, %14, %15, %16, %17, %18, %19, %20, %21, %22, %23, %24, %25, %26, %27, %28, %29, %30, %31}, %32, %33, p, 1, 1, %35, %36;\n}\n"
    : "+f"(d[0]), "+f"(d[1]), "+f"(d[2]), "+f"(d[3]), "+f"(d[4]), "+f"(d[5]), "+f"(d[6]), "+f"(d[7]), "+f"(d[8]), "+f"(d[9]), "+f"(d[10]), "+f"(d[11]), "+f"(d[12]), "+f"(d[13]), "+f"(d[14]), "+f"(d[15]), "+f"(d[16]), "+f"(d[17]), "+f"(d[18]), "+f"(d[19]), "+f"(d[20]), "+f"(d[21]), "+f"(d[22]), "+f"(d[23]), "+f"(d[24]), "+f"(d[25]), "+f"(d[26]), "+f"(d[27]), "+f"(d[28]), "+f"(d[29]), "+f"(d[30]), "+f"(d[31])
    : "l"(da), "l"(db), "r"(scale_d), "n"(TA), "n"(TB));
}
template <int TB>
__device__ __forceinline__ void wgmma_rs_n64(float (&d)[32], uint32_t a0, uint32_t a1, uint32_t a2, uint32_t a3, uint64_t db, int scale_d) {
  asm volatile("{\n.reg .pred p;\nsetp.ne.b32 p, %37, 0;\n"
    "wgmma.mma_async.sync.aligned.m64n64k16.f32.bf16.bf16 {%0, %1, %2, %3, %4, %5, %6, %7, %8, %9, %10, %11, %12, %13, %14, %15, %16, %17, %18, %19, %20, %21, %22, %23, %24, %25, %26, %27, %28, %29, %30, %31}, {%32, %33, %34, %35}, %36, p, 1, 1, %38;\n}\n"
    : "+f"(d[0]), "+f"(d[1]), "+f"(d[2]), "+f"(d[3]), "+f"(d[4]), "+f"(d[5]), "+f"(d[6]), "+f"(d[7]), "+f"(d[8]), "+f"(d[9]), "+f"(d[10]), "+f"(d[11]), "+f"(d[12]), "+f"(d[13]), "+f"(d[14]), "+f"(d[15]), "+f"(d[16]), "+f"(d[17]), "+f"(d[18]), "+f"(d[19]), "+f"(d[20]), "+f"(d[21]), "+f"(d[22]), "+f"(d[23]), "+f"(d[24]), "+f"(d[25]), "+f"(d[26]), "+f"(d[27]), "+f"(d[28]), "+f"(d[29]), "+f"(d[30]), "+f"(d[31])
    : "r"(a0), "r"(a1), "r"(a2), "r"(a3), "l"(db), "r"(scale_d), "n"(TB));
}
template <int TB, int TA = 0>
__device__ __forceinline__ void wgmma_ss_n160(float (&d)[80], uint64_t da, uint64_t db, int scale_d) {
  asm volatile("{\n.reg .pred p;\nsetp.ne.b32 p, %82, 0;\n"
    "wgmma.mma_async.sync.aligned.m64n160k16.f32.bf16.bf16 {%0, %1, %2, %3, %4, %5, %6, %7, %8, %9, %10, %11, %12, %13, %14, %15, %16, %17, %18, %19, %20, %21, %22, %23, %24, %25, %26, %27, %28, %29, %30, %31, %32, %33, %34, %35, %36, %37, %38, %39, %40, %41, %42, %43, %44, %45, %46, %47, %48, %49, %50, %51, %52, %53, %54, %55, %56, %57, %58, %59, %60, %61, %62, %63, %64, %65, %66, %67, %68, %69, %70, %71, %72, %73, %74, %75, %76, %77, %78, %79}, %80, %81, p, 1, 1, %83, %84;\n}\n"
    : "+f"(d[0]), "+f"(d[1]), "+f"(d[2]), "+f"(d[3]), "+f"(d[4]), "+f"(d[5]), "+f"(d[6]), "+f"(d[7]), "+f"(d[8]), "+f"(d[9]), "+f"(d[10]), "+f"(d[11]), "+f"(d[12]), "+f"(d[13]), "+f"(d[14]), "+f"(d[15]), "+f"(d[16]), "+f"(d[17]), "+f"(d[18]), "+f"(d[19]), "+f"(d[20]), "+f"(d[21]), "+f"(d[22]), "+f"(d[23]), "+f"(d[24]), "+f"(d[25]), "+f"(d[26]), "+f"(d[27]), "+f"(d[28]), "+f"(d[29]), "+f"(d[30]), "+f"(d[31]), "+f"(d[32]), "+f"(d[33]), "+f"(d[34]), "+f"(d[35]), "+f"(d[36]), "+f"(d[37]), "+f"(d[38]), "+f"(d[39]), "+f"(d[40]), "+f"(d[41]), "+f"(d[42]), "+f"(d[43]), "+f"(d[44]), "+f"(d[45]), "+f"(d[46]), "+f"(d[47]), "+f"(d[48]), "+f"(d[49]), "+f"(d[50]), "+f"(d[51]), "+f"(d[52]), "+f"(d[53]), "+f"(d[54]), "+f"(d[55]), "+f"(d[56]), "+f"(d[57]), "+f"(d[58]), "+f"(d[59]), "+f"(d[60]), "+f"(d[61]), "+f"(d[62]), "+f"(d[63]), "+f"(d[64]), "+f"(d[65]), "+f"(d[66]), "+f"(d[67]), "+f"(d[68]), "+f"(d[69]), "+f"(d[70]), "+f"(d[71]), "+f"(d[72]), "+f"(d[73]), "+f"(d[74]), "+f"(d[75]), "+f"(d[76]), "+f"(d[77]), "+f"(d[78]), "+f"(d[79])
    : "l"(da), "l"(db), "r"(scale_d), "n"(TA), "n"(TB));
}
template <int TB>
__device__ __forceinline__ void wgmma_rs_n160(float (&d)[80], uint32_t a0, uint32_t a1, uint32_t a2, uint32_t a3, uint64_t db, int scale_d) {
  asm volatile("{\n.reg .pred p;\nsetp.ne.b32 p, %85, 0;\n"
    "wgmma.mma_async.sync.aligned.m64n160k16.f32.bf16.bf16 {%0, %1, %2, %3, %4, %5, %6, %7, %8, %9, %10, %11, %12, %13, %14, %15, %16, %17, %18, %19, %20, %21, %22, %23, %24, %25, %26, %27, %28, %29, %30, %31, %32, %33, %34, %35, %36, %37, %38, %39, %40, %41, %42, %43, %44, %45, %46, %47, %48, %49, %50, %51, %52, %53, %54, %55, %56, %57, %58, %59, %60, %61, %62, %63, %64, %65, %66, %67, %68, %69, %70, %71, %72, %73, %74, %75, %76, %77, %78, %79}, {%80, %81, %82, %83}, %84, p, 1, 1, %86;\n}\n"
    : "+f"(d[0]), "+f"(d[1]), "+f"(d[2]), "+f"(d[3]), "+f"(d[4]), "+f"(d[5]), "+f"(d[6]), "+f"(d[7]), "+f"(d[8]), "+f"(d[9]), "+f"(d[10]), "+f"(d[11]), "+f"(d[12]), "+f"(d[13]), "+f"(d[14]), "+f"(d[15]), "+f"(d[16]), "+f"(d[17]), "+f"(d[18]), "+f"(d[19]), "+f"(d[20]), "+f"(d[21]), "+f"(d[22]), "+f"(d[23]), "+f"(d[24]), "+f"(d[25]), "+f"(d[26]), "+f"(d[27]), "+f"(d[28]), "+f"(d[29]), "+f"(d[30]), "+f"(d[31]), "+f"(d[32]), "+f"(d[33]), "+f"(d[34]), "+f"(d[35]), "+f"(d[36]), "+f"(d[37]), "+f"(d[38]), "+f"(d[39]), "+f"(d[40]), "+f"(d[41]), "+f"(d[42]), "+f"(d[43]), "+f"(d[44]), "+f"(d[45]), "+f"(d[46]), "+f"(d[47]), "+f"(d[48]), "+f"(d[49]), "+f"(d[50]), "+f"(d[51]), "+f"(d[52]), "+f"(d[53]), "+f"(d[54]), "+f"(d[55]), "+f"(d[56]), "+f"(d[57]), "+f"(d[58]), "+f"(d[59]), "+f"(d[60]), "+f"(d[61]), "+f"(d[62]), "+f"(d[63]), "+f"(d[64]), "+f"(d[65]), "+f"(d[66]), "+f"(d[67]), "+f"(d[68]), "+f"(d[69]), "+f"(d[70]), "+f"(d[71]), "+f"(d[72]), "+f"(d[73]), "+f"(d[74]), "+f"(d[75]), "+f"(d[76]), "+f"(d[77]), "+f"(d[78]), "+f"(d[79])
    : "r"(a0), "r"(a1), "r"(a2), "r"(a3), "l"(db), "r"(scale_d), "n"(TB));
}
template <int TB, int TA = 0>
__device__ __forceinline__ void wgmma_ss_n192(float (&d)[96], uint64_t da, uint64_t db, int scale_d) {
  asm volatile("{\n.reg .pred p;\nsetp.ne.b32 p, %98, 0;\n"
    "wgmma.mma_async.sync.aligned.m64n192k16.f32.bf16.bf16 {%0, %1, %2, %3, %4, %5, %6, %7, %8, %9, %10, %11, %12, %13, %14, %15, %16, %17, %18, %19, %20, %21, %22, %23, %24, %25, %26, %27, %28, %29, %30, %31, %32, %33, %34, %35, %36, %37, %38, %39, %40, %41, %42, %43, %44, %45, %46, %47, %48, %49, %50, %51, %52, %53, %54, %55, %56, %57, %58, %59, %60, %61, %62, %63, %64, %65, %66, %67, %68, %69, %70, %71, %72, %73, %74, %75, %76, %77, %78, %79, %80, %81, %82, %83, %84, %85, %86, %87, %88, %89, %90, %91, %92, %93, %94, %95}, %96, %97, p, 1, 1, %99, %100;\n}\n"
    : "+f"(d[0]), "+f"(d[1]), "+f"(d[2]), "+f"(d[3]), "+f"(d[4]), "+f"(d[5]), "+f"(d[6]), "+f"(d[7]), "+f"(d[8]), "+f"(d[9]), "+f"(d[10]), "+f"(d[11]), "+f"(d[12]), "+f"(d[13]), "+f"(d[14]), "+f"(d[15]), "+f"(d[16]), "+f"(d[17]), "+f"(d[18]), "+f"(d[19]), "+f"(d[20]), "+f"(d[21]), "+f"(d[22]), "+f"(d[23]), "+f"(d[24]), "+f"(d[25]), "+f"(d[26]), "+f"(d[27]), "+f"(d[28]), "+f"(d[29]), "+f"(d[30]), "+f"(d[31]), "+f"(d[32]), "+f"(d[33]), "+f"(d[34]), "+f"(d[35]), "+f"(d[36]), "+f"(d[37]), "+f"(d[38]), "+f"(d[39]), "+f"(d[40]), "+f"(d[41]), "+f"(d[42]), "+f"(d[43]), "+f"(d[44]), "+f"(d[45]), "+f"(d[46]), "+f"(d[47]), "+f"(d[48]), "+f"(d[49]), "+f"(d[50]), "+f"(d[51]), "+f"(d[52]), "+f"(d[53]), "+f"(d[54]), "+f"(d[55]), "+f"(d[56]), "+f"(d[57]), "+f"(d[58]), "+f"(d[59]), "+f"(d[60]), "+f"(d[61]), "+f"(d[62]), "+f"(d[63]), "+f"(d[64]), "+f"(d[65]), "+f"(d[66]), "+f"(d[67]), "+f"(d[68]), "+f"(d[69]), "+f"(d[70]), "+f"(d[71]), "+f"(d[72]), "+f"(d[73]), "+f"(d[74]), "+f"(d[75]), "+f"(d[76]), "+f"(d[77]), "+f"(d[78]), "+f"(d[79]), "+f"(d[80]), "+f"(d[81]), "+f"(d[82]), "+f"(d[83]), "+f"(d[84]), "+f"(d[85]), "+f"(d[86]), "+f"(d[87]), "+f"(d[88]), "+f"(d[89]), "+f"(d[90]), "+f"(d[91]), "+f"(d[92]), "+f"(d[93]), "+f"(d[94]), "+f"(d[95])
    : "l"(da), "l"(db), "r"(scale_d), "n"(TA), "n"(TB));
}
template <int TB>
__device__ __forceinline__ void wgmma_rs_n192(float (&d)[96], uint32_t a0, uint32_t a1, uint32_t a2, uint32_t a3, uint64_t db, int scale_d) {
  asm volatile("{\n.reg .pred p;\nsetp.ne.b32 p, %101, 0;\n"
    "wgmma.mma_async.sync.aligned.m64n192k16.f32.bf16.bf16 {%0, %1, %2, %3, %4, %5, %6, %7, %8, %9, %10, %11, %12, %13, %14, %15, %16, %17, %18, %19, %20, %21, %22, %23, %24, %25, %26, %27, %28, %29, %30, %31, %32, %33, %34, %35, %36, %37, %38, %39, %40, %41, %42, %43, %44, %45, %46, %47, %48, %49, %50, %51, %52, %53, %54, %55, %56, %57, %58, %59, %60, %61, %62, %63, %64, %65, %66, %67, %68, %69, %70, %71, %72, %73, %74, %75, %76, %77, %78, %79, %80, %81, %82, %83, %84, %85, %86, %87, %88, %89, %90, %91, %92, %93, %94, %95}, {%96, %97, %98, %99}, %100, p, 1, 1, %102;\n}\n"
    : "+f"(d[0]), "+f"(d[1]), "+f"(d[2]), "+f"(d[3]), "+f"(d[4]), "+f"(d[5]), "+f"(d[6]), "+f"(d[7]), "+f"(d[8]), "+f"(d[9]), "+f"(d[10]), "+f"(d[11]), "+f"(d[12]), "+f"(d[13]), "+f"(d[14]), "+f"(d[15]), "+f"(d[16]), "+f"(d[17]), "+f"(d[18]), "+f"(d[19]), "+f"(d[20]), "+f"(d[21]), "+f"(d[22]), "+f"(d[23]), "+f"(d[24]), "+f"(d[25]), "+f"(d[26]), "+f"(d[27]), "+f"(d[28]), "+f"(d[29]), "+f"(d[30]), "+f"(d[31]), "+f"(d[32]), "+f"(d[33]), "+f"(d[34]), "+f"(d[35]), "+f"(d[36]), "+f"(d[37]), "+f"(d[38]), "+f"(d[39]), "+f"(d[40]), "+f"(d[41]), "+f"(d[42]), "+f"(d[43]), "+f"(d[44]), "+f"(d[45]), "+f"(d[46]), "+f"(d[47]), "+f"(d[48]), "+f"(d[49]), "+f"(d[50]), "+f"(d[51]), "+f"(d[52]), "+f"(d[53]), "+f"(d[54]), "+f"(d[55]), "+f"(d[56]), "+f"(d[57]), "+f"(d[58]), "+f"(d[59]), "+f"(d[60]), "+f"(d[61]), "+f"(d[62]), "+f"(d[63]), "+f"(d[64]), "+f"(d[65]), "+f"(d[66]), "+f"(d[67]), "+f"(d[68]), "+f"(d[69]), "+f"(d[70]), "+f"(d[71]), "+f"(d[72]), "+f"(d[73]), "+f"(d[74]), "+f"(d[75]), "+f"(d[76]), "+f"(d[77]), "+f"(d[78]), "+f"(d[79]), "+f"(d[80]), "+f"(d[81]), "+f"(d[82]), "+f"(d[83]), "+f"(d[84]), "+f"(d[85]), "+f"(d[86]), "+f"(d[87]), "+f"(d[88]), "+f"(d[89]), "+f"(d[90]), "+f"(d[91]), "+f"(d[92]), "+f"(d[93]), "+f"(d[94]), "+f"(d[95])
    : "r"(a0), "r"(a1), "r"(a2), "r"(a3), "l"(db), "r"(scale_d), "n"(TB));
}

__device__ __forceinline__ uint32_t smem_u32(const void* p) { return (uint32_t)__cvta_generic_to_shared(p); }
__device__ __forceinline__ void wg_fence() { asm volatile("wgmma.fence.sync.aligned;" ::: "memory"); }
__device__ __forceinline__ void wg_commit() { asm volatile("wgmma.commit_group.sync.aligned;" ::: "memory"); }
template <int N> __device__ __forceinline__ void wg_wait() { asm volatile("wgmma.wait_group.sync.aligned %0;" ::"n"(N) : "memory"); }
__device__ __forceinline__ void sched_fence(int& keep, uint32_t zero) {
  asm volatile("{\n.reg .u32 c;\nmov.u32 c, %%clock;\nand.b32 c, c, %1;\nxor.b32 %0, %0, c;\n}\n" : "+r"(keep) : "r"(zero) : "memory");
}
template <int N> __device__ __forceinline__ void fence_regs(float (&r)[N]) {
#pragma unroll
  for (int i = 0; i < N; i++) asm volatile("" : "+f"(r[i])::"memory");
}
template <int N> __device__ __forceinline__ void fence_regs(uint32_t (&r)[N]) {
#pragma unroll
  for (int i = 0; i < N; i++) asm volatile("" : "+r"(r[i])::"memory");
}
__device__ __forceinline__ uint64_t mk_desc(uint32_t a16, uint32_t lbo, uint32_t sbo, uint32_t swz) {
  uint64_t d;
  asm("mov.b64 %0, {%1, %2};" : "=l"(d) : "r"(a16 + ((lbo >> 4) << 16)), "r"((sbo >> 4) | (swz << 30)));
  return d;
}
__device__ __forceinline__ void mbar_init(uint32_t bar, uint32_t cnt) {
  asm volatile("mbarrier.init.shared::cta.b64 [%0], %1;" ::"r"(bar), "r"(cnt) : "memory");
}
__device__ __forceinline__ void mbar_expect(uint32_t bar, uint32_t tx) {
  asm volatile("mbarrier.arrive.expect_tx.shared::cta.b64 _, [%0], %1;" ::"r"(bar), "r"(tx) : "memory");
}
__device__ __forceinline__ bool mbar_test(uint32_t bar, uint32_t ph) {
  uint32_t ok;
  asm volatile("{\n.reg .pred p;\nmbarrier.test_wait.parity.shared::cta.b64 p, [%1], %2;\nselp.u32 %0, 1, 0, p;\n}\n"
               : "=r"(ok) : "r"(bar), "r"(ph) : "memory");
  return ok;
}
__device__ __forceinline__ void mbar_wait(uint32_t bar, uint32_t ph) {
  asm volatile("{\n.reg .pred p;\n.reg .u32 n;\nmov.u32 n, 0;\n"
               "LOOP:\nadd.u32 n, n, 1;\nmbarrier.try_wait.parity.shared::cta.b64 p, [%0], %1;\n@p bra DONE;\n"
               "setp.lt.u32 p, n, 0x1000000;\n@p bra LOOP;\ntrap;\n"
               "DONE:\n}\n" ::"r"(bar), "r"(ph) : "memory");
}
template <int NS> __device__ __forceinline__ void mbar_wait_slow(uint32_t bar, uint32_t ph) {
  asm volatile("{\n.reg .pred p;\n.reg .u32 n;\nmov.u32 n, 0;\n"
               "LOOP:\nmbarrier.test_wait.parity.shared::cta.b64 p, [%0], %1;\n@p bra DONE;\n"
               "nanosleep.u32 %2;\nadd.u32 n, n, 1;\nsetp.lt.u32 p, n, 0x400000;\n@p bra LOOP;\ntrap;\n"
               "DONE:\n}\n" ::"r"(bar), "r"(ph), "n"(NS) : "memory");
}
__device__ __forceinline__ void mbar_arrive_cluster_if(bool on, uint32_t addr) {
  asm volatile("{\n.reg .pred p;\nsetp.ne.b32 p, %1, 0;\n@p mbarrier.arrive.shared::cluster.b64 _, [%0];\n}\n" ::"r"(addr), "r"((int)on) : "memory");
}
__device__ __forceinline__ void mbar_arrive_if(bool on, uint32_t addr) {
  asm volatile("{\n.reg .pred p;\nsetp.ne.b32 p, %1, 0;\n@p mbarrier.arrive.shared::cta.b64 _, [%0];\n}\n" ::"r"(addr), "r"((int)on) : "memory");
}
__device__ __forceinline__ void tma2d(uint32_t dst, const CUtensorMap* m, uint32_t bar, int c0, int c1) {
  asm volatile("cp.async.bulk.tensor.2d.shared::cluster.global.mbarrier::complete_tx::bytes [%0], [%1, {%3, %4}], [%2];"
               ::"r"(dst), "l"(m), "r"(bar), "r"(c0), "r"(c1) : "memory");
}
__device__ __forceinline__ void tma3d(uint32_t dst, const CUtensorMap* m, uint32_t bar, int c0, int c1, int c2) {
  asm volatile("cp.async.bulk.tensor.3d.shared::cluster.global.mbarrier::complete_tx::bytes [%0], [%1, {%3, %4, %5}], [%2];"
               ::"r"(dst), "l"(m), "r"(bar), "r"(c0), "r"(c1), "r"(c2) : "memory");
}
__device__ __forceinline__ void tma3d_mc(uint32_t dst, const CUtensorMap* m, uint32_t bar, int c0, int c1, int c2) {
  asm volatile("cp.async.bulk.tensor.3d.shared::cluster.global.mbarrier::complete_tx::bytes.multicast::cluster"
               " [%0], [%1, {%3, %4, %5}], [%2], %6;"
               ::"r"(dst), "l"(m), "r"(bar), "r"(c0), "r"(c1), "r"(c2), "h"((uint16_t)3) : "memory");
}
__device__ __forceinline__ void tma3d_store(const CUtensorMap* m, uint32_t src, int c0, int c1, int c2) {
  asm volatile("cp.async.bulk.tensor.3d.global.shared::cta.bulk_group [%0, {%2, %3, %4}], [%1];"
               ::"l"(m), "r"(src), "r"(c0), "r"(c1), "r"(c2) : "memory");
}
__device__ __forceinline__ void bar_sync(int id, int n) { asm volatile("bar.sync %0, %1;" ::"r"(id), "r"(n) : "memory"); }
__device__ __forceinline__ uint32_t pack_bf16(float lo, float hi) {
  uint32_t r;
  asm("cvt.rn.bf16x2.f32 %0, %1, %2;" : "=r"(r) : "f"(hi), "f"(lo));
  return r;
}
__device__ __forceinline__ float ex2(float x) {
  float y;
  asm("ex2.approx.ftz.f32 %0, %1;" : "=f"(y) : "f"(x));
  return y;
}
__device__ __forceinline__ float fadd(float a, float b) {
  float y;
  asm("add.f32 %0, %1, %2;" : "=f"(y) : "f"(a), "f"(b));
  return y;
}
__device__ __forceinline__ float rcp(float x) {
  float y;
  asm("rcp.approx.ftz.f32 %0, %1;" : "=f"(y) : "f"(x));
  return y;
}
__device__ __forceinline__ void stsm4(uint32_t addr, uint32_t a, uint32_t b, uint32_t c, uint32_t d) {
  asm volatile("stmatrix.sync.aligned.m8n8.x4.shared.b16 [%0], {%1, %2, %3, %4};" ::"r"(addr), "r"(a), "r"(b), "r"(c), "r"(d) : "memory");
}

__device__ __forceinline__ void tma4d_mc_hint(uint32_t dst, const CUtensorMap* m, uint32_t bar, int c3, uint64_t pol) {
  asm volatile("cp.async.bulk.tensor.4d.shared::cluster.global.mbarrier::complete_tx::bytes.multicast::cluster.L2::cache_hint"
               " [%0], [%1, {%3, %3, %3, %4}], [%2], %5, %6;"
               ::"r"(dst), "l"(m), "r"(bar), "r"(0), "r"(c3), "h"((uint16_t)3), "l"(pol) : "memory");
}
__device__ __forceinline__ void tma5d_mc(uint32_t dst, const CUtensorMap* m, uint32_t bar, int c2, int c4) {
  asm volatile("cp.async.bulk.tensor.5d.shared::cluster.global.mbarrier::complete_tx::bytes.multicast::cluster"
               " [%0], [%1, {%3, %3, %4, %3, %5}], [%2], %6;"
               ::"r"(dst), "l"(m), "r"(bar), "r"(0), "r"(c2), "r"(c4), "h"((uint16_t)3) : "memory");
}
__device__ __forceinline__ void bulk_load_hint(uint32_t dst, const void* src, uint32_t bytes, uint32_t bar, uint64_t pol) {
  asm volatile("cp.async.bulk.shared::cluster.global.mbarrier::complete_tx::bytes.L2::cache_hint [%0], [%1], %2, [%3], %4;"
               ::"r"(dst), "l"(src), "r"(bytes), "r"(bar), "l"(pol) : "memory");
}
__device__ __forceinline__ void stg128_hint(void* p, uint32_t a, uint32_t b, uint32_t c, uint32_t d, uint64_t pol) {
  asm volatile("st.global.L2::cache_hint.v4.b32 [%0], {%1, %2, %3, %4}, %5;" ::"l"(p), "r"(a), "r"(b), "r"(c), "r"(d), "l"(pol) : "memory");
}
__device__ __forceinline__ void stg2_if(bool on, void* p, uint32_t a, uint32_t b, uint32_t c, uint32_t d, uint32_t e, uint32_t f,
                                        uint32_t g, uint32_t h, uint64_t pol) {
  asm volatile("{\n.reg .pred p;\nsetp.ne.b32 p, %10, 0;\n"
               "@p st.global.L2::cache_hint.v4.b32 [%0], {%1, %2, %3, %4}, %9;\n"
               "@p st.global.L2::cache_hint.v4.b32 [%0 + 512], {%5, %6, %7, %8}, %9;\n}\n"
               ::"l"(p), "r"(a), "r"(b), "r"(c), "r"(d), "r"(e), "r"(f), "r"(g), "r"(h), "l"(pol), "r"((int)on) : "memory");
}
__device__ __forceinline__ uint64_t make_policy(bool first) {
  uint64_t pf, pn;
  asm("createpolicy.fractional.L2::evict_first.b64 %0, 1.0;" : "=l"(pf));
  asm("createpolicy.fractional.L2::evict_normal.b64 %0, 1.0;" : "=l"(pn));
  return first ? pf : pn;
}
__device__ __forceinline__ bool elect() {
  uint32_t ok;
  asm volatile("{\n.reg .pred p;\nelect.sync _|p, 0xffffffff;\nselp.u32 %0, 1, 0, p;\n}\n" : "=r"(ok));
  return ok;
}
__device__ __forceinline__ void mbar_arrive(uint32_t bar) {
  asm volatile("mbarrier.arrive.shared::cta.b64 _, [%0];" ::"r"(bar) : "memory");
}
__device__ __forceinline__ void stg128(void* p, uint32_t a, uint32_t b, uint32_t c, uint32_t d) {
  asm volatile("st.global.v4.b32 [%0], {%1, %2, %3, %4};" ::"l"(p), "r"(a), "r"(b), "r"(c), "r"(d) : "memory");
}
__device__ __forceinline__ void lds128(uint32_t p, uint32_t& a, uint32_t& b, uint32_t& c, uint32_t& d) {
  asm volatile("ld.shared.v4.b32 {%0, %1, %2, %3}, [%4];" : "=r"(a), "=r"(b), "=r"(c), "=r"(d) : "r"(p) : "memory");
}
__device__ __forceinline__ void wait_count(const unsigned int* p, uint32_t target) {
  asm volatile("{\n.reg .pred p;\n.reg .u32 n, v;\nmov.u32 n, 0;\n"
               "LOOP:\nld.acquire.gpu.global.u32 v, [%0];\nsetp.ge.u32 p, v, %1;\n@p bra DONE;\n"
               "nanosleep.u32 %2;\nadd.u32 n, n, 1;\nsetp.lt.u32 p, n, 0x400000;\n@p bra LOOP;\ntrap;\n"
               "DONE:\n}\n" ::"l"(p), "r"(target), "n"(200) : "memory");
}

__host__ __device__ __forceinline__ int o_wave(int a, int b, int i, int lag) {
  if (lag == 0) return a + i;
  const int p = lag < b - a - 1 ? lag : b - a - 1;
  return i < p ? b - 2 - i : i == p ? b - 1 : b - 1 - i;
}

struct Cursor {
  int bi;
  uint32_t ph;
  __device__ __forceinline__ void next() {
    if (++bi == NBAR) { bi = 0; ph ^= 1; }
  }
};

constexpr float kScaleLog2 = 0.07216878364870322f * 1.4426950408889634f;
constexpr float kSumLimit = 1048576.0f;
constexpr float kMaxLag = 8.0f;

__global__ void __cluster_dims__(2, 1, 1) __launch_bounds__(384, 1)
fused_kernel(const __grid_constant__ Params P) {
  extern __shared__ uint8_t smem_raw[];
  const uint32_t sbase = (smem_u32(smem_raw) + 1023) & ~1023u;
  const uint32_t full0 = sbase + RING, empty0 = full0 + 8 * NBAR, odone = empty0 + 8 * NBAR, oready0 = odone + 8;
  const uint32_t fenced = oready0 + 64, hready0 = fenced + 8;
  const uint32_t rank = blockIdx.x & 1;
  const int role = blockIdx.x >> 1;
  const bool helper = role >= N_CL;
  const int team = helper ? 0 : role >> 2, nt = role & 3, blk = team >> 3;
  const uint32_t* prog = P.ops[helper ? N_TEAM + 2 * (role - N_CL) : team];
  auto q_role = [&](uint32_t op) { return helper ? (int)(((op >> 3) & 60) | ((op >> 12) & 3)) : role; };
  auto o_role = [&](uint32_t op) { return helper ? (int)(((op >> 26) & 56) | ((op >> 9) & 7)) : role; };
  const int wid = __shfl_sync(0xffffffffu, (int)(threadIdx.x >> 5), 0);
  const int wg = wid >> 2;

  const uint32_t op0 = P.first[helper ? N_TEAM + role - N_CL : team];
  if (__builtin_expect(wid == 8, 1)) {
    if (elect()) {
#pragma unroll
      for (int k = 0; k < EARLY; k++) mbar_init(full0 + 8 * k, 1);
      asm volatile("fence.mbarrier_init.release.cluster;" ::: "memory");
      if ((op0 & 3) == OP_Q) {
        const int qr = q_role(op0);
#pragma unroll
        for (int k = 0; k < EARLY; k++) {
          mbar_expect(full0 + 8 * k, SZ_WQ + SZ_A);
          tma2d(sbase + k * (SZ_WQ + SZ_A) + SZ_WQ, &P.x[qr >> 5], full0 + 8 * k, 64 * k, ((qr >> 2) & 7) * kSq + rank * 128);
          tma3d(sbase + k * (SZ_WQ + SZ_A), &P.wq[qr >> 5], full0 + 8 * k, 0, 64 * k, 3 * (4 * ((op0 >> 2) & 7) + (qr & 3)));
        }
      }
      asm volatile("prefetch.tensormap [%0];" ::"l"(rank ? &P.v[blk] : &P.k[blk]) : "memory");
    }
  } else if (threadIdx.x == 0) {
#pragma unroll
    for (int i = EARLY; i < 2 * NBAR + 10 + MAX_PARK; i++) mbar_init(full0 + 8 * i, i >= NBAR && i <= 2 * NBAR ? 16 : 1);
    asm volatile("fence.mbarrier_init.release.cluster;" ::: "memory");
  }
  __syncwarp();
  asm volatile("barrier.cluster.arrive.relaxed.aligned;\nbarrier.cluster.wait.aligned;" ::: "memory");

  if (wg == 2) {
    asm volatile("setmaxnreg.dec.sync.aligned.u32 24;");
    if (wid == 8) {
      Cursor tail{0, 0};
      int head = 0, sh = 0;
      uint32_t hph = 0;
      uint32_t cur = 0, used = 0;
      uint64_t fifo = 0;
      uint32_t dst, bar, oready = oready0;
      uint64_t pol;
      asm volatile("createpolicy.fractional.L2::evict_first.b64 %0, 1.0;" : "=l"(pol));
      const uint64_t pol_o = make_policy(P.dbg & 1), pol_p = make_policy(!(P.dbg & 4));
      const CUtensorMap* kv_map = rank ? &P.v[blk] : &P.k[blk];
      auto acquire = [&](uint32_t bytes, int part = 0) {
        uint32_t fp = bytes >> 12;
        if (cur + fp > (RING >> 12)) { fp += (RING >> 12) - cur; cur = 0; }
        used += fp;
        bool more = false;
        uint32_t wbar, wph;
        while (used > (RING >> 12) || (part != 2 && sh == 5 * NBAR)) {
          if (more) mbar_wait(wbar, wph);
          more = true;
          wbar = empty0 + 8 * tail.bi; wph = tail.ph;
          tail.next();
          used -= (uint32_t)fifo & 31;
          fifo >>= 5;
          sh -= 5;
        }
        fifo += (uint64_t)fp << sh;
        dst = sbase + (cur << 12);
        bar = full0 + 8 * head;
        cur += bytes >> 12;
        if (part != 1) {
          sh += 5;
          if (++head == NBAR) { head = 0; hph ^= 1; }
        }
        if (more) mbar_wait(wbar, wph);
      };
      auto scratch = [&](const uint4* src, uint32_t bytes, int n) {
        asm volatile("fence.proxy.async.global;" ::: "memory");
#pragma unroll 1
        for (int i = 0; i < n; i++) {
          acquire(bytes);
          if (elect()) {
            bulk_load_hint(dst, src + i * (bytes / 16), bytes, bar, pol_p);
            mbar_expect(bar, bytes);
          }
        }
      };
      for (int pc = 0;; pc++) {
        const uint32_t op = prog[pc];
        const int type = op & 3, a = (op >> 2) & 7;
        if (type == OP_END) break;
        if (type == OP_Q) {
          const int qr = q_role(op);
#pragma unroll 1
          for (int k = 0; k < 10; k++) {
            acquire(SZ_WQ, 1);
            if ((pc > 0 || k >= EARLY) && (k & 1) == rank && elect()) tma3d_mc(dst, &P.wq[qr >> 5], bar, 0, 64 * k, 3 * (4 * a + (qr & 3)));
            acquire(SZ_A, 2);
            if ((pc > 0 || k >= EARLY) && elect()) {
              tma2d(dst, &P.x[qr >> 5], bar, 64 * k, ((qr >> 2) & 7) * kSq + rank * 128);
              mbar_expect(bar, SZ_WQ + SZ_A);
            }
          }
        } else if (type == OP_A) {
          const uint32_t nop = prog[pc + 1];
#pragma unroll 1
          for (int t = (op & F_PARK) ? 1 : 0; t < 33; t++) {
            int wave = a;
            if (t == 31 && (nop & 3) != OP_A) t++;
            if (t == 31) {
              wave = (nop >> 2) & 7;
              mbar_wait((nop & F_HELP) ? hready0 + 8 * ((nop >> 10) & 3) : fenced, 0);
              scratch(&g_o[((team * 2 + rank) * 96 + 3 * (4 * wave + nt)) * 1024], SZ_PARK, 2);
            }
            const int isv = t ? ~t & 1 : 0, j = (isv ? (t - 1) >> 1 : (t + 1) >> 1) & 15;
            const int row0 = ((team & 7) * kH + 4 * wave + nt) * kSk;
            acquire(SZ_KV);
            if (isv == (int)rank && t >= KV_TRANSIT) {
              const int i = head - 1 - KV_TRANSIT;
              mbar_wait(full0 + 8 * (i < 0 ? i + NBAR : i), i < 0 ? hph ^ 1 : hph);
            }
            if (elect()) {
              if (isv == (int)rank) tma4d_mc_hint(dst, kv_map, bar, row0 / 8 + 8 * j, pol);
              mbar_expect(bar, SZ_KV);
            }
          }
        } else {
          const int b = (op >> 5) & 15, ro = o_role(op);
#pragma unroll 1
          for (int i = 0; i < b - a; i++) {
            const int w = o_wave(a, b, i, (P.dbg >> 4) & 7);
            mbar_wait(oready, 0);
            oready += 8;
            asm volatile("fence.proxy.async.global;" ::: "memory");
#pragma unroll 1
            for (int k = 12 * w; k < 12 * w + 12; k++) {
              acquire(SZ_A, 1);
              if (elect()) bulk_load_hint(dst, &g_o[(((ro >> 2) * 2 + rank) * 96 + k - 12 * (w - P.slot[w])) * 1024], SZ_A, bar, pol_o);
              acquire(SZ_WO, 2);
              if (elect()) {
                tma5d_mc(dst + rank * 10240, &P.wo[ro >> 5], bar, 8 * k + 4 * rank, 5 * (ro & 3));
                mbar_expect(bar, SZ_WO + SZ_A);
              }
            }
          }
          if (op & F_LD) {
            if (op & F_PARK) mbar_wait(hready0 + 8 * (MAX_PARK - 1), 0);
            scratch(&g_part[(role * 2 + rank) * 5120], SZ_PART, 5);
          }
        }
      }
    } else if (threadIdx.x == 288) {
      uint32_t ph = 0;
      bool first = true;
      for (int pc = 0;; pc++) {
        const uint32_t op = prog[pc];
        if ((op & 3) == OP_END) break;
        if ((op & 3) != OP_A && !helper) continue;
        mbar_wait_slow<400>(odone, ph);
        ph ^= 1;
        unsigned int* flag = !helper ? &g_done[(team * 2 + rank) * 8 + ((op >> 2) & 7)]
                             : (op & 3) == OP_Q ? &g_help[(q_role(op) * 2 + rank) * MAX_PARK + ((op >> 10) & 3)]
                                                : &g_help[(o_role(op) * 2 + rank) * MAX_PARK + MAX_PARK - 1];
        asm volatile("red.release.gpu.global.add.u32 [%0], 1;" ::"l"(flag) : "memory");
        if (first) mbar_arrive(fenced);
        first = false;
      }
    } else if (threadIdx.x == 320) {
      uint32_t oready = oready0;
      for (int pc = 0;; pc++) {
        const uint32_t op = prog[pc];
        if ((op & 3) == OP_END) break;
        if ((op & 3) == OP_O) {
          const int a = (op >> 2) & 7, b = (op >> 5) & 15;
#pragma unroll 1
          for (int i = 0; i < b - a; i++) {
            const int ci = ((o_role(op) >> 2) * 2 + rank) * 8 + o_wave(a, b, i, (P.dbg >> 4) & 7);
            wait_count(&g_done[ci], 4);
            mbar_arrive(oready);
            oready += 8;
            if (atomicAdd(&g_seen[ci], 1u) == 3u) { g_seen[ci] = 0; g_done[ci] = 0; }
          }
        }
        if ((op & 3) != OP_Q && (op & F_HELP) && (op & F_PARK)) {
          unsigned int* flag = &g_help[(role * 2 + rank) * MAX_PARK + ((op >> 10) & 3)];
          wait_count(flag, 1);
          mbar_arrive(hready0 + 8 * ((op >> 10) & 3));
          *flag = 0;
        }
      }
    }
    __syncwarp();
    asm volatile("barrier.cluster.arrive.relaxed;\nbarrier.cluster.wait;" ::: "memory");
  } else {
    asm volatile("setmaxnreg.inc.sync.aligned.u32 240;");
    const int lane = threadIdx.x & 31, warp = wid & 3;
    uint32_t empty_rem;
    asm volatile("mapa.shared::cluster.u32 %0, %1, %2;" : "=r"(empty_rem) : "r"(empty0), "r"(lane & 1));
    auto release = [&](int slot) { mbar_arrive_cluster_if(lane < 2, empty_rem + 8 * slot); };
    Cursor r{0, 0};
    const uint32_t ring16 = (sbase & 0x3FFFF) >> 4;
    uint32_t cur = ring16;
    bool rdy0 = false, rdy1 = false;
    auto probe1 = [&]() { rdy0 = mbar_test(full0 + 8 * r.bi, r.ph); };
    auto probe2 = [&]() {
      Cursor n = r;
      rdy0 = mbar_test(full0 + 8 * n.bi, n.ph);
      n.next();
      rdy1 = mbar_test(full0 + 8 * n.bi, n.ph);
    };
    auto take = [&](bool rdy, uint32_t bytes, uint32_t& addr) {
      const int bi = r.bi;
      if (!__all_sync(0xffffffffu, rdy)) mbar_wait(full0 + 8 * r.bi, r.ph);
      r.next();
      if (cur > ring16 + ((RING - bytes) >> 4)) cur = ring16;
      addr = cur;
      cur += bytes >> 4;
      return bi;
    };
    auto second = [&](uint32_t bytes) {
      if (cur > ring16 + ((RING - bytes) >> 4)) cur = ring16;
      cur += bytes >> 4;
      return cur - (bytes >> 4);
    };
    const int row = wg * 64 + warp * 16 + (lane >> 2);
    int img0 = row * 4 + ((lane & 3) ^ ((row >> 1) & 3));
    uint4* pend = nullptr;
    uint64_t spol;
    int pc = 0;
    uint32_t op = prog[0];
    auto enter = [&]() {
      r.bi = (op >> 15) & 15; r.ph = (op >> 19) & 1; cur = ring16 + (((op >> 20) & 63) << 8);
      spol = make_policy(!(op & F_SOON));
    };
    auto drain = [&](uint32_t (&t)[48], uint32_t c) {
      if (!(op & (3u << 26)) || c >= 6) return;
#pragma unroll
      for (int i = 0; i < 6; i++)
        stg2_if(c == i, pend + i * 512, t[8 * i], t[8 * i + 1], t[8 * i + 2], t[8 * i + 3],
                t[8 * i + 4], t[8 * i + 5], t[8 * i + 6], t[8 * i + 7], spol);
      if ((op & (1u << 26)) && c == 5) {
        __syncwarp();
        mbar_arrive_if(lane < 2, odone);
      }
    };
    float s[32], o[96], c[80];
    uint32_t q[48], pa[16], pb[16];
    float mc0, mc1, l0, l1;
    bool gen;
    auto soft = [&](float (&s)[32], uint32_t (&pout)[16], bool first) {
      if (first) { gen = false; mc0 = 0.f; mc1 = 0.f; }
      float b0, b1;
      for (;;) {
        if (gen) {
          float m0 = fmaxf(s[0], s[1]), m1 = fmaxf(s[2], s[3]);
#pragma unroll
          for (int i = 1; i < 8; i++) { m0 = fmaxf(m0, fmaxf(s[4 * i], s[4 * i + 1])); m1 = fmaxf(m1, fmaxf(s[4 * i + 2], s[4 * i + 3])); }
          m0 = fmaxf(m0, __shfl_xor_sync(0xffffffffu, m0, 1)); m1 = fmaxf(m1, __shfl_xor_sync(0xffffffffu, m1, 1));
          m0 = fmaxf(m0, __shfl_xor_sync(0xffffffffu, m0, 2)); m1 = fmaxf(m1, __shfl_xor_sync(0xffffffffu, m1, 2));
          if (first) {
            mc0 = m0; mc1 = m1;
          } else if (__any_sync(0xffffffffu, !(m0 <= mc0 + kMaxLag && m1 <= mc1 + kMaxLag))) {
            m0 = fmaxf(mc0, m0); m1 = fmaxf(mc1, m1);
            const float a0 = ex2(mc0 - m0), a1 = ex2(mc1 - m1);
            mc0 = m0; mc1 = m1;
            l0 *= a0; l1 *= a1;
            wg_wait<0>();
            fence_regs(o);
#pragma unroll
            for (int i = 0; i < 96; i++) o[i] *= i & 2 ? a1 : a0;
          }
#pragma unroll
          for (int i = 0; i < 32; i++) s[i] -= i & 2 ? mc1 : mc0;
        }
#pragma unroll
        for (int i = 0; i < 8; i++) {
          const float e1 = ex2(s[4 * i + 1]), e0 = ex2(s[4 * i]), e3 = ex2(s[4 * i + 3]), e2 = ex2(s[4 * i + 2]);
          pout[2 * i] = pack_bf16(e0, e1);
          b0 = i ? b0 + fadd(e1, e0) : fadd(e1, e0);
          pout[2 * i + 1] = pack_bf16(e2, e3);
          b1 = i ? b1 + fadd(e3, e2) : fadd(e3, e2);
        }
        if (!__any_sync(0xffffffffu, !gen && !(fmaxf(b0, b1) <= kSumLimit && (!first || fminf(b0, b1) >= 1.0f / kSumLimit)))) break;
        gen = __any_sync(0xffffffffu, true);
      }
      l0 = first ? b0 : l0 + b0;
      l1 = first ? b1 : l1 + b1;
    };
    auto qk = [&](float (&s)[32], uint32_t ak, int k0, int k1) {
#pragma unroll
      for (int kk = k0; kk < k1; kk++)
        wgmma_rs_n64<0>(s, q[4 * kk], q[4 * kk + 1], q[4 * kk + 2], q[4 * kk + 3], mk_desc(ak + (kk >> 2) * KV_CH + (kk & 3) * 2, 16, KV_SBO, 1), kk != 0);
      wg_commit();
    };
    auto pv = [&](uint32_t (&pin)[16], uint32_t av, int acc) {
#pragma unroll
      for (int kk = 0; kk < 4; kk++)
        wgmma_rs_n192<1>(o, pin[4 * kk], pin[4 * kk + 1], pin[4 * kk + 2], pin[4 * kk + 3], mk_desc(av + kk * (KV_SBO / 8), KV_CH * 16, KV_SBO, 1), acc || (kk != 0));
      wg_commit();
    };
    auto xw = [&](uint32_t ad, int acc) {
      const uint32_t da = second(SZ_A) + wg * 512;
      wg_fence();
#pragma unroll
      for (int kk = 0; kk < 4; kk++)
        wgmma_ss_n192<1>(o, mk_desc(da + kk * 2, 16, 1024, 1), mk_desc(ad + kk * 128, 8192, 1024, 1), acc || kk != 0);
      wg_commit();
    };
    auto ow = [&](int acc, int prev) {
      uint32_t da;
      const int bi = take(rdy0, SZ_A, da);
      const uint32_t db = second(SZ_WO);
      da += wg * 256;
      wg_fence();
      wgmma_ss_n160<1>(c, mk_desc(da, 16, 512, 2), mk_desc(db, 2048, 512, 2), acc);
      wgmma_ss_n160<1>(c, mk_desc(da + 2, 16, 512, 2), mk_desc(db + 64, 2048, 512, 2), 1);
      wg_commit();
      if (acc) { wg_wait<1>(); release(prev); }
      wgmma_ss_n160<1>(c, mk_desc(da + 512, 16, 512, 2), mk_desc(db + 640, 2048, 512, 2), 1);
      wgmma_ss_n160<1>(c, mk_desc(da + 514, 16, 512, 2), mk_desc(db + 704, 2048, 512, 2), 1);
      wg_commit();
      return bi;
    };
    auto st_part = [&](int i) {
      stg2_if(true, pend + i * 512, __float_as_uint(c[8 * i]), __float_as_uint(c[8 * i + 1]), __float_as_uint(c[8 * i + 2]), __float_as_uint(c[8 * i + 3]),
              __float_as_uint(c[8 * i + 4]), __float_as_uint(c[8 * i + 5]), __float_as_uint(c[8 * i + 6]), __float_as_uint(c[8 * i + 7]), spol);
    };
#pragma unroll
    for (int i = 0; i < 48; i++) q[i] = 0;
    enter();

    if ((op & 3) == OP_Q) {
      uint32_t ad;
      int bi0 = take(false, SZ_WQ, ad), k = 0, lag = 0;
      xw(ad, 0);
      for (;;) {
#pragma unroll 1
        for (;;) {
          drain(q, k - lag);
          probe1();
          wg_wait<0>();
          release(bi0);
          bi0 = take(rdy0, SZ_WQ, ad);
          if (++k == 8) break;
          xw(ad, 1);
        }
        if (wg) bar_sync(2, 256);
        xw(ad, 1);
        const int bi9 = take(false, SZ_WQ, ad);
        xw(ad, 1);
        if (!wg) asm volatile("bar.arrive 2, 256;" ::: "memory");
        k = 0; lag = 0;
        uint32_t nop = prog[++pc];
        wg_wait<1>();
        release(bi0);
        probe2();
        wg_wait<0>();
        fence_regs(o);
        release(bi9);
#pragma unroll
        for (int i = 0; i < 48; i++) q[i] = pack_bf16(o[2 * i] * kScaleLog2, o[2 * i + 1] * kScaleLog2);
        fence_regs(q);
        if (op & F_PARK) {
          pend = &g_o[(((q_role(op) >> 2) * 2 + rank) * 96 + 3 * (4 * ((op >> 2) & 7) + (q_role(op) & 3))) * 1024 + img0];
          op = nop;
          enter();
          if ((op & 3) != OP_Q) break;
          bi0 = take(rdy0, SZ_WQ, ad);
          xw(ad, 0);
          continue;
        }
        int wave = (op >> 2) & 7, sk1;
        uint32_t ak1;
        {
          float s0[32];
          const int sk0 = take(rdy0, SZ_KV, ad);
          wg_fence();
          qk(s0, ad, 0, 12);
          sk1 = take(rdy1, SZ_KV, ak1);
          wg_fence();
          qk(s, ak1, 0, S1A);
          probe1();
          wg_wait<1>();
          fence_regs(s0);
          release(sk0);
          soft(s0, pa, true);
        }
        float i0, i1;
        auto sums = [&]() {
          l0 += __shfl_xor_sync(0xffffffffu, l0, 1); l1 += __shfl_xor_sync(0xffffffffu, l1, 1);
          l0 += __shfl_xor_sync(0xffffffffu, l0, 2); l1 += __shfl_xor_sync(0xffffffffu, l1, 2);
          i0 = rcp(l0); i1 = rcp(l1);
          asm volatile("" : "+f"(i0), "+f"(i1));
        };
        auto target = [&]() {
          pend = &g_o[((team * 2 + rank) * 96 + 3 * (4 * P.slot[wave] + nt)) * 1024 + img0];
          asm volatile("" : "+l"(pend));
        };
        for (;;) {
          nop = prog[++pc];
          {
            uint32_t av;
            const int sv = take(rdy0, SZ_KV, av);
            wg_fence();
            qk(s, ak1, S1A, 12);
            pv(pa, av, 0);
            probe2();
            wg_wait<1>();
            fence_regs(s);
            release(sk1);
            soft(s, pb, false);
            wg_wait<0>();
            fence_regs(o);
            release(sv);
          }
          auto step = [&](uint32_t (&pin)[16], uint32_t (&pout)[16]) {
            uint32_t ak, av;
            const int sk = take(rdy0, SZ_KV, ak), sv = take(rdy1, SZ_KV, av);
            wg_fence();
            qk(s, ak, 0, 12);
            pv(pin, av, 1);
            probe2();
            wg_wait<1>();
            fence_regs(s);
            release(sk);
            soft(s, pout, false);
            wg_wait<0>();
            fence_regs(o);
            release(sv);
          };
#pragma unroll 1
          for (int jj = 0; jj < 7; jj++) {
            step(pb, pa);
            step(pa, pb);
          }
          if ((nop & 3) != OP_A) break;
          uint32_t ak, av;
          {
            const int b0 = take(rdy0, SZ_PARK, ak), b1 = take(rdy1, SZ_PARK, av);
            const uint32_t ad0 = ak, ad1 = av;
            probe2();
#pragma unroll
            for (int i = 0; i < 12; i++)
              lds128(sbase + ((i < 6 ? ad0 : ad1) - ring16 + img0) * 16 + ((i % 6) >> 1) * 8192 + (i & 1) * 512, q[4 * i], q[4 * i + 1], q[4 * i + 2], q[4 * i + 3]);
            release(b0); release(b1);
          }
          const int sk0 = take(rdy0, SZ_KV, ak), sv = take(rdy1, SZ_KV, av);
          wg_fence();
          qk(s, ak, 0, 8);
          sched_fence(img0, P.zero);
          sums();
          sched_fence(img0, P.zero);
          qk(s, ak, 8, 12);
          pv(pb, av, 1);
          probe2();
          spol = make_policy(!(nop & F_SOON));
          wg_wait<1>();
          fence_regs(s);
          release(sk0);
          soft(s, pa, true);
          sk1 = take(rdy0, SZ_KV, ak1);
          rdy0 = rdy1;
          wg_wait<0>();
          target();
          fence_regs(o);
          release(sv);
          uint32_t t[48];
#pragma unroll
          for (int j = 0; j < 6; j++) {
#pragma unroll
            for (int i = 0; i < 4; i++) {
              t[8 * j + i] = pack_bf16(o[16 * j + 4 * i] * i0, o[16 * j + 4 * i + 1] * i0);
              t[8 * j + i + 4] = pack_bf16(o[16 * j + 4 * i + 2] * i1, o[16 * j + 4 * i + 3] * i1);
            }
            stg2_if(true, pend + j * 512, t[8 * j], t[8 * j + 1], t[8 * j + 2], t[8 * j + 3], t[8 * j + 4], t[8 * j + 5], t[8 * j + 6], t[8 * j + 7], spol);
            if (j == UC0) { wg_fence(); qk(s, ak1, 0, 4); }
            if (j == UC1) { wg_fence(); qk(s, ak1, 4, S1A); }
            sched_fence(img0, P.zero);
          }
          if (P.zero) {
#pragma unroll
            for (int j = 0; j < 5; j++)
              stg2_if(true, pend, t[8 * j], t[8 * j + 1], t[8 * j + 2], t[8 * j + 3], t[8 * j + 4], t[8 * j + 5], t[8 * j + 6], t[8 * j + 7], spol);
          }
          __syncwarp();
          mbar_arrive_if(lane < 2, odone);
          wave = (nop >> 2) & 7;
        }
        const int sv = take(rdy0, SZ_KV, ad);
        wg_fence();
        pv(pb, ad, 1);
        sums();
        target();
        op = nop;
        enter();
        rdy0 = rdy1;
        auto convert = [&](float (&u)[96], int j0, int j1) {
#pragma unroll
          for (int i = 4 * j0; i < 4 * j1; i++) {
            q[8 * (i >> 2) + (i & 3)] = pack_bf16(u[4 * i], u[4 * i + 1]);
            q[8 * (i >> 2) + (i & 3) + 4] = pack_bf16(u[4 * i + 2], u[4 * i + 3]);
          }
        };
        if ((op & 3) != OP_O) {
          if ((op & 3) == OP_Q) bi0 = take(rdy0, SZ_WQ, ad);
          wg_wait<0>();
          fence_regs(o);
          release(sv);
          float u[96];
#pragma unroll
          for (int i = 0; i < 96; i++) u[i] = o[i] * (i & 2 ? i1 : i0);
          if ((op & 3) != OP_Q) { convert(u, 0, 6); break; }
          fence_regs(u);
          xw(ad, 0);
          sched_fence(img0, P.zero);
          fence_regs(u);
          convert(u, 0, AQS);
          stg2_if(true, pend, q[0], q[1], q[2], q[3], q[4], q[5], q[6], q[7], spol);
          probe1();
          wg_wait<0>();
          release(bi0);
          bi0 = take(rdy0, SZ_WQ, ad);
          xw(ad, 1);
          sched_fence(img0, P.zero);
          fence_regs(u);
          convert(u, AQS, 6);
          k = 1;
          continue;
        }
        int bi = ow(0, 0);
        wg_wait<2>();
        fence_regs(o);
        release(sv);
#pragma unroll
        for (int j = 0; j < 6; j++) {
          uint32_t t[8];
#pragma unroll
          for (int i = 0; i < 4; i++) {
            t[i] = pack_bf16(o[16 * j + 4 * i] * i0, o[16 * j + 4 * i + 1] * i0);
            t[i + 4] = pack_bf16(o[16 * j + 4 * i + 2] * i1, o[16 * j + 4 * i + 3] * i1);
          }
          stg2_if(true, pend + j * 512, t[0], t[1], t[2], t[3], t[4], t[5], t[6], t[7], spol);
          if (j == 5) {
            __syncwarp();
            mbar_arrive_if(lane < 2, odone);
          }
          probe1();
          wg_wait<1>();
          bi = ow(1, bi);
          fence_regs(o);
        }
        {
          const int nk = 12 * (((op >> 5) & 15) - ((op >> 2) & 7));
#pragma unroll 1
          for (int k = 7; k < nk; k++) {
            probe1();
            wg_wait<1>();
            bi = ow(1, bi);
          }
          probe1();
        }
        nop = prog[++pc];
        if (op & F_LD) {
          uint32_t t[80];
#pragma unroll
          for (int j = 0; j < 5; j++) {
            const int b = take(rdy0, SZ_PART, ad);
            probe1();
#pragma unroll
            for (int i = 4 * j; i < 4 * j + 4; i++)
              lds128(sbase + (ad - ring16 + img0) * 16 + ((i >> 1) & 1) * 8192 + (i & 1) * 512, t[4 * i], t[4 * i + 1], t[4 * i + 2], t[4 * i + 3]);
            release(b);
          }
          wg_wait<0>();
          fence_regs(c);
#pragma unroll
          for (int i = 0; i < 80; i++) c[i] += __uint_as_float(t[i]);
        }
        if (!(op & F_ST)) {
          wg_wait<0>();
          fence_regs(c);
          goto finish;
        }
        op = nop;
        enter();
        bi0 = take(rdy0, SZ_WQ, ad);
        xw(ad, 0);
        pend = &g_part[(role * 2 + rank) * 5120 + img0];
        probe1();
        wg_wait<1>();
        fence_regs(c);
        release(bi);
        st_part(0); st_part(1);
        wg_wait<0>();
        release(bi0);
        bi0 = take(rdy0, SZ_WQ, ad);
        xw(ad, 1);
        st_part(2); st_part(3);
#pragma unroll
        for (int i = 0; i < 48; i++) q[i] = __float_as_uint(c[32 + i]);
        pend += 4 * 512;
        k = 1; lag = 2;
      }
    }
    rdy0 = false;
    {
      uint32_t t[48];
#pragma unroll
      for (int i = 0; i < 48; i++) t[i] = q[i] ^ P.zero;
      while ((op & 3) == OP_O) {
        int bi = ow(0, 0);
#pragma unroll 1
        for (int k = 1; k < 12 * (int)(((op >> 5) & 15) - ((op >> 2) & 7)); k++) {
          drain(t, k - 1);
          probe1();
          wg_wait<1>();
          bi = ow(1, bi);
        }
        rdy0 = false;
        wg_wait<0>();
        fence_regs(c);
        pc++;
        if (!(op & F_ST)) goto finish;
        release(bi);
        pend = &g_part[(o_role(op) * 2 + rank) * 5120 + img0];
#pragma unroll
        for (int i = 6; i < 10; i++) st_part(i);
#pragma unroll
        for (int i = 0; i < 48; i++) t[i] = __float_as_uint(c[i]) ^ P.zero;
        op = prog[pc];
        enter();
      }
      for (int i = 0; i < 6; i++) drain(t, i);
    }
    asm volatile("barrier.cluster.arrive.relaxed;" ::: "memory");
    if (false) {
    finish:
      asm volatile("barrier.cluster.arrive.relaxed;" ::: "memory");
      bar_sync(1, 256);
      const uint32_t wstage = sbase + (wg * 4 + warp) * 5120;
      const uint32_t sa = wstage + (lane & 15) * 64;
#pragma unroll
      for (int i = 0; i < 10; i++) {
        const int u = (i & 1) * 2 + (lane >> 4);
        stsm4(sa + (i >> 1) * 1024 + ((u ^ ((lane >> 1) & 3)) << 4), pack_bf16(c[8 * i], c[8 * i + 1]), pack_bf16(c[8 * i + 2], c[8 * i + 3]),
              pack_bf16(c[8 * i + 4], c[8 * i + 5]), pack_bf16(c[8 * i + 6], c[8 * i + 7]));
      }
      asm volatile("fence.proxy.async.shared::cta;" ::: "memory");
      __syncwarp();
      if (lane == 0) {
        tma3d_store(&P.out, wstage, 0, (team & 7) * kSq + rank * 128 + wg * 64 + warp * 16, blk * 20 + nt * 5);
        asm volatile("cp.async.bulk.commit_group;\ncp.async.bulk.wait_group.read 0;" ::: "memory");
      }
      __syncwarp();
    }
    asm volatile("barrier.cluster.wait;" ::: "memory");
  }
}

typedef CUresult (*EncodeFn)(CUtensorMap*, CUtensorMapDataType, cuuint32_t, void*, const cuuint64_t*, const cuuint64_t*,
                             const cuuint32_t*, const cuuint32_t*, CUtensorMapInterleave, CUtensorMapSwizzle,
                             CUtensorMapL2promotion, CUtensorMapFloatOOBfill);

void encode(EncodeFn fn, CUtensorMap* m, const void* ptr, int rank, const cuuint64_t* dims, const cuuint64_t* strides,
            const cuuint32_t* box, CUtensorMapSwizzle swz) {
  const cuuint32_t es[5] = {1, 1, 1, 1, 1};
  CUresult r = fn(m, CU_TENSOR_MAP_DATA_TYPE_BFLOAT16, rank, const_cast<void*>(ptr), dims, strides, box, es,
                  CU_TENSOR_MAP_INTERLEAVE_NONE, swz, CU_TENSOR_MAP_L2_PROMOTION_L2_128B, CU_TENSOR_MAP_FLOAT_OOB_FILL_NONE);
  if (r != CUDA_SUCCESS) fprintf(stderr, "cuTensorMapEncodeTiled failed: %d\n", (int)r);
}

void annotate(uint32_t* ops, int n, bool helper) {
  uint32_t items = 0, cur = 0, pend = 0;
  auto item = [&](uint32_t bytes, int count, uint32_t bytes2 = 0) {
    for (int i = 0; i < count; i++) {
      if (cur + bytes > RING) cur = 0;
      cur += bytes;
      if (cur + bytes2 > RING) cur = 0;
      cur += bytes2;
      items++;
    }
  };
  for (int i = 0; i <= n; i++) {
    const uint32_t op = ops[i];
    ops[i] |= (items % NBAR) << 15 | ((items / NBAR) & 1) << 19 | (cur >> 12) << 20 | pend << 26;
    if ((op & 3) == OP_Q) { item(SZ_WQ, 10, SZ_A); pend = (op & F_PARK) ? (helper ? 1 : 2) : 0; }
    if ((op & 3) == OP_A) {
      item(SZ_KV, (op & F_PARK) ? 30 : 31);
      if ((ops[i + 1] & 3) == OP_A) { item(SZ_PARK, 2); item(SZ_KV, 1); }
      item(SZ_KV, 1);
      pend = 1;
    }
    if ((op & 3) == OP_O) {
      item(SZ_A, 12 * (((op >> 5) & 15) - ((op >> 2) & 7)), SZ_WO);
      if (op & F_LD) item(SZ_PART, 5);
      pend = (op & F_LAZY) ? (helper ? 1 : 2) : 0;
    }
  }
}

void compile_programs(const char* const* text, bool helpers, Params& P) {
  struct Req { int when, team, wave, slot; } req[N_TEAM * MAX_PARK];
  int n_req = 0;
  for (int t = 0; t < N_TEAM; t++) {
    uint32_t* ops = P.ops[t];
    int n = 0, flags[8] = {0, 0, 0, 0, 0, 0, 0, 0}, n_park = 0, last_o = -1, when = 0, given = 0;
    for (const char* s = text[t]; *s; s++) {
      const int a = s[1] - '0';
      if (*s == 'Q' || (*s == 'H' && !helpers)) { ops[n++] = OP_Q | a << 2; when += 10; }
      else if (*s == 'P') { flags[a] = F_PARK | n_park++ << 10; ops[n++] = OP_Q | a << 2 | flags[a]; when += 10; }
      else if (*s == 'H') { req[n_req++] = {when, t, a, n_park}; flags[a] = F_PARK | F_HELP | n_park++ << 10; }
      else if (*s == 'A') { ops[n++] = OP_A | a << 2 | flags[a]; when += 32; }
      else if (*s == 'G') { given = a; if (helpers) req[n_req++] = {1000, t, 0, -a}; }
      else if (*s == 'O') {
        ops[n] = OP_O | a << 2 | (s[2] - '0') << 5;
        if (given) ops[n] = helpers ? ops[n] | F_LD | F_PARK | (MAX_PARK - 1) << 10 : ops[n] & ~(7u << 2);
        if (last_o >= 0) { ops[last_o] |= F_ST; ops[n] |= F_LD; }
        last_o = n++;
        when += 10 * (s[2] - s[1]);
      }
    }
    for (int i = 0; i + 1 < n; i++)
      if ((ops[i] & 3) == OP_O && (ops[i] & F_ST) && (ops[i + 1] & 3) == OP_Q) ops[i] |= F_LAZY;
    for (int i = n; i < MAX_OPS; i++) ops[i] = OP_END;
    annotate(ops, n, false);
    for (int i = 0; i < n; i++) {
      if ((ops[i] & 3) != OP_A && (P.dbg & 8)) ops[i + 1] |= F_SOON;
      if ((ops[i] & 3) != OP_A) continue;
      const int w = (ops[i] >> 2) & 7;
      int dist = 0;
      for (int j = i + 1; j < n; j++) {
        const int a = (ops[j] >> 2) & 7, b = (ops[j] >> 5) & 15;
        if ((ops[j] & 3) == OP_O && w < b) {
          for (int k = 0; k < b - a && o_wave(a, b, k, (P.dbg >> 4) & 7) != w; k++) dist += 10;
          break;
        }
        dist += (ops[j] & 3) == OP_Q ? 10 : (ops[j] & 3) == OP_A ? 32 : 10 * (b - a);
      }
      if (dist <= (int)((P.dbg >> 8) & 255)) ops[i + 1] |= F_SOON;
    }
  }
  for (int i = 1; i < n_req; i++)
    for (int j = i; j > 0 && req[j].when < req[j - 1].when; j--) { Req r = req[j]; req[j] = req[j - 1]; req[j - 1] = r; }
  for (int h = 0; h < N_HELP; h++) {
    uint32_t* ops = P.ops[N_TEAM + 2 * h];
    int n = 0;
    for (int i = 0; i < n_req; i++)
      for (int m = h; m < 4; m += N_HELP) {
        const uint32_t ro = 4 * req[i].team + m;
        ops[n++] = req[i].slot >= 0 ? OP_Q | req[i].wave << 2 | req[i].team << 5 | F_PARK | req[i].slot << 10 | m << 12
                                    : OP_O | -req[i].slot << 5 | F_ST | F_LAZY | F_SOON | (ro & 7) << 9 | (ro >> 3) << 29;
      }
    for (int i = n; i < 2 * MAX_OPS; i++) ops[i] = OP_END | F_SOON;
    annotate(ops, n, true);
  }
  for (int i = 0; i < 32; i++) P.first[i] = i < N_TEAM ? P.ops[i][0] : i < N_TEAM + N_HELP ? P.ops[2 * i - N_TEAM][0] : 0;
}

const char* const kPrograms[N_TEAM] = {
  "Q0A0Q1A1H2A2Q3A3O03Q4A4Q5A5Q6A6Q7A7O38",
  "Q0A0Q1A1Q2A2Q3A3O04Q4A4Q5A5Q6A6H7A7O48",
  "Q0A0H1A1Q2A2Q3A3Q4A4O05Q5A5Q6A6Q7A7O58",
  "Q0A0Q1A1Q2A2Q3A3Q4A4O05Q5A5Q6A6H7A7O58",
  "Q0A0Q1A1Q2A2O03Q3A3H4A4Q5A5Q6A6Q7A7O38",
  "Q0A0Q1A1H2A2Q3A3Q4A4O05Q5A5Q6A6Q7A7O58",
  "Q0A0Q1A1Q2A2Q3A3O03Q4A4H5A5Q6A6Q7A7O38",
  "Q0A0Q1A1Q2A2O03Q3A3Q4A4Q5A5Q6A6H7A7O38",
  "P2P3Q0A0Q1A1A2A3H4A4Q5A5Q6A6Q7A7O08",
  "P3P7Q0A0Q1A1H2A2A3Q4A4Q5A5Q6A6A7G1O18",
  "Q0A0Q1A1Q2A2O02Q3A3H4A4Q5A5Q6A6Q7A7O28",
  "P3P5Q0A0Q1A1Q2A2A3Q4A4A5Q6A6H7A7O08",
  "Q0A0Q1A1Q2A2O02Q3A3Q4A4H5A5Q6A6Q7A7O28",
  "P7Q0A0Q1A1Q2A2Q3A3Q4A4Q5A5Q6A6A7G1O18",
  "Q0A0Q1A1Q2A2H3A3Q4A4Q5A5Q6A6Q7A7O08",
  "P5Q0A0Q1A1Q2A2Q3A3Q4A4A5Q6A6H7A7O08",
};

const char* const* bench_programs() {
  return kPrograms;
}

}

extern "C" void kernel_launch(void* const* d_in, const int* in_sizes, int n_in, void* d_out, int out_size) {
  (void)in_sizes; (void)n_in; (void)out_size;
  static EncodeFn fn = nullptr;
  static int n_clusters = 0;
  if (!fn) {
    cudaDriverEntryPointQueryResult qr;
    void* f = nullptr;
    cudaGetDriverEntryPoint("cuTensorMapEncodeTiled", &f, cudaEnableDefault, &qr);
    fn = (EncodeFn)f;
    cudaFuncSetAttribute(fused_kernel, cudaFuncAttributeMaxDynamicSharedMemorySize, SMEM_BYTES);
    cudaLaunchConfig_t cfg = {};
    cfg.gridDim = dim3(132); cfg.blockDim = dim3(384); cfg.dynamicSmemBytes = SMEM_BYTES;
    cudaLaunchAttribute at[1];
    at[0].id = cudaLaunchAttributeClusterDimension; at[0].val.clusterDim.x = 2; at[0].val.clusterDim.y = 1; at[0].val.clusterDim.z = 1;
    cfg.attrs = at; cfg.numAttrs = 1;
    if (cudaOccupancyMaxActiveClusters(&n_clusters, fused_kernel, &cfg) != cudaSuccess || n_clusters < 1) n_clusters = 1;
    (void)cudaGetLastError();
  }
  Params P;
  const CUtensorMapSwizzle S128 = CU_TENSOR_MAP_SWIZZLE_128B, S64 = CU_TENSOR_MAP_SWIZZLE_64B;
  for (int blk = 0; blk < 2; blk++) {
    void* const* in = d_in + 5 * blk;
    { const cuuint64_t d[] = {kD, kB * kSq}, s[] = {kD * 2}; const cuuint32_t b[] = {64, 128};
      encode(fn, &P.x[blk], in[0], 2, d, s, b, S128); }
    { const cuuint64_t d[] = {64, 8, 3, (cuuint64_t)kB * kH * kSk / 8}, s[] = {kDh * 2, 128, 8 * kDh * 2}; const cuuint32_t b[] = {64, 8, 3, 8};
      encode(fn, &P.k[blk], in[1], 4, d, s, b, S128);
      encode(fn, &P.v[blk], in[2], 4, d, s, b, S128); }
    { const cuuint64_t d[] = {64, kD, kHD / 64}, s[] = {kHD * 2, 128}; const cuuint32_t b[] = {64, 64, 3};
      encode(fn, &P.wq[blk], in[3], 3, d, s, b, S128); }
    { const cuuint64_t d[] = {32, 2, kHD / 8, 4, kD / 32}, s[] = {kD * 2, 8 * kD * 2, 2 * kD * 2, 64}; const cuuint32_t b[] = {32, 2, 4, 4, 5};
      encode(fn, &P.wo[blk], in[4], 5, d, s, b, S64); }
  }
  { const cuuint64_t d[] = {32, kB * kSq, 2 * kD / 32}, s[] = {2 * kD * 2, 64}; const cuuint32_t b[] = {32, 16, 5};
    encode(fn, &P.out, d_out, 3, d, s, b, S64); }

  P.zero = 0;
  P.dbg = 0x5030;
  for (int w = 0; w < 8; w++) P.slot[w] = (P.dbg >> 16) & 15 ? w % ((P.dbg >> 16) & 15) : w;
  if (n_clusters >= N_CL) {
    const bool helpers = n_clusters >= N_CL + N_HELP;
    compile_programs(bench_programs(), helpers, P);
    fused_kernel<<<2 * (N_CL + (helpers ? N_HELP : 0)), 384, SMEM_BYTES>>>(P);
  } else {
    for (int phase = 0; phase < 2; phase++) {
      const char* text[N_TEAM];
      for (int t = 0; t < N_TEAM; t++) text[t] = phase ? "O08" : "Q0A0Q1A1Q2A2Q3A3Q4A4Q5A5Q6A6Q7A7";
      compile_programs(text, false, P);
      fused_kernel<<<2 * N_CL, 384, SMEM_BYTES>>>(P);
    }
  }
}
```

```cpp
#include <cuda_runtime.h>
#include <cuda_bf16.h>
#include <cuda.h>
#include <stdint.h>
#include <stdio.h>

namespace {

constexpr int kB = 8, kSq = 256, kD = 640, kH = 32, kSk = 1024, kDh = 192;
constexpr int kHD = kH * kDh;
#define S1A 7
#define UC0 3
#define UC1 4
#define AQS 1
#define RING_KB 224
constexpr uint32_t RING = RING_KB * 1024;
constexpr uint32_t SZ_KV = 24576;
constexpr uint32_t SZ_WQ = 24576, SZ_WO = 20480, SZ_A = 16384;
constexpr uint32_t SZ_PARK = 24576;
constexpr uint32_t SZ_PART = 16384;
constexpr int NBAR = 10;
#define KVT 4
constexpr int KV_TRANSIT = KVT;
#define EARLY_N 3
constexpr int EARLY = EARLY_N;
constexpr uint32_t KV_CH = 64, KV_SBO = 3072;
constexpr int SMEM_BYTES = RING + 512 + 1024;
constexpr int N_TEAM = 16, N_CL = 64, N_HELP = 2, MAX_OPS = 24, MAX_PARK = 4;
enum { OP_END = 0, OP_Q = 1, OP_A = 2, OP_O = 3, F_PARK = 1 << 9, F_LD = 1 << 12, F_ST = 1 << 13, F_HELP = 1 << 12 };

struct alignas(64) Params {
  uint32_t first[32];
  CUtensorMap x[2], wq[2], k[2], v[2], wo[2], out;
  uint32_t ops[N_TEAM + 2 * N_HELP][MAX_OPS];
  uint32_t zero;
  uint32_t dbg;
};

__device__ uint4 g_o[N_TEAM * 2 * 96 * 1024];
__device__ uint4 g_part[N_CL * 2 * 5 * 1024];
__device__ unsigned int g_done[N_TEAM * 2 * 8];
__device__ unsigned int g_help[N_CL * 2 * MAX_PARK];
__device__ unsigned int g_seen[N_TEAM * 2 * 8];

template <int TB, int TA = 0>
__device__ __forceinline__ void wgmma_ss_n64(float (&d)[32], uint64_t da, uint64_t db, int scale_d) {
  asm volatile("{\n.reg .pred p;\nsetp.ne.b32 p, %34, 0;\n"
    "wgmma.mma_async.sync.aligned.m64n64k16.f32.bf16.bf16 {%0, %1, %2, %3, %4, %5, %6, %7, %8, %9, %10, %11, %12, %13, %14, %15, %16, %17, %18, %19, %20, %21, %22, %23, %24, %25, %26, %27, %28, %29, %30, %31}, %32, %33, p, 1, 1, %35, %36;\n}\n"
    : "+f"(d[0]), "+f"(d[1]), "+f"(d[2]), "+f"(d[3]), "+f"(d[4]), "+f"(d[5]), "+f"(d[6]), "+f"(d[7]), "+f"(d[8]), "+f"(d[9]), "+f"(d[10]), "+f"(d[11]), "+f"(d[12]), "+f"(d[13]), "+f"(d[14]), "+f"(d[15]), "+f"(d[16]), "+f"(d[17]), "+f"(d[18]), "+f"(d[19]), "+f"(d[20]), "+f"(d[21]), "+f"(d[22]), "+f"(d[23]), "+f"(d[24]), "+f"(d[25]), "+f"(d[26]), "+f"(d[27]), "+f"(d[28]), "+f"(d[29]), "+f"(d[30]), "+f"(d[31])
    : "l"(da), "l"(db), "r"(scale_d), "n"(TA), "n"(TB));
}
template <int TB>
__device__ __forceinline__ void wgmma_rs_n64(float (&d)[32], uint32_t a0, uint32_t a1, uint32_t a2, uint32_t a3, uint64_t db, int scale_d) {
  asm volatile("{\n.reg .pred p;\nsetp.ne.b32 p, %37, 0;\n"
    "wgmma.mma_async.sync.aligned.m64n64k16.f32.bf16.bf16 {%0, %1, %2, %3, %4, %5, %6, %7, %8, %9, %10, %11, %12, %13, %14, %15, %16, %17, %18, %19, %20, %21, %22, %23, %24, %25, %26, %27, %28, %29, %30, %31}, {%32, %33, %34, %35}, %36, p, 1, 1, %38;\n}\n"
    : "+f"(d[0]), "+f"(d[1]), "+f"(d[2]), "+f"(d[3]), "+f"(d[4]), "+f"(d[5]), "+f"(d[6]), "+f"(d[7]), "+f"(d[8]), "+f"(d[9]), "+f"(d[10]), "+f"(d[11]), "+f"(d[12]), "+f"(d[13]), "+f"(d[14]), "+f"(d[15]), "+f"(d[16]), "+f"(d[17]), "+f"(d[18]), "+f"(d[19]), "+f"(d[20]), "+f"(d[21]), "+f"(d[22]), "+f"(d[23]), "+f"(d[24]), "+f"(d[25]), "+f"(d[26]), "+f"(d[27]), "+f"(d[28]), "+f"(d[29]), "+f"(d[30]), "+f"(d[31])
    : "r"(a0), "r"(a1), "r"(a2), "r"(a3), "l"(db), "r"(scale_d), "n"(TB));
}
template <int TB, int TA = 0>
__device__ __forceinline__ void wgmma_ss_n160(float (&d)[80], uint64_t da, uint64_t db, int scale_d) {
  asm volatile("{\n.reg .pred p;\nsetp.ne.b32 p, %82, 0;\n"
    "wgmma.mma_async.sync.aligned.m64n160k16.f32.bf16.bf16 {%0, %1, %2, %3, %4, %5, %6, %7, %8, %9, %10, %11, %12, %13, %14, %15, %16, %17, %18, %19, %20, %21, %22, %23, %24, %25, %26, %27, %28, %29, %30, %31, %32, %33, %34, %35, %36, %37, %38, %39, %40, %41, %42, %43, %44, %45, %46, %47, %48, %49, %50, %51, %52, %53, %54, %55, %56, %57, %58, %59, %60, %61, %62, %63, %64, %65, %66, %67, %68, %69, %70, %71, %72, %73, %74, %75, %76, %77, %78, %79}, %80, %81, p, 1, 1, %83, %84;\n}\n"
    : "+f"(d[0]), "+f"(d[1]), "+f"(d[2]), "+f"(d[3]), "+f"(d[4]), "+f"(d[5]), "+f"(d[6]), "+f"(d[7]), "+f"(d[8]), "+f"(d[9]), "+f"(d[10]), "+f"(d[11]), "+f"(d[12]), "+f"(d[13]), "+f"(d[14]), "+f"(d[15]), "+f"(d[16]), "+f"(d[17]), "+f"(d[18]), "+f"(d[19]), "+f"(d[20]), "+f"(d[21]), "+f"(d[22]), "+f"(d[23]), "+f"(d[24]), "+f"(d[25]), "+f"(d[26]), "+f"(d[27]), "+f"(d[28]), "+f"(d[29]), "+f"(d[30]), "+f"(d[31]), "+f"(d[32]), "+f"(d[33]), "+f"(d[34]), "+f"(d[35]), "+f"(d[36]), "+f"(d[37]), "+f"(d[38]), "+f"(d[39]), "+f"(d[40]), "+f"(d[41]), "+f"(d[42]), "+f"(d[43]), "+f"(d[44]), "+f"(d[45]), "+f"(d[46]), "+f"(d[47]), "+f"(d[48]), "+f"(d[49]), "+f"(d[50]), "+f"(d[51]), "+f"(d[52]), "+f"(d[53]), "+f"(d[54]), "+f"(d[55]), "+f"(d[56]), "+f"(d[57]), "+f"(d[58]), "+f"(d[59]), "+f"(d[60]), "+f"(d[61]), "+f"(d[62]), "+f"(d[63]), "+f"(d[64]), "+f"(d[65]), "+f"(d[66]), "+f"(d[67]), "+f"(d[68]), "+f"(d[69]), "+f"(d[70]), "+f"(d[71]), "+f"(d[72]), "+f"(d[73]), "+f"(d[74]), "+f"(d[75]), "+f"(d[76]), "+f"(d[77]), "+f"(d[78]), "+f"(d[79])
    : "l"(da), "l"(db), "r"(scale_d), "n"(TA), "n"(TB));
}
template <int TB>
__device__ __forceinline__ void wgmma_rs_n160(float (&d)[80], uint32_t a0, uint32_t a1, uint32_t a2, uint32_t a3, uint64_t db, int scale_d) {
  asm volatile("{\n.reg .pred p;\nsetp.ne.b32 p, %85, 0;\n"
    "wgmma.mma_async.sync.aligned.m64n160k16.f32.bf16.bf16 {%0, %1, %2, %3, %4, %5, %6, %7, %8, %9, %10, %11, %12, %13, %14, %15, %16, %17, %18, %19, %20, %21, %22, %23, %24, %25, %26, %27, %28, %29, %30, %31, %32, %33, %34, %35, %36, %37, %38, %39, %40, %41, %42, %43, %44, %45, %46, %47, %48, %49, %50, %51, %52, %53, %54, %55, %56, %57, %58, %59, %60, %61, %62, %63, %64, %65, %66, %67, %68, %69, %70, %71, %72, %73, %74, %75, %76, %77, %78, %79}, {%80, %81, %82, %83}, %84, p, 1, 1, %86;\n}\n"
    : "+f"(d[0]), "+f"(d[1]), "+f"(d[2]), "+f"(d[3]), "+f"(d[4]), "+f"(d[5]), "+f"(d[6]), "+f"(d[7]), "+f"(d[8]), "+f"(d[9]), "+f"(d[10]), "+f"(d[11]), "+f"(d[12]), "+f"(d[13]), "+f"(d[14]), "+f"(d[15]), "+f"(d[16]), "+f"(d[17]), "+f"(d[18]), "+f"(d[19]), "+f"(d[20]), "+f"(d[21]), "+f"(d[22]), "+f"(d[23]), "+f"(d[24]), "+f"(d[25]), "+f"(d[26]), "+f"(d[27]), "+f"(d[28]), "+f"(d[29]), "+f"(d[30]), "+f"(d[31]), "+f"(d[32]), "+f"(d[33]), "+f"(d[34]), "+f"(d[35]), "+f"(d[36]), "+f"(d[37]), "+f"(d[38]), "+f"(d[39]), "+f"(d[40]), "+f"(d[41]), "+f"(d[42]), "+f"(d[43]), "+f"(d[44]), "+f"(d[45]), "+f"(d[46]), "+f"(d[47]), "+f"(d[48]), "+f"(d[49]), "+f"(d[50]), "+f"(d[51]), "+f"(d[52]), "+f"(d[53]), "+f"(d[54]), "+f"(d[55]), "+f"(d[56]), "+f"(d[57]), "+f"(d[58]), "+f"(d[59]), "+f"(d[60]), "+f"(d[61]), "+f"(d[62]), "+f"(d[63]), "+f"(d[64]), "+f"(d[65]), "+f"(d[66]), "+f"(d[67]), "+f"(d[68]), "+f"(d[69]), "+f"(d[70]), "+f"(d[71]), "+f"(d[72]), "+f"(d[73]), "+f"(d[74]), "+f"(d[75]), "+f"(d[76]), "+f"(d[77]), "+f"(d[78]), "+f"(d[79])
    : "r"(a0), "r"(a1), "r"(a2), "r"(a3), "l"(db), "r"(scale_d), "n"(TB));
}
template <int TB, int TA = 0>
__device__ __forceinline__ void wgmma_ss_n192(float (&d)[96], uint64_t da, uint64_t db, int scale_d) {
  asm volatile("{\n.reg .pred p;\nsetp.ne.b32 p, %98, 0;\n"
    "wgmma.mma_async.sync.aligned.m64n192k16.f32.bf16.bf16 {%0, %1, %2, %3, %4, %5, %6, %7, %8, %9, %10, %11, %12, %13, %14, %15, %16, %17, %18, %19, %20, %21, %22, %23, %24, %25, %26, %27, %28, %29, %30, %31, %32, %33, %34, %35, %36, %37, %38, %39, %40, %41, %42, %43, %44, %45, %46, %47, %48, %49, %50, %51, %52, %53, %54, %55, %56, %57, %58, %59, %60, %61, %62, %63, %64, %65, %66, %67, %68, %69, %70, %71, %72, %73, %74, %75, %76, %77, %78, %79, %80, %81, %82, %83, %84, %85, %86, %87, %88, %89, %90, %91, %92, %93, %94, %95}, %96, %97, p, 1, 1, %99, %100;\n}\n"
    : "+f"(d[0]), "+f"(d[1]), "+f"(d[2]), "+f"(d[3]), "+f"(d[4]), "+f"(d[5]), "+f"(d[6]), "+f"(d[7]), "+f"(d[8]), "+f"(d[9]), "+f"(d[10]), "+f"(d[11]), "+f"(d[12]), "+f"(d[13]), "+f"(d[14]), "+f"(d[15]), "+f"(d[16]), "+f"(d[17]), "+f"(d[18]), "+f"(d[19]), "+f"(d[20]), "+f"(d[21]), "+f"(d[22]), "+f"(d[23]), "+f"(d[24]), "+f"(d[25]), "+f"(d[26]), "+f"(d[27]), "+f"(d[28]), "+f"(d[29]), "+f"(d[30]), "+f"(d[31]), "+f"(d[32]), "+f"(d[33]), "+f"(d[34]), "+f"(d[35]), "+f"(d[36]), "+f"(d[37]), "+f"(d[38]), "+f"(d[39]), "+f"(d[40]), "+f"(d[41]), "+f"(d[42]), "+f"(d[43]), "+f"(d[44]), "+f"(d[45]), "+f"(d[46]), "+f"(d[47]), "+f"(d[48]), "+f"(d[49]), "+f"(d[50]), "+f"(d[51]), "+f"(d[52]), "+f"(d[53]), "+f"(d[54]), "+f"(d[55]), "+f"(d[56]), "+f"(d[57]), "+f"(d[58]), "+f"(d[59]), "+f"(d[60]), "+f"(d[61]), "+f"(d[62]), "+f"(d[63]), "+f"(d[64]), "+f"(d[65]), "+f"(d[66]), "+f"(d[67]), "+f"(d[68]), "+f"(d[69]), "+f"(d[70]), "+f"(d[71]), "+f"(d[72]), "+f"(d[73]), "+f"(d[74]), "+f"(d[75]), "+f"(d[76]), "+f"(d[77]), "+f"(d[78]), "+f"(d[79]), "+f"(d[80]), "+f"(d[81]), "+f"(d[82]), "+f"(d[83]), "+f"(d[84]), "+f"(d[85]), "+f"(d[86]), "+f"(d[87]), "+f"(d[88]), "+f"(d[89]), "+f"(d[90]), "+f"(d[91]), "+f"(d[92]), "+f"(d[93]), "+f"(d[94]), "+f"(d[95])
    : "l"(da), "l"(db), "r"(scale_d), "n"(TA), "n"(TB));
}
template <int TB>
__device__ __forceinline__ void wgmma_rs_n192(float (&d)[96], uint32_t a0, uint32_t a1, uint32_t a2, uint32_t a3, uint64_t db, int scale_d) {
  asm volatile("{\n.reg .pred p;\nsetp.ne.b32 p, %101, 0;\n"
    "wgmma.mma_async.sync.aligned.m64n192k16.f32.bf16.bf16 {%0, %1, %2, %3, %4, %5, %6, %7, %8, %9, %10, %11, %12, %13, %14, %15, %16, %17, %18, %19, %20, %21, %22, %23, %24, %25, %26, %27, %28, %29, %30, %31, %32, %33, %34, %35, %36, %37, %38, %39, %40, %41, %42, %43, %44, %45, %46, %47, %48, %49, %50, %51, %52, %53, %54, %55, %56, %57, %58, %59, %60, %61, %62, %63, %64, %65, %66, %67, %68, %69, %70, %71, %72, %73, %74, %75, %76, %77, %78, %79, %80, %81, %82, %83, %84, %85, %86, %87, %88, %89, %90, %91, %92, %93, %94, %95}, {%96, %97, %98, %99}, %100, p, 1, 1, %102;\n}\n"
    : "+f"(d[0]), "+f"(d[1]), "+f"(d[2]), "+f"(d[3]), "+f"(d[4]), "+f"(d[5]), "+f"(d[6]), "+f"(d[7]), "+f"(d[8]), "+f"(d[9]), "+f"(d[10]), "+f"(d[11]), "+f"(d[12]), "+f"(d[13]), "+f"(d[14]), "+f"(d[15]), "+f"(d[16]), "+f"(d[17]), "+f"(d[18]), "+f"(d[19]), "+f"(d[20]), "+f"(d[21]), "+f"(d[22]), "+f"(d[23]), "+f"(d[24]), "+f"(d[25]), "+f"(d[26]), "+f"(d[27]), "+f"(d[28]), "+f"(d[29]), "+f"(d[30]), "+f"(d[31]), "+f"(d[32]), "+f"(d[33]), "+f"(d[34]), "+f"(d[35]), "+f"(d[36]), "+f"(d[37]), "+f"(d[38]), "+f"(d[39]), "+f"(d[40]), "+f"(d[41]), "+f"(d[42]), "+f"(d[43]), "+f"(d[44]), "+f"(d[45]), "+f"(d[46]), "+f"(d[47]), "+f"(d[48]), "+f"(d[49]), "+f"(d[50]), "+f"(d[51]), "+f"(d[52]), "+f"(d[53]), "+f"(d[54]), "+f"(d[55]), "+f"(d[56]), "+f"(d[57]), "+f"(d[58]), "+f"(d[59]), "+f"(d[60]), "+f"(d[61]), "+f"(d[62]), "+f"(d[63]), "+f"(d[64]), "+f"(d[65]), "+f"(d[66]), "+f"(d[67]), "+f"(d[68]), "+f"(d[69]), "+f"(d[70]), "+f"(d[71]), "+f"(d[72]), "+f"(d[73]), "+f"(d[74]), "+f"(d[75]), "+f"(d[76]), "+f"(d[77]), "+f"(d[78]), "+f"(d[79]), "+f"(d[80]), "+f"(d[81]), "+f"(d[82]), "+f"(d[83]), "+f"(d[84]), "+f"(d[85]), "+f"(d[86]), "+f"(d[87]), "+f"(d[88]), "+f"(d[89]), "+f"(d[90]), "+f"(d[91]), "+f"(d[92]), "+f"(d[93]), "+f"(d[94]), "+f"(d[95])
    : "r"(a0), "r"(a1), "r"(a2), "r"(a3), "l"(db), "r"(scale_d), "n"(TB));
}

__device__ __forceinline__ uint32_t smem_u32(const void* p) { return (uint32_t)__cvta_generic_to_shared(p); }
__device__ __forceinline__ void wg_fence() { asm volatile("wgmma.fence.sync.aligned;" ::: "memory"); }
__device__ __forceinline__ void wg_commit() { asm volatile("wgmma.commit_group.sync.aligned;" ::: "memory"); }
template <int N> __device__ __forceinline__ void wg_wait() { asm volatile("wgmma.wait_group.sync.aligned %0;" ::"n"(N) : "memory"); }
__device__ __forceinline__ void sched_fence(int& keep, uint32_t zero) {
  asm volatile("{\n.reg .u32 c;\nmov.u32 c, %%clock;\nand.b32 c, c, %1;\nxor.b32 %0, %0, c;\n}\n" : "+r"(keep) : "r"(zero) : "memory");
}
template <int N> __device__ __forceinline__ void fence_regs(float (&r)[N]) {
#pragma unroll
  for (int i = 0; i < N; i++) asm volatile("" : "+f"(r[i])::"memory");
}
template <int N> __device__ __forceinline__ void fence_regs(uint32_t (&r)[N]) {
#pragma unroll
  for (int i = 0; i < N; i++) asm volatile("" : "+r"(r[i])::"memory");
}
__device__ __forceinline__ uint64_t mk_desc(uint32_t a16, uint32_t lbo, uint32_t sbo, uint32_t swz) {
  uint64_t d;
  asm("mov.b64 %0, {%1, %2};" : "=l"(d) : "r"(a16 + ((lbo >> 4) << 16)), "r"((sbo >> 4) | (swz << 30)));
  return d;
}
__device__ __forceinline__ void mbar_init(uint32_t bar, uint32_t cnt) {
  asm volatile("mbarrier.init.shared::cta.b64 [%0], %1;" ::"r"(bar), "r"(cnt) : "memory");
}
__device__ __forceinline__ void mbar_expect(uint32_t bar, uint32_t tx) {
  asm volatile("mbarrier.arrive.expect_tx.shared::cta.b64 _, [%0], %1;" ::"r"(bar), "r"(tx) : "memory");
}
__device__ __forceinline__ bool mbar_test(uint32_t bar, uint32_t ph) {
  uint32_t ok;
  asm volatile("{\n.reg .pred p;\nmbarrier.test_wait.parity.shared::cta.b64 p, [%1], %2;\nselp.u32 %0, 1, 0, p;\n}\n"
               : "=r"(ok) : "r"(bar), "r"(ph) : "memory");
  return ok;
}
__device__ __forceinline__ void mbar_wait(uint32_t bar, uint32_t ph) {
  asm volatile("{\n.reg .pred p;\n.reg .u32 n;\nmov.u32 n, 0;\n"
               "LOOP:\nadd.u32 n, n, 1;\nmbarrier.try_wait.parity.shared::cta.b64 p, [%0], %1;\n@p bra DONE;\n"
               "setp.lt.u32 p, n, 0x1000000;\n@p bra LOOP;\ntrap;\n"
               "DONE:\n}\n" ::"r"(bar), "r"(ph) : "memory");
}
template <int NS> __device__ __forceinline__ void mbar_wait_slow(uint32_t bar, uint32_t ph) {
  asm volatile("{\n.reg .pred p;\n.reg .u32 n;\nmov.u32 n, 0;\n"
               "LOOP:\nmbarrier.test_wait.parity.shared::cta.b64 p, [%0], %1;\n@p bra DONE;\n"
               "nanosleep.u32 %2;\nadd.u32 n, n, 1;\nsetp.lt.u32 p, n, 0x400000;\n@p bra LOOP;\ntrap;\n"
               "DONE:\n}\n" ::"r"(bar), "r"(ph), "n"(NS) : "memory");
}
__device__ __forceinline__ void mbar_arrive_cluster_if(bool on, uint32_t addr) {
  asm volatile("{\n.reg .pred p;\nsetp.ne.b32 p, %1, 0;\n@p mbarrier.arrive.shared::cluster.b64 _, [%0];\n}\n" ::"r"(addr), "r"((int)on) : "memory");
}
__device__ __forceinline__ void mbar_arrive_if(bool on, uint32_t addr) {
  asm volatile("{\n.reg .pred p;\nsetp.ne.b32 p, %1, 0;\n@p mbarrier.arrive.shared::cta.b64 _, [%0];\n}\n" ::"r"(addr), "r"((int)on) : "memory");
}
__device__ __forceinline__ void tma2d(uint32_t dst, const CUtensorMap* m, uint32_t bar, int c0, int c1) {
  asm volatile("cp.async.bulk.tensor.2d.shared::cluster.global.mbarrier::complete_tx::bytes [%0], [%1, {%3, %4}], [%2];"
               ::"r"(dst), "l"(m), "r"(bar), "r"(c0), "r"(c1) : "memory");
}
__device__ __forceinline__ void tma3d(uint32_t dst, const CUtensorMap* m, uint32_t bar, int c0, int c1, int c2) {
  asm volatile("cp.async.bulk.tensor.3d.shared::cluster.global.mbarrier::complete_tx::bytes [%0], [%1, {%3, %4, %5}], [%2];"
               ::"r"(dst), "l"(m), "r"(bar), "r"(c0), "r"(c1), "r"(c2) : "memory");
}
__device__ __forceinline__ void tma3d_mc(uint32_t dst, const CUtensorMap* m, uint32_t bar, int c0, int c1, int c2) {
  asm volatile("cp.async.bulk.tensor.3d.shared::cluster.global.mbarrier::complete_tx::bytes.multicast::cluster"
               " [%0], [%1, {%3, %4, %5}], [%2], %6;"
               ::"r"(dst), "l"(m), "r"(bar), "r"(c0), "r"(c1), "r"(c2), "h"((uint16_t)3) : "memory");
}
__device__ __forceinline__ void tma3d_store(const CUtensorMap* m, uint32_t src, int c0, int c1, int c2) {
  asm volatile("cp.async.bulk.tensor.3d.global.shared::cta.bulk_group [%0, {%2, %3, %4}], [%1];"
               ::"l"(m), "r"(src), "r"(c0), "r"(c1), "r"(c2) : "memory");
}
__device__ __forceinline__ void bar_sync(int id, int n) { asm volatile("bar.sync %0, %1;" ::"r"(id), "r"(n) : "memory"); }
__device__ __forceinline__ uint32_t pack_bf16(float lo, float hi) {
  uint32_t r;
  asm("cvt.rn.bf16x2.f32 %0, %1, %2;" : "=r"(r) : "f"(hi), "f"(lo));
  return r;
}
__device__ __forceinline__ float ex2(float x) {
  float y;
  asm("ex2.approx.ftz.f32 %0, %1;" : "=f"(y) : "f"(x));
  return y;
}
__device__ __forceinline__ float fadd(float a, float b) {
  float y;
  asm("add.f32 %0, %1, %2;" : "=f"(y) : "f"(a), "f"(b));
  return y;
}
__device__ __forceinline__ float rcp(float x) {
  float y;
  asm("rcp.approx.ftz.f32 %0, %1;" : "=f"(y) : "f"(x));
  return y;
}
__device__ __forceinline__ void stsm4(uint32_t addr, uint32_t a, uint32_t b, uint32_t c, uint32_t d) {
  asm volatile("stmatrix.sync.aligned.m8n8.x4.shared.b16 [%0], {%1, %2, %3, %4};" ::"r"(addr), "r"(a), "r"(b), "r"(c), "r"(d) : "memory");
}

__device__ __forceinline__ void tma4d_mc_hint(uint32_t dst, const CUtensorMap* m, uint32_t bar, int c3, uint64_t pol) {
  asm volatile("cp.async.bulk.tensor.4d.shared::cluster.global.mbarrier::complete_tx::bytes.multicast::cluster.L2::cache_hint"
               " [%0], [%1, {%3, %3, %3, %4}], [%2], %5, %6;"
               ::"r"(dst), "l"(m), "r"(bar), "r"(0), "r"(c3), "h"((uint16_t)3), "l"(pol) : "memory");
}
__device__ __forceinline__ void tma5d_mc(uint32_t dst, const CUtensorMap* m, uint32_t bar, int c2, int c4) {
  asm volatile("cp.async.bulk.tensor.5d.shared::cluster.global.mbarrier::complete_tx::bytes.multicast::cluster"
               " [%0], [%1, {%3, %3, %4, %3, %5}], [%2], %6;"
               ::"r"(dst), "l"(m), "r"(bar), "r"(0), "r"(c2), "r"(c4), "h"((uint16_t)3) : "memory");
}
__device__ __forceinline__ void bulk_load_hint(uint32_t dst, const void* src, uint32_t bytes, uint32_t bar, uint64_t pol) {
  asm volatile("cp.async.bulk.shared::cluster.global.mbarrier::complete_tx::bytes.L2::cache_hint [%0], [%1], %2, [%3], %4;"
               ::"r"(dst), "l"(src), "r"(bytes), "r"(bar), "l"(pol) : "memory");
}
__device__ __forceinline__ void stg128_hint(void* p, uint32_t a, uint32_t b, uint32_t c, uint32_t d, uint64_t pol) {
  asm volatile("st.global.L2::cache_hint.v4.b32 [%0], {%1, %2, %3, %4}, %5;" ::"l"(p), "r"(a), "r"(b), "r"(c), "r"(d), "l"(pol) : "memory");
}
__device__ __forceinline__ void stg2_if(bool on, void* p, uint32_t a, uint32_t b, uint32_t c, uint32_t d, uint32_t e, uint32_t f,
                                        uint32_t g, uint32_t h, uint64_t pol) {
  asm volatile("{\n.reg .pred p;\nsetp.ne.b32 p, %10, 0;\n"
               "@p st.global.L2::cache_hint.v4.b32 [%0], {%1, %2, %3, %4}, %9;\n"
               "@p st.global.L2::cache_hint.v4.b32 [%0 + 512], {%5, %6, %7, %8}, %9;\n}\n"
               ::"l"(p), "r"(a), "r"(b), "r"(c), "r"(d), "r"(e), "r"(f), "r"(g), "r"(h), "l"(pol), "r"((int)on) : "memory");
}
__device__ __forceinline__ uint64_t evict_first() {
  uint64_t p;
  asm("createpolicy.fractional.L2::evict_first.b64 %0, 1.0;" : "=l"(p));
  return p;
}
__device__ __forceinline__ bool elect() {
  uint32_t ok;
  asm volatile("{\n.reg .pred p;\nelect.sync _|p, 0xffffffff;\nselp.u32 %0, 1, 0, p;\n}\n" : "=r"(ok));
  return ok;
}
__device__ __forceinline__ void mbar_arrive(uint32_t bar) {
  asm volatile("mbarrier.arrive.shared::cta.b64 _, [%0];" ::"r"(bar) : "memory");
}
__device__ __forceinline__ void stg128(void* p, uint32_t a, uint32_t b, uint32_t c, uint32_t d) {
  asm volatile("st.global.v4.b32 [%0], {%1, %2, %3, %4};" ::"l"(p), "r"(a), "r"(b), "r"(c), "r"(d) : "memory");
}
__device__ __forceinline__ void lds128(uint32_t p, uint32_t& a, uint32_t& b, uint32_t& c, uint32_t& d) {
  asm volatile("ld.shared.v4.b32 {%0, %1, %2, %3}, [%4];" : "=r"(a), "=r"(b), "=r"(c), "=r"(d) : "r"(p) : "memory");
}
__device__ __forceinline__ void wait_count(const unsigned int* p, uint32_t target) {
  asm volatile("{\n.reg .pred p;\n.reg .u32 n, v;\nmov.u32 n, 0;\n"
               "LOOP:\nld.acquire.gpu.global.u32 v, [%0];\nsetp.ge.u32 p, v, %1;\n@p bra DONE;\n"
               "nanosleep.u32 %2;\nadd.u32 n, n, 1;\nsetp.lt.u32 p, n, 0x400000;\n@p bra LOOP;\ntrap;\n"
               "DONE:\n}\n" ::"l"(p), "r"(target), "n"(200) : "memory");
}

__host__ __device__ __forceinline__ int o_wave(int a, int b, int i, int lag) {
  if (lag == 0) return a + i;
  const int p = lag < b - a - 1 ? lag : b - a - 1;
  return i < p ? b - 2 - i : i == p ? b - 1 : b - 1 - i;
}

struct Cursor {
  int bi;
  uint32_t ph;
  __device__ __forceinline__ void next() {
    if (++bi == NBAR) { bi = 0; ph ^= 1; }
  }
};

constexpr float kScaleLog2 = 0.07216878364870322f * 1.4426950408889634f;
constexpr float kSumLimit = 1048576.0f;
constexpr float kMaxLag = 8.0f;

__global__ void __cluster_dims__(2, 1, 1) __launch_bounds__(384, 1)
fused_kernel(const __grid_constant__ Params P) {
  extern __shared__ uint8_t smem_raw[];
  const uint32_t sbase = (smem_u32(smem_raw) + 1023) & ~1023u;
  const uint32_t full0 = sbase + RING, empty0 = full0 + 8 * NBAR, odone = empty0 + 8 * NBAR, oready0 = odone + 8;
  const uint32_t fenced = oready0 + 64, hready0 = fenced + 8;
  const uint32_t rank = blockIdx.x & 1;
  const int role = blockIdx.x >> 1;
  const bool helper = role >= N_CL;
  const int team = helper ? 0 : role >> 2, nt = role & 3, blk = team >> 3;
  const uint32_t* prog = P.ops[helper ? N_TEAM + 2 * (role - N_CL) : team];
  auto q_role = [&](uint32_t op) { return helper ? (int)(((op >> 3) & 60) | ((op >> 12) & 3)) : role; };
  auto o_role = [&](uint32_t op) { return helper ? (int)(((op >> 26) & 56) | ((op >> 9) & 7)) : role; };
  const int wid = __shfl_sync(0xffffffffu, (int)(threadIdx.x >> 5), 0);
  const int wg = wid >> 2;

  const uint32_t op0 = P.first[helper ? N_TEAM + role - N_CL : team];
  if (__builtin_expect(wid == 8, 1)) {
    if (elect()) {
#pragma unroll
      for (int k = 0; k < EARLY; k++) mbar_init(full0 + 8 * k, 1);
      asm volatile("fence.mbarrier_init.release.cluster;" ::: "memory");
      if ((op0 & 3) == OP_Q) {
        const int qr = q_role(op0);
#pragma unroll
        for (int k = 0; k < EARLY; k++) {
          mbar_expect(full0 + 8 * k, SZ_WQ + SZ_A);
          tma2d(sbase + k * (SZ_WQ + SZ_A) + SZ_WQ, &P.x[qr >> 5], full0 + 8 * k, 64 * k, ((qr >> 2) & 7) * kSq + rank * 128);
          tma3d(sbase + k * (SZ_WQ + SZ_A), &P.wq[qr >> 5], full0 + 8 * k, 0, 64 * k, 3 * (4 * ((op0 >> 2) & 7) + (qr & 3)));
        }
      }
      asm volatile("prefetch.tensormap [%0];" ::"l"(rank ? &P.v[blk] : &P.k[blk]) : "memory");
    }
  } else if (threadIdx.x == 0) {
#pragma unroll
    for (int i = EARLY; i < 2 * NBAR + 10 + MAX_PARK; i++) mbar_init(full0 + 8 * i, i >= NBAR && i <= 2 * NBAR ? 16 : 1);
    asm volatile("fence.mbarrier_init.release.cluster;" ::: "memory");
  }
  __syncwarp();
  asm volatile("barrier.cluster.arrive.relaxed.aligned;\nbarrier.cluster.wait.aligned;" ::: "memory");

  if (wg == 2) {
    asm volatile("setmaxnreg.dec.sync.aligned.u32 24;");
    if (wid == 8) {
      Cursor tail{0, 0};
      int head = 0, sh = 0;
      uint32_t hph = 0;
      uint32_t cur = 0, used = 0;
      uint64_t fifo = 0;
      uint32_t dst, bar, oready = oready0;
      const uint64_t pol = evict_first();
      const CUtensorMap* kv_map = rank ? &P.v[blk] : &P.k[blk];
      auto acquire = [&](uint32_t bytes, int part = 0) {
        uint32_t fp = bytes >> 12;
        if (cur + fp > (RING >> 12)) { fp += (RING >> 12) - cur; cur = 0; }
        used += fp;
        bool more = false;
        uint32_t wbar, wph;
        while (used > (RING >> 12) || (part != 2 && sh == 5 * NBAR)) {
          if (more) mbar_wait(wbar, wph);
          more = true;
          wbar = empty0 + 8 * tail.bi; wph = tail.ph;
          tail.next();
          used -= (uint32_t)fifo & 31;
          fifo >>= 5;
          sh -= 5;
        }
        fifo += (uint64_t)fp << sh;
        dst = sbase + (cur << 12);
        bar = full0 + 8 * head;
        cur += bytes >> 12;
        if (part != 1) {
          sh += 5;
          if (++head == NBAR) { head = 0; hph ^= 1; }
        }
        if (more) mbar_wait(wbar, wph);
      };
      auto scratch = [&](const uint4* src, uint32_t bytes, int n) {
        asm volatile("fence.proxy.async.global;" ::: "memory");
#pragma unroll 1
        for (int i = 0; i < n; i++) {
          acquire(bytes);
          if (elect()) {
            bulk_load_hint(dst, src + i * (bytes / 16), bytes, bar, pol);
            mbar_expect(bar, bytes);
          }
        }
      };
      for (int pc = 0;; pc++) {
        const uint32_t op = prog[pc];
        const int type = op & 3, a = (op >> 2) & 7;
        if (type == OP_END) break;
        if (type == OP_Q) {
          const int qr = q_role(op);
#pragma unroll 1
          for (int k = 0; k < 10; k++) {
            acquire(SZ_WQ, 1);
            if ((pc > 0 || k >= EARLY) && (k & 1) == rank && elect()) tma3d_mc(dst, &P.wq[qr >> 5], bar, 0, 64 * k, 3 * (4 * a + (qr & 3)));
            acquire(SZ_A, 2);
            if ((pc > 0 || k >= EARLY) && elect()) {
              tma2d(dst, &P.x[qr >> 5], bar, 64 * k, ((qr >> 2) & 7) * kSq + rank * 128);
              mbar_expect(bar, SZ_WQ + SZ_A);
            }
          }
        } else if (type == OP_A) {
          const uint32_t nop = prog[pc + 1];
#pragma unroll 1
          for (int t = (op & F_PARK) ? 1 : 0; t < 33; t++) {
            int wave = a;
            if (t == 31 && (nop & 3) != OP_A) t++;
            if (t == 31) {
              wave = (nop >> 2) & 7;
              mbar_wait((nop & F_HELP) ? hready0 + 8 * ((nop >> 10) & 3) : fenced, 0);
              scratch(&g_o[((team * 2 + rank) * 96 + 3 * (4 * wave + nt)) * 1024], SZ_PARK, 2);
            }
            const int isv = t ? ~t & 1 : 0, j = (isv ? (t - 1) >> 1 : (t + 1) >> 1) & 15;
            const int row0 = ((team & 7) * kH + 4 * wave + nt) * kSk;
            acquire(SZ_KV);
            if (isv == (int)rank && t >= KV_TRANSIT) {
              const int i = head - 1 - KV_TRANSIT;
              mbar_wait(full0 + 8 * (i < 0 ? i + NBAR : i), i < 0 ? hph ^ 1 : hph);
            }
            if (elect()) {
              if (isv == (int)rank) tma4d_mc_hint(dst, kv_map, bar, row0 / 8 + 8 * j, pol);
              mbar_expect(bar, SZ_KV);
            }
          }
        } else {
          const int b = (op >> 5) & 15, ro = o_role(op);
#pragma unroll 1
          for (int i = 0; i < b - a; i++) {
            const int w = o_wave(a, b, i, (P.dbg >> 4) & 7);
            mbar_wait(oready, 0);
            oready += 8;
            asm volatile("fence.proxy.async.global;" ::: "memory");
#pragma unroll 1
            for (int k = 12 * w; k < 12 * w + 12; k++) {
              acquire(SZ_A, 1);
              if (elect()) bulk_load_hint(dst, &g_o[(((ro >> 2) * 2 + rank) * 96 + k) * 1024], SZ_A, bar, pol);
              acquire(SZ_WO, 2);
              if (elect()) {
                tma5d_mc(dst + rank * 10240, &P.wo[ro >> 5], bar, 8 * k + 4 * rank, 5 * (ro & 3));
                mbar_expect(bar, SZ_WO + SZ_A);
              }
            }
          }
          if (op & F_LD) {
            if (op & F_PARK) mbar_wait(hready0 + 8 * (MAX_PARK - 1), 0);
            scratch(&g_part[(role * 2 + rank) * 5120], SZ_PART, 5);
          }
        }
      }
    } else if (threadIdx.x == 288) {
      uint32_t ph = 0;
      bool first = true;
      for (int pc = 0;; pc++) {
        const uint32_t op = prog[pc];
        if ((op & 3) == OP_END) break;
        if ((op & 3) != OP_A && !helper) continue;
        mbar_wait_slow<400>(odone, ph);
        ph ^= 1;
        unsigned int* flag = !helper ? &g_done[(team * 2 + rank) * 8 + ((op >> 2) & 7)]
                             : (op & 3) == OP_Q ? &g_help[(q_role(op) * 2 + rank) * MAX_PARK + ((op >> 10) & 3)]
                                                : &g_help[(o_role(op) * 2 + rank) * MAX_PARK + MAX_PARK - 1];
        asm volatile("red.release.gpu.global.add.u32 [%0], 1;" ::"l"(flag) : "memory");
        if (first) mbar_arrive(fenced);
        first = false;
      }
    } else if (threadIdx.x == 320) {
      uint32_t oready = oready0;
      for (int pc = 0;; pc++) {
        const uint32_t op = prog[pc];
        if ((op & 3) == OP_END) break;
        if ((op & 3) == OP_O) {
          const int a = (op >> 2) & 7, b = (op >> 5) & 15;
#pragma unroll 1
          for (int i = 0; i < b - a; i++) {
            const int ci = ((o_role(op) >> 2) * 2 + rank) * 8 + o_wave(a, b, i, (P.dbg >> 4) & 7);
            wait_count(&g_done[ci], 4);
            mbar_arrive(oready);
            oready += 8;
            if (atomicAdd(&g_seen[ci], 1u) == 3u) { g_seen[ci] = 0; g_done[ci] = 0; }
          }
        }
        if ((op & 3) != OP_Q && (op & F_HELP) && (op & F_PARK)) {
          unsigned int* flag = &g_help[(role * 2 + rank) * MAX_PARK + ((op >> 10) & 3)];
          wait_count(flag, 1);
          mbar_arrive(hready0 + 8 * ((op >> 10) & 3));
          *flag = 0;
        }
      }
    }
    __syncwarp();
    asm volatile("barrier.cluster.arrive.relaxed;\nbarrier.cluster.wait;" ::: "memory");
  } else {
    asm volatile("setmaxnreg.inc.sync.aligned.u32 240;");
    const int lane = threadIdx.x & 31, warp = wid & 3;
    uint32_t empty_rem;
    asm volatile("mapa.shared::cluster.u32 %0, %1, %2;" : "=r"(empty_rem) : "r"(empty0), "r"(lane & 1));
    auto release = [&](int slot) { mbar_arrive_cluster_if(lane < 2, empty_rem + 8 * slot); };
    Cursor r{0, 0};
    const uint32_t ring16 = (sbase & 0x3FFFF) >> 4;
    uint32_t cur = ring16;
    bool rdy0 = false, rdy1 = false;
    auto probe1 = [&]() { rdy0 = mbar_test(full0 + 8 * r.bi, r.ph); };
    auto probe2 = [&]() {
      Cursor n = r;
      rdy0 = mbar_test(full0 + 8 * n.bi, n.ph);
      n.next();
      rdy1 = mbar_test(full0 + 8 * n.bi, n.ph);
    };
    auto take = [&](bool rdy, uint32_t bytes, uint32_t& addr) {
      const int bi = r.bi;
      if (!__all_sync(0xffffffffu, rdy)) mbar_wait(full0 + 8 * r.bi, r.ph);
      r.next();
      if (cur > ring16 + ((RING - bytes) >> 4)) cur = ring16;
      addr = cur;
      cur += bytes >> 4;
      return bi;
    };
    auto second = [&](uint32_t bytes) {
      if (cur > ring16 + ((RING - bytes) >> 4)) cur = ring16;
      cur += bytes >> 4;
      return cur - (bytes >> 4);
    };
    const int row = wg * 64 + warp * 16 + (lane >> 2);
    int img0 = row * 4 + ((lane & 3) ^ ((row >> 1) & 3));
    uint4* pend = nullptr;
    const uint64_t spol = evict_first();
    int pc = 0;
    uint32_t op = prog[0];
    auto enter = [&]() {
      r.bi = (op >> 15) & 15; r.ph = (op >> 19) & 1; cur = ring16 + (((op >> 20) & 63) << 8);
    };
    auto drain = [&](uint32_t (&t)[48], uint32_t c) {
      if (!(op & (3u << 26)) || c >= 6) return;
#pragma unroll
      for (int i = 0; i < 6; i++)
        stg2_if(c == i, pend + i * 512, t[8 * i], t[8 * i + 1], t[8 * i + 2], t[8 * i + 3],
                t[8 * i + 4], t[8 * i + 5], t[8 * i + 6], t[8 * i + 7], spol);
      if ((op & (1u << 26)) && c == 5) {
        __syncwarp();
        mbar_arrive_if(lane < 2, odone);
      }
    };
    float s[32], o[96], c[80];
    uint32_t q[48], pa[16], pb[16];
    float mc0, mc1, l0, l1;
    bool gen;
    auto soft = [&](float (&s)[32], uint32_t (&pout)[16], bool first) {
      if (first) { gen = false; mc0 = 0.f; mc1 = 0.f; }
      float b0, b1;
      for (;;) {
        if (gen) {
          float m0 = fmaxf(s[0], s[1]), m1 = fmaxf(s[2], s[3]);
#pragma unroll
          for (int i = 1; i < 8; i++) { m0 = fmaxf(m0, fmaxf(s[4 * i], s[4 * i + 1])); m1 = fmaxf(m1, fmaxf(s[4 * i + 2], s[4 * i + 3])); }
          m0 = fmaxf(m0, __shfl_xor_sync(0xffffffffu, m0, 1)); m1 = fmaxf(m1, __shfl_xor_sync(0xffffffffu, m1, 1));
          m0 = fmaxf(m0, __shfl_xor_sync(0xffffffffu, m0, 2)); m1 = fmaxf(m1, __shfl_xor_sync(0xffffffffu, m1, 2));
          if (first) {
            mc0 = m0; mc1 = m1;
          } else if (__any_sync(0xffffffffu, !(m0 <= mc0 + kMaxLag && m1 <= mc1 + kMaxLag))) {
            m0 = fmaxf(mc0, m0); m1 = fmaxf(mc1, m1);
            const float a0 = ex2(mc0 - m0), a1 = ex2(mc1 - m1);
            mc0 = m0; mc1 = m1;
            l0 *= a0; l1 *= a1;
            wg_wait<0>();
            fence_regs(o);
#pragma unroll
            for (int i = 0; i < 96; i++) o[i] *= i & 2 ? a1 : a0;
          }
#pragma unroll
          for (int i = 0; i < 32; i++) s[i] -= i & 2 ? mc1 : mc0;
        }
#pragma unroll
        for (int i = 0; i < 8; i++) {
          const float e1 = ex2(s[4 * i + 1]), e0 = ex2(s[4 * i]), e3 = ex2(s[4 * i + 3]), e2 = ex2(s[4 * i + 2]);
          pout[2 * i] = pack_bf16(e0, e1);
          b0 = i ? b0 + fadd(e1, e0) : fadd(e1, e0);
          pout[2 * i + 1] = pack_bf16(e2, e3);
          b1 = i ? b1 + fadd(e3, e2) : fadd(e3, e2);
        }
        if (!__any_sync(0xffffffffu, !gen && !(fmaxf(b0, b1) <= kSumLimit && (!first || fminf(b0, b1) >= 1.0f / kSumLimit)))) break;
        gen = __any_sync(0xffffffffu, true);
      }
      l0 = first ? b0 : l0 + b0;
      l1 = first ? b1 : l1 + b1;
    };
    auto qk = [&](float (&s)[32], uint32_t ak, int k0, int k1) {
#pragma unroll
      for (int kk = k0; kk < k1; kk++)
        wgmma_rs_n64<0>(s, q[4 * kk], q[4 * kk + 1], q[4 * kk + 2], q[4 * kk + 3], mk_desc(ak + (kk >> 2) * KV_CH + (kk & 3) * 2, 16, KV_SBO, 1), kk != 0);
      wg_commit();
    };
    auto pv = [&](uint32_t (&pin)[16], uint32_t av, int acc) {
#pragma unroll
      for (int kk = 0; kk < 4; kk++)
        wgmma_rs_n192<1>(o, pin[4 * kk], pin[4 * kk + 1], pin[4 * kk + 2], pin[4 * kk + 3], mk_desc(av + kk * (KV_SBO / 8), KV_CH * 16, KV_SBO, 1), acc || (kk != 0));
      wg_commit();
    };
    auto xw = [&](uint32_t ad, int acc) {
      const uint32_t da = second(SZ_A) + wg * 512;
      wg_fence();
#pragma unroll
      for (int kk = 0; kk < 4; kk++)
        wgmma_ss_n192<1>(o, mk_desc(da + kk * 2, 16, 1024, 1), mk_desc(ad + kk * 128, 8192, 1024, 1), acc || kk != 0);
      wg_commit();
    };
    auto ow = [&](int acc, int prev) {
      uint32_t da;
      const int bi = take(rdy0, SZ_A, da);
      const uint32_t db = second(SZ_WO);
      da += wg * 256;
      wg_fence();
      wgmma_ss_n160<1>(c, mk_desc(da, 16, 512, 2), mk_desc(db, 2048, 512, 2), acc);
      wgmma_ss_n160<1>(c, mk_desc(da + 2, 16, 512, 2), mk_desc(db + 64, 2048, 512, 2), 1);
      wg_commit();
      if (acc) { wg_wait<1>(); release(prev); }
      wgmma_ss_n160<1>(c, mk_desc(da + 512, 16, 512, 2), mk_desc(db + 640, 2048, 512, 2), 1);
      wgmma_ss_n160<1>(c, mk_desc(da + 514, 16, 512, 2), mk_desc(db + 704, 2048, 512, 2), 1);
      wg_commit();
      return bi;
    };
    auto st_part = [&](int i) {
      stg2_if(true, pend + i * 512, __float_as_uint(c[8 * i]), __float_as_uint(c[8 * i + 1]), __float_as_uint(c[8 * i + 2]), __float_as_uint(c[8 * i + 3]),
              __float_as_uint(c[8 * i + 4]), __float_as_uint(c[8 * i + 5]), __float_as_uint(c[8 * i + 6]), __float_as_uint(c[8 * i + 7]), spol);
    };
#pragma unroll
    for (int i = 0; i < 48; i++) q[i] = 0;
    enter();

    if ((op & 3) == OP_Q) {
      uint32_t ad;
      int bi0 = take(false, SZ_WQ, ad), k = 0, lag = 0;
      xw(ad, 0);
      for (;;) {
#pragma unroll 1
        for (;;) {
          drain(q, k - lag);
          probe1();
          wg_wait<0>();
          release(bi0);
          bi0 = take(rdy0, SZ_WQ, ad);
          if (++k == 8) break;
          xw(ad, 1);
        }
        if (wg) bar_sync(2, 256);
        xw(ad, 1);
        const int bi9 = take(false, SZ_WQ, ad);
        xw(ad, 1);
        if (!wg) asm volatile("bar.arrive 2, 256;" ::: "memory");
        k = 0; lag = 0;
        uint32_t nop = prog[++pc];
        wg_wait<1>();
        release(bi0);
        probe2();
        wg_wait<0>();
        fence_regs(o);
        release(bi9);
#pragma unroll
        for (int i = 0; i < 48; i++) q[i] = pack_bf16(o[2 * i] * kScaleLog2, o[2 * i + 1] * kScaleLog2);
        fence_regs(q);
        if (op & F_PARK) {
          const int qt = helper ? (op >> 5) & 15 : team, qm = helper ? (op >> 12) & 3 : nt;
          pend = &g_o[((qt * 2 + rank) * 96 + 3 * (4 * ((op >> 2) & 7) + qm)) * 1024 + img0];
          op = nop;
          enter();
          if ((op & 3) != OP_Q) break;
          bi0 = take(rdy0, SZ_WQ, ad);
          xw(ad, 0);
          continue;
        }
        int wave = (op >> 2) & 7, sk1;
        uint32_t ak1;
        {
          float s0[32];
          const int sk0 = take(rdy0, SZ_KV, ad);
          wg_fence();
          qk(s0, ad, 0, 12);
          sk1 = take(rdy1, SZ_KV, ak1);
          wg_fence();
          qk(s, ak1, 0, S1A);
          probe1();
          wg_wait<1>();
          fence_regs(s0);
          release(sk0);
          soft(s0, pa, true);
        }
        float i0, i1;
        auto sums = [&]() {
          l0 += __shfl_xor_sync(0xffffffffu, l0, 1); l1 += __shfl_xor_sync(0xffffffffu, l1, 1);
          l0 += __shfl_xor_sync(0xffffffffu, l0, 2); l1 += __shfl_xor_sync(0xffffffffu, l1, 2);
          i0 = rcp(l0); i1 = rcp(l1);
          asm volatile("" : "+f"(i0), "+f"(i1));
        };
        auto target = [&]() {
          pend = &g_o[((team * 2 + rank) * 96 + 3 * (4 * wave + nt)) * 1024 + img0];
          asm volatile("" : "+l"(pend));
        };
        for (;;) {
          nop = prog[++pc];
          {
            uint32_t av;
            const int sv = take(rdy0, SZ_KV, av);
            wg_fence();
            qk(s, ak1, S1A, 12);
            pv(pa, av, 0);
            probe2();
            wg_wait<1>();
            fence_regs(s);
            release(sk1);
            soft(s, pb, false);
            wg_wait<0>();
            fence_regs(o);
            release(sv);
          }
          auto step = [&](uint32_t (&pin)[16], uint32_t (&pout)[16]) {
            uint32_t ak, av;
            const int sk = take(rdy0, SZ_KV, ak), sv = take(rdy1, SZ_KV, av);
            wg_fence();
            qk(s, ak, 0, 12);
            pv(pin, av, 1);
            probe2();
            wg_wait<1>();
            fence_regs(s);
            release(sk);
            soft(s, pout, false);
            wg_wait<0>();
            fence_regs(o);
            release(sv);
          };
#pragma unroll 1
          for (int jj = 0; jj < 7; jj++) {
            step(pb, pa);
            step(pa, pb);
          }
          if ((nop & 3) != OP_A) break;
          uint32_t ak, av;
          {
            const int b0 = take(rdy0, SZ_PARK, ak), b1 = take(rdy1, SZ_PARK, av);
            const uint32_t ad0 = ak, ad1 = av;
            probe2();
#pragma unroll
            for (int i = 0; i < 12; i++)
              lds128(sbase + ((i < 6 ? ad0 : ad1) - ring16 + img0) * 16 + ((i % 6) >> 1) * 8192 + (i & 1) * 512, q[4 * i], q[4 * i + 1], q[4 * i + 2], q[4 * i + 3]);
            release(b0); release(b1);
          }
          const int sk0 = take(rdy0, SZ_KV, ak), sv = take(rdy1, SZ_KV, av);
          wg_fence();
          qk(s, ak, 0, 8);
          sched_fence(img0, P.zero);
          sums();
          sched_fence(img0, P.zero);
          qk(s, ak, 8, 12);
          pv(pb, av, 1);
          probe2();
          wg_wait<1>();
          fence_regs(s);
          release(sk0);
          soft(s, pa, true);
          sk1 = take(rdy0, SZ_KV, ak1);
          rdy0 = rdy1;
          wg_wait<0>();
          target();
          fence_regs(o);
          release(sv);
          uint32_t t[48];
#pragma unroll
          for (int j = 0; j < 6; j++) {
#pragma unroll
            for (int i = 0; i < 4; i++) {
              t[8 * j + i] = pack_bf16(o[16 * j + 4 * i] * i0, o[16 * j + 4 * i + 1] * i0);
              t[8 * j + i + 4] = pack_bf16(o[16 * j + 4 * i + 2] * i1, o[16 * j + 4 * i + 3] * i1);
            }
            stg2_if(true, pend + j * 512, t[8 * j], t[8 * j + 1], t[8 * j + 2], t[8 * j + 3], t[8 * j + 4], t[8 * j + 5], t[8 * j + 6], t[8 * j + 7], spol);
            if (j == UC0) { wg_fence(); qk(s, ak1, 0, 4); }
            if (j == UC1) { wg_fence(); qk(s, ak1, 4, S1A); }
            sched_fence(img0, P.zero);
          }
          if (P.zero) {
#pragma unroll
            for (int j = 0; j < 5; j++)
              stg2_if(true, pend, t[8 * j], t[8 * j + 1], t[8 * j + 2], t[8 * j + 3], t[8 * j + 4], t[8 * j + 5], t[8 * j + 6], t[8 * j + 7], spol);
          }
          __syncwarp();
          mbar_arrive_if(lane < 2, odone);
          wave = (nop >> 2) & 7;
        }
        const int sv = take(rdy0, SZ_KV, ad);
        wg_fence();
        pv(pb, ad, 1);
        sums();
        target();
        op = nop;
        enter();
        rdy0 = rdy1;
        auto convert = [&](float (&u)[96], int j0, int j1) {
#pragma unroll
          for (int i = 4 * j0; i < 4 * j1; i++) {
            q[8 * (i >> 2) + (i & 3)] = pack_bf16(u[4 * i], u[4 * i + 1]);
            q[8 * (i >> 2) + (i & 3) + 4] = pack_bf16(u[4 * i + 2], u[4 * i + 3]);
          }
        };
        if ((op & 3) != OP_O) {
          if ((op & 3) == OP_Q) bi0 = take(rdy0, SZ_WQ, ad);
          wg_wait<0>();
          fence_regs(o);
          release(sv);
          float u[96];
#pragma unroll
          for (int i = 0; i < 96; i++) u[i] = o[i] * (i & 2 ? i1 : i0);
          if ((op & 3) != OP_Q) { convert(u, 0, 6); break; }
          fence_regs(u);
          xw(ad, 0);
          sched_fence(img0, P.zero);
          fence_regs(u);
          convert(u, 0, AQS);
          stg2_if(true, pend, q[0], q[1], q[2], q[3], q[4], q[5], q[6], q[7], spol);
          probe1();
          wg_wait<0>();
          release(bi0);
          bi0 = take(rdy0, SZ_WQ, ad);
          xw(ad, 1);
          sched_fence(img0, P.zero);
          fence_regs(u);
          convert(u, AQS, 6);
          k = 1;
          continue;
        }
        int bi = ow(0, 0);
        wg_wait<2>();
        fence_regs(o);
        release(sv);
#pragma unroll
        for (int j = 0; j < 6; j++) {
          uint32_t t[8];
#pragma unroll
          for (int i = 0; i < 4; i++) {
            t[i] = pack_bf16(o[16 * j + 4 * i] * i0, o[16 * j + 4 * i + 1] * i0);
            t[i + 4] = pack_bf16(o[16 * j + 4 * i + 2] * i1, o[16 * j + 4 * i + 3] * i1);
          }
          stg2_if(true, pend + j * 512, t[0], t[1], t[2], t[3], t[4], t[5], t[6], t[7], spol);
          if (j == 5) {
            __syncwarp();
            mbar_arrive_if(lane < 2, odone);
          }
          probe1();
          wg_wait<1>();
          bi = ow(1, bi);
          fence_regs(o);
        }
        {
          const int nk = 12 * (((op >> 5) & 15) - ((op >> 2) & 7));
#pragma unroll 1
          for (int k = 7; k < nk; k++) {
            probe1();
            wg_wait<1>();
            bi = ow(1, bi);
          }
          probe1();
        }
        nop = prog[++pc];
        if (op & F_LD) {
          uint32_t t[80];
#pragma unroll
          for (int j = 0; j < 5; j++) {
            const int b = take(rdy0, SZ_PART, ad);
            probe1();
#pragma unroll
            for (int i = 4 * j; i < 4 * j + 4; i++)
              lds128(sbase + (ad - ring16 + img0) * 16 + ((i >> 1) & 1) * 8192 + (i & 1) * 512, t[4 * i], t[4 * i + 1], t[4 * i + 2], t[4 * i + 3]);
            release(b);
          }
          wg_wait<0>();
          fence_regs(c);
#pragma unroll
          for (int i = 0; i < 80; i++) c[i] += __uint_as_float(t[i]);
        }
        if (!(op & F_ST)) {
          wg_wait<0>();
          fence_regs(c);
          goto finish;
        }
        op = nop;
        enter();
        bi0 = take(rdy0, SZ_WQ, ad);
        xw(ad, 0);
        pend = &g_part[((team * 4 + nt) * 2 + rank) * 5120 + img0];
        probe1();
        wg_wait<1>();
        fence_regs(c);
        release(bi);
        st_part(0); st_part(1);
        wg_wait<0>();
        release(bi0);
        bi0 = take(rdy0, SZ_WQ, ad);
        xw(ad, 1);
        st_part(2); st_part(3);
#pragma unroll
        for (int i = 0; i < 48; i++) q[i] = __float_as_uint(c[32 + i]);
        pend += 4 * 512;
        k = 1; lag = 2;
      }
    }
    rdy0 = false;
    {
      uint32_t t[48];
#pragma unroll
      for (int i = 0; i < 48; i++) t[i] = q[i] ^ P.zero;
      while ((op & 3) == OP_O) {
        int bi = ow(0, 0);
#pragma unroll 1
        for (int k = 1; k < 12 * (int)(((op >> 5) & 15) - ((op >> 2) & 7)); k++) {
          drain(t, k - 1);
          probe1();
          wg_wait<1>();
          bi = ow(1, bi);
        }
        rdy0 = false;
        wg_wait<0>();
        fence_regs(c);
        pc++;
        if (!(op & F_ST)) goto finish;
        release(bi);
        pend = &g_part[((((op >> 26) & 56) | ((op >> 9) & 7)) * 2 + rank) * 5120 + img0];
#pragma unroll
        for (int i = 6; i < 10; i++) st_part(i);
#pragma unroll
        for (int i = 0; i < 48; i++) t[i] = __float_as_uint(c[i]) ^ P.zero;
        op = prog[pc];
        enter();
      }
      for (int i = 0; i < 6; i++) drain(t, i);
    }
    asm volatile("barrier.cluster.arrive.relaxed;" ::: "memory");
    if (false) {
    finish:
      asm volatile("barrier.cluster.arrive.relaxed;" ::: "memory");
      bar_sync(1, 256);
      const uint32_t wstage = sbase + (wg * 4 + warp) * 5120;
      const uint32_t sa = wstage + (lane & 15) * 64;
#pragma unroll
      for (int i = 0; i < 10; i++) {
        const int u = (i & 1) * 2 + (lane >> 4);
        stsm4(sa + (i >> 1) * 1024 + ((u ^ ((lane >> 1) & 3)) << 4), pack_bf16(c[8 * i], c[8 * i + 1]), pack_bf16(c[8 * i + 2], c[8 * i + 3]),
              pack_bf16(c[8 * i + 4], c[8 * i + 5]), pack_bf16(c[8 * i + 6], c[8 * i + 7]));
      }
      asm volatile("fence.proxy.async.shared::cta;" ::: "memory");
      __syncwarp();
      if (lane == 0) {
        tma3d_store(&P.out, wstage, 0, (team & 7) * kSq + rank * 128 + wg * 64 + warp * 16, blk * 20 + nt * 5);
        asm volatile("cp.async.bulk.commit_group;\ncp.async.bulk.wait_group.read 0;" ::: "memory");
      }
      __syncwarp();
    }
    asm volatile("barrier.cluster.wait;" ::: "memory");
  }
}

typedef CUresult (*EncodeFn)(CUtensorMap*, CUtensorMapDataType, cuuint32_t, void*, const cuuint64_t*, const cuuint64_t*,
                             const cuuint32_t*, const cuuint32_t*, CUtensorMapInterleave, CUtensorMapSwizzle,
                             CUtensorMapL2promotion, CUtensorMapFloatOOBfill);

void encode(EncodeFn fn, CUtensorMap* m, const void* ptr, int rank, const cuuint64_t* dims, const cuuint64_t* strides,
            const cuuint32_t* box, CUtensorMapSwizzle swz) {
  const cuuint32_t es[5] = {1, 1, 1, 1, 1};
  CUresult r = fn(m, CU_TENSOR_MAP_DATA_TYPE_BFLOAT16, rank, const_cast<void*>(ptr), dims, strides, box, es,
                  CU_TENSOR_MAP_INTERLEAVE_NONE, swz, CU_TENSOR_MAP_L2_PROMOTION_L2_128B, CU_TENSOR_MAP_FLOAT_OOB_FILL_NONE);
  if (r != CUDA_SUCCESS) fprintf(stderr, "cuTensorMapEncodeTiled failed: %d\n", (int)r);
}

void annotate(uint32_t* ops, int n, bool helper) {
  uint32_t items = 0, cur = 0, pend = 0;
  auto item = [&](uint32_t bytes, int count, uint32_t bytes2 = 0) {
    for (int i = 0; i < count; i++) {
      if (cur + bytes > RING) cur = 0;
      cur += bytes;
      if (cur + bytes2 > RING) cur = 0;
      cur += bytes2;
      items++;
    }
  };
  for (int i = 0; i <= n; i++) {
    const uint32_t op = ops[i];
    ops[i] |= (items % NBAR) << 15 | ((items / NBAR) & 1) << 19 | (cur >> 12) << 20 | pend << 26;
    if ((op & 3) == OP_Q) { item(SZ_WQ, 10, SZ_A); pend = (op & F_PARK) ? (helper ? 1 : 2) : 0; }
    if ((op & 3) == OP_A) {
      item(SZ_KV, (op & F_PARK) ? 30 : 31);
      if ((ops[i + 1] & 3) == OP_A) { item(SZ_PARK, 2); item(SZ_KV, 1); }
      item(SZ_KV, 1);
      pend = 1;
    }
    if ((op & 3) == OP_O) {
      item(SZ_A, 12 * (((op >> 5) & 15) - ((op >> 2) & 7)), SZ_WO);
      if (op & F_LD) item(SZ_PART, 5);
      pend = (op & F_ST) ? (helper ? 1 : 2) : 0;
    }
  }
}

void compile_programs(const char* const* text, bool helpers, Params& P) {
  struct Req { int when, team, wave, slot; } req[N_TEAM * MAX_PARK];
  int n_req = 0;
  for (int t = 0; t < N_TEAM; t++) {
    uint32_t* ops = P.ops[t];
    int n = 0, flags[8] = {0, 0, 0, 0, 0, 0, 0, 0}, n_park = 0, last_o = -1, when = 0, given = 0;
    for (const char* s = text[t]; *s; s++) {
      const int a = s[1] - '0';
      if (*s == 'Q' || (*s == 'H' && !helpers)) { ops[n++] = OP_Q | a << 2; when += 10; }
      else if (*s == 'P') { flags[a] = F_PARK | n_park++ << 10; ops[n++] = OP_Q | a << 2 | flags[a]; when += 10; }
      else if (*s == 'H') { req[n_req++] = {when, t, a, n_park}; flags[a] = F_PARK | F_HELP | n_park++ << 10; }
      else if (*s == 'A') { ops[n++] = OP_A | a << 2 | flags[a]; when += 32; }
      else if (*s == 'G') { given = a; if (helpers) req[n_req++] = {1000, t, 0, -a}; }
      else if (*s == 'O') {
        ops[n] = OP_O | a << 2 | (s[2] - '0') << 5;
        if (given) ops[n] = helpers ? ops[n] | F_LD | F_PARK | (MAX_PARK - 1) << 10 : ops[n] & ~(7u << 2);
        if (last_o >= 0) { ops[last_o] |= F_ST; ops[n] |= F_LD; }
        last_o = n++;
        when += 10 * (s[2] - s[1]);
      }
    }
    for (int i = n; i < MAX_OPS; i++) ops[i] = OP_END;
    annotate(ops, n, false);
  }
  for (int i = 1; i < n_req; i++)
    for (int j = i; j > 0 && req[j].when < req[j - 1].when; j--) { Req r = req[j]; req[j] = req[j - 1]; req[j - 1] = r; }
  for (int h = 0; h < N_HELP; h++) {
    uint32_t* ops = P.ops[N_TEAM + 2 * h];
    int n = 0;
    for (int i = 0; i < n_req; i++)
      for (int m = h; m < 4; m += N_HELP) {
        const uint32_t ro = 4 * req[i].team + m;
        ops[n++] = req[i].slot >= 0 ? OP_Q | req[i].wave << 2 | req[i].team << 5 | F_PARK | req[i].slot << 10 | m << 12
                                    : OP_O | -req[i].slot << 5 | F_ST | (ro & 7) << 9 | (ro >> 3) << 29;
      }
    for (int i = n; i < 2 * MAX_OPS; i++) ops[i] = OP_END;
    annotate(ops, n, true);
  }
  for (int i = 0; i < 32; i++) P.first[i] = i < N_TEAM ? P.ops[i][0] : i < N_TEAM + N_HELP ? P.ops[2 * i - N_TEAM][0] : 0;
}

const char* const kPrograms[N_TEAM] = {
  "Q0A0Q1A1H2A2Q3A3O03Q4A4Q5A5Q6A6Q7A7O38",
  "Q0A0Q1A1Q2A2Q3A3O04Q4A4Q5A5Q6A6H7A7O48",
  "Q0A0H1A1Q2A2Q3A3Q4A4O05Q5A5Q6A6Q7A7O58",
  "Q0A0Q1A1Q2A2Q3A3Q4A4O05Q5A5Q6A6H7A7O58",
  "Q0A0Q1A1Q2A2O03Q3A3H4A4Q5A5Q6A6Q7A7O38",
  "Q0A0Q1A1H2A2Q3A3Q4A4O05Q5A5Q6A6Q7A7O58",
  "Q0A0Q1A1Q2A2Q3A3O03Q4A4H5A5Q6A6Q7A7O38",
  "Q0A0Q1A1Q2A2O03Q3A3Q4A4Q5A5Q6A6H7A7O38",
  "P2P3Q0A0Q1A1A2A3H4A4Q5A5Q6A6Q7A7O08",
  "P3P7Q0A0Q1A1H2A2A3Q4A4Q5A5Q6A6A7G1O18",
  "Q0A0Q1A1Q2A2O02Q3A3H4A4Q5A5Q6A6Q7A7O28",
  "P3P5Q0A0Q1A1Q2A2A3Q4A4A5Q6A6H7A7O08",
  "Q0A0Q1A1Q2A2O02Q3A3Q4A4H5A5Q6A6Q7A7O28",
  "P7Q0A0Q1A1Q2A2Q3A3Q4A4Q5A5Q6A6A7G1O18",
  "Q0A0Q1A1Q2A2H3A3Q4A4Q5A5Q6A6Q7A7O08",
  "P5Q0A0Q1A1Q2A2Q3A3Q4A4A5Q6A6H7A7O08",
};

const char* const* bench_programs() {
  return kPrograms;
}

}

extern "C" void kernel_launch(void* const* d_in, const int* in_sizes, int n_in, void* d_out, int out_size) {
  (void)in_sizes; (void)n_in; (void)out_size;
  static EncodeFn fn = nullptr;
  static int n_clusters = 0;
  if (!fn) {
    cudaDriverEntryPointQueryResult qr;
    void* f = nullptr;
    cudaGetDriverEntryPoint("cuTensorMapEncodeTiled", &f, cudaEnableDefault, &qr);
    fn = (EncodeFn)f;
    cudaFuncSetAttribute(fused_kernel, cudaFuncAttributeMaxDynamicSharedMemorySize, SMEM_BYTES);
    cudaLaunchConfig_t cfg = {};
    cfg.gridDim = dim3(132); cfg.blockDim = dim3(384); cfg.dynamicSmemBytes = SMEM_BYTES;
    cudaLaunchAttribute at[1];
    at[0].id = cudaLaunchAttributeClusterDimension; at[0].val.clusterDim.x = 2; at[0].val.clusterDim.y = 1; at[0].val.clusterDim.z = 1;
    cfg.attrs = at; cfg.numAttrs = 1;
    if (cudaOccupancyMaxActiveClusters(&n_clusters, fused_kernel, &cfg) != cudaSuccess || n_clusters < 1) n_clusters = 1;
    (void)cudaGetLastError();
  }
  Params P;
  const CUtensorMapSwizzle S128 = CU_TENSOR_MAP_SWIZZLE_128B, S64 = CU_TENSOR_MAP_SWIZZLE_64B;
  for (int blk = 0; blk < 2; blk++) {
    void* const* in = d_in + 5 * blk;
    { const cuuint64_t d[] = {kD, kB * kSq}, s[] = {kD * 2}; const cuuint32_t b[] = {64, 128};
      encode(fn, &P.x[blk], in[0], 2, d, s, b, S128); }
    { const cuuint64_t d[] = {64, 8, 3, (cuuint64_t)kB * kH * kSk / 8}, s[] = {kDh * 2, 128, 8 * kDh * 2}; const cuuint32_t b[] = {64, 8, 3, 8};
      encode(fn, &P.k[blk], in[1], 4, d, s, b, S128);
      encode(fn, &P.v[blk], in[2], 4, d, s, b, S128); }
    { const cuuint64_t d[] = {64, kD, kHD / 64}, s[] = {kHD * 2, 128}; const cuuint32_t b[] = {64, 64, 3};
      encode(fn, &P.wq[blk], in[3], 3, d, s, b, S128); }
    { const cuuint64_t d[] = {32, 2, kHD / 8, 4, kD / 32}, s[] = {kD * 2, 8 * kD * 2, 2 * kD * 2, 64}; const cuuint32_t b[] = {32, 2, 4, 4, 5};
      encode(fn, &P.wo[blk], in[4], 5, d, s, b, S64); }
  }
  { const cuuint64_t d[] = {32, kB * kSq, 2 * kD / 32}, s[] = {2 * kD * 2, 64}; const cuuint32_t b[] = {32, 16, 5};
    encode(fn, &P.out, d_out, 3, d, s, b, S64); }

  P.zero = 0;
  P.dbg = 0x30;
  if (n_clusters >= N_CL) {
    const bool helpers = n_clusters >= N_CL + N_HELP;
    compile_programs(bench_programs(), helpers, P);
    fused_kernel<<<2 * (N_CL + (helpers ? N_HELP : 0)), 384, SMEM_BYTES>>>(P);
  } else {
    for (int phase = 0; phase < 2; phase++) {
      const char* text[N_TEAM];
      for (int t = 0; t < N_TEAM; t++) text[t] = phase ? "O08" : "Q0A0Q1A1Q2A2Q3A3Q4A4Q5A5Q6A6Q7A7";
      compile_programs(text, false, P);
      fused_kernel<<<2 * N_CL, 384, SMEM_BYTES>>>(P);
    }
  }
}
```

```cpp
#include <cuda_runtime.h>
#include <cuda_bf16.h>
#include <cuda.h>
#include <stdint.h>
#include <stdio.h>

namespace {

constexpr int kB = 8, kSq = 256, kD = 640, kH = 32, kSk = 1024, kDh = 192;
constexpr int kHD = kH * kDh;
#define S1A 7
#define UC0 3
#define UC1 4
#define RING_KB 224
constexpr uint32_t RING = RING_KB * 1024;
constexpr uint32_t SZ_KV = 24576;
constexpr uint32_t SZ_WQ = 24576, SZ_WO = 20480, SZ_A = 16384;
constexpr uint32_t SZ_PARK = 24576;
constexpr uint32_t SZ_PART = 16384;
constexpr int NBAR = 10;
#define KVT 4
constexpr int KV_TRANSIT = KVT;
#define EARLY_N 3
constexpr int EARLY = EARLY_N;
constexpr uint32_t KV_CH = 64, KV_SBO = 3072;
constexpr int SMEM_BYTES = RING + 512 + 1024;
constexpr int N_TEAM = 16, N_CL = 64, N_HELP = 2, MAX_OPS = 24, MAX_PARK = 4;
enum { OP_END = 0, OP_Q = 1, OP_A = 2, OP_O = 3, F_PARK = 1 << 9, F_LD = 1 << 12, F_ST = 1 << 13, F_HELP = 1 << 12 };

struct alignas(64) Params {
  uint32_t first[32];
  CUtensorMap x[2], wq[2], k[2], v[2], wo[2], out;
  uint32_t ops[N_TEAM + 2 * N_HELP][MAX_OPS];
  uint32_t zero;
  uint32_t dbg;
};

__device__ uint4 g_o[N_TEAM * 2 * 96 * 1024];
__device__ uint4 g_part[N_CL * 2 * 5 * 1024];
__device__ unsigned int g_done[N_TEAM * 2 * 8];
__device__ unsigned int g_help[N_CL * 2 * MAX_PARK];
__device__ unsigned int g_seen[N_TEAM * 2 * 8];

template <int TB, int TA = 0>
__device__ __forceinline__ void wgmma_ss_n64(float (&d)[32], uint64_t da, uint64_t db, int scale_d) {
  asm volatile("{\n.reg .pred p;\nsetp.ne.b32 p, %34, 0;\n"
    "wgmma.mma_async.sync.aligned.m64n64k16.f32.bf16.bf16 {%0, %1, %2, %3, %4, %5, %6, %7, %8, %9, %10, %11, %12, %13, %14, %15, %16, %17, %18, %19, %20, %21, %22, %23, %24, %25, %26, %27, %28, %29, %30, %31}, %32, %33, p, 1, 1, %35, %36;\n}\n"
    : "+f"(d[0]), "+f"(d[1]), "+f"(d[2]), "+f"(d[3]), "+f"(d[4]), "+f"(d[5]), "+f"(d[6]), "+f"(d[7]), "+f"(d[8]), "+f"(d[9]), "+f"(d[10]), "+f"(d[11]), "+f"(d[12]), "+f"(d[13]), "+f"(d[14]), "+f"(d[15]), "+f"(d[16]), "+f"(d[17]), "+f"(d[18]), "+f"(d[19]), "+f"(d[20]), "+f"(d[21]), "+f"(d[22]), "+f"(d[23]), "+f"(d[24]), "+f"(d[25]), "+f"(d[26]), "+f"(d[27]), "+f"(d[28]), "+f"(d[29]), "+f"(d[30]), "+f"(d[31])
    : "l"(da), "l"(db), "r"(scale_d), "n"(TA), "n"(TB));
}
template <int TB>
__device__ __forceinline__ void wgmma_rs_n64(float (&d)[32], uint32_t a0, uint32_t a1, uint32_t a2, uint32_t a3, uint64_t db, int scale_d) {
  asm volatile("{\n.reg .pred p;\nsetp.ne.b32 p, %37, 0;\n"
    "wgmma.mma_async.sync.aligned.m64n64k16.f32.bf16.bf16 {%0, %1, %2, %3, %4, %5, %6, %7, %8, %9, %10, %11, %12, %13, %14, %15, %16, %17, %18, %19, %20, %21, %22, %23, %24, %25, %26, %27, %28, %29, %30, %31}, {%32, %33, %34, %35}, %36, p, 1, 1, %38;\n}\n"
    : "+f"(d[0]), "+f"(d[1]), "+f"(d[2]), "+f"(d[3]), "+f"(d[4]), "+f"(d[5]), "+f"(d[6]), "+f"(d[7]), "+f"(d[8]), "+f"(d[9]), "+f"(d[10]), "+f"(d[11]), "+f"(d[12]), "+f"(d[13]), "+f"(d[14]), "+f"(d[15]), "+f"(d[16]), "+f"(d[17]), "+f"(d[18]), "+f"(d[19]), "+f"(d[20]), "+f"(d[21]), "+f"(d[22]), "+f"(d[23]), "+f"(d[24]), "+f"(d[25]), "+f"(d[26]), "+f"(d[27]), "+f"(d[28]), "+f"(d[29]), "+f"(d[30]), "+f"(d[31])
    : "r"(a0), "r"(a1), "r"(a2), "r"(a3), "l"(db), "r"(scale_d), "n"(TB));
}
template <int TB, int TA = 0>
__device__ __forceinline__ void wgmma_ss_n160(float (&d)[80], uint64_t da, uint64_t db, int scale_d) {
  asm volatile("{\n.reg .pred p;\nsetp.ne.b32 p, %82, 0;\n"
    "wgmma.mma_async.sync.aligned.m64n160k16.f32.bf16.bf16 {%0, %1, %2, %3, %4, %5, %6, %7, %8, %9, %10, %11, %12, %13, %14, %15, %16, %17, %18, %19, %20, %21, %22, %23, %24, %25, %26, %27, %28, %29, %30, %31, %32, %33, %34, %35, %36, %37, %38, %39, %40, %41, %42, %43, %44, %45, %46, %47, %48, %49, %50, %51, %52, %53, %54, %55, %56, %57, %58, %59, %60, %61, %62, %63, %64, %65, %66, %67, %68, %69, %70, %71, %72, %73, %74, %75, %76, %77, %78, %79}, %80, %81, p, 1, 1, %83, %84;\n}\n"
    : "+f"(d[0]), "+f"(d[1]), "+f"(d[2]), "+f"(d[3]), "+f"(d[4]), "+f"(d[5]), "+f"(d[6]), "+f"(d[7]), "+f"(d[8]), "+f"(d[9]), "+f"(d[10]), "+f"(d[11]), "+f"(d[12]), "+f"(d[13]), "+f"(d[14]), "+f"(d[15]), "+f"(d[16]), "+f"(d[17]), "+f"(d[18]), "+f"(d[19]), "+f"(d[20]), "+f"(d[21]), "+f"(d[22]), "+f"(d[23]), "+f"(d[24]), "+f"(d[25]), "+f"(d[26]), "+f"(d[27]), "+f"(d[28]), "+f"(d[29]), "+f"(d[30]), "+f"(d[31]), "+f"(d[32]), "+f"(d[33]), "+f"(d[34]), "+f"(d[35]), "+f"(d[36]), "+f"(d[37]), "+f"(d[38]), "+f"(d[39]), "+f"(d[40]), "+f"(d[41]), "+f"(d[42]), "+f"(d[43]), "+f"(d[44]), "+f"(d[45]), "+f"(d[46]), "+f"(d[47]), "+f"(d[48]), "+f"(d[49]), "+f"(d[50]), "+f"(d[51]), "+f"(d[52]), "+f"(d[53]), "+f"(d[54]), "+f"(d[55]), "+f"(d[56]), "+f"(d[57]), "+f"(d[58]), "+f"(d[59]), "+f"(d[60]), "+f"(d[61]), "+f"(d[62]), "+f"(d[63]), "+f"(d[64]), "+f"(d[65]), "+f"(d[66]), "+f"(d[67]), "+f"(d[68]), "+f"(d[69]), "+f"(d[70]), "+f"(d[71]), "+f"(d[72]), "+f"(d[73]), "+f"(d[74]), "+f"(d[75]), "+f"(d[76]), "+f"(d[77]), "+f"(d[78]), "+f"(d[79])
    : "l"(da), "l"(db), "r"(scale_d), "n"(TA), "n"(TB));
}
template <int TB>
__device__ __forceinline__ void wgmma_rs_n160(float (&d)[80], uint32_t a0, uint32_t a1, uint32_t a2, uint32_t a3, uint64_t db, int scale_d) {
  asm volatile("{\n.reg .pred p;\nsetp.ne.b32 p, %85, 0;\n"
    "wgmma.mma_async.sync.aligned.m64n160k16.f32.bf16.bf16 {%0, %1, %2, %3, %4, %5, %6, %7, %8, %9, %10, %11, %12, %13, %14, %15, %16, %17, %18, %19, %20, %21, %22, %23, %24, %25, %26, %27, %28, %29, %30, %31, %32, %33, %34, %35, %36, %37, %38, %39, %40, %41, %42, %43, %44, %45, %46, %47, %48, %49, %50, %51, %52, %53, %54, %55, %56, %57, %58, %59, %60, %61, %62, %63, %64, %65, %66, %67, %68, %69, %70, %71, %72, %73, %74, %75, %76, %77, %78, %79}, {%80, %81, %82, %83}, %84, p, 1, 1, %86;\n}\n"
    : "+f"(d[0]), "+f"(d[1]), "+f"(d[2]), "+f"(d[3]), "+f"(d[4]), "+f"(d[5]), "+f"(d[6]), "+f"(d[7]), "+f"(d[8]), "+f"(d[9]), "+f"(d[10]), "+f"(d[11]), "+f"(d[12]), "+f"(d[13]), "+f"(d[14]), "+f"(d[15]), "+f"(d[16]), "+f"(d[17]), "+f"(d[18]), "+f"(d[19]), "+f"(d[20]), "+f"(d[21]), "+f"(d[22]), "+f"(d[23]), "+f"(d[24]), "+f"(d[25]), "+f"(d[26]), "+f"(d[27]), "+f"(d[28]), "+f"(d[29]), "+f"(d[30]), "+f"(d[31]), "+f"(d[32]), "+f"(d[33]), "+f"(d[34]), "+f"(d[35]), "+f"(d[36]), "+f"(d[37]), "+f"(d[38]), "+f"(d[39]), "+f"(d[40]), "+f"(d[41]), "+f"(d[42]), "+f"(d[43]), "+f"(d[44]), "+f"(d[45]), "+f"(d[46]), "+f"(d[47]), "+f"(d[48]), "+f"(d[49]), "+f"(d[50]), "+f"(d[51]), "+f"(d[52]), "+f"(d[53]), "+f"(d[54]), "+f"(d[55]), "+f"(d[56]), "+f"(d[57]), "+f"(d[58]), "+f"(d[59]), "+f"(d[60]), "+f"(d[61]), "+f"(d[62]), "+f"(d[63]), "+f"(d[64]), "+f"(d[65]), "+f"(d[66]), "+f"(d[67]), "+f"(d[68]), "+f"(d[69]), "+f"(d[70]), "+f"(d[71]), "+f"(d[72]), "+f"(d[73]), "+f"(d[74]), "+f"(d[75]), "+f"(d[76]), "+f"(d[77]), "+f"(d[78]), "+f"(d[79])
    : "r"(a0), "r"(a1), "r"(a2), "r"(a3), "l"(db), "r"(scale_d), "n"(TB));
}
template <int TB, int TA = 0>
__device__ __forceinline__ void wgmma_ss_n192(float (&d)[96], uint64_t da, uint64_t db, int scale_d) {
  asm volatile("{\n.reg .pred p;\nsetp.ne.b32 p, %98, 0;\n"
    "wgmma.mma_async.sync.aligned.m64n192k16.f32.bf16.bf16 {%0, %1, %2, %3, %4, %5, %6, %7, %8, %9, %10, %11, %12, %13, %14, %15, %16, %17, %18, %19, %20, %21, %22, %23, %24, %25, %26, %27, %28, %29, %30, %31, %32, %33, %34, %35, %36, %37, %38, %39, %40, %41, %42, %43, %44, %45, %46, %47, %48, %49, %50, %51, %52, %53, %54, %55, %56, %57, %58, %59, %60, %61, %62, %63, %64, %65, %66, %67, %68, %69, %70, %71, %72, %73, %74, %75, %76, %77, %78, %79, %80, %81, %82, %83, %84, %85, %86, %87, %88, %89, %90, %91, %92, %93, %94, %95}, %96, %97, p, 1, 1, %99, %100;\n}\n"
    : "+f"(d[0]), "+f"(d[1]), "+f"(d[2]), "+f"(d[3]), "+f"(d[4]), "+f"(d[5]), "+f"(d[6]), "+f"(d[7]), "+f"(d[8]), "+f"(d[9]), "+f"(d[10]), "+f"(d[11]), "+f"(d[12]), "+f"(d[13]), "+f"(d[14]), "+f"(d[15]), "+f"(d[16]), "+f"(d[17]), "+f"(d[18]), "+f"(d[19]), "+f"(d[20]), "+f"(d[21]), "+f"(d[22]), "+f"(d[23]), "+f"(d[24]), "+f"(d[25]), "+f"(d[26]), "+f"(d[27]), "+f"(d[28]), "+f"(d[29]), "+f"(d[30]), "+f"(d[31]), "+f"(d[32]), "+f"(d[33]), "+f"(d[34]), "+f"(d[35]), "+f"(d[36]), "+f"(d[37]), "+f"(d[38]), "+f"(d[39]), "+f"(d[40]), "+f"(d[41]), "+f"(d[42]), "+f"(d[43]), "+f"(d[44]), "+f"(d[45]), "+f"(d[46]), "+f"(d[47]), "+f"(d[48]), "+f"(d[49]), "+f"(d[50]), "+f"(d[51]), "+f"(d[52]), "+f"(d[53]), "+f"(d[54]), "+f"(d[55]), "+f"(d[56]), "+f"(d[57]), "+f"(d[58]), "+f"(d[59]), "+f"(d[60]), "+f"(d[61]), "+f"(d[62]), "+f"(d[63]), "+f"(d[64]), "+f"(d[65]), "+f"(d[66]), "+f"(d[67]), "+f"(d[68]), "+f"(d[69]), "+f"(d[70]), "+f"(d[71]), "+f"(d[72]), "+f"(d[73]), "+f"(d[74]), "+f"(d[75]), "+f"(d[76]), "+f"(d[77]), "+f"(d[78]), "+f"(d[79]), "+f"(d[80]), "+f"(d[81]), "+f"(d[82]), "+f"(d[83]), "+f"(d[84]), "+f"(d[85]), "+f"(d[86]), "+f"(d[87]), "+f"(d[88]), "+f"(d[89]), "+f"(d[90]), "+f"(d[91]), "+f"(d[92]), "+f"(d[93]), "+f"(d[94]), "+f"(d[95])
    : "l"(da), "l"(db), "r"(scale_d), "n"(TA), "n"(TB));
}
template <int TB>
__device__ __forceinline__ void wgmma_rs_n192(float (&d)[96], uint32_t a0, uint32_t a1, uint32_t a2, uint32_t a3, uint64_t db, int scale_d) {
  asm volatile("{\n.reg .pred p;\nsetp.ne.b32 p, %101, 0;\n"
    "wgmma.mma_async.sync.aligned.m64n192k16.f32.bf16.bf16 {%0, %1, %2, %3, %4, %5, %6, %7, %8, %9, %10, %11, %12, %13, %14, %15, %16, %17, %18, %19, %20, %21, %22, %23, %24, %25, %26, %27, %28, %29, %30, %31, %32, %33, %34, %35, %36, %37, %38, %39, %40, %41, %42, %43, %44, %45, %46, %47, %48, %49, %50, %51, %52, %53, %54, %55, %56, %57, %58, %59, %60, %61, %62, %63, %64, %65, %66, %67, %68, %69, %70, %71, %72, %73, %74, %75, %76, %77, %78, %79, %80, %81, %82, %83, %84, %85, %86, %87, %88, %89, %90, %91, %92, %93, %94, %95}, {%96, %97, %98, %99}, %100, p, 1, 1, %102;\n}\n"
    : "+f"(d[0]), "+f"(d[1]), "+f"(d[2]), "+f"(d[3]), "+f"(d[4]), "+f"(d[5]), "+f"(d[6]), "+f"(d[7]), "+f"(d[8]), "+f"(d[9]), "+f"(d[10]), "+f"(d[11]), "+f"(d[12]), "+f"(d[13]), "+f"(d[14]), "+f"(d[15]), "+f"(d[16]), "+f"(d[17]), "+f"(d[18]), "+f"(d[19]), "+f"(d[20]), "+f"(d[21]), "+f"(d[22]), "+f"(d[23]), "+f"(d[24]), "+f"(d[25]), "+f"(d[26]), "+f"(d[27]), "+f"(d[28]), "+f"(d[29]), "+f"(d[30]), "+f"(d[31]), "+f"(d[32]), "+f"(d[33]), "+f"(d[34]), "+f"(d[35]), "+f"(d[36]), "+f"(d[37]), "+f"(d[38]), "+f"(d[39]), "+f"(d[40]), "+f"(d[41]), "+f"(d[42]), "+f"(d[43]), "+f"(d[44]), "+f"(d[45]), "+f"(d[46]), "+f"(d[47]), "+f"(d[48]), "+f"(d[49]), "+f"(d[50]), "+f"(d[51]), "+f"(d[52]), "+f"(d[53]), "+f"(d[54]), "+f"(d[55]), "+f"(d[56]), "+f"(d[57]), "+f"(d[58]), "+f"(d[59]), "+f"(d[60]), "+f"(d[61]), "+f"(d[62]), "+f"(d[63]), "+f"(d[64]), "+f"(d[65]), "+f"(d[66]), "+f"(d[67]), "+f"(d[68]), "+f"(d[69]), "+f"(d[70]), "+f"(d[71]), "+f"(d[72]), "+f"(d[73]), "+f"(d[74]), "+f"(d[75]), "+f"(d[76]), "+f"(d[77]), "+f"(d[78]), "+f"(d[79]), "+f"(d[80]), "+f"(d[81]), "+f"(d[82]), "+f"(d[83]), "+f"(d[84]), "+f"(d[85]), "+f"(d[86]), "+f"(d[87]), "+f"(d[88]), "+f"(d[89]), "+f"(d[90]), "+f"(d[91]), "+f"(d[92]), "+f"(d[93]), "+f"(d[94]), "+f"(d[95])
    : "r"(a0), "r"(a1), "r"(a2), "r"(a3), "l"(db), "r"(scale_d), "n"(TB));
}

__device__ __forceinline__ uint32_t smem_u32(const void* p) { return (uint32_t)__cvta_generic_to_shared(p); }
__device__ __forceinline__ void wg_fence() { asm volatile("wgmma.fence.sync.aligned;" ::: "memory"); }
__device__ __forceinline__ void wg_commit() { asm volatile("wgmma.commit_group.sync.aligned;" ::: "memory"); }
template <int N> __device__ __forceinline__ void wg_wait() { asm volatile("wgmma.wait_group.sync.aligned %0;" ::"n"(N) : "memory"); }
__device__ __forceinline__ void sched_fence(int& keep, uint32_t zero) {
  asm volatile("{\n.reg .u32 c;\nmov.u32 c, %%clock;\nand.b32 c, c, %1;\nxor.b32 %0, %0, c;\n}\n" : "+r"(keep) : "r"(zero) : "memory");
}
template <int N> __device__ __forceinline__ void fence_regs(float (&r)[N]) {
#pragma unroll
  for (int i = 0; i < N; i++) asm volatile("" : "+f"(r[i])::"memory");
}
template <int N> __device__ __forceinline__ void fence_regs(uint32_t (&r)[N]) {
#pragma unroll
  for (int i = 0; i < N; i++) asm volatile("" : "+r"(r[i])::"memory");
}
__device__ __forceinline__ uint64_t mk_desc(uint32_t a16, uint32_t lbo, uint32_t sbo, uint32_t swz) {
  uint64_t d;
  asm("mov.b64 %0, {%1, %2};" : "=l"(d) : "r"(a16 + ((lbo >> 4) << 16)), "r"((sbo >> 4) | (swz << 30)));
  return d;
}
__device__ __forceinline__ void mbar_init(uint32_t bar, uint32_t cnt) {
  asm volatile("mbarrier.init.shared::cta.b64 [%0], %1;" ::"r"(bar), "r"(cnt) : "memory");
}
__device__ __forceinline__ void mbar_expect(uint32_t bar, uint32_t tx) {
  asm volatile("mbarrier.arrive.expect_tx.shared::cta.b64 _, [%0], %1;" ::"r"(bar), "r"(tx) : "memory");
}
__device__ __forceinline__ bool mbar_test(uint32_t bar, uint32_t ph) {
  uint32_t ok;
  asm volatile("{\n.reg .pred p;\nmbarrier.test_wait.parity.shared::cta.b64 p, [%1], %2;\nselp.u32 %0, 1, 0, p;\n}\n"
               : "=r"(ok) : "r"(bar), "r"(ph) : "memory");
  return ok;
}
__device__ __forceinline__ void mbar_wait(uint32_t bar, uint32_t ph) {
  asm volatile("{\n.reg .pred p;\n.reg .u32 n;\nmov.u32 n, 0;\n"
               "LOOP:\nadd.u32 n, n, 1;\nmbarrier.try_wait.parity.shared::cta.b64 p, [%0], %1;\n@p bra DONE;\n"
               "setp.lt.u32 p, n, 0x1000000;\n@p bra LOOP;\ntrap;\n"
               "DONE:\n}\n" ::"r"(bar), "r"(ph) : "memory");
}
template <int NS> __device__ __forceinline__ void mbar_wait_slow(uint32_t bar, uint32_t ph) {
  asm volatile("{\n.reg .pred p;\n.reg .u32 n;\nmov.u32 n, 0;\n"
               "LOOP:\nmbarrier.test_wait.parity.shared::cta.b64 p, [%0], %1;\n@p bra DONE;\n"
               "nanosleep.u32 %2;\nadd.u32 n, n, 1;\nsetp.lt.u32 p, n, 0x400000;\n@p bra LOOP;\ntrap;\n"
               "DONE:\n}\n" ::"r"(bar), "r"(ph), "n"(NS) : "memory");
}
__device__ __forceinline__ void mbar_arrive_cluster_if(bool on, uint32_t addr) {
  asm volatile("{\n.reg .pred p;\nsetp.ne.b32 p, %1, 0;\n@p mbarrier.arrive.shared::cluster.b64 _, [%0];\n}\n" ::"r"(addr), "r"((int)on) : "memory");
}
__device__ __forceinline__ void mbar_arrive_if(bool on, uint32_t addr) {
  asm volatile("{\n.reg .pred p;\nsetp.ne.b32 p, %1, 0;\n@p mbarrier.arrive.shared::cta.b64 _, [%0];\n}\n" ::"r"(addr), "r"((int)on) : "memory");
}
__device__ __forceinline__ void tma2d(uint32_t dst, const CUtensorMap* m, uint32_t bar, int c0, int c1) {
  asm volatile("cp.async.bulk.tensor.2d.shared::cluster.global.mbarrier::complete_tx::bytes [%0], [%1, {%3, %4}], [%2];"
               ::"r"(dst), "l"(m), "r"(bar), "r"(c0), "r"(c1) : "memory");
}
__device__ __forceinline__ void tma3d(uint32_t dst, const CUtensorMap* m, uint32_t bar, int c0, int c1, int c2) {
  asm volatile("cp.async.bulk.tensor.3d.shared::cluster.global.mbarrier::complete_tx::bytes [%0], [%1, {%3, %4, %5}], [%2];"
               ::"r"(dst), "l"(m), "r"(bar), "r"(c0), "r"(c1), "r"(c2) : "memory");
}
__device__ __forceinline__ void tma3d_mc(uint32_t dst, const CUtensorMap* m, uint32_t bar, int c0, int c1, int c2) {
  asm volatile("cp.async.bulk.tensor.3d.shared::cluster.global.mbarrier::complete_tx::bytes.multicast::cluster"
               " [%0], [%1, {%3, %4, %5}], [%2], %6;"
               ::"r"(dst), "l"(m), "r"(bar), "r"(c0), "r"(c1), "r"(c2), "h"((uint16_t)3) : "memory");
}
__device__ __forceinline__ void tma3d_store(const CUtensorMap* m, uint32_t src, int c0, int c1, int c2) {
  asm volatile("cp.async.bulk.tensor.3d.global.shared::cta.bulk_group [%0, {%2, %3, %4}], [%1];"
               ::"l"(m), "r"(src), "r"(c0), "r"(c1), "r"(c2) : "memory");
}
__device__ __forceinline__ void bar_sync(int id, int n) { asm volatile("bar.sync %0, %1;" ::"r"(id), "r"(n) : "memory"); }
__device__ __forceinline__ uint32_t pack_bf16(float lo, float hi) {
  uint32_t r;
  asm("cvt.rn.bf16x2.f32 %0, %1, %2;" : "=r"(r) : "f"(hi), "f"(lo));
  return r;
}
__device__ __forceinline__ float ex2(float x) {
  float y;
  asm("ex2.approx.ftz.f32 %0, %1;" : "=f"(y) : "f"(x));
  return y;
}
__device__ __forceinline__ float fadd(float a, float b) {
  float y;
  asm("add.f32 %0, %1, %2;" : "=f"(y) : "f"(a), "f"(b));
  return y;
}
__device__ __forceinline__ float rcp(float x) {
  float y;
  asm("rcp.approx.ftz.f32 %0, %1;" : "=f"(y) : "f"(x));
  return y;
}
__device__ __forceinline__ void stsm4(uint32_t addr, uint32_t a, uint32_t b, uint32_t c, uint32_t d) {
  asm volatile("stmatrix.sync.aligned.m8n8.x4.shared.b16 [%0], {%1, %2, %3, %4};" ::"r"(addr), "r"(a), "r"(b), "r"(c), "r"(d) : "memory");
}

__device__ __forceinline__ void tma4d_mc_hint(uint32_t dst, const CUtensorMap* m, uint32_t bar, int c3, uint64_t pol) {
  asm volatile("cp.async.bulk.tensor.4d.shared::cluster.global.mbarrier::complete_tx::bytes.multicast::cluster.L2::cache_hint"
               " [%0], [%1, {%3, %3, %3, %4}], [%2], %5, %6;"
               ::"r"(dst), "l"(m), "r"(bar), "r"(0), "r"(c3), "h"((uint16_t)3), "l"(pol) : "memory");
}
__device__ __forceinline__ void tma5d_mc(uint32_t dst, const CUtensorMap* m, uint32_t bar, int c2, int c4) {
  asm volatile("cp.async.bulk.tensor.5d.shared::cluster.global.mbarrier::complete_tx::bytes.multicast::cluster"
               " [%0], [%1, {%3, %3, %4, %3, %5}], [%2], %6;"
               ::"r"(dst), "l"(m), "r"(bar), "r"(0), "r"(c2), "r"(c4), "h"((uint16_t)3) : "memory");
}
__device__ __forceinline__ void bulk_load_hint(uint32_t dst, const void* src, uint32_t bytes, uint32_t bar, uint64_t pol) {
  asm volatile("cp.async.bulk.shared::cluster.global.mbarrier::complete_tx::bytes.L2::cache_hint [%0], [%1], %2, [%3], %4;"
               ::"r"(dst), "l"(src), "r"(bytes), "r"(bar), "l"(pol) : "memory");
}
__device__ __forceinline__ void stg128_hint(void* p, uint32_t a, uint32_t b, uint32_t c, uint32_t d, uint64_t pol) {
  asm volatile("st.global.L2::cache_hint.v4.b32 [%0], {%1, %2, %3, %4}, %5;" ::"l"(p), "r"(a), "r"(b), "r"(c), "r"(d), "l"(pol) : "memory");
}
__device__ __forceinline__ void stg2_if(bool on, void* p, uint32_t a, uint32_t b, uint32_t c, uint32_t d, uint32_t e, uint32_t f,
                                        uint32_t g, uint32_t h, uint64_t pol) {
  asm volatile("{\n.reg .pred p;\nsetp.ne.b32 p, %10, 0;\n"
               "@p st.global.L2::cache_hint.v4.b32 [%0], {%1, %2, %3, %4}, %9;\n"
               "@p st.global.L2::cache_hint.v4.b32 [%0 + 512], {%5, %6, %7, %8}, %9;\n}\n"
               ::"l"(p), "r"(a), "r"(b), "r"(c), "r"(d), "r"(e), "r"(f), "r"(g), "r"(h), "l"(pol), "r"((int)on) : "memory");
}
__device__ __forceinline__ uint64_t evict_first() {
  uint64_t p;
  asm("createpolicy.fractional.L2::evict_first.b64 %0, 1.0;" : "=l"(p));
  return p;
}
__device__ __forceinline__ bool elect() {
  uint32_t ok;
  asm volatile("{\n.reg .pred p;\nelect.sync _|p, 0xffffffff;\nselp.u32 %0, 1, 0, p;\n}\n" : "=r"(ok));
  return ok;
}
__device__ __forceinline__ void mbar_arrive(uint32_t bar) {
  asm volatile("mbarrier.arrive.shared::cta.b64 _, [%0];" ::"r"(bar) : "memory");
}
__device__ __forceinline__ void stg128(void* p, uint32_t a, uint32_t b, uint32_t c, uint32_t d) {
  asm volatile("st.global.v4.b32 [%0], {%1, %2, %3, %4};" ::"l"(p), "r"(a), "r"(b), "r"(c), "r"(d) : "memory");
}
__device__ __forceinline__ void lds128(uint32_t p, uint32_t& a, uint32_t& b, uint32_t& c, uint32_t& d) {
  asm volatile("ld.shared.v4.b32 {%0, %1, %2, %3}, [%4];" : "=r"(a), "=r"(b), "=r"(c), "=r"(d) : "r"(p) : "memory");
}
__device__ __forceinline__ void wait_count(const unsigned int* p, uint32_t target) {
  asm volatile("{\n.reg .pred p;\n.reg .u32 n, v;\nmov.u32 n, 0;\n"
               "LOOP:\nld.acquire.gpu.global.u32 v, [%0];\nsetp.ge.u32 p, v, %1;\n@p bra DONE;\n"
               "nanosleep.u32 %2;\nadd.u32 n, n, 1;\nsetp.lt.u32 p, n, 0x400000;\n@p bra LOOP;\ntrap;\n"
               "DONE:\n}\n" ::"l"(p), "r"(target), "n"(200) : "memory");
}

__host__ __device__ __forceinline__ int o_wave(int a, int b, int i, int lag) {
  if (lag == 0) return a + i;
  const int p = lag < b - a - 1 ? lag : b - a - 1;
  return i < p ? b - 2 - i : i == p ? b - 1 : b - 1 - i;
}

struct Cursor {
  int bi;
  uint32_t ph;
  __device__ __forceinline__ void next() {
    if (++bi == NBAR) { bi = 0; ph ^= 1; }
  }
};

constexpr float kScaleLog2 = 0.07216878364870322f * 1.4426950408889634f;
constexpr float kSumLimit = 1048576.0f;
constexpr float kMaxLag = 8.0f;

__global__ void __cluster_dims__(2, 1, 1) __launch_bounds__(384, 1)
fused_kernel(const __grid_constant__ Params P) {
  extern __shared__ uint8_t smem_raw[];
  const uint32_t sbase = (smem_u32(smem_raw) + 1023) & ~1023u;
  const uint32_t full0 = sbase + RING, empty0 = full0 + 8 * NBAR, odone = empty0 + 8 * NBAR, oready0 = odone + 8;
  const uint32_t fenced = oready0 + 64, hready0 = fenced + 8;
  const uint32_t rank = blockIdx.x & 1;
  const int role = blockIdx.x >> 1;
  const bool helper = role >= N_CL;
  const int team = helper ? 0 : role >> 2, nt = role & 3, blk = team >> 3;
  const uint32_t* prog = P.ops[helper ? N_TEAM + 2 * (role - N_CL) : team];
  auto q_role = [&](uint32_t op) { return helper ? (int)(((op >> 3) & 60) | ((op >> 12) & 3)) : role; };
  auto o_role = [&](uint32_t op) { return helper ? (int)(((op >> 26) & 56) | ((op >> 9) & 7)) : role; };
  const int wid = __shfl_sync(0xffffffffu, (int)(threadIdx.x >> 5), 0);
  const int wg = wid >> 2;

  const uint32_t op0 = P.first[helper ? N_TEAM + role - N_CL : team];
  if (__builtin_expect(wid == 8, 1)) {
    if (elect()) {
#pragma unroll
      for (int k = 0; k < EARLY; k++) mbar_init(full0 + 8 * k, 1);
      asm volatile("fence.mbarrier_init.release.cluster;" ::: "memory");
      if ((op0 & 3) == OP_Q) {
        const int qr = q_role(op0);
#pragma unroll
        for (int k = 0; k < EARLY; k++) {
          mbar_expect(full0 + 8 * k, SZ_WQ + SZ_A);
          tma2d(sbase + k * (SZ_WQ + SZ_A) + SZ_WQ, &P.x[qr >> 5], full0 + 8 * k, 64 * k, ((qr >> 2) & 7) * kSq + rank * 128);
          tma3d(sbase + k * (SZ_WQ + SZ_A), &P.wq[qr >> 5], full0 + 8 * k, 0, 64 * k, 3 * (4 * ((op0 >> 2) & 7) + (qr & 3)));
          tma3d(sbase + k * (SZ_WQ + SZ_A) + SZ_WQ / 2, &P.wq[qr >> 5], full0 + 8 * k, 0, 64 * k + 32, 3 * (4 * ((op0 >> 2) & 7) + (qr & 3)));
        }
      }
      asm volatile("prefetch.tensormap [%0];" ::"l"(&P.k[blk]) : "memory");
      asm volatile("prefetch.tensormap [%0];" ::"l"(&P.v[blk]) : "memory");
    }
  } else if (threadIdx.x == 0) {
#pragma unroll
    for (int i = EARLY; i < 2 * NBAR + 10 + MAX_PARK; i++) mbar_init(full0 + 8 * i, i >= NBAR && i <= 2 * NBAR ? 16 : 1);
    asm volatile("fence.mbarrier_init.release.cluster;" ::: "memory");
  }
  __syncwarp();
  asm volatile("barrier.cluster.arrive.relaxed.aligned;\nbarrier.cluster.wait.aligned;" ::: "memory");

  if (wg == 2) {
    asm volatile("setmaxnreg.dec.sync.aligned.u32 24;");
    if (wid == 8) {
      Cursor tail{0, 0};
      int head = 0, sh = 0;
      uint32_t hph = 0;
      uint32_t cur = 0, used = 0;
      uint64_t fifo = 0;
      uint32_t dst, bar, oready = oready0;
      const uint64_t pol = evict_first();
      auto acquire = [&](uint32_t bytes, int part = 0) {
        uint32_t fp = bytes >> 12;
        if (cur + fp > (RING >> 12)) { fp += (RING >> 12) - cur; cur = 0; }
        used += fp;
        bool more = false;
        uint32_t wbar, wph;
        while (used > (RING >> 12) || (part != 2 && sh == 5 * NBAR)) {
          if (more) mbar_wait(wbar, wph);
          more = true;
          wbar = empty0 + 8 * tail.bi; wph = tail.ph;
          tail.next();
          used -= (uint32_t)fifo & 31;
          fifo >>= 5;
          sh -= 5;
        }
        fifo += (uint64_t)fp << sh;
        dst = sbase + (cur << 12);
        bar = full0 + 8 * head;
        cur += bytes >> 12;
        if (part != 1) {
          sh += 5;
          if (++head == NBAR) { head = 0; hph ^= 1; }
        }
        if (more) mbar_wait(wbar, wph);
      };
      auto scratch = [&](const uint4* src, uint32_t bytes, int n) {
        asm volatile("fence.proxy.async.global;" ::: "memory");
#pragma unroll 1
        for (int i = 0; i < n; i++) {
          acquire(bytes);
          if (elect()) {
            bulk_load_hint(dst, src + i * (bytes / 16), bytes, bar, pol);
            mbar_expect(bar, bytes);
          }
        }
      };
      for (int pc = 0;; pc++) {
        const uint32_t op = prog[pc];
        const int type = op & 3, a = (op >> 2) & 7;
        if (type == OP_END) break;
        if (type == OP_Q) {
          const int qr = q_role(op);
#pragma unroll 1
          for (int k = 0; k < 10; k++) {
            acquire(SZ_WQ, 1);
            if ((pc > 0 || k >= EARLY) && elect()) tma3d_mc(dst + rank * (SZ_WQ / 2), &P.wq[qr >> 5], bar, 0, 64 * k + 32 * rank, 3 * (4 * a + (qr & 3)));
            acquire(SZ_A, 2);
            if ((pc > 0 || k >= EARLY) && elect()) {
              tma2d(dst, &P.x[qr >> 5], bar, 64 * k, ((qr >> 2) & 7) * kSq + rank * 128);
              mbar_expect(bar, SZ_WQ + SZ_A);
            }
          }
        } else if (type == OP_A) {
          const uint32_t nop = prog[pc + 1];
#pragma unroll 1
          for (int t = (op & F_PARK) ? 1 : 0; t < 33; t++) {
            int wave = a;
            if (t == 31 && (nop & 3) != OP_A) t++;
            if (t == 31) {
              wave = (nop >> 2) & 7;
              mbar_wait((nop & F_HELP) ? hready0 + 8 * ((nop >> 10) & 3) : fenced, 0);
              scratch(&g_o[((team * 2 + rank) * 96 + 3 * (4 * wave + nt)) * 1024], SZ_PARK, 2);
            }
            const int isv = t ? ~t & 1 : 0, j = (isv ? (t - 1) >> 1 : (t + 1) >> 1) & 15;
            const int row0 = ((team & 7) * kH + 4 * wave + nt) * kSk;
            acquire(SZ_KV);
            if (t >= KV_TRANSIT) {
              const int i = head - 1 - KV_TRANSIT;
              mbar_wait(full0 + 8 * (i < 0 ? i + NBAR : i), i < 0 ? hph ^ 1 : hph);
            }
            if (elect()) {
              tma4d_mc_hint(dst + rank * (SZ_KV / 2), isv ? &P.v[blk] : &P.k[blk], bar, row0 / 8 + 8 * j + 4 * rank, pol);
              mbar_expect(bar, SZ_KV);
            }
          }
        } else {
          const int b = (op >> 5) & 15, ro = o_role(op);
#pragma unroll 1
          for (int i = 0; i < b - a; i++) {
            const int w = o_wave(a, b, i, (P.dbg >> 4) & 7);
            mbar_wait(oready, 0);
            oready += 8;
            asm volatile("fence.proxy.async.global;" ::: "memory");
#pragma unroll 1
            for (int k = 12 * w; k < 12 * w + 12; k++) {
              acquire(SZ_A, 1);
              if (elect()) bulk_load_hint(dst, &g_o[(((ro >> 2) * 2 + rank) * 96 + k) * 1024], SZ_A, bar, pol);
              acquire(SZ_WO, 2);
              if (elect()) {
                tma5d_mc(dst + rank * 10240, &P.wo[ro >> 5], bar, 8 * k + 4 * rank, 5 * (ro & 3));
                mbar_expect(bar, SZ_WO + SZ_A);
              }
            }
          }
          if (op & F_LD) {
            if (op & F_PARK) mbar_wait(hready0 + 8 * (MAX_PARK - 1), 0);
            scratch(&g_part[(role * 2 + rank) * 5120], SZ_PART, 5);
          }
        }
      }
    } else if (threadIdx.x == 288) {
      uint32_t ph = 0;
      bool first = true;
      for (int pc = 0;; pc++) {
        const uint32_t op = prog[pc];
        if ((op & 3) == OP_END) break;
        if ((op & 3) != OP_A && !helper) continue;
        mbar_wait_slow<400>(odone, ph);
        ph ^= 1;
        unsigned int* flag = !helper ? &g_done[(team * 2 + rank) * 8 + ((op >> 2) & 7)]
                             : (op & 3) == OP_Q ? &g_help[(q_role(op) * 2 + rank) * MAX_PARK + ((op >> 10) & 3)]
                                                : &g_help[(o_role(op) * 2 + rank) * MAX_PARK + MAX_PARK - 1];
        asm volatile("red.release.gpu.global.add.u32 [%0], 1;" ::"l"(flag) : "memory");
        if (first) mbar_arrive(fenced);
        first = false;
      }
    } else if (threadIdx.x == 320) {
      uint32_t oready = oready0;
      for (int pc = 0;; pc++) {
        const uint32_t op = prog[pc];
        if ((op & 3) == OP_END) break;
        if ((op & 3) == OP_O) {
          const int a = (op >> 2) & 7, b = (op >> 5) & 15;
#pragma unroll 1
          for (int i = 0; i < b - a; i++) {
            const int ci = ((o_role(op) >> 2) * 2 + rank) * 8 + o_wave(a, b, i, (P.dbg >> 4) & 7);
            wait_count(&g_done[ci], 4);
            mbar_arrive(oready);
            oready += 8;
            if (atomicAdd(&g_seen[ci], 1u) == 3u) { g_seen[ci] = 0; g_done[ci] = 0; }
          }
        }
        if ((op & 3) != OP_Q && (op & F_HELP) && (op & F_PARK)) {
          unsigned int* flag = &g_help[(role * 2 + rank) * MAX_PARK + ((op >> 10) & 3)];
          wait_count(flag, 1);
          mbar_arrive(hready0 + 8 * ((op >> 10) & 3));
          *flag = 0;
        }
      }
    }
    __syncwarp();
    asm volatile("barrier.cluster.arrive.relaxed;\nbarrier.cluster.wait;" ::: "memory");
  } else {
    asm volatile("setmaxnreg.inc.sync.aligned.u32 240;");
    const int lane = threadIdx.x & 31, warp = wid & 3;
    uint32_t empty_rem;
    asm volatile("mapa.shared::cluster.u32 %0, %1, %2;" : "=r"(empty_rem) : "r"(empty0), "r"(lane & 1));
    auto release = [&](int slot) { mbar_arrive_cluster_if(lane < 2, empty_rem + 8 * slot); };
    Cursor r{0, 0};
    const uint32_t ring16 = (sbase & 0x3FFFF) >> 4;
    uint32_t cur = ring16;
    bool rdy0 = false, rdy1 = false;
    auto probe1 = [&]() { rdy0 = mbar_test(full0 + 8 * r.bi, r.ph); };
    auto probe2 = [&]() {
      Cursor n = r;
      rdy0 = mbar_test(full0 + 8 * n.bi, n.ph);
      n.next();
      rdy1 = mbar_test(full0 + 8 * n.bi, n.ph);
    };
    auto take = [&](bool rdy, uint32_t bytes, uint32_t& addr) {
      const int bi = r.bi;
      if (!__all_sync(0xffffffffu, rdy)) mbar_wait(full0 + 8 * r.bi, r.ph);
      r.next();
      if (cur > ring16 + ((RING - bytes) >> 4)) cur = ring16;
      addr = cur;
      cur += bytes >> 4;
      return bi;
    };
    auto second = [&](uint32_t bytes) {
      if (cur > ring16 + ((RING - bytes) >> 4)) cur = ring16;
      cur += bytes >> 4;
      return cur - (bytes >> 4);
    };
    const int row = wg * 64 + warp * 16 + (lane >> 2);
    int img0 = row * 4 + ((lane & 3) ^ ((row >> 1) & 3));
    uint4* pend = nullptr;
    const uint64_t spol = evict_first();
    int pc = 0;
    uint32_t op = prog[0];
    auto enter = [&]() {
      r.bi = (op >> 15) & 15; r.ph = (op >> 19) & 1; cur = ring16 + (((op >> 20) & 63) << 8);
    };
    auto drain = [&](uint32_t (&t)[48], uint32_t c) {
      if (!(op & (3u << 26)) || c >= 6) return;
#pragma unroll
      for (int i = 0; i < 6; i++)
        stg2_if(c == i, pend + i * 512, t[8 * i], t[8 * i + 1], t[8 * i + 2], t[8 * i + 3],
                t[8 * i + 4], t[8 * i + 5], t[8 * i + 6], t[8 * i + 7], spol);
      if ((op & (1u << 26)) && c == 5) {
        __syncwarp();
        mbar_arrive_if(lane < 2, odone);
      }
    };
    float s[32], o[96], c[80];
    uint32_t q[48], pa[16], pb[16];
    float mc0, mc1, l0, l1;
    bool gen;
    auto soft = [&](float (&s)[32], uint32_t (&pout)[16], bool first) {
      if (first) { gen = false; mc0 = 0.f; mc1 = 0.f; }
      float b0, b1;
      for (;;) {
        if (gen) {
          float m0 = fmaxf(s[0], s[1]), m1 = fmaxf(s[2], s[3]);
#pragma unroll
          for (int i = 1; i < 8; i++) { m0 = fmaxf(m0, fmaxf(s[4 * i], s[4 * i + 1])); m1 = fmaxf(m1, fmaxf(s[4 * i + 2], s[4 * i + 3])); }
          m0 = fmaxf(m0, __shfl_xor_sync(0xffffffffu, m0, 1)); m1 = fmaxf(m1, __shfl_xor_sync(0xffffffffu, m1, 1));
          m0 = fmaxf(m0, __shfl_xor_sync(0xffffffffu, m0, 2)); m1 = fmaxf(m1, __shfl_xor_sync(0xffffffffu, m1, 2));
          if (first) {
            mc0 = m0; mc1 = m1;
          } else if (__any_sync(0xffffffffu, !(m0 <= mc0 + kMaxLag && m1 <= mc1 + kMaxLag))) {
            m0 = fmaxf(mc0, m0); m1 = fmaxf(mc1, m1);
            const float a0 = ex2(mc0 - m0), a1 = ex2(mc1 - m1);
            mc0 = m0; mc1 = m1;
            l0 *= a0; l1 *= a1;
            wg_wait<0>();
            fence_regs(o);
#pragma unroll
            for (int i = 0; i < 96; i++) o[i] *= i & 2 ? a1 : a0;
          }
#pragma unroll
          for (int i = 0; i < 32; i++) s[i] -= i & 2 ? mc1 : mc0;
        }
#pragma unroll
        for (int i = 0; i < 8; i++) {
          const float e1 = ex2(s[4 * i + 1]), e0 = ex2(s[4 * i]), e3 = ex2(s[4 * i + 3]), e2 = ex2(s[4 * i + 2]);
          pout[2 * i] = pack_bf16(e0, e1);
          b0 = i ? b0 + fadd(e1, e0) : fadd(e1, e0);
          pout[2 * i + 1] = pack_bf16(e2, e3);
          b1 = i ? b1 + fadd(e3, e2) : fadd(e3, e2);
        }
        if (!__any_sync(0xffffffffu, !gen && !(fmaxf(b0, b1) <= kSumLimit && (!first || fminf(b0, b1) >= 1.0f / kSumLimit)))) break;
        gen = __any_sync(0xffffffffu, true);
      }
      l0 = first ? b0 : l0 + b0;
      l1 = first ? b1 : l1 + b1;
    };
    auto qk = [&](float (&s)[32], uint32_t ak, int k0, int k1) {
#pragma unroll
      for (int kk = k0; kk < k1; kk++)
        wgmma_rs_n64<0>(s, q[4 * kk], q[4 * kk + 1], q[4 * kk + 2], q[4 * kk + 3], mk_desc(ak + (kk >> 2) * KV_CH + (kk & 3) * 2, 16, KV_SBO, 1), kk != 0);
      wg_commit();
    };
    auto pv = [&](uint32_t (&pin)[16], uint32_t av, int acc) {
#pragma unroll
      for (int kk = 0; kk < 4; kk++)
        wgmma_rs_n192<1>(o, pin[4 * kk], pin[4 * kk + 1], pin[4 * kk + 2], pin[4 * kk + 3], mk_desc(av + kk * (KV_SBO / 8), KV_CH * 16, KV_SBO, 1), acc || (kk != 0));
      wg_commit();
    };
    auto xw = [&](uint32_t ad, int acc) {
      const uint32_t da = second(SZ_A) + wg * 512;
      wg_fence();
#pragma unroll
      for (int kk = 0; kk < 4; kk++)
        wgmma_ss_n192<1>(o, mk_desc(da + kk * 2, 16, 1024, 1), mk_desc(ad + (kk & 1) * 128 + (kk >> 1) * 768, 4096, 1024, 1), acc || kk != 0);
      wg_commit();
    };
    auto ow = [&](int acc, int prev) {
      uint32_t da;
      const int bi = take(rdy0, SZ_A, da);
      const uint32_t db = second(SZ_WO);
      da += wg * 256;
      wg_fence();
      wgmma_ss_n160<1>(c, mk_desc(da, 16, 512, 2), mk_desc(db, 2048, 512, 2), acc);
      wgmma_ss_n160<1>(c, mk_desc(da + 2, 16, 512, 2), mk_desc(db + 64, 2048, 512, 2), 1);
      wg_commit();
      if (acc) { wg_wait<1>(); release(prev); }
      wgmma_ss_n160<1>(c, mk_desc(da + 512, 16, 512, 2), mk_desc(db + 640, 2048, 512, 2), 1);
      wgmma_ss_n160<1>(c, mk_desc(da + 514, 16, 512, 2), mk_desc(db + 704, 2048, 512, 2), 1);
      wg_commit();
      return bi;
    };
    auto st_part = [&](int i) {
      stg2_if(true, pend + i * 512, __float_as_uint(c[8 * i]), __float_as_uint(c[8 * i + 1]), __float_as_uint(c[8 * i + 2]), __float_as_uint(c[8 * i + 3]),
              __float_as_uint(c[8 * i + 4]), __float_as_uint(c[8 * i + 5]), __float_as_uint(c[8 * i + 6]), __float_as_uint(c[8 * i + 7]), spol);
    };
#pragma unroll
    for (int i = 0; i < 48; i++) q[i] = 0;
    enter();

    if ((op & 3) == OP_Q) {
      uint32_t ad;
      int bi0 = take(false, SZ_WQ, ad), k = 0, lag = 0;
      xw(ad, 0);
      for (;;) {
#pragma unroll 1
        for (;;) {
          drain(q, k - lag);
          probe1();
          wg_wait<0>();
          release(bi0);
          bi0 = take(rdy0, SZ_WQ, ad);
          if (++k == 8) break;
          xw(ad, 1);
        }
        if (wg) bar_sync(2, 256);
        xw(ad, 1);
        const int bi9 = take(false, SZ_WQ, ad);
        xw(ad, 1);
        if (!wg) asm volatile("bar.arrive 2, 256;" ::: "memory");
        k = 0; lag = 0;
        uint32_t nop = prog[++pc];
        wg_wait<1>();
        release(bi0);
        probe2();
        wg_wait<0>();
        fence_regs(o);
        release(bi9);
#pragma unroll
        for (int i = 0; i < 48; i++) q[i] = pack_bf16(o[2 * i] * kScaleLog2, o[2 * i + 1] * kScaleLog2);
        fence_regs(q);
        if (op & F_PARK) {
          const int qt = helper ? (op >> 5) & 15 : team, qm = helper ? (op >> 12) & 3 : nt;
          pend = &g_o[((qt * 2 + rank) * 96 + 3 * (4 * ((op >> 2) & 7) + qm)) * 1024 + img0];
          op = nop;
          enter();
          if ((op & 3) != OP_Q) break;
          bi0 = take(rdy0, SZ_WQ, ad);
          xw(ad, 0);
          continue;
        }
        int wave = (op >> 2) & 7, sk1;
        uint32_t ak1;
        {
          float s0[32];
          const int sk0 = take(rdy0, SZ_KV, ad);
          wg_fence();
          qk(s0, ad, 0, 12);
          sk1 = take(rdy1, SZ_KV, ak1);
          wg_fence();
          qk(s, ak1, 0, S1A);
          probe1();
          wg_wait<1>();
          fence_regs(s0);
          release(sk0);
          soft(s0, pa, true);
        }
        float i0, i1;
        auto sums = [&]() {
          l0 += __shfl_xor_sync(0xffffffffu, l0, 1); l1 += __shfl_xor_sync(0xffffffffu, l1, 1);
          l0 += __shfl_xor_sync(0xffffffffu, l0, 2); l1 += __shfl_xor_sync(0xffffffffu, l1, 2);
          i0 = rcp(l0); i1 = rcp(l1);
          asm volatile("" : "+f"(i0), "+f"(i1));
        };
        auto target = [&]() {
          pend = &g_o[((team * 2 + rank) * 96 + 3 * (4 * wave + nt)) * 1024 + img0];
          asm volatile("" : "+l"(pend));
        };
        for (;;) {
          nop = prog[++pc];
          {
            uint32_t av;
            const int sv = take(rdy0, SZ_KV, av);
            wg_fence();
            qk(s, ak1, S1A, 12);
            pv(pa, av, 0);
            probe2();
            wg_wait<1>();
            fence_regs(s);
            release(sk1);
            soft(s, pb, false);
            wg_wait<0>();
            fence_regs(o);
            release(sv);
          }
          auto step = [&](uint32_t (&pin)[16], uint32_t (&pout)[16]) {
            uint32_t ak, av;
            const int sk = take(rdy0, SZ_KV, ak), sv = take(rdy1, SZ_KV, av);
            wg_fence();
            qk(s, ak, 0, 12);
            pv(pin, av, 1);
            probe2();
            wg_wait<1>();
            fence_regs(s);
            release(sk);
            soft(s, pout, false);
            wg_wait<0>();
            fence_regs(o);
            release(sv);
          };
#pragma unroll 1
          for (int jj = 0; jj < 7; jj++) {
            step(pb, pa);
            step(pa, pb);
          }
          if ((nop & 3) != OP_A) break;
          uint32_t ak, av;
          {
            const int b0 = take(rdy0, SZ_PARK, ak), b1 = take(rdy1, SZ_PARK, av);
            const uint32_t ad0 = ak, ad1 = av;
            probe2();
#pragma unroll
            for (int i = 0; i < 12; i++)
              lds128(sbase + ((i < 6 ? ad0 : ad1) - ring16 + img0) * 16 + ((i % 6) >> 1) * 8192 + (i & 1) * 512, q[4 * i], q[4 * i + 1], q[4 * i + 2], q[4 * i + 3]);
            release(b0); release(b1);
          }
          const int sk0 = take(rdy0, SZ_KV, ak), sv = take(rdy1, SZ_KV, av);
          wg_fence();
          qk(s, ak, 0, 8);
          sched_fence(img0, P.zero);
          sums();
          sched_fence(img0, P.zero);
          qk(s, ak, 8, 12);
          pv(pb, av, 1);
          probe2();
          wg_wait<1>();
          fence_regs(s);
          release(sk0);
          soft(s, pa, true);
          sk1 = take(rdy0, SZ_KV, ak1);
          rdy0 = rdy1;
          wg_wait<0>();
          target();
          fence_regs(o);
          release(sv);
          uint32_t t[48];
#pragma unroll
          for (int j = 0; j < 6; j++) {
#pragma unroll
            for (int i = 0; i < 4; i++) {
              t[8 * j + i] = pack_bf16(o[16 * j + 4 * i] * i0, o[16 * j + 4 * i + 1] * i0);
              t[8 * j + i + 4] = pack_bf16(o[16 * j + 4 * i + 2] * i1, o[16 * j + 4 * i + 3] * i1);
            }
            stg2_if(true, pend + j * 512, t[8 * j], t[8 * j + 1], t[8 * j + 2], t[8 * j + 3], t[8 * j + 4], t[8 * j + 5], t[8 * j + 6], t[8 * j + 7], spol);
            if (j == UC0) { wg_fence(); qk(s, ak1, 0, 4); }
            if (j == UC1) { wg_fence(); qk(s, ak1, 4, S1A); }
            sched_fence(img0, P.zero);
          }
          if (P.zero) {
#pragma unroll
            for (int j = 0; j < 5; j++)
              stg2_if(true, pend, t[8 * j], t[8 * j + 1], t[8 * j + 2], t[8 * j + 3], t[8 * j + 4], t[8 * j + 5], t[8 * j + 6], t[8 * j + 7], spol);
          }
          __syncwarp();
          mbar_arrive_if(lane < 2, odone);
          wave = (nop >> 2) & 7;
        }
        const int sv = take(rdy0, SZ_KV, ad);
        wg_fence();
        pv(pb, ad, 1);
        sums();
        target();
        op = nop;
        enter();
        rdy0 = rdy1;
        auto convert = [&](float (&u)[96], int j0, int j1) {
#pragma unroll
          for (int i = 4 * j0; i < 4 * j1; i++) {
            q[8 * (i >> 2) + (i & 3)] = pack_bf16(u[4 * i], u[4 * i + 1]);
            q[8 * (i >> 2) + (i & 3) + 4] = pack_bf16(u[4 * i + 2], u[4 * i + 3]);
          }
        };
        if ((op & 3) != OP_O) {
          if ((op & 3) == OP_Q) bi0 = take(rdy0, SZ_WQ, ad);
          wg_wait<0>();
          fence_regs(o);
          release(sv);
          float u[96];
#pragma unroll
          for (int i = 0; i < 96; i++) u[i] = o[i] * (i & 2 ? i1 : i0);
          if ((op & 3) != OP_Q) { convert(u, 0, 6); break; }
          fence_regs(u);
          xw(ad, 0);
          sched_fence(img0, P.zero);
          fence_regs(u);
          convert(u, 0, 1);
          stg2_if(true, pend, q[0], q[1], q[2], q[3], q[4], q[5], q[6], q[7], spol);
          probe1();
          wg_wait<0>();
          release(bi0);
          bi0 = take(rdy0, SZ_WQ, ad);
          xw(ad, 1);
          sched_fence(img0, P.zero);
          fence_regs(u);
          convert(u, 1, 6);
          k = 1;
          continue;
        }
        int bi = ow(0, 0);
        wg_wait<2>();
        fence_regs(o);
        release(sv);
#pragma unroll
        for (int j = 0; j < 6; j++) {
          uint32_t t[8];
#pragma unroll
          for (int i = 0; i < 4; i++) {
            t[i] = pack_bf16(o[16 * j + 4 * i] * i0, o[16 * j + 4 * i + 1] * i0);
            t[i + 4] = pack_bf16(o[16 * j + 4 * i + 2] * i1, o[16 * j + 4 * i + 3] * i1);
          }
          stg2_if(true, pend + j * 512, t[0], t[1], t[2], t[3], t[4], t[5], t[6], t[7], spol);
          if (j == 5) {
            __syncwarp();
            mbar_arrive_if(lane < 2, odone);
          }
          probe1();
          wg_wait<1>();
          bi = ow(1, bi);
          fence_regs(o);
        }
        {
          const int nk = 12 * (((op >> 5) & 15) - ((op >> 2) & 7));
#pragma unroll 1
          for (int k = 7; k < nk; k++) {
            probe1();
            wg_wait<1>();
            bi = ow(1, bi);
          }
          probe1();
        }
        nop = prog[++pc];
        if (op & F_LD) {
          uint32_t t[80];
#pragma unroll
          for (int j = 0; j < 5; j++) {
            const int b = take(rdy0, SZ_PART, ad);
            probe1();
#pragma unroll
            for (int i = 4 * j; i < 4 * j + 4; i++)
              lds128(sbase + (ad - ring16 + img0) * 16 + ((i >> 1) & 1) * 8192 + (i & 1) * 512, t[4 * i], t[4 * i + 1], t[4 * i + 2], t[4 * i + 3]);
            release(b);
          }
          wg_wait<0>();
          fence_regs(c);
#pragma unroll
          for (int i = 0; i < 80; i++) c[i] += __uint_as_float(t[i]);
        }
        if (!(op & F_ST)) {
          wg_wait<0>();
          fence_regs(c);
          goto finish;
        }
        op = nop;
        enter();
        bi0 = take(rdy0, SZ_WQ, ad);
        xw(ad, 0);
        pend = &g_part[((team * 4 + nt) * 2 + rank) * 5120 + img0];
        probe1();
        wg_wait<1>();
        fence_regs(c);
        release(bi);
        st_part(0); st_part(1);
        wg_wait<0>();
        release(bi0);
        bi0 = take(rdy0, SZ_WQ, ad);
        xw(ad, 1);
        st_part(2); st_part(3);
#pragma unroll
        for (int i = 0; i < 48; i++) q[i] = __float_as_uint(c[32 + i]);
        pend += 4 * 512;
        k = 1; lag = 2;
      }
    }
    rdy0 = false;
    {
      uint32_t t[48];
#pragma unroll
      for (int i = 0; i < 48; i++) t[i] = q[i] ^ P.zero;
      while ((op & 3) == OP_O) {
        int bi = ow(0, 0);
#pragma unroll 1
        for (int k = 1; k < 12 * (int)(((op >> 5) & 15) - ((op >> 2) & 7)); k++) {
          drain(t, k - 1);
          probe1();
          wg_wait<1>();
          bi = ow(1, bi);
        }
        rdy0 = false;
        wg_wait<0>();
        fence_regs(c);
        pc++;
        if (!(op & F_ST)) goto finish;
        release(bi);
        pend = &g_part[((((op >> 26) & 56) | ((op >> 9) & 7)) * 2 + rank) * 5120 + img0];
#pragma unroll
        for (int i = 6; i < 10; i++) st_part(i);
#pragma unroll
        for (int i = 0; i < 48; i++) t[i] = __float_as_uint(c[i]) ^ P.zero;
        op = prog[pc];
        enter();
      }
      for (int i = 0; i < 6; i++) drain(t, i);
    }
    asm volatile("barrier.cluster.arrive.relaxed;" ::: "memory");
    if (false) {
    finish:
      asm volatile("barrier.cluster.arrive.relaxed;" ::: "memory");
      bar_sync(1, 256);
      const uint32_t wstage = sbase + (wg * 4 + warp) * 5120;
      const uint32_t sa = wstage + (lane & 15) * 64;
#pragma unroll
      for (int i = 0; i < 10; i++) {
        const int u = (i & 1) * 2 + (lane >> 4);
        stsm4(sa + (i >> 1) * 1024 + ((u ^ ((lane >> 1) & 3)) << 4), pack_bf16(c[8 * i], c[8 * i + 1]), pack_bf16(c[8 * i + 2], c[8 * i + 3]),
              pack_bf16(c[8 * i + 4], c[8 * i + 5]), pack_bf16(c[8 * i + 6], c[8 * i + 7]));
      }
      asm volatile("fence.proxy.async.shared::cta;" ::: "memory");
      __syncwarp();
      if (lane == 0) {
        tma3d_store(&P.out, wstage, 0, (team & 7) * kSq + rank * 128 + wg * 64 + warp * 16, blk * 20 + nt * 5);
        asm volatile("cp.async.bulk.commit_group;\ncp.async.bulk.wait_group.read 0;" ::: "memory");
      }
      __syncwarp();
    }
    asm volatile("barrier.cluster.wait;" ::: "memory");
  }
}

typedef CUresult (*EncodeFn)(CUtensorMap*, CUtensorMapDataType, cuuint32_t, void*, const cuuint64_t*, const cuuint64_t*,
                             const cuuint32_t*, const cuuint32_t*, CUtensorMapInterleave, CUtensorMapSwizzle,
                             CUtensorMapL2promotion, CUtensorMapFloatOOBfill);

void encode(EncodeFn fn, CUtensorMap* m, const void* ptr, int rank, const cuuint64_t* dims, const cuuint64_t* strides,
            const cuuint32_t* box, CUtensorMapSwizzle swz) {
  const cuuint32_t es[5] = {1, 1, 1, 1, 1};
  CUresult r = fn(m, CU_TENSOR_MAP_DATA_TYPE_BFLOAT16, rank, const_cast<void*>(ptr), dims, strides, box, es,
                  CU_TENSOR_MAP_INTERLEAVE_NONE, swz, CU_TENSOR_MAP_L2_PROMOTION_L2_128B, CU_TENSOR_MAP_FLOAT_OOB_FILL_NONE);
  if (r != CUDA_SUCCESS) fprintf(stderr, "cuTensorMapEncodeTiled failed: %d\n", (int)r);
}

void annotate(uint32_t* ops, int n, bool helper) {
  uint32_t items = 0, cur = 0, pend = 0;
  auto item = [&](uint32_t bytes, int count, uint32_t bytes2 = 0) {
    for (int i = 0; i < count; i++) {
      if (cur + bytes > RING) cur = 0;
      cur += bytes;
      if (cur + bytes2 > RING) cur = 0;
      cur += bytes2;
      items++;
    }
  };
  for (int i = 0; i <= n; i++) {
    const uint32_t op = ops[i];
    ops[i] |= (items % NBAR) << 15 | ((items / NBAR) & 1) << 19 | (cur >> 12) << 20 | pend << 26;
    if ((op & 3) == OP_Q) { item(SZ_WQ, 10, SZ_A); pend = (op & F_PARK) ? (helper ? 1 : 2) : 0; }
    if ((op & 3) == OP_A) {
      item(SZ_KV, (op & F_PARK) ? 30 : 31);
      if ((ops[i + 1] & 3) == OP_A) { item(SZ_PARK, 2); item(SZ_KV, 1); }
      item(SZ_KV, 1);
      pend = 1;
    }
    if ((op & 3) == OP_O) {
      item(SZ_A, 12 * (((op >> 5) & 15) - ((op >> 2) & 7)), SZ_WO);
      if (op & F_LD) item(SZ_PART, 5);
      pend = (op & F_ST) ? (helper ? 1 : 2) : 0;
    }
  }
}

void compile_programs(const char* const* text, bool helpers, Params& P) {
  struct Req { int when, team, wave, slot; } req[N_TEAM * MAX_PARK];
  int n_req = 0;
  for (int t = 0; t < N_TEAM; t++) {
    uint32_t* ops = P.ops[t];
    int n = 0, flags[8] = {0, 0, 0, 0, 0, 0, 0, 0}, n_park = 0, last_o = -1, when = 0, given = 0;
    for (const char* s = text[t]; *s; s++) {
      const int a = s[1] - '0';
      if (*s == 'Q' || (*s == 'H' && !helpers)) { ops[n++] = OP_Q | a << 2; when += 10; }
      else if (*s == 'P') { flags[a] = F_PARK | n_park++ << 10; ops[n++] = OP_Q | a << 2 | flags[a]; when += 10; }
      else if (*s == 'H') { req[n_req++] = {when, t, a, n_park}; flags[a] = F_PARK | F_HELP | n_park++ << 10; }
      else if (*s == 'A') { ops[n++] = OP_A | a << 2 | flags[a]; when += 32; }
      else if (*s == 'G') { given = a; if (helpers) req[n_req++] = {1000, t, 0, -a}; }
      else if (*s == 'O') {
        ops[n] = OP_O | a << 2 | (s[2] - '0') << 5;
        if (given) ops[n] = helpers ? ops[n] | F_LD | F_PARK | (MAX_PARK - 1) << 10 : ops[n] & ~(7u << 2);
        if (last_o >= 0) { ops[last_o] |= F_ST; ops[n] |= F_LD; }
        last_o = n++;
        when += 10 * (s[2] - s[1]);
      }
    }
    for (int i = n; i < MAX_OPS; i++) ops[i] = OP_END;
    annotate(ops, n, false);
  }
  for (int i = 1; i < n_req; i++)
    for (int j = i; j > 0 && req[j].when < req[j - 1].when; j--) { Req r = req[j]; req[j] = req[j - 1]; req[j - 1] = r; }
  for (int h = 0; h < N_HELP; h++) {
    uint32_t* ops = P.ops[N_TEAM + 2 * h];
    int n = 0;
    for (int i = 0; i < n_req; i++)
      for (int m = h; m < 4; m += N_HELP) {
        const uint32_t ro = 4 * req[i].team + m;
        ops[n++] = req[i].slot >= 0 ? OP_Q | req[i].wave << 2 | req[i].team << 5 | F_PARK | req[i].slot << 10 | m << 12
                                    : OP_O | -req[i].slot << 5 | F_ST | (ro & 7) << 9 | (ro >> 3) << 29;
      }
    for (int i = n; i < 2 * MAX_OPS; i++) ops[i] = OP_END;
    annotate(ops, n, true);
  }
  for (int i = 0; i < 32; i++) P.first[i] = i < N_TEAM ? P.ops[i][0] : i < N_TEAM + N_HELP ? P.ops[2 * i - N_TEAM][0] : 0;
}

const char* const kPrograms[N_TEAM] = {
  "Q0A0Q1A1H2A2Q3A3O03Q4A4Q5A5Q6A6Q7A7O38",
  "Q0A0Q1A1Q2A2Q3A3O04Q4A4Q5A5Q6A6H7A7O48",
  "Q0A0H1A1Q2A2Q3A3Q4A4O05Q5A5Q6A6Q7A7O58",
  "Q0A0Q1A1Q2A2Q3A3Q4A4O05Q5A5Q6A6H7A7O58",
  "Q0A0Q1A1Q2A2O03Q3A3H4A4Q5A5Q6A6Q7A7O38",
  "Q0A0Q1A1H2A2Q3A3Q4A4O05Q5A5Q6A6Q7A7O58",
  "Q0A0Q1A1Q2A2Q3A3O03Q4A4H5A5Q6A6Q7A7O38",
  "Q0A0Q1A1Q2A2O03Q3A3Q4A4Q5A5Q6A6H7A7O38",
  "P2P3Q0A0Q1A1A2A3H4A4Q5A5Q6A6Q7A7O08",
  "P3P7Q0A0Q1A1H2A2A3Q4A4Q5A5Q6A6A7G1O18",
  "Q0A0Q1A1Q2A2O02Q3A3H4A4Q5A5Q6A6Q7A7O28",
  "P3P5Q0A0Q1A1Q2A2A3Q4A4A5Q6A6H7A7O08",
  "Q0A0Q1A1Q2A2O02Q3A3Q4A4H5A5Q6A6Q7A7O28",
  "P7Q0A0Q1A1Q2A2Q3A3Q4A4Q5A5Q6A6A7G1O18",
  "Q0A0Q1A1Q2A2H3A3Q4A4Q5A5Q6A6Q7A7O08",
  "P5Q0A0Q1A1Q2A2Q3A3Q4A4A5Q6A6H7A7O08",
};

const char* const* bench_programs() {
  return kPrograms;
}

}

extern "C" void kernel_launch(void* const* d_in, const int* in_sizes, int n_in, void* d_out, int out_size) {
  (void)in_sizes; (void)n_in; (void)out_size;
  static EncodeFn fn = nullptr;
  static int n_clusters = 0;
  if (!fn) {
    cudaDriverEntryPointQueryResult qr;
    void* f = nullptr;
    cudaGetDriverEntryPoint("cuTensorMapEncodeTiled", &f, cudaEnableDefault, &qr);
    fn = (EncodeFn)f;
    cudaFuncSetAttribute(fused_kernel, cudaFuncAttributeMaxDynamicSharedMemorySize, SMEM_BYTES);
    cudaLaunchConfig_t cfg = {};
    cfg.gridDim = dim3(132); cfg.blockDim = dim3(384); cfg.dynamicSmemBytes = SMEM_BYTES;
    cudaLaunchAttribute at[1];
    at[0].id = cudaLaunchAttributeClusterDimension; at[0].val.clusterDim.x = 2; at[0].val.clusterDim.y = 1; at[0].val.clusterDim.z = 1;
    cfg.attrs = at; cfg.numAttrs = 1;
    if (cudaOccupancyMaxActiveClusters(&n_clusters, fused_kernel, &cfg) != cudaSuccess || n_clusters < 1) n_clusters = 1;
    (void)cudaGetLastError();
  }
  Params P;
  const CUtensorMapSwizzle S128 = CU_TENSOR_MAP_SWIZZLE_128B, S64 = CU_TENSOR_MAP_SWIZZLE_64B;
  for (int blk = 0; blk < 2; blk++) {
    void* const* in = d_in + 5 * blk;
    { const cuuint64_t d[] = {kD, kB * kSq}, s[] = {kD * 2}; const cuuint32_t b[] = {64, 128};
      encode(fn, &P.x[blk], in[0], 2, d, s, b, S128); }
    { const cuuint64_t d[] = {64, 8, 3, (cuuint64_t)kB * kH * kSk / 8}, s[] = {kDh * 2, 128, 8 * kDh * 2}; const cuuint32_t b[] = {64, 8, 3, 4};
      encode(fn, &P.k[blk], in[1], 4, d, s, b, S128);
      encode(fn, &P.v[blk], in[2], 4, d, s, b, S128); }
    { const cuuint64_t d[] = {64, kD, kHD / 64}, s[] = {kHD * 2, 128}; const cuuint32_t b[] = {64, 32, 3};
      encode(fn, &P.wq[blk], in[3], 3, d, s, b, S128); }
    { const cuuint64_t d[] = {32, 2, kHD / 8, 4, kD / 32}, s[] = {kD * 2, 8 * kD * 2, 2 * kD * 2, 64}; const cuuint32_t b[] = {32, 2, 4, 4, 5};
      encode(fn, &P.wo[blk], in[4], 5, d, s, b, S64); }
  }
  { const cuuint64_t d[] = {32, kB * kSq, 2 * kD / 32}, s[] = {2 * kD * 2, 64}; const cuuint32_t b[] = {32, 16, 5};
    encode(fn, &P.out, d_out, 3, d, s, b, S64); }

  P.zero = 0;
  P.dbg = 0x30;
  if (n_clusters >= N_CL) {
    const bool helpers = n_clusters >= N_CL + N_HELP;
    compile_programs(bench_programs(), helpers, P);
    fused_kernel<<<2 * (N_CL + (helpers ? N_HELP : 0)), 384, SMEM_BYTES>>>(P);
  } else {
    for (int phase = 0; phase < 2; phase++) {
      const char* text[N_TEAM];
      for (int t = 0; t < N_TEAM; t++) text[t] = phase ? "O08" : "Q0A0Q1A1Q2A2Q3A3Q4A4Q5A5Q6A6Q7A7";
      compile_programs(text, false, P);
      fused_kernel<<<2 * N_CL, 384, SMEM_BYTES>>>(P);
    }
  }
}
```

```cpp
#include <cuda_runtime.h>
#include <cuda_bf16.h>
#include <cuda.h>
#include <stdint.h>
#include <stdio.h>

namespace {

constexpr int kB = 8, kSq = 256, kD = 640, kH = 32, kSk = 1024, kDh = 192;
constexpr int kHD = kH * kDh;
#define S1A 7
#define UC0 3
#define UC1 4
#define RING_KB 224
constexpr uint32_t RING = RING_KB * 1024;
constexpr uint32_t SZ_KV = 24576;
constexpr uint32_t SZ_WQ = 24576, SZ_WO = 20480, SZ_A = 16384;
constexpr uint32_t SZ_PARK = 24576;
constexpr uint32_t SZ_PART = 16384;
constexpr int NBAR = 16, NFLIGHT = 12;
#define KVT 4
constexpr int KV_TRANSIT = KVT;
#define EARLY_N 3
constexpr int EARLY = EARLY_N;
constexpr uint32_t KV_CH = 64, KV_SBO = 3072;
constexpr int SMEM_BYTES = RING + 512 + 1024;
constexpr int N_TEAM = 16, N_CL = 64, N_HELP = 2, MAX_OPS = 24, MAX_PARK = 4;
enum { OP_END = 0, OP_Q = 1, OP_A = 2, OP_O = 3, F_PARK = 1 << 9, F_LD = 1 << 12, F_ST = 1 << 13, F_HELP = 1 << 12 };

struct alignas(64) Params {
  uint32_t first[32];
  CUtensorMap x[2], wq[2], k[2], v[2], wo[2], out;
  uint32_t ops[N_TEAM + 2 * N_HELP][MAX_OPS];
  uint32_t zero;
  uint32_t dbg;
};

__device__ uint4 g_o[N_TEAM * 2 * 96 * 1024];
__device__ uint4 g_part[N_CL * 2 * 5 * 1024];
__device__ unsigned int g_done[N_TEAM * 2 * 8];
__device__ unsigned int g_help[N_CL * 2 * MAX_PARK];
__device__ unsigned int g_seen[N_TEAM * 2 * 8];

template <int TB, int TA = 0>
__device__ __forceinline__ void wgmma_ss_n64(float (&d)[32], uint64_t da, uint64_t db, int scale_d) {
  asm volatile("{\n.reg .pred p;\nsetp.ne.b32 p, %34, 0;\n"
    "wgmma.mma_async.sync.aligned.m64n64k16.f32.bf16.bf16 {%0, %1, %2, %3, %4, %5, %6, %7, %8, %9, %10, %11, %12, %13, %14, %15, %16, %17, %18, %19, %20, %21, %22, %23, %24, %25, %26, %27, %28, %29, %30, %31}, %32, %33, p, 1, 1, %35, %36;\n}\n"
    : "+f"(d[0]), "+f"(d[1]), "+f"(d[2]), "+f"(d[3]), "+f"(d[4]), "+f"(d[5]), "+f"(d[6]), "+f"(d[7]), "+f"(d[8]), "+f"(d[9]), "+f"(d[10]), "+f"(d[11]), "+f"(d[12]), "+f"(d[13]), "+f"(d[14]), "+f"(d[15]), "+f"(d[16]), "+f"(d[17]), "+f"(d[18]), "+f"(d[19]), "+f"(d[20]), "+f"(d[21]), "+f"(d[22]), "+f"(d[23]), "+f"(d[24]), "+f"(d[25]), "+f"(d[26]), "+f"(d[27]), "+f"(d[28]), "+f"(d[29]), "+f"(d[30]), "+f"(d[31])
    : "l"(da), "l"(db), "r"(scale_d), "n"(TA), "n"(TB));
}
template <int TB>
__device__ __forceinline__ void wgmma_rs_n64(float (&d)[32], uint32_t a0, uint32_t a1, uint32_t a2, uint32_t a3, uint64_t db, int scale_d) {
  asm volatile("{\n.reg .pred p;\nsetp.ne.b32 p, %37, 0;\n"
    "wgmma.mma_async.sync.aligned.m64n64k16.f32.bf16.bf16 {%0, %1, %2, %3, %4, %5, %6, %7, %8, %9, %10, %11, %12, %13, %14, %15, %16, %17, %18, %19, %20, %21, %22, %23, %24, %25, %26, %27, %28, %29, %30, %31}, {%32, %33, %34, %35}, %36, p, 1, 1, %38;\n}\n"
    : "+f"(d[0]), "+f"(d[1]), "+f"(d[2]), "+f"(d[3]), "+f"(d[4]), "+f"(d[5]), "+f"(d[6]), "+f"(d[7]), "+f"(d[8]), "+f"(d[9]), "+f"(d[10]), "+f"(d[11]), "+f"(d[12]), "+f"(d[13]), "+f"(d[14]), "+f"(d[15]), "+f"(d[16]), "+f"(d[17]), "+f"(d[18]), "+f"(d[19]), "+f"(d[20]), "+f"(d[21]), "+f"(d[22]), "+f"(d[23]), "+f"(d[24]), "+f"(d[25]), "+f"(d[26]), "+f"(d[27]), "+f"(d[28]), "+f"(d[29]), "+f"(d[30]), "+f"(d[31])
    : "r"(a0), "r"(a1), "r"(a2), "r"(a3), "l"(db), "r"(scale_d), "n"(TB));
}
template <int TB, int TA = 0>
__device__ __forceinline__ void wgmma_ss_n160(float (&d)[80], uint64_t da, uint64_t db, int scale_d) {
  asm volatile("{\n.reg .pred p;\nsetp.ne.b32 p, %82, 0;\n"
    "wgmma.mma_async.sync.aligned.m64n160k16.f32.bf16.bf16 {%0, %1, %2, %3, %4, %5, %6, %7, %8, %9, %10, %11, %12, %13, %14, %15, %16, %17, %18, %19, %20, %21, %22, %23, %24, %25, %26, %27, %28, %29, %30, %31, %32, %33, %34, %35, %36, %37, %38, %39, %40, %41, %42, %43, %44, %45, %46, %47, %48, %49, %50, %51, %52, %53, %54, %55, %56, %57, %58, %59, %60, %61, %62, %63, %64, %65, %66, %67, %68, %69, %70, %71, %72, %73, %74, %75, %76, %77, %78, %79}, %80, %81, p, 1, 1, %83, %84;\n}\n"
    : "+f"(d[0]), "+f"(d[1]), "+f"(d[2]), "+f"(d[3]), "+f"(d[4]), "+f"(d[5]), "+f"(d[6]), "+f"(d[7]), "+f"(d[8]), "+f"(d[9]), "+f"(d[10]), "+f"(d[11]), "+f"(d[12]), "+f"(d[13]), "+f"(d[14]), "+f"(d[15]), "+f"(d[16]), "+f"(d[17]), "+f"(d[18]), "+f"(d[19]), "+f"(d[20]), "+f"(d[21]), "+f"(d[22]), "+f"(d[23]), "+f"(d[24]), "+f"(d[25]), "+f"(d[26]), "+f"(d[27]), "+f"(d[28]), "+f"(d[29]), "+f"(d[30]), "+f"(d[31]), "+f"(d[32]), "+f"(d[33]), "+f"(d[34]), "+f"(d[35]), "+f"(d[36]), "+f"(d[37]), "+f"(d[38]), "+f"(d[39]), "+f"(d[40]), "+f"(d[41]), "+f"(d[42]), "+f"(d[43]), "+f"(d[44]), "+f"(d[45]), "+f"(d[46]), "+f"(d[47]), "+f"(d[48]), "+f"(d[49]), "+f"(d[50]), "+f"(d[51]), "+f"(d[52]), "+f"(d[53]), "+f"(d[54]), "+f"(d[55]), "+f"(d[56]), "+f"(d[57]), "+f"(d[58]), "+f"(d[59]), "+f"(d[60]), "+f"(d[61]), "+f"(d[62]), "+f"(d[63]), "+f"(d[64]), "+f"(d[65]), "+f"(d[66]), "+f"(d[67]), "+f"(d[68]), "+f"(d[69]), "+f"(d[70]), "+f"(d[71]), "+f"(d[72]), "+f"(d[73]), "+f"(d[74]), "+f"(d[75]), "+f"(d[76]), "+f"(d[77]), "+f"(d[78]), "+f"(d[79])
    : "l"(da), "l"(db), "r"(scale_d), "n"(TA), "n"(TB));
}
template <int TB>
__device__ __forceinline__ void wgmma_rs_n160(float (&d)[80], uint32_t a0, uint32_t a1, uint32_t a2, uint32_t a3, uint64_t db, int scale_d) {
  asm volatile("{\n.reg .pred p;\nsetp.ne.b32 p, %85, 0;\n"
    "wgmma.mma_async.sync.aligned.m64n160k16.f32.bf16.bf16 {%0, %1, %2, %3, %4, %5, %6, %7, %8, %9, %10, %11, %12, %13, %14, %15, %16, %17, %18, %19, %20, %21, %22, %23, %24, %25, %26, %27, %28, %29, %30, %31, %32, %33, %34, %35, %36, %37, %38, %39, %40, %41, %42, %43, %44, %45, %46, %47, %48, %49, %50, %51, %52, %53, %54, %55, %56, %57, %58, %59, %60, %61, %62, %63, %64, %65, %66, %67, %68, %69, %70, %71, %72, %73, %74, %75, %76, %77, %78, %79}, {%80, %81, %82, %83}, %84, p, 1, 1, %86;\n}\n"
    : "+f"(d[0]), "+f"(d[1]), "+f"(d[2]), "+f"(d[3]), "+f"(d[4]), "+f"(d[5]), "+f"(d[6]), "+f"(d[7]), "+f"(d[8]), "+f"(d[9]), "+f"(d[10]), "+f"(d[11]), "+f"(d[12]), "+f"(d[13]), "+f"(d[14]), "+f"(d[15]), "+f"(d[16]), "+f"(d[17]), "+f"(d[18]), "+f"(d[19]), "+f"(d[20]), "+f"(d[21]), "+f"(d[22]), "+f"(d[23]), "+f"(d[24]), "+f"(d[25]), "+f"(d[26]), "+f"(d[27]), "+f"(d[28]), "+f"(d[29]), "+f"(d[30]), "+f"(d[31]), "+f"(d[32]), "+f"(d[33]), "+f"(d[34]), "+f"(d[35]), "+f"(d[36]), "+f"(d[37]), "+f"(d[38]), "+f"(d[39]), "+f"(d[40]), "+f"(d[41]), "+f"(d[42]), "+f"(d[43]), "+f"(d[44]), "+f"(d[45]), "+f"(d[46]), "+f"(d[47]), "+f"(d[48]), "+f"(d[49]), "+f"(d[50]), "+f"(d[51]), "+f"(d[52]), "+f"(d[53]), "+f"(d[54]), "+f"(d[55]), "+f"(d[56]), "+f"(d[57]), "+f"(d[58]), "+f"(d[59]), "+f"(d[60]), "+f"(d[61]), "+f"(d[62]), "+f"(d[63]), "+f"(d[64]), "+f"(d[65]), "+f"(d[66]), "+f"(d[67]), "+f"(d[68]), "+f"(d[69]), "+f"(d[70]), "+f"(d[71]), "+f"(d[72]), "+f"(d[73]), "+f"(d[74]), "+f"(d[75]), "+f"(d[76]), "+f"(d[77]), "+f"(d[78]), "+f"(d[79])
    : "r"(a0), "r"(a1), "r"(a2), "r"(a3), "l"(db), "r"(scale_d), "n"(TB));
}
template <int TB, int TA = 0>
__device__ __forceinline__ void wgmma_ss_n192(float (&d)[96], uint64_t da, uint64_t db, int scale_d) {
  asm volatile("{\n.reg .pred p;\nsetp.ne.b32 p, %98, 0;\n"
    "wgmma.mma_async.sync.aligned.m64n192k16.f32.bf16.bf16 {%0, %1, %2, %3, %4, %5, %6, %7, %8, %9, %10, %11, %12, %13, %14, %15, %16, %17, %18, %19, %20, %21, %22, %23, %24, %25, %26, %27, %28, %29, %30, %31, %32, %33, %34, %35, %36, %37, %38, %39, %40, %41, %42, %43, %44, %45, %46, %47, %48, %49, %50, %51, %52, %53, %54, %55, %56, %57, %58, %59, %60, %61, %62, %63, %64, %65, %66, %67, %68, %69, %70, %71, %72, %73, %74, %75, %76, %77, %78, %79, %80, %81, %82, %83, %84, %85, %86, %87, %88, %89, %90, %91, %92, %93, %94, %95}, %96, %97, p, 1, 1, %99, %100;\n}\n"
    : "+f"(d[0]), "+f"(d[1]), "+f"(d[2]), "+f"(d[3]), "+f"(d[4]), "+f"(d[5]), "+f"(d[6]), "+f"(d[7]), "+f"(d[8]), "+f"(d[9]), "+f"(d[10]), "+f"(d[11]), "+f"(d[12]), "+f"(d[13]), "+f"(d[14]), "+f"(d[15]), "+f"(d[16]), "+f"(d[17]), "+f"(d[18]), "+f"(d[19]), "+f"(d[20]), "+f"(d[21]), "+f"(d[22]), "+f"(d[23]), "+f"(d[24]), "+f"(d[25]), "+f"(d[26]), "+f"(d[27]), "+f"(d[28]), "+f"(d[29]), "+f"(d[30]), "+f"(d[31]), "+f"(d[32]), "+f"(d[33]), "+f"(d[34]), "+f"(d[35]), "+f"(d[36]), "+f"(d[37]), "+f"(d[38]), "+f"(d[39]), "+f"(d[40]), "+f"(d[41]), "+f"(d[42]), "+f"(d[43]), "+f"(d[44]), "+f"(d[45]), "+f"(d[46]), "+f"(d[47]), "+f"(d[48]), "+f"(d[49]), "+f"(d[50]), "+f"(d[51]), "+f"(d[52]), "+f"(d[53]), "+f"(d[54]), "+f"(d[55]), "+f"(d[56]), "+f"(d[57]), "+f"(d[58]), "+f"(d[59]), "+f"(d[60]), "+f"(d[61]), "+f"(d[62]), "+f"(d[63]), "+f"(d[64]), "+f"(d[65]), "+f"(d[66]), "+f"(d[67]), "+f"(d[68]), "+f"(d[69]), "+f"(d[70]), "+f"(d[71]), "+f"(d[72]), "+f"(d[73]), "+f"(d[74]), "+f"(d[75]), "+f"(d[76]), "+f"(d[77]), "+f"(d[78]), "+f"(d[79]), "+f"(d[80]), "+f"(d[81]), "+f"(d[82]), "+f"(d[83]), "+f"(d[84]), "+f"(d[85]), "+f"(d[86]), "+f"(d[87]), "+f"(d[88]), "+f"(d[89]), "+f"(d[90]), "+f"(d[91]), "+f"(d[92]), "+f"(d[93]), "+f"(d[94]), "+f"(d[95])
    : "l"(da), "l"(db), "r"(scale_d), "n"(TA), "n"(TB));
}
template <int TB>
__device__ __forceinline__ void wgmma_rs_n192(float (&d)[96], uint32_t a0, uint32_t a1, uint32_t a2, uint32_t a3, uint64_t db, int scale_d) {
  asm volatile("{\n.reg .pred p;\nsetp.ne.b32 p, %101, 0;\n"
    "wgmma.mma_async.sync.aligned.m64n192k16.f32.bf16.bf16 {%0, %1, %2, %3, %4, %5, %6, %7, %8, %9, %10, %11, %12, %13, %14, %15, %16, %17, %18, %19, %20, %21, %22, %23, %24, %25, %26, %27, %28, %29, %30, %31, %32, %33, %34, %35, %36, %37, %38, %39, %40, %41, %42, %43, %44, %45, %46, %47, %48, %49, %50, %51, %52, %53, %54, %55, %56, %57, %58, %59, %60, %61, %62, %63, %64, %65, %66, %67, %68, %69, %70, %71, %72, %73, %74, %75, %76, %77, %78, %79, %80, %81, %82, %83, %84, %85, %86, %87, %88, %89, %90, %91, %92, %93, %94, %95}, {%96, %97, %98, %99}, %100, p, 1, 1, %102;\n}\n"
    : "+f"(d[0]), "+f"(d[1]), "+f"(d[2]), "+f"(d[3]), "+f"(d[4]), "+f"(d[5]), "+f"(d[6]), "+f"(d[7]), "+f"(d[8]), "+f"(d[9]), "+f"(d[10]), "+f"(d[11]), "+f"(d[12]), "+f"(d[13]), "+f"(d[14]), "+f"(d[15]), "+f"(d[16]), "+f"(d[17]), "+f"(d[18]), "+f"(d[19]), "+f"(d[20]), "+f"(d[21]), "+f"(d[22]), "+f"(d[23]), "+f"(d[24]), "+f"(d[25]), "+f"(d[26]), "+f"(d[27]), "+f"(d[28]), "+f"(d[29]), "+f"(d[30]), "+f"(d[31]), "+f"(d[32]), "+f"(d[33]), "+f"(d[34]), "+f"(d[35]), "+f"(d[36]), "+f"(d[37]), "+f"(d[38]), "+f"(d[39]), "+f"(d[40]), "+f"(d[41]), "+f"(d[42]), "+f"(d[43]), "+f"(d[44]), "+f"(d[45]), "+f"(d[46]), "+f"(d[47]), "+f"(d[48]), "+f"(d[49]), "+f"(d[50]), "+f"(d[51]), "+f"(d[52]), "+f"(d[53]), "+f"(d[54]), "+f"(d[55]), "+f"(d[56]), "+f"(d[57]), "+f"(d[58]), "+f"(d[59]), "+f"(d[60]), "+f"(d[61]), "+f"(d[62]), "+f"(d[63]), "+f"(d[64]), "+f"(d[65]), "+f"(d[66]), "+f"(d[67]), "+f"(d[68]), "+f"(d[69]), "+f"(d[70]), "+f"(d[71]), "+f"(d[72]), "+f"(d[73]), "+f"(d[74]), "+f"(d[75]), "+f"(d[76]), "+f"(d[77]), "+f"(d[78]), "+f"(d[79]), "+f"(d[80]), "+f"(d[81]), "+f"(d[82]), "+f"(d[83]), "+f"(d[84]), "+f"(d[85]), "+f"(d[86]), "+f"(d[87]), "+f"(d[88]), "+f"(d[89]), "+f"(d[90]), "+f"(d[91]), "+f"(d[92]), "+f"(d[93]), "+f"(d[94]), "+f"(d[95])
    : "r"(a0), "r"(a1), "r"(a2), "r"(a3), "l"(db), "r"(scale_d), "n"(TB));
}

__device__ __forceinline__ uint32_t smem_u32(const void* p) { return (uint32_t)__cvta_generic_to_shared(p); }
__device__ __forceinline__ void wg_fence() { asm volatile("wgmma.fence.sync.aligned;" ::: "memory"); }
__device__ __forceinline__ void wg_commit() { asm volatile("wgmma.commit_group.sync.aligned;" ::: "memory"); }
template <int N> __device__ __forceinline__ void wg_wait() { asm volatile("wgmma.wait_group.sync.aligned %0;" ::"n"(N) : "memory"); }
__device__ __forceinline__ void sched_fence(int& keep, uint32_t zero) {
  asm volatile("{\n.reg .u32 c;\nmov.u32 c, %%clock;\nand.b32 c, c, %1;\nxor.b32 %0, %0, c;\n}\n" : "+r"(keep) : "r"(zero) : "memory");
}
template <int N> __device__ __forceinline__ void fence_regs(float (&r)[N]) {
#pragma unroll
  for (int i = 0; i < N; i++) asm volatile("" : "+f"(r[i])::"memory");
}
template <int N> __device__ __forceinline__ void fence_regs(uint32_t (&r)[N]) {
#pragma unroll
  for (int i = 0; i < N; i++) asm volatile("" : "+r"(r[i])::"memory");
}
__device__ __forceinline__ uint64_t mk_desc(uint32_t a16, uint32_t lbo, uint32_t sbo, uint32_t swz) {
  uint64_t d;
  asm("mov.b64 %0, {%1, %2};" : "=l"(d) : "r"(a16 + ((lbo >> 4) << 16)), "r"((sbo >> 4) | (swz << 30)));
  return d;
}
__device__ __forceinline__ void mbar_init(uint32_t bar, uint32_t cnt) {
  asm volatile("mbarrier.init.shared::cta.b64 [%0], %1;" ::"r"(bar), "r"(cnt) : "memory");
}
__device__ __forceinline__ void mbar_expect(uint32_t bar, uint32_t tx) {
  asm volatile("mbarrier.arrive.expect_tx.shared::cta.b64 _, [%0], %1;" ::"r"(bar), "r"(tx) : "memory");
}
__device__ __forceinline__ bool mbar_test(uint32_t bar, uint32_t ph) {
  uint32_t ok;
  asm volatile("{\n.reg .pred p;\nmbarrier.test_wait.parity.shared::cta.b64 p, [%1], %2;\nselp.u32 %0, 1, 0, p;\n}\n"
               : "=r"(ok) : "r"(bar), "r"(ph) : "memory");
  return ok;
}
__device__ __forceinline__ void mbar_wait(uint32_t bar, uint32_t ph) {
  asm volatile("{\n.reg .pred p;\n.reg .u32 n;\nmov.u32 n, 0;\n"
               "LOOP:\nadd.u32 n, n, 1;\nmbarrier.try_wait.parity.shared::cta.b64 p, [%0], %1;\n@p bra DONE;\n"
               "setp.lt.u32 p, n, 0x1000000;\n@p bra LOOP;\ntrap;\n"
               "DONE:\n}\n" ::"r"(bar), "r"(ph) : "memory");
}
template <int NS> __device__ __forceinline__ void mbar_wait_slow(uint32_t bar, uint32_t ph) {
  asm volatile("{\n.reg .pred p;\n.reg .u32 n;\nmov.u32 n, 0;\n"
               "LOOP:\nmbarrier.test_wait.parity.shared::cta.b64 p, [%0], %1;\n@p bra DONE;\n"
               "nanosleep.u32 %2;\nadd.u32 n, n, 1;\nsetp.lt.u32 p, n, 0x400000;\n@p bra LOOP;\ntrap;\n"
               "DONE:\n}\n" ::"r"(bar), "r"(ph), "n"(NS) : "memory");
}
__device__ __forceinline__ void mbar_arrive_cluster_if(bool on, uint32_t addr) {
  asm volatile("{\n.reg .pred p;\nsetp.ne.b32 p, %1, 0;\n@p mbarrier.arrive.shared::cluster.b64 _, [%0];\n}\n" ::"r"(addr), "r"((int)on) : "memory");
}
__device__ __forceinline__ void mbar_arrive_if(bool on, uint32_t addr) {
  asm volatile("{\n.reg .pred p;\nsetp.ne.b32 p, %1, 0;\n@p mbarrier.arrive.shared::cta.b64 _, [%0];\n}\n" ::"r"(addr), "r"((int)on) : "memory");
}
__device__ __forceinline__ void tma2d(uint32_t dst, const CUtensorMap* m, uint32_t bar, int c0, int c1) {
  asm volatile("cp.async.bulk.tensor.2d.shared::cluster.global.mbarrier::complete_tx::bytes [%0], [%1, {%3, %4}], [%2];"
               ::"r"(dst), "l"(m), "r"(bar), "r"(c0), "r"(c1) : "memory");
}
__device__ __forceinline__ void tma3d(uint32_t dst, const CUtensorMap* m, uint32_t bar, int c0, int c1, int c2) {
  asm volatile("cp.async.bulk.tensor.3d.shared::cluster.global.mbarrier::complete_tx::bytes [%0], [%1, {%3, %4, %5}], [%2];"
               ::"r"(dst), "l"(m), "r"(bar), "r"(c0), "r"(c1), "r"(c2) : "memory");
}
__device__ __forceinline__ void tma3d_mc(uint32_t dst, const CUtensorMap* m, uint32_t bar, int c0, int c1, int c2) {
  asm volatile("cp.async.bulk.tensor.3d.shared::cluster.global.mbarrier::complete_tx::bytes.multicast::cluster"
               " [%0], [%1, {%3, %4, %5}], [%2], %6;"
               ::"r"(dst), "l"(m), "r"(bar), "r"(c0), "r"(c1), "r"(c2), "h"((uint16_t)3) : "memory");
}
__device__ __forceinline__ void tma3d_store(const CUtensorMap* m, uint32_t src, int c0, int c1, int c2) {
  asm volatile("cp.async.bulk.tensor.3d.global.shared::cta.bulk_group [%0, {%2, %3, %4}], [%1];"
               ::"l"(m), "r"(src), "r"(c0), "r"(c1), "r"(c2) : "memory");
}
__device__ __forceinline__ void bar_sync(int id, int n) { asm volatile("bar.sync %0, %1;" ::"r"(id), "r"(n) : "memory"); }
__device__ __forceinline__ uint32_t pack_bf16(float lo, float hi) {
  uint32_t r;
  asm("cvt.rn.bf16x2.f32 %0, %1, %2;" : "=r"(r) : "f"(hi), "f"(lo));
  return r;
}
__device__ __forceinline__ float ex2(float x) {
  float y;
  asm("ex2.approx.ftz.f32 %0, %1;" : "=f"(y) : "f"(x));
  return y;
}
__device__ __forceinline__ float fadd(float a, float b) {
  float y;
  asm("add.f32 %0, %1, %2;" : "=f"(y) : "f"(a), "f"(b));
  return y;
}
__device__ __forceinline__ float rcp(float x) {
  float y;
  asm("rcp.approx.ftz.f32 %0, %1;" : "=f"(y) : "f"(x));
  return y;
}
__device__ __forceinline__ void stsm4(uint32_t addr, uint32_t a, uint32_t b, uint32_t c, uint32_t d) {
  asm volatile("stmatrix.sync.aligned.m8n8.x4.shared.b16 [%0], {%1, %2, %3, %4};" ::"r"(addr), "r"(a), "r"(b), "r"(c), "r"(d) : "memory");
}

__device__ __forceinline__ void tma4d_mc_hint(uint32_t dst, const CUtensorMap* m, uint32_t bar, int c3, uint64_t pol) {
  asm volatile("cp.async.bulk.tensor.4d.shared::cluster.global.mbarrier::complete_tx::bytes.multicast::cluster.L2::cache_hint"
               " [%0], [%1, {%3, %3, %3, %4}], [%2], %5, %6;"
               ::"r"(dst), "l"(m), "r"(bar), "r"(0), "r"(c3), "h"((uint16_t)3), "l"(pol) : "memory");
}
__device__ __forceinline__ void tma5d_mc(uint32_t dst, const CUtensorMap* m, uint32_t bar, int c2, int c4) {
  asm volatile("cp.async.bulk.tensor.5d.shared::cluster.global.mbarrier::complete_tx::bytes.multicast::cluster"
               " [%0], [%1, {%3, %3, %4, %3, %5}], [%2], %6;"
               ::"r"(dst), "l"(m), "r"(bar), "r"(0), "r"(c2), "r"(c4), "h"((uint16_t)3) : "memory");
}
__device__ __forceinline__ void bulk_load_hint(uint32_t dst, const void* src, uint32_t bytes, uint32_t bar, uint64_t pol) {
  asm volatile("cp.async.bulk.shared::cluster.global.mbarrier::complete_tx::bytes.L2::cache_hint [%0], [%1], %2, [%3], %4;"
               ::"r"(dst), "l"(src), "r"(bytes), "r"(bar), "l"(pol) : "memory");
}
__device__ __forceinline__ void stg128_hint(void* p, uint32_t a, uint32_t b, uint32_t c, uint32_t d, uint64_t pol) {
  asm volatile("st.global.L2::cache_hint.v4.b32 [%0], {%1, %2, %3, %4}, %5;" ::"l"(p), "r"(a), "r"(b), "r"(c), "r"(d), "l"(pol) : "memory");
}
__device__ __forceinline__ void stg2_if(bool on, void* p, uint32_t a, uint32_t b, uint32_t c, uint32_t d, uint32_t e, uint32_t f,
                                        uint32_t g, uint32_t h, uint64_t pol) {
  asm volatile("{\n.reg .pred p;\nsetp.ne.b32 p, %10, 0;\n"
               "@p st.global.L2::cache_hint.v4.b32 [%0], {%1, %2, %3, %4}, %9;\n"
               "@p st.global.L2::cache_hint.v4.b32 [%0 + 512], {%5, %6, %7, %8}, %9;\n}\n"
               ::"l"(p), "r"(a), "r"(b), "r"(c), "r"(d), "r"(e), "r"(f), "r"(g), "r"(h), "l"(pol), "r"((int)on) : "memory");
}
__device__ __forceinline__ uint64_t evict_first() {
  uint64_t p;
  asm("createpolicy.fractional.L2::evict_first.b64 %0, 1.0;" : "=l"(p));
  return p;
}
__device__ __forceinline__ bool elect() {
  uint32_t ok;
  asm volatile("{\n.reg .pred p;\nelect.sync _|p, 0xffffffff;\nselp.u32 %0, 1, 0, p;\n}\n" : "=r"(ok));
  return ok;
}
__device__ __forceinline__ void mbar_arrive(uint32_t bar) {
  asm volatile("mbarrier.arrive.shared::cta.b64 _, [%0];" ::"r"(bar) : "memory");
}
__device__ __forceinline__ void stg128(void* p, uint32_t a, uint32_t b, uint32_t c, uint32_t d) {
  asm volatile("st.global.v4.b32 [%0], {%1, %2, %3, %4};" ::"l"(p), "r"(a), "r"(b), "r"(c), "r"(d) : "memory");
}
__device__ __forceinline__ void lds128(uint32_t p, uint32_t& a, uint32_t& b, uint32_t& c, uint32_t& d) {
  asm volatile("ld.shared.v4.b32 {%0, %1, %2, %3}, [%4];" : "=r"(a), "=r"(b), "=r"(c), "=r"(d) : "r"(p) : "memory");
}
__device__ __forceinline__ void wait_count(const unsigned int* p, uint32_t target) {
  asm volatile("{\n.reg .pred p;\n.reg .u32 n, v;\nmov.u32 n, 0;\n"
               "LOOP:\nld.acquire.gpu.global.u32 v, [%0];\nsetp.ge.u32 p, v, %1;\n@p bra DONE;\n"
               "nanosleep.u32 %2;\nadd.u32 n, n, 1;\nsetp.lt.u32 p, n, 0x400000;\n@p bra LOOP;\ntrap;\n"
               "DONE:\n}\n" ::"l"(p), "r"(target), "n"(200) : "memory");
}

__host__ __device__ __forceinline__ int o_wave(int a, int b, int i, int lag) {
  if (lag == 0) return a + i;
  const int p = lag < b - a - 1 ? lag : b - a - 1;
  return i < p ? b - 2 - i : i == p ? b - 1 : b - 1 - i;
}

struct Cursor {
  uint32_t n;
  __device__ __forceinline__ uint32_t off() const { return n & (8 * NBAR - 8); }
  __device__ __forceinline__ uint32_t ph() const { return (n / (8 * NBAR)) & 1; }
  __device__ __forceinline__ void next() { n += 8; }
};

constexpr float kScaleLog2 = 0.07216878364870322f * 1.4426950408889634f;
constexpr float kSumLimit = 1048576.0f;
constexpr float kMaxLag = 8.0f;

__global__ void __cluster_dims__(2, 1, 1) __launch_bounds__(384, 1)
fused_kernel(const __grid_constant__ Params P) {
  extern __shared__ uint8_t smem_raw[];
  const uint32_t sbase = (smem_u32(smem_raw) + 1023) & ~1023u;
  const uint32_t full0 = sbase + RING, empty0 = full0 + 8 * NBAR, odone = empty0 + 8 * NBAR, oready0 = odone + 8;
  const uint32_t fenced = oready0 + 64, hready0 = fenced + 8;
  const uint32_t rank = blockIdx.x & 1;
  const int role = blockIdx.x >> 1;
  const bool helper = role >= N_CL;
  const int team = helper ? 0 : role >> 2, nt = role & 3, blk = team >> 3;
  const uint32_t* prog = P.ops[helper ? N_TEAM + 2 * (role - N_CL) : team];
  auto q_role = [&](uint32_t op) { return helper ? (int)(((op >> 3) & 60) | ((op >> 12) & 3)) : role; };
  auto o_role = [&](uint32_t op) { return helper ? (int)(((op >> 26) & 56) | ((op >> 9) & 7)) : role; };
  const int wid = __shfl_sync(0xffffffffu, (int)(threadIdx.x >> 5), 0);
  const int wg = wid >> 2;

  const uint32_t op0 = P.first[helper ? N_TEAM + role - N_CL : team];
  if (__builtin_expect(wid == 8, 1)) {
    if (elect()) {
#pragma unroll
      for (int k = 0; k < EARLY; k++) mbar_init(full0 + 8 * k, 1);
      asm volatile("fence.mbarrier_init.release.cluster;" ::: "memory");
      if ((op0 & 3) == OP_Q) {
        const int qr = q_role(op0);
#pragma unroll
        for (int k = 0; k < EARLY; k++) {
          mbar_expect(full0 + 8 * k, SZ_WQ + SZ_A);
          tma2d(sbase + k * (SZ_WQ + SZ_A) + SZ_WQ, &P.x[qr >> 5], full0 + 8 * k, 64 * k, ((qr >> 2) & 7) * kSq + rank * 128);
          tma3d(sbase + k * (SZ_WQ + SZ_A), &P.wq[qr >> 5], full0 + 8 * k, 0, 64 * k, 3 * (4 * ((op0 >> 2) & 7) + (qr & 3)));
          tma3d(sbase + k * (SZ_WQ + SZ_A) + SZ_WQ / 2, &P.wq[qr >> 5], full0 + 8 * k, 0, 64 * k + 32, 3 * (4 * ((op0 >> 2) & 7) + (qr & 3)));
        }
      }
      asm volatile("prefetch.tensormap [%0];" ::"l"(&P.k[blk]) : "memory");
      asm volatile("prefetch.tensormap [%0];" ::"l"(&P.v[blk]) : "memory");
    }
  } else if (threadIdx.x == 0) {
#pragma unroll
    for (int i = EARLY; i < 2 * NBAR + 10 + MAX_PARK; i++) mbar_init(full0 + 8 * i, i >= NBAR && i <= 2 * NBAR ? 16 : 1);
    asm volatile("fence.mbarrier_init.release.cluster;" ::: "memory");
  }
  __syncwarp();
  asm volatile("barrier.cluster.arrive.relaxed.aligned;\nbarrier.cluster.wait.aligned;" ::: "memory");

  if (wg == 2) {
    asm volatile("setmaxnreg.dec.sync.aligned.u32 24;");
    if (wid == 8) {
      Cursor tail{0}, head{0};
      int sh = 0;
      uint32_t cur = 0, used = 0;
      uint64_t fifo = 0;
      uint32_t dst, bar, oready = oready0;
      const uint64_t pol = evict_first();
      auto acquire = [&](uint32_t bytes, int part = 0) {
        uint32_t fp = bytes >> 12;
        if (cur + fp > (RING >> 12)) { fp += (RING >> 12) - cur; cur = 0; }
        used += fp;
        bool more = false;
        uint32_t wbar, wph;
        while (used > (RING >> 12) || (part != 2 && sh == 5 * NFLIGHT)) {
          if (more) mbar_wait(wbar, wph);
          more = true;
          wbar = empty0 + tail.off(); wph = tail.ph();
          tail.next();
          used -= (uint32_t)fifo & 31;
          fifo >>= 5;
          sh -= 5;
        }
        fifo += (uint64_t)fp << sh;
        dst = sbase + (cur << 12);
        bar = full0 + head.off();
        cur += bytes >> 12;
        if (part != 1) {
          sh += 5;
          head.next();
        }
        if (more) mbar_wait(wbar, wph);
      };
      auto scratch = [&](const uint4* src, uint32_t bytes, int n) {
        asm volatile("fence.proxy.async.global;" ::: "memory");
#pragma unroll 1
        for (int i = 0; i < n; i++) {
          acquire(bytes);
          if (elect()) {
            bulk_load_hint(dst, src + i * (bytes / 16), bytes, bar, pol);
            mbar_expect(bar, bytes);
          }
        }
      };
      for (int pc = 0;; pc++) {
        const uint32_t op = prog[pc];
        const int type = op & 3, a = (op >> 2) & 7;
        if (type == OP_END) break;
        if (type == OP_Q) {
          const int qr = q_role(op);
#pragma unroll 1
          for (int k = 0; k < 10; k++) {
            acquire(SZ_WQ, 1);
            if ((pc > 0 || k >= EARLY) && elect()) tma3d_mc(dst + rank * (SZ_WQ / 2), &P.wq[qr >> 5], bar, 0, 64 * k + 32 * rank, 3 * (4 * a + (qr & 3)));
            acquire(SZ_A, 2);
            if ((pc > 0 || k >= EARLY) && elect()) {
              tma2d(dst, &P.x[qr >> 5], bar, 64 * k, ((qr >> 2) & 7) * kSq + rank * 128);
              mbar_expect(bar, SZ_WQ + SZ_A);
            }
          }
        } else if (type == OP_A) {
          const uint32_t nop = prog[pc + 1];
#pragma unroll 1
          for (int t = (op & F_PARK) ? 1 : 0; t < 33; t++) {
            int wave = a;
            if (t == 31 && (nop & 3) != OP_A) t++;
            if (t == 31) {
              wave = (nop >> 2) & 7;
              mbar_wait((nop & F_HELP) ? hready0 + 8 * ((nop >> 10) & 3) : fenced, 0);
              scratch(&g_o[((team * 2 + rank) * 96 + 3 * (4 * wave + nt)) * 1024], SZ_PARK, 2);
            }
            const int isv = t ? ~t & 1 : 0, j = (isv ? (t - 1) >> 1 : (t + 1) >> 1) & 15;
            const int row0 = ((team & 7) * kH + 4 * wave + nt) * kSk;
            acquire(SZ_KV);
            if (t >= KV_TRANSIT) {
              const Cursor c{head.n - 8 * (KV_TRANSIT + 1)};
              mbar_wait(full0 + c.off(), c.ph());
            }
            if (elect()) {
              tma4d_mc_hint(dst + rank * (SZ_KV / 2), isv ? &P.v[blk] : &P.k[blk], bar, row0 / 8 + 8 * j + 4 * rank, pol);
              mbar_expect(bar, SZ_KV);
            }
          }
        } else {
          const int b = (op >> 5) & 15, ro = o_role(op);
#pragma unroll 1
          for (int i = 0; i < b - a; i++) {
            const int w = o_wave(a, b, i, (P.dbg >> 4) & 7);
            mbar_wait(oready, 0);
            oready += 8;
            asm volatile("fence.proxy.async.global;" ::: "memory");
#pragma unroll 1
            for (int k = 12 * w; k < 12 * w + 12; k++) {
              acquire(SZ_A, 1);
              if (elect()) bulk_load_hint(dst, &g_o[(((ro >> 2) * 2 + rank) * 96 + k) * 1024], SZ_A, bar, pol);
              acquire(SZ_WO, 2);
              if (elect()) {
                tma5d_mc(dst + rank * 10240, &P.wo[ro >> 5], bar, 8 * k + 4 * rank, 5 * (ro & 3));
                mbar_expect(bar, SZ_WO + SZ_A);
              }
            }
          }
          if (op & F_LD) {
            if (op & F_PARK) mbar_wait(hready0 + 8 * (MAX_PARK - 1), 0);
            scratch(&g_part[(role * 2 + rank) * 5120], SZ_PART, 5);
          }
        }
      }
    } else if (threadIdx.x == 288) {
      uint32_t ph = 0;
      bool first = true;
      for (int pc = 0;; pc++) {
        const uint32_t op = prog[pc];
        if ((op & 3) == OP_END) break;
        if ((op & 3) != OP_A && !helper) continue;
        mbar_wait_slow<400>(odone, ph);
        ph ^= 1;
        unsigned int* flag = !helper ? &g_done[(team * 2 + rank) * 8 + ((op >> 2) & 7)]
                             : (op & 3) == OP_Q ? &g_help[(q_role(op) * 2 + rank) * MAX_PARK + ((op >> 10) & 3)]
                                                : &g_help[(o_role(op) * 2 + rank) * MAX_PARK + MAX_PARK - 1];
        asm volatile("red.release.gpu.global.add.u32 [%0], 1;" ::"l"(flag) : "memory");
        if (first) mbar_arrive(fenced);
        first = false;
      }
    } else if (threadIdx.x == 320) {
      uint32_t oready = oready0;
      for (int pc = 0;; pc++) {
        const uint32_t op = prog[pc];
        if ((op & 3) == OP_END) break;
        if ((op & 3) == OP_O) {
          const int a = (op >> 2) & 7, b = (op >> 5) & 15;
#pragma unroll 1
          for (int i = 0; i < b - a; i++) {
            const int ci = ((o_role(op) >> 2) * 2 + rank) * 8 + o_wave(a, b, i, (P.dbg >> 4) & 7);
            wait_count(&g_done[ci], 4);
            mbar_arrive(oready);
            oready += 8;
            if (atomicAdd(&g_seen[ci], 1u) == 3u) { g_seen[ci] = 0; g_done[ci] = 0; }
          }
        }
        if ((op & 3) != OP_Q && (op & F_HELP) && (op & F_PARK)) {
          unsigned int* flag = &g_help[(role * 2 + rank) * MAX_PARK + ((op >> 10) & 3)];
          wait_count(flag, 1);
          mbar_arrive(hready0 + 8 * ((op >> 10) & 3));
          *flag = 0;
        }
      }
    }
    __syncwarp();
    asm volatile("barrier.cluster.arrive.relaxed;\nbarrier.cluster.wait;" ::: "memory");
  } else {
    asm volatile("setmaxnreg.inc.sync.aligned.u32 240;");
    const int lane = threadIdx.x & 31, warp = wid & 3;
    uint32_t empty_rem;
    asm volatile("mapa.shared::cluster.u32 %0, %1, %2;" : "=r"(empty_rem) : "r"(empty0), "r"(lane & 1));
    auto release = [&](int slot) { mbar_arrive_cluster_if(lane < 2, empty_rem + slot); };
    Cursor r{0};
    const uint32_t ring16 = (sbase & 0x3FFFF) >> 4;
    uint32_t cur = ring16;
    bool rdy0 = false, rdy1 = false;
    auto probe1 = [&]() { rdy0 = mbar_test(full0 + r.off(), r.ph()); };
    auto probe2 = [&]() {
      Cursor n = r;
      rdy0 = mbar_test(full0 + n.off(), n.ph());
      n.next();
      rdy1 = mbar_test(full0 + n.off(), n.ph());
    };
    auto take = [&](bool rdy, uint32_t bytes, uint32_t& addr) {
      const int bi = r.off();
      if (!__all_sync(0xffffffffu, rdy)) mbar_wait(full0 + r.off(), r.ph());
      r.next();
      if (cur > ring16 + ((RING - bytes) >> 4)) cur = ring16;
      addr = cur;
      cur += bytes >> 4;
      return bi;
    };
    auto second = [&](uint32_t bytes) {
      if (cur > ring16 + ((RING - bytes) >> 4)) cur = ring16;
      cur += bytes >> 4;
      return cur - (bytes >> 4);
    };
    const int row = wg * 64 + warp * 16 + (lane >> 2);
    int img0 = row * 4 + ((lane & 3) ^ ((row >> 1) & 3));
    uint4* pend = nullptr;
    const uint64_t spol = evict_first();
    int pc = 0;
    uint32_t op = prog[0];
    auto enter = [&]() {
      r.n = op >> 12; cur = ring16 + (((op >> 20) & 63) << 8);
    };
    auto drain = [&](uint32_t (&t)[48], uint32_t c) {
      if (!(op & (3u << 26)) || c >= 6) return;
#pragma unroll
      for (int i = 0; i < 6; i++)
        stg2_if(c == i, pend + i * 512, t[8 * i], t[8 * i + 1], t[8 * i + 2], t[8 * i + 3],
                t[8 * i + 4], t[8 * i + 5], t[8 * i + 6], t[8 * i + 7], spol);
      if ((op & (1u << 26)) && c == 5) {
        __syncwarp();
        mbar_arrive_if(lane < 2, odone);
      }
    };
    float s[32], o[96], c[80];
    uint32_t q[48], pa[16], pb[16];
    float mc0, mc1, l0, l1;
    bool gen;
    auto soft = [&](float (&s)[32], uint32_t (&pout)[16], bool first) {
      if (first) { gen = false; mc0 = 0.f; mc1 = 0.f; }
      float b0, b1;
      for (;;) {
        if (gen) {
          float m0 = fmaxf(s[0], s[1]), m1 = fmaxf(s[2], s[3]);
#pragma unroll
          for (int i = 1; i < 8; i++) { m0 = fmaxf(m0, fmaxf(s[4 * i], s[4 * i + 1])); m1 = fmaxf(m1, fmaxf(s[4 * i + 2], s[4 * i + 3])); }
          m0 = fmaxf(m0, __shfl_xor_sync(0xffffffffu, m0, 1)); m1 = fmaxf(m1, __shfl_xor_sync(0xffffffffu, m1, 1));
          m0 = fmaxf(m0, __shfl_xor_sync(0xffffffffu, m0, 2)); m1 = fmaxf(m1, __shfl_xor_sync(0xffffffffu, m1, 2));
          if (first) {
            mc0 = m0; mc1 = m1;
          } else if (__any_sync(0xffffffffu, !(m0 <= mc0 + kMaxLag && m1 <= mc1 + kMaxLag))) {
            m0 = fmaxf(mc0, m0); m1 = fmaxf(mc1, m1);
            const float a0 = ex2(mc0 - m0), a1 = ex2(mc1 - m1);
            mc0 = m0; mc1 = m1;
            l0 *= a0; l1 *= a1;
            wg_wait<0>();
            fence_regs(o);
#pragma unroll
            for (int i = 0; i < 96; i++) o[i] *= i & 2 ? a1 : a0;
          }
#pragma unroll
          for (int i = 0; i < 32; i++) s[i] -= i & 2 ? mc1 : mc0;
        }
#pragma unroll
        for (int i = 0; i < 8; i++) {
          const float e1 = ex2(s[4 * i + 1]), e0 = ex2(s[4 * i]), e3 = ex2(s[4 * i + 3]), e2 = ex2(s[4 * i + 2]);
          pout[2 * i] = pack_bf16(e0, e1);
          b0 = i ? b0 + fadd(e1, e0) : fadd(e1, e0);
          pout[2 * i + 1] = pack_bf16(e2, e3);
          b1 = i ? b1 + fadd(e3, e2) : fadd(e3, e2);
        }
        if (!__any_sync(0xffffffffu, !gen && !(fmaxf(b0, b1) <= kSumLimit && (!first || fminf(b0, b1) >= 1.0f / kSumLimit)))) break;
        gen = __any_sync(0xffffffffu, true);
      }
      l0 = first ? b0 : l0 + b0;
      l1 = first ? b1 : l1 + b1;
    };
    auto qk = [&](float (&s)[32], uint32_t ak, int k0, int k1) {
#pragma unroll
      for (int kk = k0; kk < k1; kk++)
        wgmma_rs_n64<0>(s, q[4 * kk], q[4 * kk + 1], q[4 * kk + 2], q[4 * kk + 3], mk_desc(ak + (kk >> 2) * KV_CH + (kk & 3) * 2, 16, KV_SBO, 1), kk != 0);
      wg_commit();
    };
    auto pv = [&](uint32_t (&pin)[16], uint32_t av, int acc) {
#pragma unroll
      for (int kk = 0; kk < 4; kk++)
        wgmma_rs_n192<1>(o, pin[4 * kk], pin[4 * kk + 1], pin[4 * kk + 2], pin[4 * kk + 3], mk_desc(av + kk * (KV_SBO / 8), KV_CH * 16, KV_SBO, 1), acc || (kk != 0));
      wg_commit();
    };
    auto xw = [&](uint32_t ad, int acc) {
      const uint32_t da = second(SZ_A) + wg * 512;
      wg_fence();
#pragma unroll
      for (int kk = 0; kk < 4; kk++)
        wgmma_ss_n192<1>(o, mk_desc(da + kk * 2, 16, 1024, 1), mk_desc(ad + (kk & 1) * 128 + (kk >> 1) * 768, 4096, 1024, 1), acc || kk != 0);
      wg_commit();
    };
    auto ow = [&](int acc, int prev) {
      uint32_t da;
      const int bi = take(rdy0, SZ_A, da);
      const uint32_t db = second(SZ_WO);
      da += wg * 256;
      wg_fence();
      wgmma_ss_n160<1>(c, mk_desc(da, 16, 512, 2), mk_desc(db, 2048, 512, 2), acc);
      wgmma_ss_n160<1>(c, mk_desc(da + 2, 16, 512, 2), mk_desc(db + 64, 2048, 512, 2), 1);
      wg_commit();
      if (acc) { wg_wait<1>(); release(prev); }
      wgmma_ss_n160<1>(c, mk_desc(da + 512, 16, 512, 2), mk_desc(db + 640, 2048, 512, 2), 1);
      wgmma_ss_n160<1>(c, mk_desc(da + 514, 16, 512, 2), mk_desc(db + 704, 2048, 512, 2), 1);
      wg_commit();
      return bi;
    };
    auto st_part = [&](int i) {
      stg2_if(true, pend + i * 512, __float_as_uint(c[8 * i]), __float_as_uint(c[8 * i + 1]), __float_as_uint(c[8 * i + 2]), __float_as_uint(c[8 * i + 3]),
              __float_as_uint(c[8 * i + 4]), __float_as_uint(c[8 * i + 5]), __float_as_uint(c[8 * i + 6]), __float_as_uint(c[8 * i + 7]), spol);
    };
#pragma unroll
    for (int i = 0; i < 48; i++) q[i] = 0;
    enter();

    if ((op & 3) == OP_Q) {
      uint32_t ad;
      int bi0 = take(false, SZ_WQ, ad), k = 0, lag = 0;
      xw(ad, 0);
      for (;;) {
#pragma unroll 1
        for (;;) {
          drain(q, k - lag);
          probe1();
          wg_wait<0>();
          release(bi0);
          bi0 = take(rdy0, SZ_WQ, ad);
          if (++k == 8) break;
          xw(ad, 1);
        }
        if (wg) bar_sync(2, 256);
        xw(ad, 1);
        const int bi9 = take(false, SZ_WQ, ad);
        xw(ad, 1);
        if (!wg) asm volatile("bar.arrive 2, 256;" ::: "memory");
        k = 0; lag = 0;
        uint32_t nop = prog[++pc];
        wg_wait<1>();
        release(bi0);
        probe2();
        wg_wait<0>();
        fence_regs(o);
        release(bi9);
#pragma unroll
        for (int i = 0; i < 48; i++) q[i] = pack_bf16(o[2 * i] * kScaleLog2, o[2 * i + 1] * kScaleLog2);
        fence_regs(q);
        if (op & F_PARK) {
          const int qt = helper ? (op >> 5) & 15 : team, qm = helper ? (op >> 12) & 3 : nt;
          pend = &g_o[((qt * 2 + rank) * 96 + 3 * (4 * ((op >> 2) & 7) + qm)) * 1024 + img0];
          op = nop;
          enter();
          if ((op & 3) != OP_Q) break;
          bi0 = take(rdy0, SZ_WQ, ad);
          xw(ad, 0);
          continue;
        }
        int wave = (op >> 2) & 7, sk1;
        uint32_t ak1;
        {
          float s0[32];
          const int sk0 = take(rdy0, SZ_KV, ad);
          wg_fence();
          qk(s0, ad, 0, 12);
          sk1 = take(rdy1, SZ_KV, ak1);
          wg_fence();
          qk(s, ak1, 0, S1A);
          probe1();
          wg_wait<1>();
          fence_regs(s0);
          release(sk0);
          soft(s0, pa, true);
        }
        float i0, i1;
        auto sums = [&]() {
          l0 += __shfl_xor_sync(0xffffffffu, l0, 1); l1 += __shfl_xor_sync(0xffffffffu, l1, 1);
          l0 += __shfl_xor_sync(0xffffffffu, l0, 2); l1 += __shfl_xor_sync(0xffffffffu, l1, 2);
          i0 = rcp(l0); i1 = rcp(l1);
          asm volatile("" : "+f"(i0), "+f"(i1));
        };
        auto target = [&]() {
          pend = &g_o[((team * 2 + rank) * 96 + 3 * (4 * wave + nt)) * 1024 + img0];
          asm volatile("" : "+l"(pend));
        };
        for (;;) {
          nop = prog[++pc];
          {
            uint32_t av;
            const int sv = take(rdy0, SZ_KV, av);
            wg_fence();
            qk(s, ak1, S1A, 12);
            pv(pa, av, 0);
            probe2();
            wg_wait<1>();
            fence_regs(s);
            release(sk1);
            soft(s, pb, false);
            wg_wait<0>();
            fence_regs(o);
            release(sv);
          }
          auto step = [&](uint32_t (&pin)[16], uint32_t (&pout)[16]) {
            uint32_t ak, av;
            const int sk = take(rdy0, SZ_KV, ak), sv = take(rdy1, SZ_KV, av);
            wg_fence();
            qk(s, ak, 0, 12);
            pv(pin, av, 1);
            probe2();
            wg_wait<1>();
            fence_regs(s);
            release(sk);
            soft(s, pout, false);
            wg_wait<0>();
            fence_regs(o);
            release(sv);
          };
#pragma unroll 1
          for (int jj = 0; jj < 7; jj++) {
            step(pb, pa);
            step(pa, pb);
          }
          if ((nop & 3) != OP_A) break;
          uint32_t ak, av;
          {
            const int b0 = take(rdy0, SZ_PARK, ak), b1 = take(rdy1, SZ_PARK, av);
            const uint32_t ad0 = ak, ad1 = av;
            probe2();
#pragma unroll
            for (int i = 0; i < 12; i++)
              lds128(sbase + ((i < 6 ? ad0 : ad1) - ring16 + img0) * 16 + ((i % 6) >> 1) * 8192 + (i & 1) * 512, q[4 * i], q[4 * i + 1], q[4 * i + 2], q[4 * i + 3]);
            release(b0); release(b1);
          }
          const int sk0 = take(rdy0, SZ_KV, ak), sv = take(rdy1, SZ_KV, av);
          wg_fence();
          qk(s, ak, 0, 8);
          sched_fence(img0, P.zero);
          sums();
          sched_fence(img0, P.zero);
          qk(s, ak, 8, 12);
          pv(pb, av, 1);
          probe2();
          wg_wait<1>();
          fence_regs(s);
          release(sk0);
          soft(s, pa, true);
          sk1 = take(rdy0, SZ_KV, ak1);
          rdy0 = rdy1;
          wg_wait<0>();
          target();
          fence_regs(o);
          release(sv);
          uint32_t t[48];
#pragma unroll
          for (int j = 0; j < 6; j++) {
#pragma unroll
            for (int i = 0; i < 4; i++) {
              t[8 * j + i] = pack_bf16(o[16 * j + 4 * i] * i0, o[16 * j + 4 * i + 1] * i0);
              t[8 * j + i + 4] = pack_bf16(o[16 * j + 4 * i + 2] * i1, o[16 * j + 4 * i + 3] * i1);
            }
            stg2_if(true, pend + j * 512, t[8 * j], t[8 * j + 1], t[8 * j + 2], t[8 * j + 3], t[8 * j + 4], t[8 * j + 5], t[8 * j + 6], t[8 * j + 7], spol);
            if (j == UC0) { wg_fence(); qk(s, ak1, 0, 4); }
            if (j == UC1) { wg_fence(); qk(s, ak1, 4, S1A); }
            sched_fence(img0, P.zero);
          }
          if (P.zero) {
#pragma unroll
            for (int j = 0; j < 5; j++)
              stg2_if(true, pend, t[8 * j], t[8 * j + 1], t[8 * j + 2], t[8 * j + 3], t[8 * j + 4], t[8 * j + 5], t[8 * j + 6], t[8 * j + 7], spol);
          }
          __syncwarp();
          mbar_arrive_if(lane < 2, odone);
          wave = (nop >> 2) & 7;
        }
        const int sv = take(rdy0, SZ_KV, ad);
        wg_fence();
        pv(pb, ad, 1);
        sums();
        target();
        op = nop;
        enter();
        rdy0 = rdy1;
        auto convert = [&](float (&u)[96], int j0, int j1) {
#pragma unroll
          for (int i = 4 * j0; i < 4 * j1; i++) {
            q[8 * (i >> 2) + (i & 3)] = pack_bf16(u[4 * i], u[4 * i + 1]);
            q[8 * (i >> 2) + (i & 3) + 4] = pack_bf16(u[4 * i + 2], u[4 * i + 3]);
          }
        };
        if ((op & 3) != OP_O) {
          if ((op & 3) == OP_Q) bi0 = take(rdy0, SZ_WQ, ad);
          wg_wait<0>();
          fence_regs(o);
          release(sv);
          float u[96];
#pragma unroll
          for (int i = 0; i < 96; i++) u[i] = o[i] * (i & 2 ? i1 : i0);
          if ((op & 3) != OP_Q) { convert(u, 0, 6); break; }
          fence_regs(u);
          xw(ad, 0);
          sched_fence(img0, P.zero);
          fence_regs(u);
          convert(u, 0, 1);
          stg2_if(true, pend, q[0], q[1], q[2], q[3], q[4], q[5], q[6], q[7], spol);
          probe1();
          wg_wait<0>();
          release(bi0);
          bi0 = take(rdy0, SZ_WQ, ad);
          xw(ad, 1);
          sched_fence(img0, P.zero);
          fence_regs(u);
          convert(u, 1, 6);
          k = 1;
          continue;
        }
        int bi = ow(0, 0);
        wg_wait<2>();
        fence_regs(o);
        release(sv);
#pragma unroll
        for (int j = 0; j < 6; j++) {
          uint32_t t[8];
#pragma unroll
          for (int i = 0; i < 4; i++) {
            t[i] = pack_bf16(o[16 * j + 4 * i] * i0, o[16 * j + 4 * i + 1] * i0);
            t[i + 4] = pack_bf16(o[16 * j + 4 * i + 2] * i1, o[16 * j + 4 * i + 3] * i1);
          }
          stg2_if(true, pend + j * 512, t[0], t[1], t[2], t[3], t[4], t[5], t[6], t[7], spol);
          if (j == 5) {
            __syncwarp();
            mbar_arrive_if(lane < 2, odone);
          }
          probe1();
          wg_wait<1>();
          bi = ow(1, bi);
          fence_regs(o);
        }
        {
          const int nk = 12 * (((op >> 5) & 15) - ((op >> 2) & 7));
#pragma unroll 1
          for (int k = 7; k < nk; k++) {
            probe1();
            wg_wait<1>();
            bi = ow(1, bi);
          }
          probe1();
        }
        nop = prog[++pc];
        if (op & F_LD) {
          uint32_t t[80];
#pragma unroll
          for (int j = 0; j < 5; j++) {
            const int b = take(rdy0, SZ_PART, ad);
            probe1();
#pragma unroll
            for (int i = 4 * j; i < 4 * j + 4; i++)
              lds128(sbase + (ad - ring16 + img0) * 16 + ((i >> 1) & 1) * 8192 + (i & 1) * 512, t[4 * i], t[4 * i + 1], t[4 * i + 2], t[4 * i + 3]);
            release(b);
          }
          wg_wait<0>();
          fence_regs(c);
#pragma unroll
          for (int i = 0; i < 80; i++) c[i] += __uint_as_float(t[i]);
        }
        if (!(op & F_ST)) {
          wg_wait<0>();
          fence_regs(c);
          goto finish;
        }
        op = nop;
        enter();
        bi0 = take(rdy0, SZ_WQ, ad);
        xw(ad, 0);
        pend = &g_part[((team * 4 + nt) * 2 + rank) * 5120 + img0];
        probe1();
        wg_wait<1>();
        fence_regs(c);
        release(bi);
        st_part(0); st_part(1);
        wg_wait<0>();
        release(bi0);
        bi0 = take(rdy0, SZ_WQ, ad);
        xw(ad, 1);
        st_part(2); st_part(3);
#pragma unroll
        for (int i = 0; i < 48; i++) q[i] = __float_as_uint(c[32 + i]);
        pend += 4 * 512;
        k = 1; lag = 2;
      }
    }
    rdy0 = false;
    {
      uint32_t t[48];
#pragma unroll
      for (int i = 0; i < 48; i++) t[i] = q[i] ^ P.zero;
      while ((op & 3) == OP_O) {
        int bi = ow(0, 0);
#pragma unroll 1
        for (int k = 1; k < 12 * (int)(((op >> 5) & 15) - ((op >> 2) & 7)); k++) {
          drain(t, k - 1);
          probe1();
          wg_wait<1>();
          bi = ow(1, bi);
        }
        rdy0 = false;
        wg_wait<0>();
        fence_regs(c);
        pc++;
        if (!(op & F_ST)) goto finish;
        release(bi);
        pend = &g_part[((((op >> 26) & 56) | ((op >> 9) & 7)) * 2 + rank) * 5120 + img0];
#pragma unroll
        for (int i = 6; i < 10; i++) st_part(i);
#pragma unroll
        for (int i = 0; i < 48; i++) t[i] = __float_as_uint(c[i]) ^ P.zero;
        op = prog[pc];
        enter();
      }
      for (int i = 0; i < 6; i++) drain(t, i);
    }
    asm volatile("barrier.cluster.arrive.relaxed;" ::: "memory");
    if (false) {
    finish:
      asm volatile("barrier.cluster.arrive.relaxed;" ::: "memory");
      bar_sync(1, 256);
      const uint32_t wstage = sbase + (wg * 4 + warp) * 5120;
      const uint32_t sa = wstage + (lane & 15) * 64;
#pragma unroll
      for (int i = 0; i < 10; i++) {
        const int u = (i & 1) * 2 + (lane >> 4);
        stsm4(sa + (i >> 1) * 1024 + ((u ^ ((lane >> 1) & 3)) << 4), pack_bf16(c[8 * i], c[8 * i + 1]), pack_bf16(c[8 * i + 2], c[8 * i + 3]),
              pack_bf16(c[8 * i + 4], c[8 * i + 5]), pack_bf16(c[8 * i + 6], c[8 * i + 7]));
      }
      asm volatile("fence.proxy.async.shared::cta;" ::: "memory");
      __syncwarp();
      if (lane == 0) {
        tma3d_store(&P.out, wstage, 0, (team & 7) * kSq + rank * 128 + wg * 64 + warp * 16, blk * 20 + nt * 5);
        asm volatile("cp.async.bulk.commit_group;\ncp.async.bulk.wait_group.read 0;" ::: "memory");
      }
      __syncwarp();
    }
    asm volatile("barrier.cluster.wait;" ::: "memory");
  }
}

typedef CUresult (*EncodeFn)(CUtensorMap*, CUtensorMapDataType, cuuint32_t, void*, const cuuint64_t*, const cuuint64_t*,
                             const cuuint32_t*, const cuuint32_t*, CUtensorMapInterleave, CUtensorMapSwizzle,
                             CUtensorMapL2promotion, CUtensorMapFloatOOBfill);

void encode(EncodeFn fn, CUtensorMap* m, const void* ptr, int rank, const cuuint64_t* dims, const cuuint64_t* strides,
            const cuuint32_t* box, CUtensorMapSwizzle swz) {
  const cuuint32_t es[5] = {1, 1, 1, 1, 1};
  CUresult r = fn(m, CU_TENSOR_MAP_DATA_TYPE_BFLOAT16, rank, const_cast<void*>(ptr), dims, strides, box, es,
                  CU_TENSOR_MAP_INTERLEAVE_NONE, swz, CU_TENSOR_MAP_L2_PROMOTION_L2_128B, CU_TENSOR_MAP_FLOAT_OOB_FILL_NONE);
  if (r != CUDA_SUCCESS) fprintf(stderr, "cuTensorMapEncodeTiled failed: %d\n", (int)r);
}

void annotate(uint32_t* ops, int n, bool helper) {
  uint32_t items = 0, cur = 0, pend = 0;
  auto item = [&](uint32_t bytes, int count, uint32_t bytes2 = 0) {
    for (int i = 0; i < count; i++) {
      if (cur + bytes > RING) cur = 0;
      cur += bytes;
      if (cur + bytes2 > RING) cur = 0;
      cur += bytes2;
      items++;
    }
  };
  for (int i = 0; i <= n; i++) {
    const uint32_t op = ops[i];
    ops[i] |= (items % (2 * NBAR)) << 15 | (cur >> 12) << 20 | pend << 26;
    if ((op & 3) == OP_Q) { item(SZ_WQ, 10, SZ_A); pend = (op & F_PARK) ? (helper ? 1 : 2) : 0; }
    if ((op & 3) == OP_A) {
      item(SZ_KV, (op & F_PARK) ? 30 : 31);
      if ((ops[i + 1] & 3) == OP_A) { item(SZ_PARK, 2); item(SZ_KV, 1); }
      item(SZ_KV, 1);
      pend = 1;
    }
    if ((op & 3) == OP_O) {
      item(SZ_A, 12 * (((op >> 5) & 15) - ((op >> 2) & 7)), SZ_WO);
      if (op & F_LD) item(SZ_PART, 5);
      pend = (op & F_ST) ? (helper ? 1 : 2) : 0;
    }
  }
}

void compile_programs(const char* const* text, bool helpers, Params& P) {
  struct Req { int when, team, wave, slot; } req[N_TEAM * MAX_PARK];
  int n_req = 0;
  for (int t = 0; t < N_TEAM; t++) {
    uint32_t* ops = P.ops[t];
    int n = 0, flags[8] = {0, 0, 0, 0, 0, 0, 0, 0}, n_park = 0, last_o = -1, when = 0, given = 0;
    for (const char* s = text[t]; *s; s++) {
      const int a = s[1] - '0';
      if (*s == 'Q' || (*s == 'H' && !helpers)) { ops[n++] = OP_Q | a << 2; when += 10; }
      else if (*s == 'P') { flags[a] = F_PARK; ops[n++] = OP_Q | a << 2 | flags[a]; when += 10; }
      else if (*s == 'H') { req[n_req++] = {when, t, a, n_park}; flags[a] = F_PARK | F_HELP | n_park++ << 10; }
      else if (*s == 'A') { ops[n++] = OP_A | a << 2 | flags[a]; when += 32; }
      else if (*s == 'G') { given = a; if (helpers) req[n_req++] = {1000, t, 0, -a}; }
      else if (*s == 'O') {
        ops[n] = OP_O | a << 2 | (s[2] - '0') << 5;
        if (given) ops[n] = helpers ? ops[n] | F_LD | F_PARK | (MAX_PARK - 1) << 10 : ops[n] & ~(7u << 2);
        if (last_o >= 0) { ops[last_o] |= F_ST; ops[n] |= F_LD; }
        last_o = n++;
        when += 10 * (s[2] - s[1]);
      }
    }
    for (int i = n; i < MAX_OPS; i++) ops[i] = OP_END;
    annotate(ops, n, false);
  }
  for (int i = 1; i < n_req; i++)
    for (int j = i; j > 0 && req[j].when < req[j - 1].when; j--) { Req r = req[j]; req[j] = req[j - 1]; req[j - 1] = r; }
  for (int h = 0; h < N_HELP; h++) {
    uint32_t* ops = P.ops[N_TEAM + 2 * h];
    int n = 0;
    for (int i = 0; i < n_req; i++)
      for (int m = h; m < 4; m += N_HELP) {
        const uint32_t ro = 4 * req[i].team + m;
        ops[n++] = req[i].slot >= 0 ? OP_Q | req[i].wave << 2 | req[i].team << 5 | F_PARK | req[i].slot << 10 | m << 12
                                    : OP_O | -req[i].slot << 5 | F_ST | (ro & 7) << 9 | (ro >> 3) << 29;
      }
    for (int i = n; i < 2 * MAX_OPS; i++) ops[i] = OP_END;
    annotate(ops, n, true);
  }
  for (int i = 0; i < 32; i++) P.first[i] = i < N_TEAM ? P.ops[i][0] : i < N_TEAM + N_HELP ? P.ops[2 * i - N_TEAM][0] : 0;
}

const char* const kPrograms[N_TEAM] = {
  "Q0A0Q1A1H2A2Q3A3O03Q4A4Q5A5Q6A6Q7A7O38",
  "Q0A0Q1A1Q2A2Q3A3O04Q4A4Q5A5Q6A6H7A7O48",
  "Q0A0H1A1Q2A2Q3A3Q4A4O05Q5A5Q6A6Q7A7O58",
  "Q0A0Q1A1Q2A2Q3A3Q4A4O05Q5A5Q6A6H7A7O58",
  "Q0A0Q1A1Q2A2O03Q3A3H4A4Q5A5Q6A6Q7A7O38",
  "Q0A0Q1A1H2A2Q3A3Q4A4O05Q5A5Q6A6Q7A7O58",
  "Q0A0Q1A1Q2A2Q3A3O03Q4A4H5A5Q6A6Q7A7O38",
  "Q0A0Q1A1Q2A2O03Q3A3Q4A4Q5A5Q6A6H7A7O38",
  "P2P3Q0A0Q1A1A2A3H4A4Q5A5Q6A6Q7A7O08",
  "P3P7Q0A0Q1A1H2A2A3Q4A4Q5A5Q6A6A7G1O18",
  "Q0A0Q1A1Q2A2O02Q3A3H4A4Q5A5Q6A6Q7A7O28",
  "P3P5Q0A0Q1A1Q2A2A3Q4A4A5Q6A6H7A7O08",
  "Q0A0Q1A1Q2A2O02Q3A3Q4A4H5A5Q6A6Q7A7O28",
  "P7Q0A0Q1A1Q2A2Q3A3Q4A4Q5A5Q6A6A7G1O18",
  "Q0A0Q1A1Q2A2H3A3Q4A4Q5A5Q6A6Q7A7O08",
  "P5Q0A0Q1A1Q2A2Q3A3Q4A4A5Q6A6H7A7O08",
};

const char* const* bench_programs() {
  return kPrograms;
}

}

extern "C" void kernel_launch(void* const* d_in, const int* in_sizes, int n_in, void* d_out, int out_size) {
  (void)in_sizes; (void)n_in; (void)out_size;
  static EncodeFn fn = nullptr;
  static int n_clusters = 0;
  if (!fn) {
    cudaDriverEntryPointQueryResult qr;
    void* f = nullptr;
    cudaGetDriverEntryPoint("cuTensorMapEncodeTiled", &f, cudaEnableDefault, &qr);
    fn = (EncodeFn)f;
    cudaFuncSetAttribute(fused_kernel, cudaFuncAttributeMaxDynamicSharedMemorySize, SMEM_BYTES);
    cudaLaunchConfig_t cfg = {};
    cfg.gridDim = dim3(132); cfg.blockDim = dim3(384); cfg.dynamicSmemBytes = SMEM_BYTES;
    cudaLaunchAttribute at[1];
    at[0].id = cudaLaunchAttributeClusterDimension; at[0].val.clusterDim.x = 2; at[0].val.clusterDim.y = 1; at[0].val.clusterDim.z = 1;
    cfg.attrs = at; cfg.numAttrs = 1;
    if (cudaOccupancyMaxActiveClusters(&n_clusters, fused_kernel, &cfg) != cudaSuccess || n_clusters < 1) n_clusters = 1;
    (void)cudaGetLastError();
  }
  Params P;
  const CUtensorMapSwizzle S128 = CU_TENSOR_MAP_SWIZZLE_128B, S64 = CU_TENSOR_MAP_SWIZZLE_64B;
  for (int blk = 0; blk < 2; blk++) {
    void* const* in = d_in + 5 * blk;
    { const cuuint64_t d[] = {kD, kB * kSq}, s[] = {kD * 2}; const cuuint32_t b[] = {64, 128};
      encode(fn, &P.x[blk], in[0], 2, d, s, b, S128); }
    { const cuuint64_t d[] = {64, 8, 3, (cuuint64_t)kB * kH * kSk / 8}, s[] = {kDh * 2, 128, 8 * kDh * 2}; const cuuint32_t b[] = {64, 8, 3, 4};
      encode(fn, &P.k[blk], in[1], 4, d, s, b, S128);
      encode(fn, &P.v[blk], in[2], 4, d, s, b, S128); }
    { const cuuint64_t d[] = {64, kD, kHD / 64}, s[] = {kHD * 2, 128}; const cuuint32_t b[] = {64, 32, 3};
      encode(fn, &P.wq[blk], in[3], 3, d, s, b, S128); }
    { const cuuint64_t d[] = {32, 2, kHD / 8, 4, kD / 32}, s[] = {kD * 2, 8 * kD * 2, 2 * kD * 2, 64}; const cuuint32_t b[] = {32, 2, 4, 4, 5};
      encode(fn, &P.wo[blk], in[4], 5, d, s, b, S64); }
  }
  { const cuuint64_t d[] = {32, kB * kSq, 2 * kD / 32}, s[] = {2 * kD * 2, 64}; const cuuint32_t b[] = {32, 16, 5};
    encode(fn, &P.out, d_out, 3, d, s, b, S64); }

  P.zero = 0;
  P.dbg = 0x30;
  if (n_clusters >= N_CL) {
    const bool helpers = n_clusters >= N_CL + N_HELP;
    compile_programs(bench_programs(), helpers, P);
    fused_kernel<<<2 * (N_CL + (helpers ? N_HELP : 0)), 384, SMEM_BYTES>>>(P);
  } else {
    for (int phase = 0; phase < 2; phase++) {
      const char* text[N_TEAM];
      for (int t = 0; t < N_TEAM; t++) text[t] = phase ? "O08" : "Q0A0Q1A1Q2A2Q3A3Q4A4Q5A5Q6A6Q7A7";
      compile_programs(text, false, P);
      fused_kernel<<<2 * N_CL, 384, SMEM_BYTES>>>(P);
    }
  }
}
```

```cpp
#include <cuda_runtime.h>
#include <cuda_bf16.h>
#include <cuda.h>
#include <stdint.h>
#include <stdio.h>

namespace {

constexpr int kB = 8, kSq = 256, kD = 640, kH = 32, kSk = 1024, kDh = 192;
constexpr int kHD = kH * kDh;
#define S1A 7
#define UC0 3
#define UC1 4
#define RING_KB 224
constexpr uint32_t RING = RING_KB * 1024;
constexpr uint32_t SZ_KV = 24576;
constexpr uint32_t SZ_WQ = 24576, SZ_WO = 20480, SZ_A = 16384;
constexpr uint32_t SZ_PARK = 24576;
constexpr uint32_t SZ_PART = 16384;
constexpr int NBAR = 16, NFLIGHT = 12;
#define KVT 4
constexpr int KV_TRANSIT = KVT;
#define EARLY_N 3
constexpr int EARLY = EARLY_N;
constexpr uint32_t KV_CH = 64, KV_SBO = 3072;
constexpr int SMEM_BYTES = RING + 512 + 1024;
constexpr int N_TEAM = 16, N_CL = 64, N_HELP = 2, MAX_OPS = 24, MAX_PARK = 4;
enum { OP_END = 0, OP_Q = 1, OP_A = 2, OP_O = 3, F_PARK = 1 << 9, F_LD = 1 << 12, F_ST = 1 << 13, F_HELP = 1 << 12 };

struct alignas(64) Params {
  uint32_t first[32];
  CUtensorMap x[2], wq[2], k[2], v[2], wo[2], out;
  uint32_t ops[N_TEAM + 2 * N_HELP][MAX_OPS];
  uint32_t zero;
  uint32_t dbg;
};

__device__ uint4 g_o[N_TEAM * 2 * 96 * 1024];
__device__ uint4 g_part[N_CL * 2 * 5 * 1024];
__device__ unsigned int g_done[N_TEAM * 2 * 8];
__device__ unsigned int g_help[N_CL * 2 * MAX_PARK];
__device__ unsigned int g_seen[N_TEAM * 2 * 8];

template <int TB, int TA = 0>
__device__ __forceinline__ void wgmma_ss_n64(float (&d)[32], uint64_t da, uint64_t db, int scale_d) {
  asm volatile("{\n.reg .pred p;\nsetp.ne.b32 p, %34, 0;\n"
    "wgmma.mma_async.sync.aligned.m64n64k16.f32.bf16.bf16 {%0, %1, %2, %3, %4, %5, %6, %7, %8, %9, %10, %11, %12, %13, %14, %15, %16, %17, %18, %19, %20, %21, %22, %23, %24, %25, %26, %27, %28, %29, %30, %31}, %32, %33, p, 1, 1, %35, %36;\n}\n"
    : "+f"(d[0]), "+f"(d[1]), "+f"(d[2]), "+f"(d[3]), "+f"(d[4]), "+f"(d[5]), "+f"(d[6]), "+f"(d[7]), "+f"(d[8]), "+f"(d[9]), "+f"(d[10]), "+f"(d[11]), "+f"(d[12]), "+f"(d[13]), "+f"(d[14]), "+f"(d[15]), "+f"(d[16]), "+f"(d[17]), "+f"(d[18]), "+f"(d[19]), "+f"(d[20]), "+f"(d[21]), "+f"(d[22]), "+f"(d[23]), "+f"(d[24]), "+f"(d[25]), "+f"(d[26]), "+f"(d[27]), "+f"(d[28]), "+f"(d[29]), "+f"(d[30]), "+f"(d[31])
    : "l"(da), "l"(db), "r"(scale_d), "n"(TA), "n"(TB));
}
template <int TB>
__device__ __forceinline__ void wgmma_rs_n64(float (&d)[32], uint32_t a0, uint32_t a1, uint32_t a2, uint32_t a3, uint64_t db, int scale_d) {
  asm volatile("{\n.reg .pred p;\nsetp.ne.b32 p, %37, 0;\n"
    "wgmma.mma_async.sync.aligned.m64n64k16.f32.bf16.bf16 {%0, %1, %2, %3, %4, %5, %6, %7, %8, %9, %10, %11, %12, %13, %14, %15, %16, %17, %18, %19, %20, %21, %22, %23, %24, %25, %26, %27, %28, %29, %30, %31}, {%32, %33, %34, %35}, %36, p, 1, 1, %38;\n}\n"
    : "+f"(d[0]), "+f"(d[1]), "+f"(d[2]), "+f"(d[3]), "+f"(d[4]), "+f"(d[5]), "+f"(d[6]), "+f"(d[7]), "+f"(d[8]), "+f"(d[9]), "+f"(d[10]), "+f"(d[11]), "+f"(d[12]), "+f"(d[13]), "+f"(d[14]), "+f"(d[15]), "+f"(d[16]), "+f"(d[17]), "+f"(d[18]), "+f"(d[19]), "+f"(d[20]), "+f"(d[21]), "+f"(d[22]), "+f"(d[23]), "+f"(d[24]), "+f"(d[25]), "+f"(d[26]), "+f"(d[27]), "+f"(d[28]), "+f"(d[29]), "+f"(d[30]), "+f"(d[31])
    : "r"(a0), "r"(a1), "r"(a2), "r"(a3), "l"(db), "r"(scale_d), "n"(TB));
}
template <int TB, int TA = 0>
__device__ __forceinline__ void wgmma_ss_n160(float (&d)[80], uint64_t da, uint64_t db, int scale_d) {
  asm volatile("{\n.reg .pred p;\nsetp.ne.b32 p, %82, 0;\n"
    "wgmma.mma_async.sync.aligned.m64n160k16.f32.bf16.bf16 {%0, %1, %2, %3, %4, %5, %6, %7, %8, %9, %10, %11, %12, %13, %14, %15, %16, %17, %18, %19, %20, %21, %22, %23, %24, %25, %26, %27, %28, %29, %30, %31, %32, %33, %34, %35, %36, %37, %38, %39, %40, %41, %42, %43, %44, %45, %46, %47, %48, %49, %50, %51, %52, %53, %54, %55, %56, %57, %58, %59, %60, %61, %62, %63, %64, %65, %66, %67, %68, %69, %70, %71, %72, %73, %74, %75, %76, %77, %78, %79}, %80, %81, p, 1, 1, %83, %84;\n}\n"
    : "+f"(d[0]), "+f"(d[1]), "+f"(d[2]), "+f"(d[3]), "+f"(d[4]), "+f"(d[5]), "+f"(d[6]), "+f"(d[7]), "+f"(d[8]), "+f"(d[9]), "+f"(d[10]), "+f"(d[11]), "+f"(d[12]), "+f"(d[13]), "+f"(d[14]), "+f"(d[15]), "+f"(d[16]), "+f"(d[17]), "+f"(d[18]), "+f"(d[19]), "+f"(d[20]), "+f"(d[21]), "+f"(d[22]), "+f"(d[23]), "+f"(d[24]), "+f"(d[25]), "+f"(d[26]), "+f"(d[27]), "+f"(d[28]), "+f"(d[29]), "+f"(d[30]), "+f"(d[31]), "+f"(d[32]), "+f"(d[33]), "+f"(d[34]), "+f"(d[35]), "+f"(d[36]), "+f"(d[37]), "+f"(d[38]), "+f"(d[39]), "+f"(d[40]), "+f"(d[41]), "+f"(d[42]), "+f"(d[43]), "+f"(d[44]), "+f"(d[45]), "+f"(d[46]), "+f"(d[47]), "+f"(d[48]), "+f"(d[49]), "+f"(d[50]), "+f"(d[51]), "+f"(d[52]), "+f"(d[53]), "+f"(d[54]), "+f"(d[55]), "+f"(d[56]), "+f"(d[57]), "+f"(d[58]), "+f"(d[59]), "+f"(d[60]), "+f"(d[61]), "+f"(d[62]), "+f"(d[63]), "+f"(d[64]), "+f"(d[65]), "+f"(d[66]), "+f"(d[67]), "+f"(d[68]), "+f"(d[69]), "+f"(d[70]), "+f"(d[71]), "+f"(d[72]), "+f"(d[73]), "+f"(d[74]), "+f"(d[75]), "+f"(d[76]), "+f"(d[77]), "+f"(d[78]), "+f"(d[79])
    : "l"(da), "l"(db), "r"(scale_d), "n"(TA), "n"(TB));
}
template <int TB>
__device__ __forceinline__ void wgmma_rs_n160(float (&d)[80], uint32_t a0, uint32_t a1, uint32_t a2, uint32_t a3, uint64_t db, int scale_d) {
  asm volatile("{\n.reg .pred p;\nsetp.ne.b32 p, %85, 0;\n"
    "wgmma.mma_async.sync.aligned.m64n160k16.f32.bf16.bf16 {%0, %1, %2, %3, %4, %5, %6, %7, %8, %9, %10, %11, %12, %13, %14, %15, %16, %17, %18, %19, %20, %21, %22, %23, %24, %25, %26, %27, %28, %29, %30, %31, %32, %33, %34, %35, %36, %37, %38, %39, %40, %41, %42, %43, %44, %45, %46, %47, %48, %49, %50, %51, %52, %53, %54, %55, %56, %57, %58, %59, %60, %61, %62, %63, %64, %65, %66, %67, %68, %69, %70, %71, %72, %73, %74, %75, %76, %77, %78, %79}, {%80, %81, %82, %83}, %84, p, 1, 1, %86;\n}\n"
    : "+f"(d[0]), "+f"(d[1]), "+f"(d[2]), "+f"(d[3]), "+f"(d[4]), "+f"(d[5]), "+f"(d[6]), "+f"(d[7]), "+f"(d[8]), "+f"(d[9]), "+f"(d[10]), "+f"(d[11]), "+f"(d[12]), "+f"(d[13]), "+f"(d[14]), "+f"(d[15]), "+f"(d[16]), "+f"(d[17]), "+f"(d[18]), "+f"(d[19]), "+f"(d[20]), "+f"(d[21]), "+f"(d[22]), "+f"(d[23]), "+f"(d[24]), "+f"(d[25]), "+f"(d[26]), "+f"(d[27]), "+f"(d[28]), "+f"(d[29]), "+f"(d[30]), "+f"(d[31]), "+f"(d[32]), "+f"(d[33]), "+f"(d[34]), "+f"(d[35]), "+f"(d[36]), "+f"(d[37]), "+f"(d[38]), "+f"(d[39]), "+f"(d[40]), "+f"(d[41]), "+f"(d[42]), "+f"(d[43]), "+f"(d[44]), "+f"(d[45]), "+f"(d[46]), "+f"(d[47]), "+f"(d[48]), "+f"(d[49]), "+f"(d[50]), "+f"(d[51]), "+f"(d[52]), "+f"(d[53]), "+f"(d[54]), "+f"(d[55]), "+f"(d[56]), "+f"(d[57]), "+f"(d[58]), "+f"(d[59]), "+f"(d[60]), "+f"(d[61]), "+f"(d[62]), "+f"(d[63]), "+f"(d[64]), "+f"(d[65]), "+f"(d[66]), "+f"(d[67]), "+f"(d[68]), "+f"(d[69]), "+f"(d[70]), "+f"(d[71]), "+f"(d[72]), "+f"(d[73]), "+f"(d[74]), "+f"(d[75]), "+f"(d[76]), "+f"(d[77]), "+f"(d[78]), "+f"(d[79])
    : "r"(a0), "r"(a1), "r"(a2), "r"(a3), "l"(db), "r"(scale_d), "n"(TB));
}
template <int TB, int TA = 0>
__device__ __forceinline__ void wgmma_ss_n192(float (&d)[96], uint64_t da, uint64_t db, int scale_d) {
  asm volatile("{\n.reg .pred p;\nsetp.ne.b32 p, %98, 0;\n"
    "wgmma.mma_async.sync.aligned.m64n192k16.f32.bf16.bf16 {%0, %1, %2, %3, %4, %5, %6, %7, %8, %9, %10, %11, %12, %13, %14, %15, %16, %17, %18, %19, %20, %21, %22, %23, %24, %25, %26, %27, %28, %29, %30, %31, %32, %33, %34, %35, %36, %37, %38, %39, %40, %41, %42, %43, %44, %45, %46, %47, %48, %49, %50, %51, %52, %53, %54, %55, %56, %57, %58, %59, %60, %61, %62, %63, %64, %65, %66, %67, %68, %69, %70, %71, %72, %73, %74, %75, %76, %77, %78, %79, %80, %81, %82, %83, %84, %85, %86, %87, %88, %89, %90, %91, %92, %93, %94, %95}, %96, %97, p, 1, 1, %99, %100;\n}\n"
    : "+f"(d[0]), "+f"(d[1]), "+f"(d[2]), "+f"(d[3]), "+f"(d[4]), "+f"(d[5]), "+f"(d[6]), "+f"(d[7]), "+f"(d[8]), "+f"(d[9]), "+f"(d[10]), "+f"(d[11]), "+f"(d[12]), "+f"(d[13]), "+f"(d[14]), "+f"(d[15]), "+f"(d[16]), "+f"(d[17]), "+f"(d[18]), "+f"(d[19]), "+f"(d[20]), "+f"(d[21]), "+f"(d[22]), "+f"(d[23]), "+f"(d[24]), "+f"(d[25]), "+f"(d[26]), "+f"(d[27]), "+f"(d[28]), "+f"(d[29]), "+f"(d[30]), "+f"(d[31]), "+f"(d[32]), "+f"(d[33]), "+f"(d[34]), "+f"(d[35]), "+f"(d[36]), "+f"(d[37]), "+f"(d[38]), "+f"(d[39]), "+f"(d[40]), "+f"(d[41]), "+f"(d[42]), "+f"(d[43]), "+f"(d[44]), "+f"(d[45]), "+f"(d[46]), "+f"(d[47]), "+f"(d[48]), "+f"(d[49]), "+f"(d[50]), "+f"(d[51]), "+f"(d[52]), "+f"(d[53]), "+f"(d[54]), "+f"(d[55]), "+f"(d[56]), "+f"(d[57]), "+f"(d[58]), "+f"(d[59]), "+f"(d[60]), "+f"(d[61]), "+f"(d[62]), "+f"(d[63]), "+f"(d[64]), "+f"(d[65]), "+f"(d[66]), "+f"(d[67]), "+f"(d[68]), "+f"(d[69]), "+f"(d[70]), "+f"(d[71]), "+f"(d[72]), "+f"(d[73]), "+f"(d[74]), "+f"(d[75]), "+f"(d[76]), "+f"(d[77]), "+f"(d[78]), "+f"(d[79]), "+f"(d[80]), "+f"(d[81]), "+f"(d[82]), "+f"(d[83]), "+f"(d[84]), "+f"(d[85]), "+f"(d[86]), "+f"(d[87]), "+f"(d[88]), "+f"(d[89]), "+f"(d[90]), "+f"(d[91]), "+f"(d[92]), "+f"(d[93]), "+f"(d[94]), "+f"(d[95])
    : "l"(da), "l"(db), "r"(scale_d), "n"(TA), "n"(TB));
}
template <int TB>
__device__ __forceinline__ void wgmma_rs_n192(float (&d)[96], uint32_t a0, uint32_t a1, uint32_t a2, uint32_t a3, uint64_t db, int scale_d) {
  asm volatile("{\n.reg .pred p;\nsetp.ne.b32 p, %101, 0;\n"
    "wgmma.mma_async.sync.aligned.m64n192k16.f32.bf16.bf16 {%0, %1, %2, %3, %4, %5, %6, %7, %8, %9, %10, %11, %12, %13, %14, %15, %16, %17, %18, %19, %20, %21, %22, %23, %24, %25, %26, %27, %28, %29, %30, %31, %32, %33, %34, %35, %36, %37, %38, %39, %40, %41, %42, %43, %44, %45, %46, %47, %48, %49, %50, %51, %52, %53, %54, %55, %56, %57, %58, %59, %60, %61, %62, %63, %64, %65, %66, %67, %68, %69, %70, %71, %72, %73, %74, %75, %76, %77, %78, %79, %80, %81, %82, %83, %84, %85, %86, %87, %88, %89, %90, %91, %92, %93, %94, %95}, {%96, %97, %98, %99}, %100, p, 1, 1, %102;\n}\n"
    : "+f"(d[0]), "+f"(d[1]), "+f"(d[2]), "+f"(d[3]), "+f"(d[4]), "+f"(d[5]), "+f"(d[6]), "+f"(d[7]), "+f"(d[8]), "+f"(d[9]), "+f"(d[10]), "+f"(d[11]), "+f"(d[12]), "+f"(d[13]), "+f"(d[14]), "+f"(d[15]), "+f"(d[16]), "+f"(d[17]), "+f"(d[18]), "+f"(d[19]), "+f"(d[20]), "+f"(d[21]), "+f"(d[22]), "+f"(d[23]), "+f"(d[24]), "+f"(d[25]), "+f"(d[26]), "+f"(d[27]), "+f"(d[28]), "+f"(d[29]), "+f"(d[30]), "+f"(d[31]), "+f"(d[32]), "+f"(d[33]), "+f"(d[34]), "+f"(d[35]), "+f"(d[36]), "+f"(d[37]), "+f"(d[38]), "+f"(d[39]), "+f"(d[40]), "+f"(d[41]), "+f"(d[42]), "+f"(d[43]), "+f"(d[44]), "+f"(d[45]), "+f"(d[46]), "+f"(d[47]), "+f"(d[48]), "+f"(d[49]), "+f"(d[50]), "+f"(d[51]), "+f"(d[52]), "+f"(d[53]), "+f"(d[54]), "+f"(d[55]), "+f"(d[56]), "+f"(d[57]), "+f"(d[58]), "+f"(d[59]), "+f"(d[60]), "+f"(d[61]), "+f"(d[62]), "+f"(d[63]), "+f"(d[64]), "+f"(d[65]), "+f"(d[66]), "+f"(d[67]), "+f"(d[68]), "+f"(d[69]), "+f"(d[70]), "+f"(d[71]), "+f"(d[72]), "+f"(d[73]), "+f"(d[74]), "+f"(d[75]), "+f"(d[76]), "+f"(d[77]), "+f"(d[78]), "+f"(d[79]), "+f"(d[80]), "+f"(d[81]), "+f"(d[82]), "+f"(d[83]), "+f"(d[84]), "+f"(d[85]), "+f"(d[86]), "+f"(d[87]), "+f"(d[88]), "+f"(d[89]), "+f"(d[90]), "+f"(d[91]), "+f"(d[92]), "+f"(d[93]), "+f"(d[94]), "+f"(d[95])
    : "r"(a0), "r"(a1), "r"(a2), "r"(a3), "l"(db), "r"(scale_d), "n"(TB));
}

__device__ __forceinline__ uint32_t smem_u32(const void* p) { return (uint32_t)__cvta_generic_to_shared(p); }
__device__ __forceinline__ void wg_fence() { asm volatile("wgmma.fence.sync.aligned;" ::: "memory"); }
__device__ __forceinline__ void wg_commit() { asm volatile("wgmma.commit_group.sync.aligned;" ::: "memory"); }
template <int N> __device__ __forceinline__ void wg_wait() { asm volatile("wgmma.wait_group.sync.aligned %0;" ::"n"(N) : "memory"); }
__device__ __forceinline__ void sched_fence(int& keep, uint32_t zero) {
  asm volatile("{\n.reg .u32 c;\nmov.u32 c, %%clock;\nand.b32 c, c, %1;\nxor.b32 %0, %0, c;\n}\n" : "+r"(keep) : "r"(zero) : "memory");
}
template <int N> __device__ __forceinline__ void fence_regs(float (&r)[N]) {
#pragma unroll
  for (int i = 0; i < N; i++) asm volatile("" : "+f"(r[i])::"memory");
}
template <int N> __device__ __forceinline__ void fence_regs(uint32_t (&r)[N]) {
#pragma unroll
  for (int i = 0; i < N; i++) asm volatile("" : "+r"(r[i])::"memory");
}
__device__ __forceinline__ uint64_t mk_desc(uint32_t a16, uint32_t lbo, uint32_t sbo, uint32_t swz, uint32_t off = 0) {
  uint64_t d;
  asm("mov.b64 %0, {%1, %2};" : "=l"(d) : "r"(a16), "r"((sbo >> 4) | (swz << 30)));
  return d + (off + ((lbo >> 4) << 16));
}
__device__ __forceinline__ void mbar_init(uint32_t bar, uint32_t cnt) {
  asm volatile("mbarrier.init.shared::cta.b64 [%0], %1;" ::"r"(bar), "r"(cnt) : "memory");
}
__device__ __forceinline__ void mbar_expect(uint32_t bar, uint32_t tx) {
  asm volatile("mbarrier.arrive.expect_tx.shared::cta.b64 _, [%0], %1;" ::"r"(bar), "r"(tx) : "memory");
}
__device__ __forceinline__ bool mbar_test(uint32_t bar, uint32_t ph) {
  uint32_t ok;
  asm volatile("{\n.reg .pred p;\nmbarrier.test_wait.parity.shared::cta.b64 p, [%1], %2;\nselp.u32 %0, 1, 0, p;\n}\n"
               : "=r"(ok) : "r"(bar), "r"(ph) : "memory");
  return ok;
}
__device__ __forceinline__ void mbar_wait(uint32_t bar, uint32_t ph) {
  asm volatile("{\n.reg .pred p;\n.reg .u32 n;\nmov.u32 n, 0;\n"
               "LOOP:\nadd.u32 n, n, 1;\nmbarrier.try_wait.parity.shared::cta.b64 p, [%0], %1;\n@p bra DONE;\n"
               "setp.lt.u32 p, n, 0x1000000;\n@p bra LOOP;\ntrap;\n"
               "DONE:\n}\n" ::"r"(bar), "r"(ph) : "memory");
}
template <int NS> __device__ __forceinline__ void mbar_wait_slow(uint32_t bar, uint32_t ph) {
  asm volatile("{\n.reg .pred p;\n.reg .u32 n;\nmov.u32 n, 0;\n"
               "LOOP:\nmbarrier.test_wait.parity.shared::cta.b64 p, [%0], %1;\n@p bra DONE;\n"
               "nanosleep.u32 %2;\nadd.u32 n, n, 1;\nsetp.lt.u32 p, n, 0x400000;\n@p bra LOOP;\ntrap;\n"
               "DONE:\n}\n" ::"r"(bar), "r"(ph), "n"(NS) : "memory");
}
__device__ __forceinline__ void mbar_arrive_cluster_if(bool on, uint32_t addr) {
  asm volatile("{\n.reg .pred p;\nsetp.ne.b32 p, %1, 0;\n@p mbarrier.arrive.shared::cluster.b64 _, [%0];\n}\n" ::"r"(addr), "r"((int)on) : "memory");
}
__device__ __forceinline__ void mbar_arrive_if(bool on, uint32_t addr) {
  asm volatile("{\n.reg .pred p;\nsetp.ne.b32 p, %1, 0;\n@p mbarrier.arrive.shared::cta.b64 _, [%0];\n}\n" ::"r"(addr), "r"((int)on) : "memory");
}
__device__ __forceinline__ void tma2d(uint32_t dst, const CUtensorMap* m, uint32_t bar, int c0, int c1) {
  asm volatile("cp.async.bulk.tensor.2d.shared::cluster.global.mbarrier::complete_tx::bytes [%0], [%1, {%3, %4}], [%2];"
               ::"r"(dst), "l"(m), "r"(bar), "r"(c0), "r"(c1) : "memory");
}
__device__ __forceinline__ void tma3d(uint32_t dst, const CUtensorMap* m, uint32_t bar, int c0, int c1, int c2) {
  asm volatile("cp.async.bulk.tensor.3d.shared::cluster.global.mbarrier::complete_tx::bytes [%0], [%1, {%3, %4, %5}], [%2];"
               ::"r"(dst), "l"(m), "r"(bar), "r"(c0), "r"(c1), "r"(c2) : "memory");
}
__device__ __forceinline__ void tma3d_mc(uint32_t dst, const CUtensorMap* m, uint32_t bar, int c0, int c1, int c2) {
  asm volatile("cp.async.bulk.tensor.3d.shared::cluster.global.mbarrier::complete_tx::bytes.multicast::cluster"
               " [%0], [%1, {%3, %4, %5}], [%2], %6;"
               ::"r"(dst), "l"(m), "r"(bar), "r"(c0), "r"(c1), "r"(c2), "h"((uint16_t)3) : "memory");
}
__device__ __forceinline__ void tma3d_store(const CUtensorMap* m, uint32_t src, int c0, int c1, int c2) {
  asm volatile("cp.async.bulk.tensor.3d.global.shared::cta.bulk_group [%0, {%2, %3, %4}], [%1];"
               ::"l"(m), "r"(src), "r"(c0), "r"(c1), "r"(c2) : "memory");
}
__device__ __forceinline__ void bar_sync(int id, int n) { asm volatile("bar.sync %0, %1;" ::"r"(id), "r"(n) : "memory"); }
__device__ __forceinline__ uint32_t pack_bf16(float lo, float hi) {
  uint32_t r;
  asm("cvt.rn.bf16x2.f32 %0, %1, %2;" : "=r"(r) : "f"(hi), "f"(lo));
  return r;
}
__device__ __forceinline__ float ex2(float x) {
  float y;
  asm("ex2.approx.ftz.f32 %0, %1;" : "=f"(y) : "f"(x));
  return y;
}
__device__ __forceinline__ float fadd(float a, float b) {
  float y;
  asm("add.f32 %0, %1, %2;" : "=f"(y) : "f"(a), "f"(b));
  return y;
}
__device__ __forceinline__ float rcp(float x) {
  float y;
  asm("rcp.approx.ftz.f32 %0, %1;" : "=f"(y) : "f"(x));
  return y;
}
__device__ __forceinline__ void stsm4(uint32_t addr, uint32_t a, uint32_t b, uint32_t c, uint32_t d) {
  asm volatile("stmatrix.sync.aligned.m8n8.x4.shared.b16 [%0], {%1, %2, %3, %4};" ::"r"(addr), "r"(a), "r"(b), "r"(c), "r"(d) : "memory");
}

__device__ __forceinline__ void tma4d_mc_hint(uint32_t dst, const CUtensorMap* m, uint32_t bar, int c3, uint64_t pol) {
  asm volatile("cp.async.bulk.tensor.4d.shared::cluster.global.mbarrier::complete_tx::bytes.multicast::cluster.L2::cache_hint"
               " [%0], [%1, {%3, %3, %3, %4}], [%2], %5, %6;"
               ::"r"(dst), "l"(m), "r"(bar), "r"(0), "r"(c3), "h"((uint16_t)3), "l"(pol) : "memory");
}
__device__ __forceinline__ void tma5d_mc(uint32_t dst, const CUtensorMap* m, uint32_t bar, int c2, int c4) {
  asm volatile("cp.async.bulk.tensor.5d.shared::cluster.global.mbarrier::complete_tx::bytes.multicast::cluster"
               " [%0], [%1, {%3, %3, %4, %3, %5}], [%2], %6;"
               ::"r"(dst), "l"(m), "r"(bar), "r"(0), "r"(c2), "r"(c4), "h"((uint16_t)3) : "memory");
}
__device__ __forceinline__ void bulk_load_hint(uint32_t dst, const void* src, uint32_t bytes, uint32_t bar, uint64_t pol) {
  asm volatile("cp.async.bulk.shared::cluster.global.mbarrier::complete_tx::bytes.L2::cache_hint [%0], [%1], %2, [%3], %4;"
               ::"r"(dst), "l"(src), "r"(bytes), "r"(bar), "l"(pol) : "memory");
}
__device__ __forceinline__ void stg128_hint(void* p, uint32_t a, uint32_t b, uint32_t c, uint32_t d, uint64_t pol) {
  asm volatile("st.global.L2::cache_hint.v4.b32 [%0], {%1, %2, %3, %4}, %5;" ::"l"(p), "r"(a), "r"(b), "r"(c), "r"(d), "l"(pol) : "memory");
}
__device__ __forceinline__ void stg2_if(bool on, void* p, uint32_t a, uint32_t b, uint32_t c, uint32_t d, uint32_t e, uint32_t f,
                                        uint32_t g, uint32_t h, uint64_t pol) {
  asm volatile("{\n.reg .pred p;\nsetp.ne.b32 p, %10, 0;\n"
               "@p st.global.L2::cache_hint.v4.b32 [%0], {%1, %2, %3, %4}, %9;\n"
               "@p st.global.L2::cache_hint.v4.b32 [%0 + 512], {%5, %6, %7, %8}, %9;\n}\n"
               ::"l"(p), "r"(a), "r"(b), "r"(c), "r"(d), "r"(e), "r"(f), "r"(g), "r"(h), "l"(pol), "r"((int)on) : "memory");
}
__device__ __forceinline__ uint64_t evict_first() {
  uint64_t p;
  asm("createpolicy.fractional.L2::evict_first.b64 %0, 1.0;" : "=l"(p));
  return p;
}
__device__ __forceinline__ bool elect() {
  uint32_t ok;
  asm volatile("{\n.reg .pred p;\nelect.sync _|p, 0xffffffff;\nselp.u32 %0, 1, 0, p;\n}\n" : "=r"(ok));
  return ok;
}
__device__ __forceinline__ void mbar_arrive(uint32_t bar) {
  asm volatile("mbarrier.arrive.shared::cta.b64 _, [%0];" ::"r"(bar) : "memory");
}
__device__ __forceinline__ void stg128(void* p, uint32_t a, uint32_t b, uint32_t c, uint32_t d) {
  asm volatile("st.global.v4.b32 [%0], {%1, %2, %3, %4};" ::"l"(p), "r"(a), "r"(b), "r"(c), "r"(d) : "memory");
}
__device__ __forceinline__ void lds128(uint32_t p, uint32_t& a, uint32_t& b, uint32_t& c, uint32_t& d) {
  asm volatile("ld.shared.v4.b32 {%0, %1, %2, %3}, [%4];" : "=r"(a), "=r"(b), "=r"(c), "=r"(d) : "r"(p) : "memory");
}
__device__ __forceinline__ void wait_count(const unsigned int* p, uint32_t target) {
  asm volatile("{\n.reg .pred p;\n.reg .u32 n, v;\nmov.u32 n, 0;\n"
               "LOOP:\nld.acquire.gpu.global.u32 v, [%0];\nsetp.ge.u32 p, v, %1;\n@p bra DONE;\n"
               "nanosleep.u32 %2;\nadd.u32 n, n, 1;\nsetp.lt.u32 p, n, 0x400000;\n@p bra LOOP;\ntrap;\n"
               "DONE:\n}\n" ::"l"(p), "r"(target), "n"(200) : "memory");
}

__host__ __device__ __forceinline__ int o_wave(int a, int b, int i, int lag) {
  if (lag == 0) return a + i;
  const int p = lag < b - a - 1 ? lag : b - a - 1;
  return i < p ? b - 2 - i : i == p ? b - 1 : b - 1 - i;
}

struct Cursor {
  uint32_t n;
  __device__ __forceinline__ uint32_t off() const { return n & (8 * NBAR - 8); }
  __device__ __forceinline__ uint32_t ph() const { return (n / (8 * NBAR)) & 1; }
  __device__ __forceinline__ void next() { n += 8; }
};

constexpr float kScaleLog2 = 0.07216878364870322f * 1.4426950408889634f;
constexpr float kSumLimit = 1048576.0f;
constexpr float kMaxLag = 8.0f;

__global__ void __cluster_dims__(2, 1, 1) __launch_bounds__(384, 1)
fused_kernel(const __grid_constant__ Params P) {
  extern __shared__ uint8_t smem_raw[];
  const uint32_t sbase = (smem_u32(smem_raw) + 1023) & ~1023u;
  const uint32_t full0 = sbase + RING, empty0 = full0 + 8 * NBAR, odone = empty0 + 8 * NBAR, oready0 = odone + 8;
  const uint32_t fenced = oready0 + 64, hready0 = fenced + 8;
  const uint32_t rank = blockIdx.x & 1;
  const int role = blockIdx.x >> 1;
  const bool helper = role >= N_CL;
  const int team = helper ? 0 : role >> 2, nt = role & 3, blk = team >> 3;
  const uint32_t* prog = P.ops[helper ? N_TEAM + 2 * (role - N_CL) : team];
  auto q_role = [&](uint32_t op) { return helper ? (int)(((op >> 3) & 60) | ((op >> 12) & 3)) : role; };
  auto o_role = [&](uint32_t op) { return helper ? (int)(((op >> 26) & 56) | ((op >> 9) & 7)) : role; };
  const int wid = __shfl_sync(0xffffffffu, (int)(threadIdx.x >> 5), 0);
  const int wg = wid >> 2;

  const uint32_t op0 = P.first[helper ? N_TEAM + role - N_CL : team];
  if (__builtin_expect(wid == 8, 1)) {
    if (elect()) {
#pragma unroll
      for (int k = 0; k < EARLY; k++) mbar_init(full0 + 8 * k, 1);
      asm volatile("fence.mbarrier_init.release.cluster;" ::: "memory");
      if ((op0 & 3) == OP_Q) {
        const int qr = q_role(op0);
#pragma unroll
        for (int k = 0; k < EARLY; k++) {
          mbar_expect(full0 + 8 * k, SZ_WQ + SZ_A);
          tma2d(sbase + k * (SZ_WQ + SZ_A) + SZ_WQ, &P.x[qr >> 5], full0 + 8 * k, 64 * k, ((qr >> 2) & 7) * kSq + rank * 128);
          tma3d(sbase + k * (SZ_WQ + SZ_A), &P.wq[qr >> 5], full0 + 8 * k, 0, 64 * k, 3 * (4 * ((op0 >> 2) & 7) + (qr & 3)));
          tma3d(sbase + k * (SZ_WQ + SZ_A) + SZ_WQ / 2, &P.wq[qr >> 5], full0 + 8 * k, 0, 64 * k + 32, 3 * (4 * ((op0 >> 2) & 7) + (qr & 3)));
        }
      }
      asm volatile("prefetch.tensormap [%0];" ::"l"(&P.k[blk]) : "memory");
      asm volatile("prefetch.tensormap [%0];" ::"l"(&P.v[blk]) : "memory");
    }
  } else if (threadIdx.x == 0) {
#pragma unroll
    for (int i = EARLY; i < 2 * NBAR + 10 + MAX_PARK; i++) mbar_init(full0 + 8 * i, i >= NBAR && i <= 2 * NBAR ? 16 : 1);
    asm volatile("fence.mbarrier_init.release.cluster;" ::: "memory");
  }
  __syncwarp();
  asm volatile("barrier.cluster.arrive.relaxed.aligned;\nbarrier.cluster.wait.aligned;" ::: "memory");

  if (wg == 2) {
    asm volatile("setmaxnreg.dec.sync.aligned.u32 24;");
    if (wid == 8) {
      Cursor tail{0}, head{0};
      int sh = 0;
      uint32_t cur = 0, used = 0;
      uint64_t fifo = 0;
      uint32_t dst, bar, oready = oready0;
      const uint64_t pol = evict_first();
      auto acquire = [&](uint32_t bytes, int part = 0) {
        uint32_t fp = bytes >> 12;
        if (cur + fp > (RING >> 12)) { fp += (RING >> 12) - cur; cur = 0; }
        used += fp;
        bool more = false;
        uint32_t wbar, wph;
        while (used > (RING >> 12) || (part != 2 && sh == 5 * NFLIGHT)) {
          if (more) mbar_wait(wbar, wph);
          more = true;
          wbar = empty0 + tail.off(); wph = tail.ph();
          tail.next();
          used -= (uint32_t)fifo & 31;
          fifo >>= 5;
          sh -= 5;
        }
        fifo += (uint64_t)fp << sh;
        dst = sbase + (cur << 12);
        bar = full0 + head.off();
        cur += bytes >> 12;
        if (part != 1) {
          sh += 5;
          head.next();
        }
        if (more) mbar_wait(wbar, wph);
      };
      auto scratch = [&](const uint4* src, uint32_t bytes, int n) {
        asm volatile("fence.proxy.async.global;" ::: "memory");
#pragma unroll 1
        for (int i = 0; i < n; i++) {
          acquire(bytes);
          if (elect()) {
            bulk_load_hint(dst, src + i * (bytes / 16), bytes, bar, pol);
            mbar_expect(bar, bytes);
          }
        }
      };
      for (int pc = 0;; pc++) {
        const uint32_t op = prog[pc];
        const int type = op & 3, a = (op >> 2) & 7;
        if (type == OP_END) break;
        if (type == OP_Q) {
          const int qr = q_role(op);
#pragma unroll 1
          for (int k = 0; k < 10; k++) {
            acquire(SZ_WQ, 1);
            if ((pc > 0 || k >= EARLY) && elect()) tma3d_mc(dst + rank * (SZ_WQ / 2), &P.wq[qr >> 5], bar, 0, 64 * k + 32 * rank, 3 * (4 * a + (qr & 3)));
            acquire(SZ_A, 2);
            if ((pc > 0 || k >= EARLY) && elect()) {
              tma2d(dst, &P.x[qr >> 5], bar, 64 * k, ((qr >> 2) & 7) * kSq + rank * 128);
              mbar_expect(bar, SZ_WQ + SZ_A);
            }
          }
        } else if (type == OP_A) {
          const uint32_t nop = prog[pc + 1];
#pragma unroll 1
          for (int t = (op & F_PARK) ? 1 : 0; t < 33; t++) {
            int wave = a;
            if (t == 31 && (nop & 3) != OP_A) t++;
            if (t == 31) {
              wave = (nop >> 2) & 7;
              mbar_wait((nop & F_HELP) ? hready0 + 8 * ((nop >> 10) & 3) : fenced, 0);
              scratch(&g_o[((team * 2 + rank) * 96 + 3 * (4 * wave + nt)) * 1024], SZ_PARK, 2);
            }
            const int isv = t ? ~t & 1 : 0, j = (isv ? (t - 1) >> 1 : (t + 1) >> 1) & 15;
            const int row0 = ((team & 7) * kH + 4 * wave + nt) * kSk;
            acquire(SZ_KV);
            if (t >= KV_TRANSIT) {
              const Cursor c{head.n - 8 * (KV_TRANSIT + 1)};
              mbar_wait(full0 + c.off(), c.ph());
            }
            if (elect()) {
              tma4d_mc_hint(dst + rank * (SZ_KV / 2), isv ? &P.v[blk] : &P.k[blk], bar, row0 / 8 + 8 * j + 4 * rank, pol);
              mbar_expect(bar, SZ_KV);
            }
          }
        } else {
          const int b = (op >> 5) & 15, ro = o_role(op);
#pragma unroll 1
          for (int i = 0; i < b - a; i++) {
            const int w = o_wave(a, b, i, (P.dbg >> 4) & 7);
            mbar_wait(oready, 0);
            oready += 8;
            asm volatile("fence.proxy.async.global;" ::: "memory");
#pragma unroll 1
            for (int k = 12 * w; k < 12 * w + 12; k++) {
              acquire(SZ_A, 1);
              if (elect()) bulk_load_hint(dst, &g_o[(((ro >> 2) * 2 + rank) * 96 + k) * 1024], SZ_A, bar, pol);
              acquire(SZ_WO, 2);
              if (elect()) {
                tma5d_mc(dst + rank * 10240, &P.wo[ro >> 5], bar, 8 * k + 4 * rank, 5 * (ro & 3));
                mbar_expect(bar, SZ_WO + SZ_A);
              }
            }
          }
          if (op & F_LD) {
            if (op & F_PARK) mbar_wait(hready0 + 8 * (MAX_PARK - 1), 0);
            scratch(&g_part[(role * 2 + rank) * 5120], SZ_PART, 5);
          }
        }
      }
    } else if (threadIdx.x == 288) {
      uint32_t ph = 0;
      bool first = true;
      for (int pc = 0;; pc++) {
        const uint32_t op = prog[pc];
        if ((op & 3) == OP_END) break;
        if ((op & 3) != OP_A && !helper) continue;
        mbar_wait_slow<400>(odone, ph);
        ph ^= 1;
        unsigned int* flag = !helper ? &g_done[(team * 2 + rank) * 8 + ((op >> 2) & 7)]
                             : (op & 3) == OP_Q ? &g_help[(q_role(op) * 2 + rank) * MAX_PARK + ((op >> 10) & 3)]
                                                : &g_help[(o_role(op) * 2 + rank) * MAX_PARK + MAX_PARK - 1];
        asm volatile("red.release.gpu.global.add.u32 [%0], 1;" ::"l"(flag) : "memory");
        if (first) mbar_arrive(fenced);
        first = false;
      }
    } else if (threadIdx.x == 320) {
      uint32_t oready = oready0;
      for (int pc = 0;; pc++) {
        const uint32_t op = prog[pc];
        if ((op & 3) == OP_END) break;
        if ((op & 3) == OP_O) {
          const int a = (op >> 2) & 7, b = (op >> 5) & 15;
#pragma unroll 1
          for (int i = 0; i < b - a; i++) {
            const int ci = ((o_role(op) >> 2) * 2 + rank) * 8 + o_wave(a, b, i, (P.dbg >> 4) & 7);
            wait_count(&g_done[ci], 4);
            mbar_arrive(oready);
            oready += 8;
            if (atomicAdd(&g_seen[ci], 1u) == 3u) { g_seen[ci] = 0; g_done[ci] = 0; }
          }
        }
        if ((op & 3) != OP_Q && (op & F_HELP) && (op & F_PARK)) {
          unsigned int* flag = &g_help[(role * 2 + rank) * MAX_PARK + ((op >> 10) & 3)];
          wait_count(flag, 1);
          mbar_arrive(hready0 + 8 * ((op >> 10) & 3));
          *flag = 0;
        }
      }
    }
    __syncwarp();
    asm volatile("barrier.cluster.arrive.relaxed;\nbarrier.cluster.wait;" ::: "memory");
  } else {
    asm volatile("setmaxnreg.inc.sync.aligned.u32 240;");
    const int lane = threadIdx.x & 31, warp = wid & 3;
    uint32_t empty_rem;
    asm volatile("mapa.shared::cluster.u32 %0, %1, %2;" : "=r"(empty_rem) : "r"(empty0), "r"(lane & 1));
    auto release = [&](int slot) { mbar_arrive_cluster_if(lane < 2, empty_rem + slot); };
    Cursor r{0};
    const uint32_t ring16 = (sbase & 0x3FFFF) >> 4;
    uint32_t cur = ring16;
    bool rdy0 = false, rdy1 = false;
    auto probe1 = [&]() { rdy0 = mbar_test(full0 + r.off(), r.ph()); };
    auto probe2 = [&]() {
      Cursor n = r;
      rdy0 = mbar_test(full0 + n.off(), n.ph());
      n.next();
      rdy1 = mbar_test(full0 + n.off(), n.ph());
    };
    auto take = [&](bool rdy, uint32_t bytes, uint32_t& addr) {
      const int bi = r.off();
      if (!__all_sync(0xffffffffu, rdy)) mbar_wait(full0 + r.off(), r.ph());
      r.next();
      if (cur > ring16 + ((RING - bytes) >> 4)) cur = ring16;
      addr = cur;
      cur += bytes >> 4;
      return bi;
    };
    auto second = [&](uint32_t bytes) {
      if (cur > ring16 + ((RING - bytes) >> 4)) cur = ring16;
      cur += bytes >> 4;
      return cur - (bytes >> 4);
    };
    const int row = wg * 64 + warp * 16 + (lane >> 2);
    int img0 = row * 4 + ((lane & 3) ^ ((row >> 1) & 3));
    uint4* pend = nullptr;
    const uint64_t spol = evict_first();
    int pc = 0;
    uint32_t op = prog[0];
    auto enter = [&]() {
      r.n = op >> 12; cur = ring16 + (((op >> 20) & 63) << 8);
    };
    auto drain = [&](uint32_t (&t)[48], uint32_t c) {
      if (!(op & (3u << 26)) || c >= 6) return;
#pragma unroll
      for (int i = 0; i < 6; i++)
        stg2_if(c == i, pend + i * 512, t[8 * i], t[8 * i + 1], t[8 * i + 2], t[8 * i + 3],
                t[8 * i + 4], t[8 * i + 5], t[8 * i + 6], t[8 * i + 7], spol);
      if ((op & (1u << 26)) && c == 5) {
        __syncwarp();
        mbar_arrive_if(lane < 2, odone);
      }
    };
    float s[32], o[96], c[80];
    uint32_t q[48], pa[16], pb[16];
    float mc0, mc1, l0, l1;
    bool gen;
    auto soft = [&](float (&s)[32], uint32_t (&pout)[16], bool first) {
      if (first) { gen = false; mc0 = 0.f; mc1 = 0.f; }
      float b0, b1;
      for (;;) {
        if (gen) {
          float m0 = fmaxf(s[0], s[1]), m1 = fmaxf(s[2], s[3]);
#pragma unroll
          for (int i = 1; i < 8; i++) { m0 = fmaxf(m0, fmaxf(s[4 * i], s[4 * i + 1])); m1 = fmaxf(m1, fmaxf(s[4 * i + 2], s[4 * i + 3])); }
          m0 = fmaxf(m0, __shfl_xor_sync(0xffffffffu, m0, 1)); m1 = fmaxf(m1, __shfl_xor_sync(0xffffffffu, m1, 1));
          m0 = fmaxf(m0, __shfl_xor_sync(0xffffffffu, m0, 2)); m1 = fmaxf(m1, __shfl_xor_sync(0xffffffffu, m1, 2));
          if (first) {
            mc0 = m0; mc1 = m1;
          } else if (__any_sync(0xffffffffu, !(m0 <= mc0 + kMaxLag && m1 <= mc1 + kMaxLag))) {
            m0 = fmaxf(mc0, m0); m1 = fmaxf(mc1, m1);
            const float a0 = ex2(mc0 - m0), a1 = ex2(mc1 - m1);
            mc0 = m0; mc1 = m1;
            l0 *= a0; l1 *= a1;
            wg_wait<0>();
            fence_regs(o);
#pragma unroll
            for (int i = 0; i < 96; i++) o[i] *= i & 2 ? a1 : a0;
          }
#pragma unroll
          for (int i = 0; i < 32; i++) s[i] -= i & 2 ? mc1 : mc0;
        }
#pragma unroll
        for (int i = 0; i < 8; i++) {
          const float e1 = ex2(s[4 * i + 1]), e0 = ex2(s[4 * i]), e3 = ex2(s[4 * i + 3]), e2 = ex2(s[4 * i + 2]);
          pout[2 * i] = pack_bf16(e0, e1);
          b0 = i ? b0 + fadd(e1, e0) : fadd(e1, e0);
          pout[2 * i + 1] = pack_bf16(e2, e3);
          b1 = i ? b1 + fadd(e3, e2) : fadd(e3, e2);
        }
        if (!__any_sync(0xffffffffu, !gen && !(fmaxf(b0, b1) <= kSumLimit && (!first || fminf(b0, b1) >= 1.0f / kSumLimit)))) break;
        gen = __any_sync(0xffffffffu, true);
      }
      l0 = first ? b0 : l0 + b0;
      l1 = first ? b1 : l1 + b1;
    };
    auto qk = [&](float (&s)[32], uint32_t ak, int k0, int k1) {
#pragma unroll
      for (int kk = k0; kk < k1; kk++)
        wgmma_rs_n64<0>(s, q[4 * kk], q[4 * kk + 1], q[4 * kk + 2], q[4 * kk + 3], mk_desc(ak, 16, KV_SBO, 1, (kk >> 2) * KV_CH + (kk & 3) * 2), kk != 0);
      wg_commit();
    };
    auto pv = [&](uint32_t (&pin)[16], uint32_t av, int acc) {
#pragma unroll
      for (int kk = 0; kk < 4; kk++)
        wgmma_rs_n192<1>(o, pin[4 * kk], pin[4 * kk + 1], pin[4 * kk + 2], pin[4 * kk + 3], mk_desc(av, KV_CH * 16, KV_SBO, 1, kk * (KV_SBO / 8)), acc || (kk != 0));
      wg_commit();
    };
    auto xw = [&](uint32_t ad, int acc) {
      const uint32_t da = second(SZ_A) + wg * 512;
      wg_fence();
#pragma unroll
      for (int kk = 0; kk < 4; kk++)
        wgmma_ss_n192<1>(o, mk_desc(da, 16, 1024, 1, kk * 2), mk_desc(ad, 4096, 1024, 1, (kk & 1) * 128 + (kk >> 1) * 768), acc || kk != 0);
      wg_commit();
    };
    auto ow = [&](int acc, int prev) {
      uint32_t da;
      const int bi = take(rdy0, SZ_A, da);
      const uint32_t db = second(SZ_WO);
      da += wg * 256;
      wg_fence();
      wgmma_ss_n160<1>(c, mk_desc(da, 16, 512, 2), mk_desc(db, 2048, 512, 2), acc);
      wgmma_ss_n160<1>(c, mk_desc(da, 16, 512, 2, 2), mk_desc(db, 2048, 512, 2, 64), 1);
      wg_commit();
      if (acc) { wg_wait<1>(); release(prev); }
      wgmma_ss_n160<1>(c, mk_desc(da, 16, 512, 2, 512), mk_desc(db, 2048, 512, 2, 640), 1);
      wgmma_ss_n160<1>(c, mk_desc(da, 16, 512, 2, 514), mk_desc(db, 2048, 512, 2, 704), 1);
      wg_commit();
      return bi;
    };
    auto st_part = [&](int i) {
      stg2_if(true, pend + i * 512, __float_as_uint(c[8 * i]), __float_as_uint(c[8 * i + 1]), __float_as_uint(c[8 * i + 2]), __float_as_uint(c[8 * i + 3]),
              __float_as_uint(c[8 * i + 4]), __float_as_uint(c[8 * i + 5]), __float_as_uint(c[8 * i + 6]), __float_as_uint(c[8 * i + 7]), spol);
    };
#pragma unroll
    for (int i = 0; i < 48; i++) q[i] = 0;
    enter();

    if ((op & 3) == OP_Q) {
      uint32_t ad;
      int bi0 = take(false, SZ_WQ, ad), k = 0, lag = 0;
      xw(ad, 0);
      for (;;) {
#pragma unroll 1
        for (;;) {
          drain(q, k - lag);
          probe1();
          wg_wait<0>();
          release(bi0);
          bi0 = take(rdy0, SZ_WQ, ad);
          if (++k == 8) break;
          xw(ad, 1);
        }
        if (wg) bar_sync(2, 256);
        xw(ad, 1);
        const int bi9 = take(false, SZ_WQ, ad);
        xw(ad, 1);
        if (!wg) asm volatile("bar.arrive 2, 256;" ::: "memory");
        k = 0; lag = 0;
        uint32_t nop = prog[++pc];
        wg_wait<1>();
        release(bi0);
        probe2();
        wg_wait<0>();
        fence_regs(o);
        release(bi9);
#pragma unroll
        for (int i = 0; i < 48; i++) q[i] = pack_bf16(o[2 * i] * kScaleLog2, o[2 * i + 1] * kScaleLog2);
        fence_regs(q);
        if (op & F_PARK) {
          const int qt = helper ? (op >> 5) & 15 : team, qm = helper ? (op >> 12) & 3 : nt;
          pend = &g_o[((qt * 2 + rank) * 96 + 3 * (4 * ((op >> 2) & 7) + qm)) * 1024 + img0];
          op = nop;
          enter();
          if ((op & 3) != OP_Q) break;
          bi0 = take(rdy0, SZ_WQ, ad);
          xw(ad, 0);
          continue;
        }
        int wave = (op >> 2) & 7, sk1;
        uint32_t ak1;
        {
          float s0[32];
          const int sk0 = take(rdy0, SZ_KV, ad);
          wg_fence();
          qk(s0, ad, 0, 12);
          sk1 = take(rdy1, SZ_KV, ak1);
          wg_fence();
          qk(s, ak1, 0, S1A);
          probe1();
          wg_wait<1>();
          fence_regs(s0);
          release(sk0);
          soft(s0, pa, true);
        }
        float i0, i1;
        auto sums = [&]() {
          l0 += __shfl_xor_sync(0xffffffffu, l0, 1); l1 += __shfl_xor_sync(0xffffffffu, l1, 1);
          l0 += __shfl_xor_sync(0xffffffffu, l0, 2); l1 += __shfl_xor_sync(0xffffffffu, l1, 2);
          i0 = rcp(l0); i1 = rcp(l1);
          asm volatile("" : "+f"(i0), "+f"(i1));
        };
        auto target = [&]() {
          pend = &g_o[((team * 2 + rank) * 96 + 3 * (4 * wave + nt)) * 1024 + img0];
          asm volatile("" : "+l"(pend));
        };
        for (;;) {
          nop = prog[++pc];
          {
            uint32_t av;
            const int sv = take(rdy0, SZ_KV, av);
            wg_fence();
            qk(s, ak1, S1A, 12);
            pv(pa, av, 0);
            probe2();
            wg_wait<1>();
            fence_regs(s);
            release(sk1);
            soft(s, pb, false);
            wg_wait<0>();
            fence_regs(o);
            release(sv);
          }
          auto step = [&](uint32_t (&pin)[16], uint32_t (&pout)[16]) {
            uint32_t ak, av;
            const int sk = take(rdy0, SZ_KV, ak), sv = take(rdy1, SZ_KV, av);
            wg_fence();
            qk(s, ak, 0, 12);
            pv(pin, av, 1);
            probe2();
            wg_wait<1>();
            fence_regs(s);
            release(sk);
            soft(s, pout, false);
            wg_wait<0>();
            fence_regs(o);
            release(sv);
          };
#pragma unroll 1
          for (int jj = 0; jj < 7; jj++) {
            step(pb, pa);
            step(pa, pb);
          }
          if ((nop & 3) != OP_A) break;
          uint32_t ak, av;
          {
            const int b0 = take(rdy0, SZ_PARK, ak), b1 = take(rdy1, SZ_PARK, av);
            const uint32_t ad0 = ak, ad1 = av;
            probe2();
#pragma unroll
            for (int i = 0; i < 12; i++)
              lds128(sbase + ((i < 6 ? ad0 : ad1) - ring16 + img0) * 16 + ((i % 6) >> 1) * 8192 + (i & 1) * 512, q[4 * i], q[4 * i + 1], q[4 * i + 2], q[4 * i + 3]);
            release(b0); release(b1);
          }
          const int sk0 = take(rdy0, SZ_KV, ak), sv = take(rdy1, SZ_KV, av);
          wg_fence();
          qk(s, ak, 0, 8);
          sched_fence(img0, P.zero);
          sums();
          sched_fence(img0, P.zero);
          qk(s, ak, 8, 12);
          pv(pb, av, 1);
          probe2();
          wg_wait<1>();
          fence_regs(s);
          release(sk0);
          soft(s, pa, true);
          sk1 = take(rdy0, SZ_KV, ak1);
          rdy0 = rdy1;
          wg_wait<0>();
          target();
          fence_regs(o);
          release(sv);
          uint32_t t[48];
#pragma unroll
          for (int j = 0; j < 6; j++) {
#pragma unroll
            for (int i = 0; i < 4; i++) {
              t[8 * j + i] = pack_bf16(o[16 * j + 4 * i] * i0, o[16 * j + 4 * i + 1] * i0);
              t[8 * j + i + 4] = pack_bf16(o[16 * j + 4 * i + 2] * i1, o[16 * j + 4 * i + 3] * i1);
            }
            stg2_if(true, pend + j * 512, t[8 * j], t[8 * j + 1], t[8 * j + 2], t[8 * j + 3], t[8 * j + 4], t[8 * j + 5], t[8 * j + 6], t[8 * j + 7], spol);
            if (j == UC0) { wg_fence(); qk(s, ak1, 0, 4); }
            if (j == UC1) { wg_fence(); qk(s, ak1, 4, S1A); }
            sched_fence(img0, P.zero);
          }
          if (P.zero) {
#pragma unroll
            for (int j = 0; j < 5; j++)
              stg2_if(true, pend, t[8 * j], t[8 * j + 1], t[8 * j + 2], t[8 * j + 3], t[8 * j + 4], t[8 * j + 5], t[8 * j + 6], t[8 * j + 7], spol);
          }
          __syncwarp();
          mbar_arrive_if(lane < 2, odone);
          wave = (nop >> 2) & 7;
        }
        const int sv = take(rdy0, SZ_KV, ad);
        wg_fence();
        pv(pb, ad, 1);
        sums();
        target();
        op = nop;
        enter();
        rdy0 = rdy1;
        auto convert = [&](float (&u)[96], int j0, int j1) {
#pragma unroll
          for (int i = 4 * j0; i < 4 * j1; i++) {
            q[8 * (i >> 2) + (i & 3)] = pack_bf16(u[4 * i], u[4 * i + 1]);
            q[8 * (i >> 2) + (i & 3) + 4] = pack_bf16(u[4 * i + 2], u[4 * i + 3]);
          }
        };
        if ((op & 3) != OP_O) {
          if ((op & 3) == OP_Q) bi0 = take(rdy0, SZ_WQ, ad);
          wg_wait<0>();
          fence_regs(o);
          release(sv);
          float u[96];
#pragma unroll
          for (int i = 0; i < 96; i++) u[i] = o[i] * (i & 2 ? i1 : i0);
          if ((op & 3) != OP_Q) { convert(u, 0, 6); break; }
          fence_regs(u);
          xw(ad, 0);
          sched_fence(img0, P.zero);
          fence_regs(u);
          convert(u, 0, 1);
          stg2_if(true, pend, q[0], q[1], q[2], q[3], q[4], q[5], q[6], q[7], spol);
          probe1();
          wg_wait<0>();
          release(bi0);
          bi0 = take(rdy0, SZ_WQ, ad);
          xw(ad, 1);
          sched_fence(img0, P.zero);
          fence_regs(u);
          convert(u, 1, 6);
          k = 1;
          continue;
        }
        int bi = ow(0, 0);
        wg_wait<2>();
        fence_regs(o);
        release(sv);
#pragma unroll
        for (int j = 0; j < 6; j++) {
          uint32_t t[8];
#pragma unroll
          for (int i = 0; i < 4; i++) {
            t[i] = pack_bf16(o[16 * j + 4 * i] * i0, o[16 * j + 4 * i + 1] * i0);
            t[i + 4] = pack_bf16(o[16 * j + 4 * i + 2] * i1, o[16 * j + 4 * i + 3] * i1);
          }
          stg2_if(true, pend + j * 512, t[0], t[1], t[2], t[3], t[4], t[5], t[6], t[7], spol);
          if (j == 5) {
            __syncwarp();
            mbar_arrive_if(lane < 2, odone);
          }
          probe1();
          wg_wait<1>();
          bi = ow(1, bi);
          fence_regs(o);
        }
        {
          const int nk = 12 * (((op >> 5) & 15) - ((op >> 2) & 7));
#pragma unroll 1
          for (int k = 7; k < nk; k++) {
            probe1();
            wg_wait<1>();
            bi = ow(1, bi);
          }
          probe1();
        }
        nop = prog[++pc];
        if (op & F_LD) {
          uint32_t t[80];
#pragma unroll
          for (int j = 0; j < 5; j++) {
            const int b = take(rdy0, SZ_PART, ad);
            probe1();
#pragma unroll
            for (int i = 4 * j; i < 4 * j + 4; i++)
              lds128(sbase + (ad - ring16 + img0) * 16 + ((i >> 1) & 1) * 8192 + (i & 1) * 512, t[4 * i], t[4 * i + 1], t[4 * i + 2], t[4 * i + 3]);
            release(b);
          }
          wg_wait<0>();
          fence_regs(c);
#pragma unroll
          for (int i = 0; i < 80; i++) c[i] += __uint_as_float(t[i]);
        }
        if (!(op & F_ST)) {
          wg_wait<0>();
          fence_regs(c);
          goto finish;
        }
        op = nop;
        enter();
        bi0 = take(rdy0, SZ_WQ, ad);
        xw(ad, 0);
        pend = &g_part[((team * 4 + nt) * 2 + rank) * 5120 + img0];
        probe1();
        wg_wait<1>();
        fence_regs(c);
        release(bi);
        st_part(0); st_part(1);
        wg_wait<0>();
        release(bi0);
        bi0 = take(rdy0, SZ_WQ, ad);
        xw(ad, 1);
        st_part(2); st_part(3);
#pragma unroll
        for (int i = 0; i < 48; i++) q[i] = __float_as_uint(c[32 + i]);
        pend += 4 * 512;
        k = 1; lag = 2;
      }
    }
    rdy0 = false;
    {
      uint32_t t[48];
#pragma unroll
      for (int i = 0; i < 48; i++) t[i] = q[i] ^ P.zero;
      while ((op & 3) == OP_O) {
        int bi = ow(0, 0);
#pragma unroll 1
        for (int k = 1; k < 12 * (int)(((op >> 5) & 15) - ((op >> 2) & 7)); k++) {
          drain(t, k - 1);
          probe1();
          wg_wait<1>();
          bi = ow(1, bi);
        }
        rdy0 = false;
        wg_wait<0>();
        fence_regs(c);
        pc++;
        if (!(op & F_ST)) goto finish;
        release(bi);
        pend = &g_part[((((op >> 26) & 56) | ((op >> 9) & 7)) * 2 + rank) * 5120 + img0];
#pragma unroll
        for (int i = 6; i < 10; i++) st_part(i);
#pragma unroll
        for (int i = 0; i < 48; i++) t[i] = __float_as_uint(c[i]) ^ P.zero;
        op = prog[pc];
        enter();
      }
      for (int i = 0; i < 6; i++) drain(t, i);
    }
    asm volatile("barrier.cluster.arrive.relaxed;" ::: "memory");
    if (false) {
    finish:
      asm volatile("barrier.cluster.arrive.relaxed;" ::: "memory");
      bar_sync(1, 256);
      const uint32_t wstage = sbase + (wg * 4 + warp) * 5120;
      const uint32_t sa = wstage + (lane & 15) * 64;
#pragma unroll
      for (int i = 0; i < 10; i++) {
        const int u = (i & 1) * 2 + (lane >> 4);
        stsm4(sa + (i >> 1) * 1024 + ((u ^ ((lane >> 1) & 3)) << 4), pack_bf16(c[8 * i], c[8 * i + 1]), pack_bf16(c[8 * i + 2], c[8 * i + 3]),
              pack_bf16(c[8 * i + 4], c[8 * i + 5]), pack_bf16(c[8 * i + 6], c[8 * i + 7]));
      }
      asm volatile("fence.proxy.async.shared::cta;" ::: "memory");
      __syncwarp();
      if (lane == 0) {
        tma3d_store(&P.out, wstage, 0, (team & 7) * kSq + rank * 128 + wg * 64 + warp * 16, blk * 20 + nt * 5);
        asm volatile("cp.async.bulk.commit_group;\ncp.async.bulk.wait_group.read 0;" ::: "memory");
      }
      __syncwarp();
    }
    asm volatile("barrier.cluster.wait;" ::: "memory");
  }
}

typedef CUresult (*EncodeFn)(CUtensorMap*, CUtensorMapDataType, cuuint32_t, void*, const cuuint64_t*, const cuuint64_t*,
                             const cuuint32_t*, const cuuint32_t*, CUtensorMapInterleave, CUtensorMapSwizzle,
                             CUtensorMapL2promotion, CUtensorMapFloatOOBfill);

void encode(EncodeFn fn, CUtensorMap* m, const void* ptr, int rank, const cuuint64_t* dims, const cuuint64_t* strides,
            const cuuint32_t* box, CUtensorMapSwizzle swz) {
  const cuuint32_t es[5] = {1, 1, 1, 1, 1};
  CUresult r = fn(m, CU_TENSOR_MAP_DATA_TYPE_BFLOAT16, rank, const_cast<void*>(ptr), dims, strides, box, es,
                  CU_TENSOR_MAP_INTERLEAVE_NONE, swz, CU_TENSOR_MAP_L2_PROMOTION_L2_128B, CU_TENSOR_MAP_FLOAT_OOB_FILL_NONE);
  if (r != CUDA_SUCCESS) fprintf(stderr, "cuTensorMapEncodeTiled failed: %d\n", (int)r);
}

void annotate(uint32_t* ops, int n, bool helper) {
  uint32_t items = 0, cur = 0, pend = 0;
  auto item = [&](uint32_t bytes, int count, uint32_t bytes2 = 0) {
    for (int i = 0; i < count; i++) {
      if (cur + bytes > RING) cur = 0;
      cur += bytes;
      if (cur + bytes2 > RING) cur = 0;
      cur += bytes2;
      items++;
    }
  };
  for (int i = 0; i <= n; i++) {
    const uint32_t op = ops[i];
    ops[i] |= (items % (2 * NBAR)) << 15 | (cur >> 12) << 20 | pend << 26;
    if ((op & 3) == OP_Q) { item(SZ_WQ, 10, SZ_A); pend = (op & F_PARK) ? (helper ? 1 : 2) : 0; }
    if ((op & 3) == OP_A) {
      item(SZ_KV, (op & F_PARK) ? 30 : 31);
      if ((ops[i + 1] & 3) == OP_A) { item(SZ_PARK, 2); item(SZ_KV, 1); }
      item(SZ_KV, 1);
      pend = 1;
    }
    if ((op & 3) == OP_O) {
      item(SZ_A, 12 * (((op >> 5) & 15) - ((op >> 2) & 7)), SZ_WO);
      if (op & F_LD) item(SZ_PART, 5);
      pend = (op & F_ST) ? (helper ? 1 : 2) : 0;
    }
  }
}

void compile_programs(const char* const* text, bool helpers, Params& P) {
  struct Req { int when, team, wave, slot; } req[N_TEAM * MAX_PARK];
  int n_req = 0;
  for (int t = 0; t < N_TEAM; t++) {
    uint32_t* ops = P.ops[t];
    int n = 0, flags[8] = {0, 0, 0, 0, 0, 0, 0, 0}, n_park = 0, last_o = -1, when = 0, given = 0;
    for (const char* s = text[t]; *s; s++) {
      const int a = s[1] - '0';
      if (*s == 'Q' || (*s == 'H' && !helpers)) { ops[n++] = OP_Q | a << 2; when += 10; }
      else if (*s == 'P') { flags[a] = F_PARK; ops[n++] = OP_Q | a << 2 | flags[a]; when += 10; }
      else if (*s == 'H') { req[n_req++] = {when, t, a, n_park}; flags[a] = F_PARK | F_HELP | n_park++ << 10; }
      else if (*s == 'A') { ops[n++] = OP_A | a << 2 | flags[a]; when += 32; }
      else if (*s == 'G') { given = a; if (helpers) req[n_req++] = {1000, t, 0, -a}; }
      else if (*s == 'O') {
        ops[n] = OP_O | a << 2 | (s[2] - '0') << 5;
        if (given) ops[n] = helpers ? ops[n] | F_LD | F_PARK | (MAX_PARK - 1) << 10 : ops[n] & ~(7u << 2);
        if (last_o >= 0) { ops[last_o] |= F_ST; ops[n] |= F_LD; }
        last_o = n++;
        when += 10 * (s[2] - s[1]);
      }
    }
    for (int i = n; i < MAX_OPS; i++) ops[i] = OP_END;
    annotate(ops, n, false);
  }
  for (int i = 1; i < n_req; i++)
    for (int j = i; j > 0 && req[j].when < req[j - 1].when; j--) { Req r = req[j]; req[j] = req[j - 1]; req[j - 1] = r; }
  for (int h = 0; h < N_HELP; h++) {
    uint32_t* ops = P.ops[N_TEAM + 2 * h];
    int n = 0;
    for (int i = 0; i < n_req; i++)
      for (int m = h; m < 4; m += N_HELP) {
        const uint32_t ro = 4 * req[i].team + m;
        ops[n++] = req[i].slot >= 0 ? OP_Q | req[i].wave << 2 | req[i].team << 5 | F_PARK | req[i].slot << 10 | m << 12
                                    : OP_O | -req[i].slot << 5 | F_ST | (ro & 7) << 9 | (ro >> 3) << 29;
      }
    for (int i = n; i < 2 * MAX_OPS; i++) ops[i] = OP_END;
    annotate(ops, n, true);
  }
  for (int i = 0; i < 32; i++) P.first[i] = i < N_TEAM ? P.ops[i][0] : i < N_TEAM + N_HELP ? P.ops[2 * i - N_TEAM][0] : 0;
}

const char* const kPrograms[N_TEAM] = {
  "Q0A0Q1A1H2A2O03Q3A3Q4A4Q5A5Q6A6Q7A7O38",
  "Q0A0Q1A1Q2A2Q3A3O04Q4A4Q5A5Q6A6H7A7O48",
  "Q0A0H1A1Q2A2Q3A3Q4A4O05Q5A5Q6A6Q7A7O58",
  "Q0A0Q1A1Q2A2O03Q3A3Q4A4Q5A5Q6A6H7A7O38",
  "Q0A0Q1A1Q2A2O03Q3A3H4A4Q5A5Q6A6Q7A7O38",
  "Q0A0Q1A1H2A2Q3A3Q4A4O05Q5A5Q6A6Q7A7O58",
  "Q0A0Q1A1Q2A2Q3A3O03Q4A4H5A5Q6A6Q7A7O38",
  "Q0A0Q1A1Q2A2Q3A3Q4A4O05Q5A5Q6A6H7A7O58",
  "P3Q0A0Q1A1Q2A2A3H4A4Q5A5Q6A6Q7A7O08",
  "P5P7Q0A0Q1A1Q2A2H3A3Q4A4A5Q6A6A7G1O18",
  "Q0A0Q1A1Q2A2O02Q3A3H4A4Q5A5Q6A6Q7A7O28",
  "P3P5Q0A0Q1A1Q2A2A3Q4A4A5Q6A6H7A7O08",
  "Q0A0Q1A1Q2A2O02Q3A3Q4A4H5A5Q6A6Q7A7O28",
  "P7Q0A0Q1A1Q2A2Q3A3Q4A4Q5A5Q6A6A7G1O18",
  "P5Q0A0Q1A1Q2A2Q3A3Q4A4A5Q6A6H7A7O08",
  "Q0A0Q1A1Q2A2H3A3Q4A4Q5A5Q6A6Q7A7O08",
};

const char* const* bench_programs() {
  return kPrograms;
}

}

extern "C" void kernel_launch(void* const* d_in, const int* in_sizes, int n_in, void* d_out, int out_size) {
  (void)in_sizes; (void)n_in; (void)out_size;
  static EncodeFn fn = nullptr;
  static int n_clusters = 0;
  if (!fn) {
    cudaDriverEntryPointQueryResult qr;
    void* f = nullptr;
    cudaGetDriverEntryPoint("cuTensorMapEncodeTiled", &f, cudaEnableDefault, &qr);
    fn = (EncodeFn)f;
    cudaFuncSetAttribute(fused_kernel, cudaFuncAttributeMaxDynamicSharedMemorySize, SMEM_BYTES);
    cudaLaunchConfig_t cfg = {};
    cfg.gridDim = dim3(132); cfg.blockDim = dim3(384); cfg.dynamicSmemBytes = SMEM_BYTES;
    cudaLaunchAttribute at[1];
    at[0].id = cudaLaunchAttributeClusterDimension; at[0].val.clusterDim.x = 2; at[0].val.clusterDim.y = 1; at[0].val.clusterDim.z = 1;
    cfg.attrs = at; cfg.numAttrs = 1;
    if (cudaOccupancyMaxActiveClusters(&n_clusters, fused_kernel, &cfg) != cudaSuccess || n_clusters < 1) n_clusters = 1;
    (void)cudaGetLastError();
  }
  Params P;
  const CUtensorMapSwizzle S128 = CU_TENSOR_MAP_SWIZZLE_128B, S64 = CU_TENSOR_MAP_SWIZZLE_64B;
  for (int blk = 0; blk < 2; blk++) {
    void* const* in = d_in + 5 * blk;
    { const cuuint64_t d[] = {kD, kB * kSq}, s[] = {kD * 2}; const cuuint32_t b[] = {64, 128};
      encode(fn, &P.x[blk], in[0], 2, d, s, b, S128); }
    { const cuuint64_t d[] = {64, 8, 3, (cuuint64_t)kB * kH * kSk / 8}, s[] = {kDh * 2, 128, 8 * kDh * 2}; const cuuint32_t b[] = {64, 8, 3, 4};
      encode(fn, &P.k[blk], in[1], 4, d, s, b, S128);
      encode(fn, &P.v[blk], in[2], 4, d, s, b, S128); }
    { const cuuint64_t d[] = {64, kD, kHD / 64}, s[] = {kHD * 2, 128}; const cuuint32_t b[] = {64, 32, 3};
      encode(fn, &P.wq[blk], in[3], 3, d, s, b, S128); }
    { const cuuint64_t d[] = {32, 2, kHD / 8, 4, kD / 32}, s[] = {kD * 2, 8 * kD * 2, 2 * kD * 2, 64}; const cuuint32_t b[] = {32, 2, 4, 4, 5};
      encode(fn, &P.wo[blk], in[4], 5, d, s, b, S64); }
  }
  { const cuuint64_t d[] = {32, kB * kSq, 2 * kD / 32}, s[] = {2 * kD * 2, 64}; const cuuint32_t b[] = {32, 16, 5};
    encode(fn, &P.out, d_out, 3, d, s, b, S64); }

  P.zero = 0;
  P.dbg = 0x30;
  if (n_clusters >= N_CL) {
    const bool helpers = n_clusters >= N_CL + N_HELP;
    compile_programs(bench_programs(), helpers, P);
    fused_kernel<<<2 * (N_CL + (helpers ? N_HELP : 0)), 384, SMEM_BYTES>>>(P);
  } else {
    for (int phase = 0; phase < 2; phase++) {
      const char* text[N_TEAM];
      for (int t = 0; t < N_TEAM; t++) text[t] = phase ? "O08" : "Q0A0Q1A1Q2A2Q3A3Q4A4Q5A5Q6A6Q7A7";
      compile_programs(text, false, P);
      fused_kernel<<<2 * N_CL, 384, SMEM_BYTES>>>(P);
    }
  }
}
```

```cpp
#include <cuda_runtime.h>
#include <cuda_bf16.h>
#include <cuda.h>
#include <stdint.h>
#include <stdio.h>

namespace {

constexpr int kB = 8, kSq = 256, kD = 640, kH = 32, kSk = 1024, kDh = 192;
constexpr int kHD = kH * kDh;
#define S1A 7
#define UC0 3
#define UC1 5
#define RING_KB 224
constexpr uint32_t RING = RING_KB * 1024;
constexpr uint32_t SZ_KV = 24576;
constexpr uint32_t SZ_WQ = 24576, SZ_WO = 20480, SZ_A = 16384;
constexpr uint32_t SZ_OUT = 40960;
constexpr uint32_t SZ_PARK = 24576;
constexpr uint32_t SZ_PART = 16384;
constexpr int NBAR = 16, NFLIGHT = 12;
#define KVT 4
constexpr int KV_TRANSIT = KVT;
#define EARLY_N 3
constexpr int EARLY = EARLY_N;
constexpr uint32_t KV_CH = 64, KV_SBO = 3072;
constexpr int SMEM_BYTES = RING + 512 + 1024;
constexpr int N_TEAM = 16, N_CL = 64, N_HELP = 2, MAX_OPS = 24, MAX_PARK = 4;
enum { OP_END = 0, OP_Q = 1, OP_A = 2, OP_O = 3, F_PARK = 1 << 9, F_LD = 1 << 12, F_ST = 1 << 13, F_HELP = 1 << 12 };

struct alignas(64) Params {
  uint32_t first[32];
  CUtensorMap x[2], wq[2], k[2], v[2], wo[2], out;
  uint32_t ops[N_TEAM + 2 * N_HELP][MAX_OPS];
  uint32_t zero;
  uint32_t dbg;
};

__device__ uint4 g_o[N_TEAM * 2 * 96 * 1024];
__device__ uint4 g_part[N_CL * 2 * 5 * 1024];
__device__ unsigned int g_done[N_TEAM * 2 * 8];
__device__ unsigned int g_help[N_CL * 2 * MAX_PARK];
__device__ unsigned int g_seen[N_TEAM * 2 * 8];

template <int TB, int TA = 0>
__device__ __forceinline__ void wgmma_ss_n64(float (&d)[32], uint64_t da, uint64_t db, int scale_d) {
  asm volatile("{\n.reg .pred p;\nsetp.ne.b32 p, %34, 0;\n"
    "wgmma.mma_async.sync.aligned.m64n64k16.f32.bf16.bf16 {%0, %1, %2, %3, %4, %5, %6, %7, %8, %9, %10, %11, %12, %13, %14, %15, %16, %17, %18, %19, %20, %21, %22, %23, %24, %25, %26, %27, %28, %29, %30, %31}, %32, %33, p, 1, 1, %35, %36;\n}\n"
    : "+f"(d[0]), "+f"(d[1]), "+f"(d[2]), "+f"(d[3]), "+f"(d[4]), "+f"(d[5]), "+f"(d[6]), "+f"(d[7]), "+f"(d[8]), "+f"(d[9]), "+f"(d[10]), "+f"(d[11]), "+f"(d[12]), "+f"(d[13]), "+f"(d[14]), "+f"(d[15]), "+f"(d[16]), "+f"(d[17]), "+f"(d[18]), "+f"(d[19]), "+f"(d[20]), "+f"(d[21]), "+f"(d[22]), "+f"(d[23]), "+f"(d[24]), "+f"(d[25]), "+f"(d[26]), "+f"(d[27]), "+f"(d[28]), "+f"(d[29]), "+f"(d[30]), "+f"(d[31])
    : "l"(da), "l"(db), "r"(scale_d), "n"(TA), "n"(TB));
}
template <int TB>
__device__ __forceinline__ void wgmma_rs_n64(float (&d)[32], uint32_t a0, uint32_t a1, uint32_t a2, uint32_t a3, uint64_t db, int scale_d) {
  asm volatile("{\n.reg .pred p;\nsetp.ne.b32 p, %37, 0;\n"
    "wgmma.mma_async.sync.aligned.m64n64k16.f32.bf16.bf16 {%0, %1, %2, %3, %4, %5, %6, %7, %8, %9, %10, %11, %12, %13, %14, %15, %16, %17, %18, %19, %20, %21, %22, %23, %24, %25, %26, %27, %28, %29, %30, %31}, {%32, %33, %34, %35}, %36, p, 1, 1, %38;\n}\n"
    : "+f"(d[0]), "+f"(d[1]), "+f"(d[2]), "+f"(d[3]), "+f"(d[4]), "+f"(d[5]), "+f"(d[6]), "+f"(d[7]), "+f"(d[8]), "+f"(d[9]), "+f"(d[10]), "+f"(d[11]), "+f"(d[12]), "+f"(d[13]), "+f"(d[14]), "+f"(d[15]), "+f"(d[16]), "+f"(d[17]), "+f"(d[18]), "+f"(d[19]), "+f"(d[20]), "+f"(d[21]), "+f"(d[22]), "+f"(d[23]), "+f"(d[24]), "+f"(d[25]), "+f"(d[26]), "+f"(d[27]), "+f"(d[28]), "+f"(d[29]), "+f"(d[30]), "+f"(d[31])
    : "r"(a0), "r"(a1), "r"(a2), "r"(a3), "l"(db), "r"(scale_d), "n"(TB));
}
template <int TB, int TA = 0>
__device__ __forceinline__ void wgmma_ss_n160(float (&d)[80], uint64_t da, uint64_t db, int scale_d) {
  asm volatile("{\n.reg .pred p;\nsetp.ne.b32 p, %82, 0;\n"
    "wgmma.mma_async.sync.aligned.m64n160k16.f32.bf16.bf16 {%0, %1, %2, %3, %4, %5, %6, %7, %8, %9, %10, %11, %12, %13, %14, %15, %16, %17, %18, %19, %20, %21, %22, %23, %24, %25, %26, %27, %28, %29, %30, %31, %32, %33, %34, %35, %36, %37, %38, %39, %40, %41, %42, %43, %44, %45, %46, %47, %48, %49, %50, %51, %52, %53, %54, %55, %56, %57, %58, %59, %60, %61, %62, %63, %64, %65, %66, %67, %68, %69, %70, %71, %72, %73, %74, %75, %76, %77, %78, %79}, %80, %81, p, 1, 1, %83, %84;\n}\n"
    : "+f"(d[0]), "+f"(d[1]), "+f"(d[2]), "+f"(d[3]), "+f"(d[4]), "+f"(d[5]), "+f"(d[6]), "+f"(d[7]), "+f"(d[8]), "+f"(d[9]), "+f"(d[10]), "+f"(d[11]), "+f"(d[12]), "+f"(d[13]), "+f"(d[14]), "+f"(d[15]), "+f"(d[16]), "+f"(d[17]), "+f"(d[18]), "+f"(d[19]), "+f"(d[20]), "+f"(d[21]), "+f"(d[22]), "+f"(d[23]), "+f"(d[24]), "+f"(d[25]), "+f"(d[26]), "+f"(d[27]), "+f"(d[28]), "+f"(d[29]), "+f"(d[30]), "+f"(d[31]), "+f"(d[32]), "+f"(d[33]), "+f"(d[34]), "+f"(d[35]), "+f"(d[36]), "+f"(d[37]), "+f"(d[38]), "+f"(d[39]), "+f"(d[40]), "+f"(d[41]), "+f"(d[42]), "+f"(d[43]), "+f"(d[44]), "+f"(d[45]), "+f"(d[46]), "+f"(d[47]), "+f"(d[48]), "+f"(d[49]), "+f"(d[50]), "+f"(d[51]), "+f"(d[52]), "+f"(d[53]), "+f"(d[54]), "+f"(d[55]), "+f"(d[56]), "+f"(d[57]), "+f"(d[58]), "+f"(d[59]), "+f"(d[60]), "+f"(d[61]), "+f"(d[62]), "+f"(d[63]), "+f"(d[64]), "+f"(d[65]), "+f"(d[66]), "+f"(d[67]), "+f"(d[68]), "+f"(d[69]), "+f"(d[70]), "+f"(d[71]), "+f"(d[72]), "+f"(d[73]), "+f"(d[74]), "+f"(d[75]), "+f"(d[76]), "+f"(d[77]), "+f"(d[78]), "+f"(d[79])
    : "l"(da), "l"(db), "r"(scale_d), "n"(TA), "n"(TB));
}
template <int TB>
__device__ __forceinline__ void wgmma_rs_n160(float (&d)[80], uint32_t a0, uint32_t a1, uint32_t a2, uint32_t a3, uint64_t db, int scale_d) {
  asm volatile("{\n.reg .pred p;\nsetp.ne.b32 p, %85, 0;\n"
    "wgmma.mma_async.sync.aligned.m64n160k16.f32.bf16.bf16 {%0, %1, %2, %3, %4, %5, %6, %7, %8, %9, %10, %11, %12, %13, %14, %15, %16, %17, %18, %19, %20, %21, %22, %23, %24, %25, %26, %27, %28, %29, %30, %31, %32, %33, %34, %35, %36, %37, %38, %39, %40, %41, %42, %43, %44, %45, %46, %47, %48, %49, %50, %51, %52, %53, %54, %55, %56, %57, %58, %59, %60, %61, %62, %63, %64, %65, %66, %67, %68, %69, %70, %71, %72, %73, %74, %75, %76, %77, %78, %79}, {%80, %81, %82, %83}, %84, p, 1, 1, %86;\n}\n"
    : "+f"(d[0]), "+f"(d[1]), "+f"(d[2]), "+f"(d[3]), "+f"(d[4]), "+f"(d[5]), "+f"(d[6]), "+f"(d[7]), "+f"(d[8]), "+f"(d[9]), "+f"(d[10]), "+f"(d[11]), "+f"(d[12]), "+f"(d[13]), "+f"(d[14]), "+f"(d[15]), "+f"(d[16]), "+f"(d[17]), "+f"(d[18]), "+f"(d[19]), "+f"(d[20]), "+f"(d[21]), "+f"(d[22]), "+f"(d[23]), "+f"(d[24]), "+f"(d[25]), "+f"(d[26]), "+f"(d[27]), "+f"(d[28]), "+f"(d[29]), "+f"(d[30]), "+f"(d[31]), "+f"(d[32]), "+f"(d[33]), "+f"(d[34]), "+f"(d[35]), "+f"(d[36]), "+f"(d[37]), "+f"(d[38]), "+f"(d[39]), "+f"(d[40]), "+f"(d[41]), "+f"(d[42]), "+f"(d[43]), "+f"(d[44]), "+f"(d[45]), "+f"(d[46]), "+f"(d[47]), "+f"(d[48]), "+f"(d[49]), "+f"(d[50]), "+f"(d[51]), "+f"(d[52]), "+f"(d[53]), "+f"(d[54]), "+f"(d[55]), "+f"(d[56]), "+f"(d[57]), "+f"(d[58]), "+f"(d[59]), "+f"(d[60]), "+f"(d[61]), "+f"(d[62]), "+f"(d[63]), "+f"(d[64]), "+f"(d[65]), "+f"(d[66]), "+f"(d[67]), "+f"(d[68]), "+f"(d[69]), "+f"(d[70]), "+f"(d[71]), "+f"(d[72]), "+f"(d[73]), "+f"(d[74]), "+f"(d[75]), "+f"(d[76]), "+f"(d[77]), "+f"(d[78]), "+f"(d[79])
    : "r"(a0), "r"(a1), "r"(a2), "r"(a3), "l"(db), "r"(scale_d), "n"(TB));
}
template <int TB, int TA = 0>
__device__ __forceinline__ void wgmma_ss_n192(float (&d)[96], uint64_t da, uint64_t db, int scale_d) {
  asm volatile("{\n.reg .pred p;\nsetp.ne.b32 p, %98, 0;\n"
    "wgmma.mma_async.sync.aligned.m64n192k16.f32.bf16.bf16 {%0, %1, %2, %3, %4, %5, %6, %7, %8, %9, %10, %11, %12, %13, %14, %15, %16, %17, %18, %19, %20, %21, %22, %23, %24, %25, %26, %27, %28, %29, %30, %31, %32, %33, %34, %35, %36, %37, %38, %39, %40, %41, %42, %43, %44, %45, %46, %47, %48, %49, %50, %51, %52, %53, %54, %55, %56, %57, %58, %59, %60, %61, %62, %63, %64, %65, %66, %67, %68, %69, %70, %71, %72, %73, %74, %75, %76, %77, %78, %79, %80, %81, %82, %83, %84, %85, %86, %87, %88, %89, %90, %91, %92, %93, %94, %95}, %96, %97, p, 1, 1, %99, %100;\n}\n"
    : "+f"(d[0]), "+f"(d[1]), "+f"(d[2]), "+f"(d[3]), "+f"(d[4]), "+f"(d[5]), "+f"(d[6]), "+f"(d[7]), "+f"(d[8]), "+f"(d[9]), "+f"(d[10]), "+f"(d[11]), "+f"(d[12]), "+f"(d[13]), "+f"(d[14]), "+f"(d[15]), "+f"(d[16]), "+f"(d[17]), "+f"(d[18]), "+f"(d[19]), "+f"(d[20]), "+f"(d[21]), "+f"(d[22]), "+f"(d[23]), "+f"(d[24]), "+f"(d[25]), "+f"(d[26]), "+f"(d[27]), "+f"(d[28]), "+f"(d[29]), "+f"(d[30]), "+f"(d[31]), "+f"(d[32]), "+f"(d[33]), "+f"(d[34]), "+f"(d[35]), "+f"(d[36]), "+f"(d[37]), "+f"(d[38]), "+f"(d[39]), "+f"(d[40]), "+f"(d[41]), "+f"(d[42]), "+f"(d[43]), "+f"(d[44]), "+f"(d[45]), "+f"(d[46]), "+f"(d[47]), "+f"(d[48]), "+f"(d[49]), "+f"(d[50]), "+f"(d[51]), "+f"(d[52]), "+f"(d[53]), "+f"(d[54]), "+f"(d[55]), "+f"(d[56]), "+f"(d[57]), "+f"(d[58]), "+f"(d[59]), "+f"(d[60]), "+f"(d[61]), "+f"(d[62]), "+f"(d[63]), "+f"(d[64]), "+f"(d[65]), "+f"(d[66]), "+f"(d[67]), "+f"(d[68]), "+f"(d[69]), "+f"(d[70]), "+f"(d[71]), "+f"(d[72]), "+f"(d[73]), "+f"(d[74]), "+f"(d[75]), "+f"(d[76]), "+f"(d[77]), "+f"(d[78]), "+f"(d[79]), "+f"(d[80]), "+f"(d[81]), "+f"(d[82]), "+f"(d[83]), "+f"(d[84]), "+f"(d[85]), "+f"(d[86]), "+f"(d[87]), "+f"(d[88]), "+f"(d[89]), "+f"(d[90]), "+f"(d[91]), "+f"(d[92]), "+f"(d[93]), "+f"(d[94]), "+f"(d[95])
    : "l"(da), "l"(db), "r"(scale_d), "n"(TA), "n"(TB));
}
template <int TB>
__device__ __forceinline__ void wgmma_rs_n192(float (&d)[96], uint32_t a0, uint32_t a1, uint32_t a2, uint32_t a3, uint64_t db, int scale_d) {
  asm volatile("{\n.reg .pred p;\nsetp.ne.b32 p, %101, 0;\n"
    "wgmma.mma_async.sync.aligned.m64n192k16.f32.bf16.bf16 {%0, %1, %2, %3, %4, %5, %6, %7, %8, %9, %10, %11, %12, %13, %14, %15, %16, %17, %18, %19, %20, %21, %22, %23, %24, %25, %26, %27, %28, %29, %30, %31, %32, %33, %34, %35, %36, %37, %38, %39, %40, %41, %42, %43, %44, %45, %46, %47, %48, %49, %50, %51, %52, %53, %54, %55, %56, %57, %58, %59, %60, %61, %62, %63, %64, %65, %66, %67, %68, %69, %70, %71, %72, %73, %74, %75, %76, %77, %78, %79, %80, %81, %82, %83, %84, %85, %86, %87, %88, %89, %90, %91, %92, %93, %94, %95}, {%96, %97, %98, %99}, %100, p, 1, 1, %102;\n}\n"
    : "+f"(d[0]), "+f"(d[1]), "+f"(d[2]), "+f"(d[3]), "+f"(d[4]), "+f"(d[5]), "+f"(d[6]), "+f"(d[7]), "+f"(d[8]), "+f"(d[9]), "+f"(d[10]), "+f"(d[11]), "+f"(d[12]), "+f"(d[13]), "+f"(d[14]), "+f"(d[15]), "+f"(d[16]), "+f"(d[17]), "+f"(d[18]), "+f"(d[19]), "+f"(d[20]), "+f"(d[21]), "+f"(d[22]), "+f"(d[23]), "+f"(d[24]), "+f"(d[25]), "+f"(d[26]), "+f"(d[27]), "+f"(d[28]), "+f"(d[29]), "+f"(d[30]), "+f"(d[31]), "+f"(d[32]), "+f"(d[33]), "+f"(d[34]), "+f"(d[35]), "+f"(d[36]), "+f"(d[37]), "+f"(d[38]), "+f"(d[39]), "+f"(d[40]), "+f"(d[41]), "+f"(d[42]), "+f"(d[43]), "+f"(d[44]), "+f"(d[45]), "+f"(d[46]), "+f"(d[47]), "+f"(d[48]), "+f"(d[49]), "+f"(d[50]), "+f"(d[51]), "+f"(d[52]), "+f"(d[53]), "+f"(d[54]), "+f"(d[55]), "+f"(d[56]), "+f"(d[57]), "+f"(d[58]), "+f"(d[59]), "+f"(d[60]), "+f"(d[61]), "+f"(d[62]), "+f"(d[63]), "+f"(d[64]), "+f"(d[65]), "+f"(d[66]), "+f"(d[67]), "+f"(d[68]), "+f"(d[69]), "+f"(d[70]), "+f"(d[71]), "+f"(d[72]), "+f"(d[73]), "+f"(d[74]), "+f"(d[75]), "+f"(d[76]), "+f"(d[77]), "+f"(d[78]), "+f"(d[79]), "+f"(d[80]), "+f"(d[81]), "+f"(d[82]), "+f"(d[83]), "+f"(d[84]), "+f"(d[85]), "+f"(d[86]), "+f"(d[87]), "+f"(d[88]), "+f"(d[89]), "+f"(d[90]), "+f"(d[91]), "+f"(d[92]), "+f"(d[93]), "+f"(d[94]), "+f"(d[95])
    : "r"(a0), "r"(a1), "r"(a2), "r"(a3), "l"(db), "r"(scale_d), "n"(TB));
}

__device__ __forceinline__ uint32_t smem_u32(const void* p) { return (uint32_t)__cvta_generic_to_shared(p); }
__device__ __forceinline__ void wg_fence() { asm volatile("wgmma.fence.sync.aligned;" ::: "memory"); }
__device__ __forceinline__ void wg_commit() { asm volatile("wgmma.commit_group.sync.aligned;" ::: "memory"); }
template <int N> __device__ __forceinline__ void wg_wait() { asm volatile("wgmma.wait_group.sync.aligned %0;" ::"n"(N) : "memory"); }
__device__ __forceinline__ void sched_fence(int& keep, uint32_t zero) {
  asm volatile("{\n.reg .u32 c;\nmov.u32 c, %%clock;\nand.b32 c, c, %1;\nxor.b32 %0, %0, c;\n}\n" : "+r"(keep) : "r"(zero) : "memory");
}
template <int N> __device__ __forceinline__ void fence_regs(float (&r)[N]) {
#pragma unroll
  for (int i = 0; i < N; i++) asm volatile("" : "+f"(r[i])::"memory");
}
template <int N> __device__ __forceinline__ void fence_regs(uint32_t (&r)[N]) {
#pragma unroll
  for (int i = 0; i < N; i++) asm volatile("" : "+r"(r[i])::"memory");
}
__device__ __forceinline__ uint64_t mk_desc(uint32_t a16, uint32_t lbo, uint32_t sbo, uint32_t swz, uint32_t off = 0) {
  uint64_t d;
  asm("mov.b64 %0, {%1, %2};" : "=l"(d) : "r"(a16), "r"((sbo >> 4) | (swz << 30)));
  return d + (off + ((lbo >> 4) << 16));
}
__device__ __forceinline__ void mbar_init(uint32_t bar, uint32_t cnt) {
  asm volatile("mbarrier.init.shared::cta.b64 [%0], %1;" ::"r"(bar), "r"(cnt) : "memory");
}
__device__ __forceinline__ void mbar_expect(uint32_t bar, uint32_t tx) {
  asm volatile("mbarrier.arrive.expect_tx.shared::cta.b64 _, [%0], %1;" ::"r"(bar), "r"(tx) : "memory");
}
__device__ __forceinline__ bool mbar_test(uint32_t bar, uint32_t ph) {
  uint32_t ok;
  asm volatile("{\n.reg .pred p;\nmbarrier.test_wait.parity.shared::cta.b64 p, [%1], %2;\nselp.u32 %0, 1, 0, p;\n}\n"
               : "=r"(ok) : "r"(bar), "r"(ph) : "memory");
  return ok;
}
__device__ __forceinline__ void mbar_wait(uint32_t bar, uint32_t ph) {
  asm volatile("{\n.reg .pred p;\n.reg .u32 n;\nmov.u32 n, 0;\n"
               "LOOP:\nadd.u32 n, n, 1;\nmbarrier.try_wait.parity.shared::cta.b64 p, [%0], %1;\n@p bra DONE;\n"
               "setp.lt.u32 p, n, 0x1000000;\n@p bra LOOP;\ntrap;\n"
               "DONE:\n}\n" ::"r"(bar), "r"(ph) : "memory");
}
template <int NS> __device__ __forceinline__ void mbar_wait_slow(uint32_t bar, uint32_t ph) {
  asm volatile("{\n.reg .pred p;\n.reg .u32 n;\nmov.u32 n, 0;\n"
               "LOOP:\nmbarrier.test_wait.parity.shared::cta.b64 p, [%0], %1;\n@p bra DONE;\n"
               "nanosleep.u32 %2;\nadd.u32 n, n, 1;\nsetp.lt.u32 p, n, 0x400000;\n@p bra LOOP;\ntrap;\n"
               "DONE:\n}\n" ::"r"(bar), "r"(ph), "n"(NS) : "memory");
}
__device__ __forceinline__ void mbar_arrive_cluster_if(bool on, uint32_t addr) {
  asm volatile("{\n.reg .pred p;\nsetp.ne.b32 p, %1, 0;\n@p mbarrier.arrive.shared::cluster.b64 _, [%0];\n}\n" ::"r"(addr), "r"((int)on) : "memory");
}
__device__ __forceinline__ void mbar_arrive_if(bool on, uint32_t addr) {
  asm volatile("{\n.reg .pred p;\nsetp.ne.b32 p, %1, 0;\n@p mbarrier.arrive.shared::cta.b64 _, [%0];\n}\n" ::"r"(addr), "r"((int)on) : "memory");
}
__device__ __forceinline__ void tma2d(uint32_t dst, const CUtensorMap* m, uint32_t bar, int c0, int c1) {
  asm volatile("cp.async.bulk.tensor.2d.shared::cluster.global.mbarrier::complete_tx::bytes [%0], [%1, {%3, %4}], [%2];"
               ::"r"(dst), "l"(m), "r"(bar), "r"(c0), "r"(c1) : "memory");
}
__device__ __forceinline__ void tma3d(uint32_t dst, const CUtensorMap* m, uint32_t bar, int c0, int c1, int c2) {
  asm volatile("cp.async.bulk.tensor.3d.shared::cluster.global.mbarrier::complete_tx::bytes [%0], [%1, {%3, %4, %5}], [%2];"
               ::"r"(dst), "l"(m), "r"(bar), "r"(c0), "r"(c1), "r"(c2) : "memory");
}
__device__ __forceinline__ void tma3d_mc(uint32_t dst, const CUtensorMap* m, uint32_t bar, int c0, int c1, int c2) {
  asm volatile("cp.async.bulk.tensor.3d.shared::cluster.global.mbarrier::complete_tx::bytes.multicast::cluster"
               " [%0], [%1, {%3, %4, %5}], [%2], %6;"
               ::"r"(dst), "l"(m), "r"(bar), "r"(c0), "r"(c1), "r"(c2), "h"((uint16_t)3) : "memory");
}
__device__ __forceinline__ void tma3d_store(const CUtensorMap* m, uint32_t src, int c0, int c1, int c2) {
  asm volatile("cp.async.bulk.tensor.3d.global.shared::cta.bulk_group [%0, {%2, %3, %4}], [%1];"
               ::"l"(m), "r"(src), "r"(c0), "r"(c1), "r"(c2) : "memory");
}
__device__ __forceinline__ void bar_sync(int id, int n) { asm volatile("bar.sync %0, %1;" ::"r"(id), "r"(n) : "memory"); }
__device__ __forceinline__ uint32_t pack_bf16(float lo, float hi) {
  uint32_t r;
  asm("cvt.rn.bf16x2.f32 %0, %1, %2;" : "=r"(r) : "f"(hi), "f"(lo));
  return r;
}
__device__ __forceinline__ float ex2(float x) {
  float y;
  asm("ex2.approx.ftz.f32 %0, %1;" : "=f"(y) : "f"(x));
  return y;
}
__device__ __forceinline__ float fadd(float a, float b) {
  float y;
  asm("add.f32 %0, %1, %2;" : "=f"(y) : "f"(a), "f"(b));
  return y;
}
__device__ __forceinline__ float rcp(float x) {
  float y;
  asm("rcp.approx.ftz.f32 %0, %1;" : "=f"(y) : "f"(x));
  return y;
}
__device__ __forceinline__ void stsm4(uint32_t addr, uint32_t a, uint32_t b, uint32_t c, uint32_t d) {
  asm volatile("stmatrix.sync.aligned.m8n8.x4.shared.b16 [%0], {%1, %2, %3, %4};" ::"r"(addr), "r"(a), "r"(b), "r"(c), "r"(d) : "memory");
}

__device__ __forceinline__ void tma4d_mc_hint(uint32_t dst, const CUtensorMap* m, uint32_t bar, int c3, uint64_t pol) {
  asm volatile("cp.async.bulk.tensor.4d.shared::cluster.global.mbarrier::complete_tx::bytes.multicast::cluster.L2::cache_hint"
               " [%0], [%1, {%3, %3, %3, %4}], [%2], %5, %6;"
               ::"r"(dst), "l"(m), "r"(bar), "r"(0), "r"(c3), "h"((uint16_t)3), "l"(pol) : "memory");
}
__device__ __forceinline__ void tma5d_mc(uint32_t dst, const CUtensorMap* m, uint32_t bar, int c2, int c4) {
  asm volatile("cp.async.bulk.tensor.5d.shared::cluster.global.mbarrier::complete_tx::bytes.multicast::cluster"
               " [%0], [%1, {%3, %3, %4, %3, %5}], [%2], %6;"
               ::"r"(dst), "l"(m), "r"(bar), "r"(0), "r"(c2), "r"(c4), "h"((uint16_t)3) : "memory");
}
__device__ __forceinline__ void bulk_load_hint(uint32_t dst, const void* src, uint32_t bytes, uint32_t bar, uint64_t pol) {
  asm volatile("cp.async.bulk.shared::cluster.global.mbarrier::complete_tx::bytes.L2::cache_hint [%0], [%1], %2, [%3], %4;"
               ::"r"(dst), "l"(src), "r"(bytes), "r"(bar), "l"(pol) : "memory");
}
__device__ __forceinline__ void stg128_hint(void* p, uint32_t a, uint32_t b, uint32_t c, uint32_t d, uint64_t pol) {
  asm volatile("st.global.L2::cache_hint.v4.b32 [%0], {%1, %2, %3, %4}, %5;" ::"l"(p), "r"(a), "r"(b), "r"(c), "r"(d), "l"(pol) : "memory");
}
__device__ __forceinline__ void stg2_if(bool on, void* p, uint32_t a, uint32_t b, uint32_t c, uint32_t d, uint32_t e, uint32_t f,
                                        uint32_t g, uint32_t h, uint64_t pol) {
  asm volatile("{\n.reg .pred p;\nsetp.ne.b32 p, %10, 0;\n"
               "@p st.global.L2::cache_hint.v4.b32 [%0], {%1, %2, %3, %4}, %9;\n"
               "@p st.global.L2::cache_hint.v4.b32 [%0 + 512], {%5, %6, %7, %8}, %9;\n}\n"
               ::"l"(p), "r"(a), "r"(b), "r"(c), "r"(d), "r"(e), "r"(f), "r"(g), "r"(h), "l"(pol), "r"((int)on) : "memory");
}
__device__ __forceinline__ uint64_t evict_first() {
  uint64_t p;
  asm("createpolicy.fractional.L2::evict_first.b64 %0, 1.0;" : "=l"(p));
  return p;
}
__device__ __forceinline__ bool elect() {
  uint32_t ok;
  asm volatile("{\n.reg .pred p;\nelect.sync _|p, 0xffffffff;\nselp.u32 %0, 1, 0, p;\n}\n" : "=r"(ok));
  return ok;
}
__device__ __forceinline__ void mbar_arrive(uint32_t bar) {
  asm volatile("mbarrier.arrive.shared::cta.b64 _, [%0];" ::"r"(bar) : "memory");
}
__device__ __forceinline__ void stg128(void* p, uint32_t a, uint32_t b, uint32_t c, uint32_t d) {
  asm volatile("st.global.v4.b32 [%0], {%1, %2, %3, %4};" ::"l"(p), "r"(a), "r"(b), "r"(c), "r"(d) : "memory");
}
__device__ __forceinline__ void lds128(uint32_t p, uint32_t& a, uint32_t& b, uint32_t& c, uint32_t& d) {
  asm volatile("ld.shared.v4.b32 {%0, %1, %2, %3}, [%4];" : "=r"(a), "=r"(b), "=r"(c), "=r"(d) : "r"(p) : "memory");
}
__device__ __forceinline__ void wait_count(const unsigned int* p, uint32_t target) {
  asm volatile("{\n.reg .pred p;\n.reg .u32 n, v;\nmov.u32 n, 0;\n"
               "LOOP:\nld.acquire.gpu.global.u32 v, [%0];\nsetp.ge.u32 p, v, %1;\n@p bra DONE;\n"
               "nanosleep.u32 %2;\nadd.u32 n, n, 1;\nsetp.lt.u32 p, n, 0x400000;\n@p bra LOOP;\ntrap;\n"
               "DONE:\n}\n" ::"l"(p), "r"(target), "n"(200) : "memory");
}

__host__ __device__ __forceinline__ int o_wave(int a, int b, int i, int lag) {
  if (lag == 0) return a + i;
  const int p = lag < b - a - 1 ? lag : b - a - 1;
  return i < p ? b - 2 - i : i == p ? b - 1 : b - 1 - i;
}

struct Cursor {
  uint32_t n;
  __device__ __forceinline__ uint32_t off() const { return n & (8 * NBAR - 8); }
  __device__ __forceinline__ uint32_t ph() const { return (n / (8 * NBAR)) & 1; }
  __device__ __forceinline__ void next() { n += 8; }
};

constexpr float kScaleLog2 = 0.07216878364870322f * 1.4426950408889634f;
constexpr float kSumLimit = 1048576.0f;
constexpr float kMaxLag = 8.0f;

__global__ void __cluster_dims__(2, 1, 1) __launch_bounds__(384, 1)
fused_kernel(const __grid_constant__ Params P) {
  extern __shared__ uint8_t smem_raw[];
  const uint32_t sbase = (smem_u32(smem_raw) + 1023) & ~1023u;
  const uint32_t full0 = sbase + RING, empty0 = full0 + 8 * NBAR, odone = empty0 + 8 * NBAR, oready0 = odone + 8;
  const uint32_t fenced = oready0 + 64, hready0 = fenced + 8;
  const uint32_t rank = blockIdx.x & 1;
  const int role = blockIdx.x >> 1;
  const bool helper = role >= N_CL;
  const int team = helper ? 0 : role >> 2, nt = role & 3, blk = team >> 3;
  const uint32_t* prog = P.ops[helper ? N_TEAM + 2 * (role - N_CL) : team];
  auto q_role = [&](uint32_t op) { return helper ? (int)(((op >> 3) & 60) | ((op >> 12) & 3)) : role; };
  auto o_role = [&](uint32_t op) { return helper ? (int)(((op >> 26) & 56) | ((op >> 9) & 7)) : role; };
  const int wid = __shfl_sync(0xffffffffu, (int)(threadIdx.x >> 5), 0);
  const int wg = wid >> 2;

  const uint32_t op0 = P.first[helper ? N_TEAM + role - N_CL : team];
  if (__builtin_expect(wid == 8, 1)) {
    if (elect()) {
#pragma unroll
      for (int k = 0; k < EARLY; k++) mbar_init(full0 + 8 * k, 1);
      asm volatile("fence.mbarrier_init.release.cluster;" ::: "memory");
      if ((op0 & 3) == OP_Q) {
        const int qr = q_role(op0);
#pragma unroll
        for (int k = 0; k < EARLY; k++) {
          mbar_expect(full0 + 8 * k, SZ_WQ + SZ_A);
          tma2d(sbase + k * (SZ_WQ + SZ_A) + SZ_WQ, &P.x[qr >> 5], full0 + 8 * k, 64 * k, ((qr >> 2) & 7) * kSq + rank * 128);
          tma3d(sbase + k * (SZ_WQ + SZ_A), &P.wq[qr >> 5], full0 + 8 * k, 0, 64 * k, 3 * (4 * ((op0 >> 2) & 7) + (qr & 3)));
          tma3d(sbase + k * (SZ_WQ + SZ_A) + SZ_WQ / 2, &P.wq[qr >> 5], full0 + 8 * k, 0, 64 * k + 32, 3 * (4 * ((op0 >> 2) & 7) + (qr & 3)));
        }
      }
      asm volatile("prefetch.tensormap [%0];" ::"l"(&P.k[blk]) : "memory");
      asm volatile("prefetch.tensormap [%0];" ::"l"(&P.v[blk]) : "memory");
    }
  } else if (threadIdx.x == 0) {
#pragma unroll
    for (int i = EARLY; i < 2 * NBAR + 10 + MAX_PARK; i++) mbar_init(full0 + 8 * i, i >= NBAR && i <= 2 * NBAR ? 16 : 1);
    asm volatile("fence.mbarrier_init.release.cluster;" ::: "memory");
  }
  __syncwarp();
  asm volatile("barrier.cluster.arrive.relaxed.aligned;\nbarrier.cluster.wait.aligned;" ::: "memory");

  if (wg == 2) {
    asm volatile("setmaxnreg.dec.sync.aligned.u32 24;");
    if (wid == 8) {
      Cursor tail{0}, head{0};
      int sh = 0;
      uint32_t cur = 0, used = 0;
      uint64_t fifo = 0;
      uint32_t dst, bar, oready = oready0;
      const uint64_t pol = evict_first();
      auto acquire = [&](uint32_t bytes, int part = 0) {
        uint32_t fp = bytes >> 12;
        if (cur + fp > (RING >> 12)) { fp += (RING >> 12) - cur; cur = 0; }
        used += fp;
        bool more = false;
        uint32_t wbar, wph;
        while (used > (RING >> 12) || (part != 2 && sh == 5 * NFLIGHT)) {
          if (more) mbar_wait(wbar, wph);
          more = true;
          wbar = empty0 + tail.off(); wph = tail.ph();
          tail.next();
          used -= (uint32_t)fifo & 31;
          fifo >>= 5;
          sh -= 5;
        }
        fifo += (uint64_t)fp << sh;
        dst = sbase + (cur << 12);
        bar = full0 + head.off();
        cur += bytes >> 12;
        if (part != 1) {
          sh += 5;
          head.next();
        }
        if (more) mbar_wait(wbar, wph);
      };
      auto scratch = [&](const uint4* src, uint32_t bytes, int n) {
        asm volatile("fence.proxy.async.global;" ::: "memory");
#pragma unroll 1
        for (int i = 0; i < n; i++) {
          acquire(bytes);
          if (elect()) {
            bulk_load_hint(dst, src + i * (bytes / 16), bytes, bar, pol);
            mbar_expect(bar, bytes);
          }
        }
      };
      for (int pc = 0;; pc++) {
        const uint32_t op = prog[pc];
        const int type = op & 3, a = (op >> 2) & 7;
        if (type == OP_END) break;
        if (type == OP_Q) {
          const int qr = q_role(op);
#pragma unroll 1
          for (int k = 0; k < 10; k++) {
            acquire(SZ_WQ, 1);
            if ((pc > 0 || k >= EARLY) && elect()) tma3d_mc(dst + rank * (SZ_WQ / 2), &P.wq[qr >> 5], bar, 0, 64 * k + 32 * rank, 3 * (4 * a + (qr & 3)));
            acquire(SZ_A, 2);
            if ((pc > 0 || k >= EARLY) && elect()) {
              tma2d(dst, &P.x[qr >> 5], bar, 64 * k, ((qr >> 2) & 7) * kSq + rank * 128);
              mbar_expect(bar, SZ_WQ + SZ_A);
            }
          }
        } else if (type == OP_A) {
          const uint32_t nop = prog[pc + 1];
#pragma unroll 1
          for (int t = (op & F_PARK) ? 1 : 0; t < 33; t++) {
            int wave = a;
            if (t == 31 && (nop & 3) != OP_A) t++;
            if (t == 31) {
              wave = (nop >> 2) & 7;
              mbar_wait((nop & F_HELP) ? hready0 + 8 * ((nop >> 10) & 3) : fenced, 0);
              scratch(&g_o[((team * 2 + rank) * 96 + 3 * (4 * wave + nt)) * 1024], SZ_PARK, 2);
            }
            const int isv = t ? ~t & 1 : 0, j = (isv ? (t - 1) >> 1 : (t + 1) >> 1) & 15;
            const int row0 = ((team & 7) * kH + 4 * wave + nt) * kSk;
            acquire(SZ_KV);
            if (t >= KV_TRANSIT) {
              const Cursor c{head.n - 8 * (KV_TRANSIT + 1)};
              mbar_wait(full0 + c.off(), c.ph());
            }
            if (elect()) {
              tma4d_mc_hint(dst + rank * (SZ_KV / 2), isv ? &P.v[blk] : &P.k[blk], bar, row0 / 8 + 8 * j + 4 * rank, pol);
              mbar_expect(bar, SZ_KV);
            }
          }
        } else {
          const int b = (op >> 5) & 15, ro = o_role(op);
#pragma unroll 1
          for (int i = 0; i < b - a; i++) {
            const int w = o_wave(a, b, i, (P.dbg >> 4) & 7);
            mbar_wait(oready, 0);
            oready += 8;
            asm volatile("fence.proxy.async.global;" ::: "memory");
#pragma unroll 1
            for (int k = 12 * w; k < 12 * w + 12; k++) {
              acquire(SZ_A, 1);
              if (elect()) bulk_load_hint(dst, &g_o[(((ro >> 2) * 2 + rank) * 96 + k) * 1024], SZ_A, bar, pol);
              acquire(SZ_WO, 2);
              if (elect()) {
                tma5d_mc(dst + rank * 10240, &P.wo[ro >> 5], bar, 8 * k + 4 * rank, 5 * (ro & 3));
                mbar_expect(bar, SZ_WO + SZ_A);
              }
            }
          }
          if (op & F_LD) {
            if (op & F_PARK) mbar_wait(hready0 + 8 * (MAX_PARK - 1), 0);
            scratch(&g_part[(role * 2 + rank) * 5120], SZ_PART, 5);
          }
          if (!(op & F_ST)) {
            acquire(SZ_OUT);
            if (elect()) mbar_arrive(bar);
            __syncwarp();
            sh -= 5;
          }
        }
      }
      for (; sh > 0; sh -= 5) {
        mbar_wait(empty0 + tail.off(), tail.ph());
        tail.next();
      }
    } else if (threadIdx.x == 288) {
      uint32_t ph = 0;
      bool first = true;
      for (int pc = 0;; pc++) {
        const uint32_t op = prog[pc];
        if ((op & 3) == OP_END) break;
        if ((op & 3) != OP_A && !helper) continue;
        mbar_wait_slow<400>(odone, ph);
        ph ^= 1;
        unsigned int* flag = !helper ? &g_done[(team * 2 + rank) * 8 + ((op >> 2) & 7)]
                             : (op & 3) == OP_Q ? &g_help[(q_role(op) * 2 + rank) * MAX_PARK + ((op >> 10) & 3)]
                                                : &g_help[(o_role(op) * 2 + rank) * MAX_PARK + MAX_PARK - 1];
        asm volatile("red.release.gpu.global.add.u32 [%0], 1;" ::"l"(flag) : "memory");
        if (first) mbar_arrive(fenced);
        first = false;
      }
    } else if (threadIdx.x == 320) {
      uint32_t oready = oready0;
      for (int pc = 0;; pc++) {
        const uint32_t op = prog[pc];
        if ((op & 3) == OP_END) break;
        if ((op & 3) == OP_O) {
          const int a = (op >> 2) & 7, b = (op >> 5) & 15;
#pragma unroll 1
          for (int i = 0; i < b - a; i++) {
            const int ci = ((o_role(op) >> 2) * 2 + rank) * 8 + o_wave(a, b, i, (P.dbg >> 4) & 7);
            wait_count(&g_done[ci], 4);
            mbar_arrive(oready);
            oready += 8;
            if (atomicAdd(&g_seen[ci], 1u) == 3u) { g_seen[ci] = 0; g_done[ci] = 0; }
          }
        }
        if ((op & 3) != OP_Q && (op & F_HELP) && (op & F_PARK)) {
          unsigned int* flag = &g_help[(role * 2 + rank) * MAX_PARK + ((op >> 10) & 3)];
          wait_count(flag, 1);
          mbar_arrive(hready0 + 8 * ((op >> 10) & 3));
          *flag = 0;
        }
      }
    }
  } else {
    asm volatile("setmaxnreg.inc.sync.aligned.u32 240;");
    const int lane = threadIdx.x & 31, warp = wid & 3;
    uint32_t empty_rem;
    asm volatile("mapa.shared::cluster.u32 %0, %1, %2;" : "=r"(empty_rem) : "r"(empty0), "r"(lane & 1));
    auto release = [&](int slot) { mbar_arrive_cluster_if(lane < 2, empty_rem + slot); };
    Cursor r{0};
    const uint32_t ring16 = (sbase & 0x3FFFF) >> 4;
    uint32_t cur = ring16;
    bool rdy0 = false, rdy1 = false;
    auto probe1 = [&]() { rdy0 = mbar_test(full0 + r.off(), r.ph()); };
    auto probe2 = [&]() {
      Cursor n = r;
      rdy0 = mbar_test(full0 + n.off(), n.ph());
      n.next();
      rdy1 = mbar_test(full0 + n.off(), n.ph());
    };
    auto take = [&](bool rdy, uint32_t bytes, uint32_t& addr) {
      const int bi = r.off();
      if (!__all_sync(0xffffffffu, rdy)) mbar_wait(full0 + r.off(), r.ph());
      r.next();
      if (cur > ring16 + ((RING - bytes) >> 4)) cur = ring16;
      addr = cur;
      cur += bytes >> 4;
      return bi;
    };
    auto second = [&](uint32_t bytes) {
      if (cur > ring16 + ((RING - bytes) >> 4)) cur = ring16;
      cur += bytes >> 4;
      return cur - (bytes >> 4);
    };
    const int row = wg * 64 + warp * 16 + (lane >> 2);
    int img0 = row * 4 + ((lane & 3) ^ ((row >> 1) & 3));
    uint4* pend = nullptr;
    const uint64_t spol = evict_first();
    int pc = 0;
    uint32_t op = prog[0];
    auto enter = [&]() {
      r.n = op >> 12; cur = ring16 + (((op >> 20) & 63) << 8);
    };
    auto drain = [&](uint32_t (&t)[48], uint32_t c) {
      if (!(op & (3u << 26)) || c >= 6) return;
#pragma unroll
      for (int i = 0; i < 6; i++)
        stg2_if(c == i, pend + i * 512, t[8 * i], t[8 * i + 1], t[8 * i + 2], t[8 * i + 3],
                t[8 * i + 4], t[8 * i + 5], t[8 * i + 6], t[8 * i + 7], spol);
      if ((op & (1u << 26)) && c == 5) {
        __syncwarp();
        mbar_arrive_if(lane < 2, odone);
      }
    };
    float s[32], o[96], c[80];
    uint32_t q[48], pa[16], pb[16];
    float mc0, mc1, l0, l1;
    bool gen;
    auto soft = [&](float (&s)[32], uint32_t (&pout)[16], bool first) {
      if (first) { gen = false; mc0 = 0.f; mc1 = 0.f; }
      float b0, b1;
      for (;;) {
        if (gen) {
          float m0 = fmaxf(s[0], s[1]), m1 = fmaxf(s[2], s[3]);
#pragma unroll
          for (int i = 1; i < 8; i++) { m0 = fmaxf(m0, fmaxf(s[4 * i], s[4 * i + 1])); m1 = fmaxf(m1, fmaxf(s[4 * i + 2], s[4 * i + 3])); }
          m0 = fmaxf(m0, __shfl_xor_sync(0xffffffffu, m0, 1)); m1 = fmaxf(m1, __shfl_xor_sync(0xffffffffu, m1, 1));
          m0 = fmaxf(m0, __shfl_xor_sync(0xffffffffu, m0, 2)); m1 = fmaxf(m1, __shfl_xor_sync(0xffffffffu, m1, 2));
          if (first) {
            mc0 = m0; mc1 = m1;
          } else if (__any_sync(0xffffffffu, !(m0 <= mc0 + kMaxLag && m1 <= mc1 + kMaxLag))) {
            m0 = fmaxf(mc0, m0); m1 = fmaxf(mc1, m1);
            const float a0 = ex2(mc0 - m0), a1 = ex2(mc1 - m1);
            mc0 = m0; mc1 = m1;
            l0 *= a0; l1 *= a1;
            wg_wait<0>();
            fence_regs(o);
#pragma unroll
            for (int i = 0; i < 96; i++) o[i] *= i & 2 ? a1 : a0;
          }
#pragma unroll
          for (int i = 0; i < 32; i++) s[i] -= i & 2 ? mc1 : mc0;
        }
#pragma unroll
        for (int i = 0; i < 8; i++) {
          const float e1 = ex2(s[4 * i + 1]), e0 = ex2(s[4 * i]), e3 = ex2(s[4 * i + 3]), e2 = ex2(s[4 * i + 2]);
          pout[2 * i] = pack_bf16(e0, e1);
          b0 = i ? b0 + fadd(e1, e0) : fadd(e1, e0);
          pout[2 * i + 1] = pack_bf16(e2, e3);
          b1 = i ? b1 + fadd(e3, e2) : fadd(e3, e2);
        }
        if (!__any_sync(0xffffffffu, !gen && !(fmaxf(b0, b1) <= kSumLimit && (!first || fminf(b0, b1) >= 1.0f / kSumLimit)))) break;
        gen = __any_sync(0xffffffffu, true);
      }
      l0 = first ? b0 : l0 + b0;
      l1 = first ? b1 : l1 + b1;
    };
    auto qk = [&](float (&s)[32], uint32_t ak, int k0, int k1) {
#pragma unroll
      for (int kk = k0; kk < k1; kk++)
        wgmma_rs_n64<0>(s, q[4 * kk], q[4 * kk + 1], q[4 * kk + 2], q[4 * kk + 3], mk_desc(ak, 16, KV_SBO, 1, (kk >> 2) * KV_CH + (kk & 3) * 2), kk != 0);
      wg_commit();
    };
    auto pv = [&](uint32_t (&pin)[16], uint32_t av, int acc) {
#pragma unroll
      for (int kk = 0; kk < 4; kk++)
        wgmma_rs_n192<1>(o, pin[4 * kk], pin[4 * kk + 1], pin[4 * kk + 2], pin[4 * kk + 3], mk_desc(av, KV_CH * 16, KV_SBO, 1, kk * (KV_SBO / 8)), acc || (kk != 0));
      wg_commit();
    };
    auto xw = [&](uint32_t ad, int acc) {
      const uint32_t da = second(SZ_A) + wg * 512;
      wg_fence();
#pragma unroll
      for (int kk = 0; kk < 4; kk++)
        wgmma_ss_n192<1>(o, mk_desc(da, 16, 1024, 1, kk * 2), mk_desc(ad, 4096, 1024, 1, (kk & 1) * 128 + (kk >> 1) * 768), acc || kk != 0);
      wg_commit();
    };
    auto ow = [&](int acc, int prev) {
      uint32_t da;
      const int bi = take(rdy0, SZ_A, da);
      const uint32_t db = second(SZ_WO);
      da += wg * 256;
      wg_fence();
      wgmma_ss_n160<1>(c, mk_desc(da, 16, 512, 2), mk_desc(db, 2048, 512, 2), acc);
      wgmma_ss_n160<1>(c, mk_desc(da, 16, 512, 2, 2), mk_desc(db, 2048, 512, 2, 64), 1);
      wg_commit();
      if (acc == 1) { wg_wait<1>(); release(prev); }
      wgmma_ss_n160<1>(c, mk_desc(da, 16, 512, 2, 512), mk_desc(db, 2048, 512, 2, 640), 1);
      wgmma_ss_n160<1>(c, mk_desc(da, 16, 512, 2, 514), mk_desc(db, 2048, 512, 2, 704), 1);
      wg_commit();
      return bi;
    };
    auto st_part = [&](int i) {
      stg2_if(true, pend + i * 512, __float_as_uint(c[8 * i]), __float_as_uint(c[8 * i + 1]), __float_as_uint(c[8 * i + 2]), __float_as_uint(c[8 * i + 3]),
              __float_as_uint(c[8 * i + 4]), __float_as_uint(c[8 * i + 5]), __float_as_uint(c[8 * i + 6]), __float_as_uint(c[8 * i + 7]), spol);
    };
#pragma unroll
    for (int i = 0; i < 48; i++) q[i] = 0;
    enter();

    if ((op & 3) == OP_Q) {
      uint32_t ad;
      int bi0 = take(false, SZ_WQ, ad), k = 0, lag = 0;
      xw(ad, 0);
      for (;;) {
#pragma unroll 1
        for (;;) {
          drain(q, k - lag);
          probe1();
          wg_wait<0>();
          release(bi0);
          bi0 = take(rdy0, SZ_WQ, ad);
          if (++k == 8) break;
          xw(ad, 1);
        }
        if (wg) bar_sync(2, 256);
        xw(ad, 1);
        const int bi9 = take(false, SZ_WQ, ad);
        xw(ad, 1);
        if (!wg) asm volatile("bar.arrive 2, 256;" ::: "memory");
        k = 0; lag = 0;
        uint32_t nop = prog[++pc];
        wg_wait<1>();
        release(bi0);
        probe2();
        wg_wait<0>();
        fence_regs(o);
        release(bi9);
#pragma unroll
        for (int i = 0; i < 48; i++) q[i] = pack_bf16(o[2 * i] * kScaleLog2, o[2 * i + 1] * kScaleLog2);
        fence_regs(q);
        if (op & F_PARK) {
          const int qt = helper ? (op >> 5) & 15 : team, qm = helper ? (op >> 12) & 3 : nt;
          pend = &g_o[((qt * 2 + rank) * 96 + 3 * (4 * ((op >> 2) & 7) + qm)) * 1024 + img0];
          op = nop;
          enter();
          if ((op & 3) != OP_Q) break;
          bi0 = take(rdy0, SZ_WQ, ad);
          xw(ad, 0);
          continue;
        }
        int wave = (op >> 2) & 7, sk1;
        uint32_t ak1;
        {
          float s0[32];
          const int sk0 = take(rdy0, SZ_KV, ad);
          wg_fence();
          qk(s0, ad, 0, 12);
          sk1 = take(rdy1, SZ_KV, ak1);
          wg_fence();
          qk(s, ak1, 0, S1A);
          probe1();
          wg_wait<1>();
          fence_regs(s0);
          release(sk0);
          soft(s0, pa, true);
        }
        float i0, i1;
        auto sums = [&]() {
          l0 += __shfl_xor_sync(0xffffffffu, l0, 1); l1 += __shfl_xor_sync(0xffffffffu, l1, 1);
          l0 += __shfl_xor_sync(0xffffffffu, l0, 2); l1 += __shfl_xor_sync(0xffffffffu, l1, 2);
          i0 = rcp(l0); i1 = rcp(l1);
          asm volatile("" : "+f"(i0), "+f"(i1));
        };
        auto target = [&]() {
          pend = &g_o[((team * 2 + rank) * 96 + 3 * (4 * wave + nt)) * 1024 + img0];
          asm volatile("" : "+l"(pend));
        };
        bool late = false;
#pragma unroll
        for (int i = 0; i < 16; i++) pb[i] = 0;
        for (;;) {
          nop = prog[++pc];
          {
            uint32_t av;
            const int sv = take(rdy0, SZ_KV, av);
            wg_fence();
            qk(s, ak1, S1A, 12);
            pv(pa, av, 0);
            if (late) {
              stg2_if(true, pend + 4 * 512, pb[0], pb[1], pb[2], pb[3], pb[4], pb[5], pb[6], pb[7], spol);
              stg2_if(true, pend + 5 * 512, pb[8], pb[9], pb[10], pb[11], pb[12], pb[13], pb[14], pb[15], spol);
              __syncwarp();
              mbar_arrive_if(lane < 2, odone);
            }
            probe2();
            wg_wait<1>();
            fence_regs(s);
            release(sk1);
            soft(s, pb, false);
            wg_wait<0>();
            fence_regs(o);
            release(sv);
          }
          auto step = [&](uint32_t (&pin)[16], uint32_t (&pout)[16]) {
            uint32_t ak, av;
            const int sk = take(rdy0, SZ_KV, ak), sv = take(rdy1, SZ_KV, av);
            wg_fence();
            qk(s, ak, 0, 12);
            pv(pin, av, 1);
            probe2();
            wg_wait<1>();
            fence_regs(s);
            release(sk);
            soft(s, pout, false);
            wg_wait<0>();
            fence_regs(o);
            release(sv);
          };
#pragma unroll 1
          for (int jj = 0; jj < 7; jj++) {
            step(pb, pa);
            step(pa, pb);
          }
          if ((nop & 3) != OP_A) break;
          uint32_t ak, av;
          {
            const int b0 = take(rdy0, SZ_PARK, ak), b1 = take(rdy1, SZ_PARK, av);
            const uint32_t ad0 = ak, ad1 = av;
            probe2();
#pragma unroll
            for (int i = 0; i < 12; i++)
              lds128(sbase + ((i < 6 ? ad0 : ad1) - ring16 + img0) * 16 + ((i % 6) >> 1) * 8192 + (i & 1) * 512, q[4 * i], q[4 * i + 1], q[4 * i + 2], q[4 * i + 3]);
            release(b0); release(b1);
          }
          const int sk0 = take(rdy0, SZ_KV, ak), sv = take(rdy1, SZ_KV, av);
          wg_fence();
          qk(s, ak, 0, 8);
          sched_fence(img0, P.zero);
          sums();
          sched_fence(img0, P.zero);
          qk(s, ak, 8, 12);
          pv(pb, av, 1);
          probe2();
          wg_wait<1>();
          fence_regs(s);
          release(sk0);
          soft(s, pa, true);
          sk1 = take(rdy0, SZ_KV, ak1);
          rdy0 = rdy1;
          wg_wait<0>();
          target();
          fence_regs(o);
          release(sv);
          uint32_t t[48];
#pragma unroll
          for (int j = 0; j < 6; j++) {
#pragma unroll
            for (int i = 0; i < 4; i++) {
              t[8 * j + i] = pack_bf16(o[16 * j + 4 * i] * i0, o[16 * j + 4 * i + 1] * i0);
              t[8 * j + i + 4] = pack_bf16(o[16 * j + 4 * i + 2] * i1, o[16 * j + 4 * i + 3] * i1);
            }
            if (j < 4)
            stg2_if(true, pend + j * 512, t[8 * j], t[8 * j + 1], t[8 * j + 2], t[8 * j + 3], t[8 * j + 4], t[8 * j + 5], t[8 * j + 6], t[8 * j + 7], spol);
            if (j == UC0) { wg_fence(); qk(s, ak1, 0, 4); }
            if (j == UC1) { wg_fence(); qk(s, ak1, 4, S1A); }
            sched_fence(img0, P.zero);
          }
          if (P.zero) {
#pragma unroll
            for (int j = 0; j < 4; j++)
              stg2_if(true, pend, t[8 * j], t[8 * j + 1], t[8 * j + 2], t[8 * j + 3], t[8 * j + 4], t[8 * j + 5], t[8 * j + 6], t[8 * j + 7], spol);
          }
          late = true;
#pragma unroll
          for (int i = 0; i < 16; i++) pb[i] = t[32 + i];
          wave = (nop >> 2) & 7;
        }
        const int sv = take(rdy0, SZ_KV, ad);
        wg_fence();
        pv(pb, ad, 1);
        sums();
        target();
        op = nop;
        enter();
        rdy0 = rdy1;
        auto convert = [&](float (&u)[96], int j0, int j1) {
#pragma unroll
          for (int i = 4 * j0; i < 4 * j1; i++) {
            q[8 * (i >> 2) + (i & 3)] = pack_bf16(u[4 * i], u[4 * i + 1]);
            q[8 * (i >> 2) + (i & 3) + 4] = pack_bf16(u[4 * i + 2], u[4 * i + 3]);
          }
        };
        if ((op & 3) != OP_O) {
          if ((op & 3) == OP_Q) bi0 = take(rdy0, SZ_WQ, ad);
          wg_wait<0>();
          fence_regs(o);
          release(sv);
          float u[96];
#pragma unroll
          for (int i = 0; i < 96; i++) u[i] = o[i] * (i & 2 ? i1 : i0);
          if ((op & 3) != OP_Q) { convert(u, 0, 6); break; }
          fence_regs(u);
          xw(ad, 0);
          sched_fence(img0, P.zero);
          fence_regs(u);
          convert(u, 0, 1);
          stg2_if(true, pend, q[0], q[1], q[2], q[3], q[4], q[5], q[6], q[7], spol);
          probe1();
          wg_wait<0>();
          release(bi0);
          bi0 = take(rdy0, SZ_WQ, ad);
          xw(ad, 1);
          sched_fence(img0, P.zero);
          fence_regs(u);
          convert(u, 1, 6);
          k = 1;
          continue;
        }
        int bi = ow(0, 0);
        wg_wait<2>();
        fence_regs(o);
        release(sv);
#pragma unroll
        for (int j = 0; j < 6; j++) {
          uint32_t t[8];
#pragma unroll
          for (int i = 0; i < 4; i++) {
            t[i] = pack_bf16(o[16 * j + 4 * i] * i0, o[16 * j + 4 * i + 1] * i0);
            t[i + 4] = pack_bf16(o[16 * j + 4 * i + 2] * i1, o[16 * j + 4 * i + 3] * i1);
          }
          stg2_if(true, pend + j * 512, t[0], t[1], t[2], t[3], t[4], t[5], t[6], t[7], spol);
          if (j == 5) {
            __syncwarp();
            mbar_arrive_if(lane < 2, odone);
          }
          probe1();
          wg_wait<1>();
          bi = ow(1, bi);
          fence_regs(o);
        }
        {
          const int nk = 12 * (((op >> 5) & 15) - ((op >> 2) & 7)) - ((op & F_ST) ? 0 : 2);
#pragma unroll 1
          for (int k = 7; k < nk; k++) {
            probe1();
            wg_wait<1>();
            bi = ow(1, bi);
          }
        }
        if (!(op & F_ST)) {
          probe2();
          wg_wait<1>();
          if (wg) {
            wg_wait<0>();
            release(bi);
            bar_sync(2, 256);
          }
          bi0 = ow(2, 0);
          rdy0 = rdy1;
          const int b = ow(2, 0);
          if (!wg) asm volatile("bar.arrive 2, 256;" ::: "memory");
          wg_wait<4>();
          mbar_arrive_cluster_if(lane < 2 && !wg, empty_rem + bi);
          bi = b;
        }
        probe1();
        nop = prog[++pc];
        if (op & F_LD) {
          uint32_t t[80];
#pragma unroll
          for (int j = 0; j < 5; j++) {
            const int b = take(rdy0, SZ_PART, ad);
            probe1();
#pragma unroll
            for (int i = 4 * j; i < 4 * j + 4; i++)
              lds128(sbase + (ad - ring16 + img0) * 16 + ((i >> 1) & 1) * 8192 + (i & 1) * 512, t[4 * i], t[4 * i + 1], t[4 * i + 2], t[4 * i + 3]);
            release(b);
          }
          wg_wait<0>();
          fence_regs(c);
#pragma unroll
          for (int i = 0; i < 80; i++) c[i] += __uint_as_float(t[i]);
        }
        if (!(op & F_ST)) {
          wg_wait<0>();
          fence_regs(c);
          release(bi0);
          release(bi);
          goto finish;
        }
        op = nop;
        enter();
        bi0 = take(rdy0, SZ_WQ, ad);
        xw(ad, 0);
        pend = &g_part[((team * 4 + nt) * 2 + rank) * 5120 + img0];
        probe1();
        wg_wait<1>();
        fence_regs(c);
        release(bi);
        st_part(0); st_part(1);
        wg_wait<0>();
        release(bi0);
        bi0 = take(rdy0, SZ_WQ, ad);
        xw(ad, 1);
        st_part(2); st_part(3);
#pragma unroll
        for (int i = 0; i < 48; i++) q[i] = __float_as_uint(c[32 + i]);
        pend += 4 * 512;
        k = 1; lag = 2;
      }
    }
    rdy0 = false;
    {
      uint32_t t[48];
#pragma unroll
      for (int i = 0; i < 48; i++) t[i] = q[i] ^ P.zero;
      while ((op & 3) == OP_O) {
        int bi = ow(0, 0);
#pragma unroll 1
        for (int k = 1; k < 12 * (int)(((op >> 5) & 15) - ((op >> 2) & 7)); k++) {
          drain(t, k - 1);
          probe1();
          wg_wait<1>();
          bi = ow(1, bi);
        }
        rdy0 = false;
        wg_wait<0>();
        fence_regs(c);
        pc++;
        release(bi);
        if (!(op & F_ST)) goto finish;
        pend = &g_part[((((op >> 26) & 56) | ((op >> 9) & 7)) * 2 + rank) * 5120 + img0];
#pragma unroll
        for (int i = 6; i < 10; i++) st_part(i);
#pragma unroll
        for (int i = 0; i < 48; i++) t[i] = __float_as_uint(c[i]) ^ P.zero;
        op = prog[pc];
        enter();
      }
      for (int i = 0; i < 6; i++) drain(t, i);
    }
    if (false) {
    finish:
      uint32_t ad;
      take(rdy0, SZ_OUT, ad);
      const uint32_t wstage = sbase + (ad - ring16) * 16 + (wg * 4 + warp) * 5120;
      const uint32_t sa = wstage + (lane & 15) * 64;
#pragma unroll
      for (int i = 0; i < 10; i++) {
        const int u = (i & 1) * 2 + (lane >> 4);
        stsm4(sa + (i >> 1) * 1024 + ((u ^ ((lane >> 1) & 3)) << 4), pack_bf16(c[8 * i], c[8 * i + 1]), pack_bf16(c[8 * i + 2], c[8 * i + 3]),
              pack_bf16(c[8 * i + 4], c[8 * i + 5]), pack_bf16(c[8 * i + 6], c[8 * i + 7]));
      }
      asm volatile("fence.proxy.async.shared::cta;" ::: "memory");
      __syncwarp();
      if (lane == 0) {
        tma3d_store(&P.out, wstage, 0, (team & 7) * kSq + rank * 128 + wg * 64 + warp * 16, blk * 20 + nt * 5);
        asm volatile("cp.async.bulk.commit_group;\ncp.async.bulk.wait_group.read 0;" ::: "memory");
      }
    }
  }
}

typedef CUresult (*EncodeFn)(CUtensorMap*, CUtensorMapDataType, cuuint32_t, void*, const cuuint64_t*, const cuuint64_t*,
                             const cuuint32_t*, const cuuint32_t*, CUtensorMapInterleave, CUtensorMapSwizzle,
                             CUtensorMapL2promotion, CUtensorMapFloatOOBfill);

void encode(EncodeFn fn, CUtensorMap* m, const void* ptr, int rank, const cuuint64_t* dims, const cuuint64_t* strides,
            const cuuint32_t* box, CUtensorMapSwizzle swz) {
  const cuuint32_t es[5] = {1, 1, 1, 1, 1};
  CUresult r = fn(m, CU_TENSOR_MAP_DATA_TYPE_BFLOAT16, rank, const_cast<void*>(ptr), dims, strides, box, es,
                  CU_TENSOR_MAP_INTERLEAVE_NONE, swz, CU_TENSOR_MAP_L2_PROMOTION_L2_128B, CU_TENSOR_MAP_FLOAT_OOB_FILL_NONE);
  if (r != CUDA_SUCCESS) fprintf(stderr, "cuTensorMapEncodeTiled failed: %d\n", (int)r);
}

void annotate(uint32_t* ops, int n, bool helper) {
  uint32_t items = 0, cur = 0, pend = 0;
  auto item = [&](uint32_t bytes, int count, uint32_t bytes2 = 0) {
    for (int i = 0; i < count; i++) {
      if (cur + bytes > RING) cur = 0;
      cur += bytes;
      if (cur + bytes2 > RING) cur = 0;
      cur += bytes2;
      items++;
    }
  };
  for (int i = 0; i <= n; i++) {
    const uint32_t op = ops[i];
    ops[i] |= (items % (2 * NBAR)) << 15 | (cur >> 12) << 20 | pend << 26;
    if ((op & 3) == OP_Q) { item(SZ_WQ, 10, SZ_A); pend = (op & F_PARK) ? (helper ? 1 : 2) : 0; }
    if ((op & 3) == OP_A) {
      item(SZ_KV, (op & F_PARK) ? 30 : 31);
      if ((ops[i + 1] & 3) == OP_A) { item(SZ_PARK, 2); item(SZ_KV, 1); }
      item(SZ_KV, 1);
      pend = 1;
    }
    if ((op & 3) == OP_O) {
      item(SZ_A, 12 * (((op >> 5) & 15) - ((op >> 2) & 7)), SZ_WO);
      if (op & F_LD) item(SZ_PART, 5);
      pend = (op & F_ST) ? (helper ? 1 : 2) : 0;
    }
  }
}

void compile_programs(const char* const* text, bool helpers, Params& P) {
  struct Req { int when, team, wave, slot; } req[N_TEAM * MAX_PARK];
  int n_req = 0;
  for (int t = 0; t < N_TEAM; t++) {
    uint32_t* ops = P.ops[t];
    int n = 0, flags[8] = {0, 0, 0, 0, 0, 0, 0, 0}, n_park = 0, last_o = -1, when = 0, given = 0;
    for (const char* s = text[t]; *s; s++) {
      const int a = s[1] - '0';
      if (*s == 'Q' || (*s == 'H' && !helpers)) { ops[n++] = OP_Q | a << 2; when += 10; }
      else if (*s == 'P') { flags[a] = F_PARK; ops[n++] = OP_Q | a << 2 | flags[a]; when += 10; }
      else if (*s == 'H') { req[n_req++] = {when, t, a, n_park}; flags[a] = F_PARK | F_HELP | n_park++ << 10; }
      else if (*s == 'A') { ops[n++] = OP_A | a << 2 | flags[a]; when += 32; }
      else if (*s == 'G') { given = a; if (helpers) req[n_req++] = {1000, t, 0, -a}; }
      else if (*s == 'O') {
        ops[n] = OP_O | a << 2 | (s[2] - '0') << 5;
        if (given) ops[n] = helpers ? ops[n] | F_LD | F_PARK | (MAX_PARK - 1) << 10 : ops[n] & ~(7u << 2);
        if (last_o >= 0) { ops[last_o] |= F_ST; ops[n] |= F_LD; }
        last_o = n++;
        when += 10 * (s[2] - s[1]);
      }
    }
    for (int i = n; i < MAX_OPS; i++) ops[i] = OP_END;
    annotate(ops, n, false);
  }
  for (int i = 1; i < n_req; i++)
    for (int j = i; j > 0 && req[j].when < req[j - 1].when; j--) { Req r = req[j]; req[j] = req[j - 1]; req[j - 1] = r; }
  for (int h = 0; h < N_HELP; h++) {
    uint32_t* ops = P.ops[N_TEAM + 2 * h];
    int n = 0;
    for (int i = 0; i < n_req; i++)
      for (int m = h; m < 4; m += N_HELP) {
        const uint32_t ro = 4 * req[i].team + m;
        ops[n++] = req[i].slot >= 0 ? OP_Q | req[i].wave << 2 | req[i].team << 5 | F_PARK | req[i].slot << 10 | m << 12
                                    : OP_O | -req[i].slot << 5 | F_ST | (ro & 7) << 9 | (ro >> 3) << 29;
      }
    for (int i = n; i < 2 * MAX_OPS; i++) ops[i] = OP_END;
    annotate(ops, n, true);
  }
  for (int i = 0; i < 32; i++) P.first[i] = i < N_TEAM ? P.ops[i][0] : i < N_TEAM + N_HELP ? P.ops[2 * i - N_TEAM][0] : 0;
}

const char* const kPrograms[N_TEAM] = {
  "Q0A0Q1A1H2A2O03Q3A3Q4A4Q5A5Q6A6Q7A7O38",
  "Q0A0Q1A1Q2A2Q3A3O04Q4A4Q5A5Q6A6H7A7O48",
  "Q0A0H1A1Q2A2Q3A3Q4A4O05Q5A5Q6A6Q7A7O58",
  "Q0A0Q1A1Q2A2O03Q3A3Q4A4Q5A5Q6A6H7A7O38",
  "Q0A0Q1A1Q2A2O03Q3A3H4A4Q5A5Q6A6Q7A7O38",
  "Q0A0Q1A1H2A2Q3A3Q4A4O05Q5A5Q6A6Q7A7O58",
  "Q0A0Q1A1Q2A2Q3A3O03Q4A4H5A5Q6A6Q7A7O38",
  "Q0A0Q1A1Q2A2Q3A3Q4A4O05Q5A5Q6A6H7A7O58",
  "P3Q0A0Q1A1Q2A2A3H4A4Q5A5Q6A6Q7A7O08",
  "P5P7Q0A0Q1A1Q2A2H3A3Q4A4A5Q6A6A7G1O18",
  "Q0A0Q1A1Q2A2O02Q3A3H4A4Q5A5Q6A6Q7A7O28",
  "P3P5Q0A0Q1A1Q2A2A3Q4A4A5Q6A6H7A7O08",
  "Q0A0Q1A1Q2A2O02Q3A3Q4A4H5A5Q6A6Q7A7O28",
  "P7Q0A0Q1A1Q2A2Q3A3Q4A4Q5A5Q6A6A7G1O18",
  "P5Q0A0Q1A1Q2A2Q3A3Q4A4A5Q6A6H7A7O08",
  "Q0A0Q1A1Q2A2H3A3Q4A4Q5A5Q6A6Q7A7O08",
};

const char* const* bench_programs() {
  return kPrograms;
}

}

extern "C" void kernel_launch(void* const* d_in, const int* in_sizes, int n_in, void* d_out, int out_size) {
  (void)in_sizes; (void)n_in; (void)out_size;
  static EncodeFn fn = nullptr;
  static int n_clusters = 0;
  if (!fn) {
    cudaDriverEntryPointQueryResult qr;
    void* f = nullptr;
    cudaGetDriverEntryPoint("cuTensorMapEncodeTiled", &f, cudaEnableDefault, &qr);
    fn = (EncodeFn)f;
    cudaFuncSetAttribute(fused_kernel, cudaFuncAttributeMaxDynamicSharedMemorySize, SMEM_BYTES);
    cudaLaunchConfig_t cfg = {};
    cfg.gridDim = dim3(132); cfg.blockDim = dim3(384); cfg.dynamicSmemBytes = SMEM_BYTES;
    cudaLaunchAttribute at[1];
    at[0].id = cudaLaunchAttributeClusterDimension; at[0].val.clusterDim.x = 2; at[0].val.clusterDim.y = 1; at[0].val.clusterDim.z = 1;
    cfg.attrs = at; cfg.numAttrs = 1;
    if (cudaOccupancyMaxActiveClusters(&n_clusters, fused_kernel, &cfg) != cudaSuccess || n_clusters < 1) n_clusters = 1;
    (void)cudaGetLastError();
  }
  Params P;
  const CUtensorMapSwizzle S128 = CU_TENSOR_MAP_SWIZZLE_128B, S64 = CU_TENSOR_MAP_SWIZZLE_64B;
  for (int blk = 0; blk < 2; blk++) {
    void* const* in = d_in + 5 * blk;
    { const cuuint64_t d[] = {kD, kB * kSq}, s[] = {kD * 2}; const cuuint32_t b[] = {64, 128};
      encode(fn, &P.x[blk], in[0], 2, d, s, b, S128); }
    { const cuuint64_t d[] = {64, 8, 3, (cuuint64_t)kB * kH * kSk / 8}, s[] = {kDh * 2, 128, 8 * kDh * 2}; const cuuint32_t b[] = {64, 8, 3, 4};
      encode(fn, &P.k[blk], in[1], 4, d, s, b, S128);
      encode(fn, &P.v[blk], in[2], 4, d, s, b, S128); }
    { const cuuint64_t d[] = {64, kD, kHD / 64}, s[] = {kHD * 2, 128}; const cuuint32_t b[] = {64, 32, 3};
      encode(fn, &P.wq[blk], in[3], 3, d, s, b, S128); }
    { const cuuint64_t d[] = {32, 2, kHD / 8, 4, kD / 32}, s[] = {kD * 2, 8 * kD * 2, 2 * kD * 2, 64}; const cuuint32_t b[] = {32, 2, 4, 4, 5};
      encode(fn, &P.wo[blk], in[4], 5, d, s, b, S64); }
  }
  { const cuuint64_t d[] = {32, kB * kSq, 2 * kD / 32}, s[] = {2 * kD * 2, 64}; const cuuint32_t b[] = {32, 16, 5};
    encode(fn, &P.out, d_out, 3, d, s, b, S64); }

  P.zero = 0;
  P.dbg = 0x30;
  if (n_clusters >= N_CL) {
    const bool helpers = n_clusters >= N_CL + N_HELP;
    compile_programs(bench_programs(), helpers, P);
    fused_kernel<<<2 * (N_CL + (helpers ? N_HELP : 0)), 384, SMEM_BYTES>>>(P);
  } else {
    for (int phase = 0; phase < 2; phase++) {
      const char* text[N_TEAM];
      for (int t = 0; t < N_TEAM; t++) text[t] = phase ? "O08" : "Q0A0Q1A1Q2A2Q3A3Q4A4Q5A5Q6A6Q7A7";
      compile_programs(text, false, P);
      fused_kernel<<<2 * N_CL, 384, SMEM_BYTES>>>(P);
    }
  }
}
```

```cpp
#include <cuda_runtime.h>
#include <cuda_bf16.h>
#include <cuda.h>
#include <stdint.h>
#include <stdio.h>

namespace {

constexpr int kB = 8, kSq = 256, kD = 640, kH = 32, kSk = 1024, kDh = 192;
constexpr int kHD = kH * kDh;
constexpr uint32_t RING = 224 * 1024;
constexpr uint32_t SZ_KV = 24576;
constexpr uint32_t SZ_WQ = 24576, SZ_WO = 20480, SZ_A = 16384;
constexpr uint32_t SZ_OUT = 40960;
constexpr uint32_t SZ_PARK = 24576;
constexpr uint32_t SZ_PART = 16384;
constexpr int NBAR = 16, NFLIGHT = 12;
constexpr int KV_TRANSIT = 4;
constexpr int EARLY = 3;
constexpr int S1A = 7;
constexpr uint32_t KV_CH = 64, KV_SBO = 3072;
constexpr int SMEM_BYTES = RING + 512 + 1024;
constexpr int N_TEAM = 16, N_CL = 64, N_HELP = 2, MAX_OPS = 24, MAX_PARK = 4;
enum { OP_END = 0, OP_Q = 1, OP_A = 2, OP_O = 3, F_PARK = 1 << 9, F_LD = 1 << 12, F_ST = 1 << 13, F_HELP = 1 << 12 };

struct alignas(64) Params {
  uint32_t first[32];
  CUtensorMap x[2], wq[2], k[2], v[2], wo[2], out;
  uint32_t ops[N_TEAM + 2 * N_HELP][MAX_OPS];
  uint32_t zero;
};

__device__ uint4 g_o[N_TEAM * 2 * 96 * 1024];
__device__ uint4 g_part[N_CL * 2 * 5 * 1024];
__device__ unsigned int g_done[N_TEAM * 2 * 8];
__device__ unsigned int g_help[N_CL * 2 * MAX_PARK];
__device__ unsigned int g_seen[N_TEAM * 2 * 8];

template <int TB>
__device__ __forceinline__ void wgmma_rs_n64(float (&d)[32], uint32_t a0, uint32_t a1, uint32_t a2, uint32_t a3, uint64_t db, int scale_d) {
  asm volatile("{\n.reg .pred p;\nsetp.ne.b32 p, %37, 0;\n"
    "wgmma.mma_async.sync.aligned.m64n64k16.f32.bf16.bf16 {%0, %1, %2, %3, %4, %5, %6, %7, %8, %9, %10, %11, %12, %13, %14, %15, %16, %17, %18, %19, %20, %21, %22, %23, %24, %25, %26, %27, %28, %29, %30, %31}, {%32, %33, %34, %35}, %36, p, 1, 1, %38;\n}\n"
    : "+f"(d[0]), "+f"(d[1]), "+f"(d[2]), "+f"(d[3]), "+f"(d[4]), "+f"(d[5]), "+f"(d[6]), "+f"(d[7]), "+f"(d[8]), "+f"(d[9]), "+f"(d[10]), "+f"(d[11]), "+f"(d[12]), "+f"(d[13]), "+f"(d[14]), "+f"(d[15]), "+f"(d[16]), "+f"(d[17]), "+f"(d[18]), "+f"(d[19]), "+f"(d[20]), "+f"(d[21]), "+f"(d[22]), "+f"(d[23]), "+f"(d[24]), "+f"(d[25]), "+f"(d[26]), "+f"(d[27]), "+f"(d[28]), "+f"(d[29]), "+f"(d[30]), "+f"(d[31])
    : "r"(a0), "r"(a1), "r"(a2), "r"(a3), "l"(db), "r"(scale_d), "n"(TB));
}
template <int TB, int TA = 0>
__device__ __forceinline__ void wgmma_ss_n160(float (&d)[80], uint64_t da, uint64_t db, int scale_d) {
  asm volatile("{\n.reg .pred p;\nsetp.ne.b32 p, %82, 0;\n"
    "wgmma.mma_async.sync.aligned.m64n160k16.f32.bf16.bf16 {%0, %1, %2, %3, %4, %5, %6, %7, %8, %9, %10, %11, %12, %13, %14, %15, %16, %17, %18, %19, %20, %21, %22, %23, %24, %25, %26, %27, %28, %29, %30, %31, %32, %33, %34, %35, %36, %37, %38, %39, %40, %41, %42, %43, %44, %45, %46, %47, %48, %49, %50, %51, %52, %53, %54, %55, %56, %57, %58, %59, %60, %61, %62, %63, %64, %65, %66, %67, %68, %69, %70, %71, %72, %73, %74, %75, %76, %77, %78, %79}, %80, %81, p, 1, 1, %83, %84;\n}\n"
    : "+f"(d[0]), "+f"(d[1]), "+f"(d[2]), "+f"(d[3]), "+f"(d[4]), "+f"(d[5]), "+f"(d[6]), "+f"(d[7]), "+f"(d[8]), "+f"(d[9]), "+f"(d[10]), "+f"(d[11]), "+f"(d[12]), "+f"(d[13]), "+f"(d[14]), "+f"(d[15]), "+f"(d[16]), "+f"(d[17]), "+f"(d[18]), "+f"(d[19]), "+f"(d[20]), "+f"(d[21]), "+f"(d[22]), "+f"(d[23]), "+f"(d[24]), "+f"(d[25]), "+f"(d[26]), "+f"(d[27]), "+f"(d[28]), "+f"(d[29]), "+f"(d[30]), "+f"(d[31]), "+f"(d[32]), "+f"(d[33]), "+f"(d[34]), "+f"(d[35]), "+f"(d[36]), "+f"(d[37]), "+f"(d[38]), "+f"(d[39]), "+f"(d[40]), "+f"(d[41]), "+f"(d[42]), "+f"(d[43]), "+f"(d[44]), "+f"(d[45]), "+f"(d[46]), "+f"(d[47]), "+f"(d[48]), "+f"(d[49]), "+f"(d[50]), "+f"(d[51]), "+f"(d[52]), "+f"(d[53]), "+f"(d[54]), "+f"(d[55]), "+f"(d[56]), "+f"(d[57]), "+f"(d[58]), "+f"(d[59]), "+f"(d[60]), "+f"(d[61]), "+f"(d[62]), "+f"(d[63]), "+f"(d[64]), "+f"(d[65]), "+f"(d[66]), "+f"(d[67]), "+f"(d[68]), "+f"(d[69]), "+f"(d[70]), "+f"(d[71]), "+f"(d[72]), "+f"(d[73]), "+f"(d[74]), "+f"(d[75]), "+f"(d[76]), "+f"(d[77]), "+f"(d[78]), "+f"(d[79])
    : "l"(da), "l"(db), "r"(scale_d), "n"(TA), "n"(TB));
}
template <int TB, int TA = 0>
__device__ __forceinline__ void wgmma_ss_n192(float (&d)[96], uint64_t da, uint64_t db, int scale_d) {
  asm volatile("{\n.reg .pred p;\nsetp.ne.b32 p, %98, 0;\n"
    "wgmma.mma_async.sync.aligned.m64n192k16.f32.bf16.bf16 {%0, %1, %2, %3, %4, %5, %6, %7, %8, %9, %10, %11, %12, %13, %14, %15, %16, %17, %18, %19, %20, %21, %22, %23, %24, %25, %26, %27, %28, %29, %30, %31, %32, %33, %34, %35, %36, %37, %38, %39, %40, %41, %42, %43, %44, %45, %46, %47, %48, %49, %50, %51, %52, %53, %54, %55, %56, %57, %58, %59, %60, %61, %62, %63, %64, %65, %66, %67, %68, %69, %70, %71, %72, %73, %74, %75, %76, %77, %78, %79, %80, %81, %82, %83, %84, %85, %86, %87, %88, %89, %90, %91, %92, %93, %94, %95}, %96, %97, p, 1, 1, %99, %100;\n}\n"
    : "+f"(d[0]), "+f"(d[1]), "+f"(d[2]), "+f"(d[3]), "+f"(d[4]), "+f"(d[5]), "+f"(d[6]), "+f"(d[7]), "+f"(d[8]), "+f"(d[9]), "+f"(d[10]), "+f"(d[11]), "+f"(d[12]), "+f"(d[13]), "+f"(d[14]), "+f"(d[15]), "+f"(d[16]), "+f"(d[17]), "+f"(d[18]), "+f"(d[19]), "+f"(d[20]), "+f"(d[21]), "+f"(d[22]), "+f"(d[23]), "+f"(d[24]), "+f"(d[25]), "+f"(d[26]), "+f"(d[27]), "+f"(d[28]), "+f"(d[29]), "+f"(d[30]), "+f"(d[31]), "+f"(d[32]), "+f"(d[33]), "+f"(d[34]), "+f"(d[35]), "+f"(d[36]), "+f"(d[37]), "+f"(d[38]), "+f"(d[39]), "+f"(d[40]), "+f"(d[41]), "+f"(d[42]), "+f"(d[43]), "+f"(d[44]), "+f"(d[45]), "+f"(d[46]), "+f"(d[47]), "+f"(d[48]), "+f"(d[49]), "+f"(d[50]), "+f"(d[51]), "+f"(d[52]), "+f"(d[53]), "+f"(d[54]), "+f"(d[55]), "+f"(d[56]), "+f"(d[57]), "+f"(d[58]), "+f"(d[59]), "+f"(d[60]), "+f"(d[61]), "+f"(d[62]), "+f"(d[63]), "+f"(d[64]), "+f"(d[65]), "+f"(d[66]), "+f"(d[67]), "+f"(d[68]), "+f"(d[69]), "+f"(d[70]), "+f"(d[71]), "+f"(d[72]), "+f"(d[73]), "+f"(d[74]), "+f"(d[75]), "+f"(d[76]), "+f"(d[77]), "+f"(d[78]), "+f"(d[79]), "+f"(d[80]), "+f"(d[81]), "+f"(d[82]), "+f"(d[83]), "+f"(d[84]), "+f"(d[85]), "+f"(d[86]), "+f"(d[87]), "+f"(d[88]), "+f"(d[89]), "+f"(d[90]), "+f"(d[91]), "+f"(d[92]), "+f"(d[93]), "+f"(d[94]), "+f"(d[95])
    : "l"(da), "l"(db), "r"(scale_d), "n"(TA), "n"(TB));
}
template <int TB>
__device__ __forceinline__ void wgmma_rs_n192(float (&d)[96], uint32_t a0, uint32_t a1, uint32_t a2, uint32_t a3, uint64_t db, int scale_d) {
  asm volatile("{\n.reg .pred p;\nsetp.ne.b32 p, %101, 0;\n"
    "wgmma.mma_async.sync.aligned.m64n192k16.f32.bf16.bf16 {%0, %1, %2, %3, %4, %5, %6, %7, %8, %9, %10, %11, %12, %13, %14, %15, %16, %17, %18, %19, %20, %21, %22, %23, %24, %25, %26, %27, %28, %29, %30, %31, %32, %33, %34, %35, %36, %37, %38, %39, %40, %41, %42, %43, %44, %45, %46, %47, %48, %49, %50, %51, %52, %53, %54, %55, %56, %57, %58, %59, %60, %61, %62, %63, %64, %65, %66, %67, %68, %69, %70, %71, %72, %73, %74, %75, %76, %77, %78, %79, %80, %81, %82, %83, %84, %85, %86, %87, %88, %89, %90, %91, %92, %93, %94, %95}, {%96, %97, %98, %99}, %100, p, 1, 1, %102;\n}\n"
    : "+f"(d[0]), "+f"(d[1]), "+f"(d[2]), "+f"(d[3]), "+f"(d[4]), "+f"(d[5]), "+f"(d[6]), "+f"(d[7]), "+f"(d[8]), "+f"(d[9]), "+f"(d[10]), "+f"(d[11]), "+f"(d[12]), "+f"(d[13]), "+f"(d[14]), "+f"(d[15]), "+f"(d[16]), "+f"(d[17]), "+f"(d[18]), "+f"(d[19]), "+f"(d[20]), "+f"(d[21]), "+f"(d[22]), "+f"(d[23]), "+f"(d[24]), "+f"(d[25]), "+f"(d[26]), "+f"(d[27]), "+f"(d[28]), "+f"(d[29]), "+f"(d[30]), "+f"(d[31]), "+f"(d[32]), "+f"(d[33]), "+f"(d[34]), "+f"(d[35]), "+f"(d[36]), "+f"(d[37]), "+f"(d[38]), "+f"(d[39]), "+f"(d[40]), "+f"(d[41]), "+f"(d[42]), "+f"(d[43]), "+f"(d[44]), "+f"(d[45]), "+f"(d[46]), "+f"(d[47]), "+f"(d[48]), "+f"(d[49]), "+f"(d[50]), "+f"(d[51]), "+f"(d[52]), "+f"(d[53]), "+f"(d[54]), "+f"(d[55]), "+f"(d[56]), "+f"(d[57]), "+f"(d[58]), "+f"(d[59]), "+f"(d[60]), "+f"(d[61]), "+f"(d[62]), "+f"(d[63]), "+f"(d[64]), "+f"(d[65]), "+f"(d[66]), "+f"(d[67]), "+f"(d[68]), "+f"(d[69]), "+f"(d[70]), "+f"(d[71]), "+f"(d[72]), "+f"(d[73]), "+f"(d[74]), "+f"(d[75]), "+f"(d[76]), "+f"(d[77]), "+f"(d[78]), "+f"(d[79]), "+f"(d[80]), "+f"(d[81]), "+f"(d[82]), "+f"(d[83]), "+f"(d[84]), "+f"(d[85]), "+f"(d[86]), "+f"(d[87]), "+f"(d[88]), "+f"(d[89]), "+f"(d[90]), "+f"(d[91]), "+f"(d[92]), "+f"(d[93]), "+f"(d[94]), "+f"(d[95])
    : "r"(a0), "r"(a1), "r"(a2), "r"(a3), "l"(db), "r"(scale_d), "n"(TB));
}

__device__ __forceinline__ uint32_t smem_u32(const void* p) { return (uint32_t)__cvta_generic_to_shared(p); }
__device__ __forceinline__ void wg_fence() { asm volatile("wgmma.fence.sync.aligned;" ::: "memory"); }
__device__ __forceinline__ void wg_commit() { asm volatile("wgmma.commit_group.sync.aligned;" ::: "memory"); }
template <int N> __device__ __forceinline__ void wg_wait() { asm volatile("wgmma.wait_group.sync.aligned %0;" ::"n"(N) : "memory"); }
__device__ __forceinline__ void sched_fence(int& keep, uint32_t zero) {
  asm volatile("{\n.reg .u32 c;\nmov.u32 c, %%clock;\nand.b32 c, c, %1;\nxor.b32 %0, %0, c;\n}\n" : "+r"(keep) : "r"(zero) : "memory");
}
template <int N> __device__ __forceinline__ void fence_regs(float (&r)[N]) {
#pragma unroll
  for (int i = 0; i < N; i++) asm volatile("" : "+f"(r[i])::"memory");
}
template <int N> __device__ __forceinline__ void fence_regs(uint32_t (&r)[N]) {
#pragma unroll
  for (int i = 0; i < N; i++) asm volatile("" : "+r"(r[i])::"memory");
}
__device__ __forceinline__ uint64_t mk_desc(uint32_t a16, uint32_t lbo, uint32_t sbo, uint32_t swz, uint32_t off = 0) {
  uint64_t d;
  asm("mov.b64 %0, {%1, %2};" : "=l"(d) : "r"(a16), "r"((sbo >> 4) | (swz << 30)));
  return d + (off + ((lbo >> 4) << 16));
}
__device__ __forceinline__ void mbar_init(uint32_t bar, uint32_t cnt) {
  asm volatile("mbarrier.init.shared::cta.b64 [%0], %1;" ::"r"(bar), "r"(cnt) : "memory");
}
__device__ __forceinline__ void mbar_expect(uint32_t bar, uint32_t tx) {
  asm volatile("mbarrier.arrive.expect_tx.shared::cta.b64 _, [%0], %1;" ::"r"(bar), "r"(tx) : "memory");
}
__device__ __forceinline__ bool mbar_test(uint32_t bar, uint32_t ph) {
  uint32_t ok;
  asm volatile("{\n.reg .pred p;\nmbarrier.test_wait.parity.shared::cta.b64 p, [%1], %2;\nselp.u32 %0, 1, 0, p;\n}\n"
               : "=r"(ok) : "r"(bar), "r"(ph) : "memory");
  return ok;
}
__device__ __forceinline__ void mbar_wait(uint32_t bar, uint32_t ph) {
  asm volatile("{\n.reg .pred p;\n.reg .u32 n;\nmov.u32 n, 0;\n"
               "LOOP:\nadd.u32 n, n, 1;\nmbarrier.try_wait.parity.shared::cta.b64 p, [%0], %1;\n@p bra DONE;\n"
               "setp.lt.u32 p, n, 0x1000000;\n@p bra LOOP;\ntrap;\n"
               "DONE:\n}\n" ::"r"(bar), "r"(ph) : "memory");
}
template <int NS> __device__ __forceinline__ void mbar_wait_slow(uint32_t bar, uint32_t ph) {
  asm volatile("{\n.reg .pred p;\n.reg .u32 n;\nmov.u32 n, 0;\n"
               "LOOP:\nmbarrier.test_wait.parity.shared::cta.b64 p, [%0], %1;\n@p bra DONE;\n"
               "nanosleep.u32 %2;\nadd.u32 n, n, 1;\nsetp.lt.u32 p, n, 0x400000;\n@p bra LOOP;\ntrap;\n"
               "DONE:\n}\n" ::"r"(bar), "r"(ph), "n"(NS) : "memory");
}
__device__ __forceinline__ void mbar_arrive_cluster_if(bool on, uint32_t addr) {
  asm volatile("{\n.reg .pred p;\nsetp.ne.b32 p, %1, 0;\n@p mbarrier.arrive.shared::cluster.b64 _, [%0];\n}\n" ::"r"(addr), "r"((int)on) : "memory");
}
__device__ __forceinline__ void mbar_arrive_if(bool on, uint32_t addr) {
  asm volatile("{\n.reg .pred p;\nsetp.ne.b32 p, %1, 0;\n@p mbarrier.arrive.shared::cta.b64 _, [%0];\n}\n" ::"r"(addr), "r"((int)on) : "memory");
}
__device__ __forceinline__ void tma2d(uint32_t dst, const CUtensorMap* m, uint32_t bar, int c0, int c1) {
  asm volatile("cp.async.bulk.tensor.2d.shared::cluster.global.mbarrier::complete_tx::bytes [%0], [%1, {%3, %4}], [%2];"
               ::"r"(dst), "l"(m), "r"(bar), "r"(c0), "r"(c1) : "memory");
}
__device__ __forceinline__ void tma3d(uint32_t dst, const CUtensorMap* m, uint32_t bar, int c0, int c1, int c2) {
  asm volatile("cp.async.bulk.tensor.3d.shared::cluster.global.mbarrier::complete_tx::bytes [%0], [%1, {%3, %4, %5}], [%2];"
               ::"r"(dst), "l"(m), "r"(bar), "r"(c0), "r"(c1), "r"(c2) : "memory");
}
__device__ __forceinline__ void tma3d_mc(uint32_t dst, const CUtensorMap* m, uint32_t bar, int c0, int c1, int c2) {
  asm volatile("cp.async.bulk.tensor.3d.shared::cluster.global.mbarrier::complete_tx::bytes.multicast::cluster"
               " [%0], [%1, {%3, %4, %5}], [%2], %6;"
               ::"r"(dst), "l"(m), "r"(bar), "r"(c0), "r"(c1), "r"(c2), "h"((uint16_t)3) : "memory");
}
__device__ __forceinline__ void tma3d_store(const CUtensorMap* m, uint32_t src, int c0, int c1, int c2) {
  asm volatile("cp.async.bulk.tensor.3d.global.shared::cta.bulk_group [%0, {%2, %3, %4}], [%1];"
               ::"l"(m), "r"(src), "r"(c0), "r"(c1), "r"(c2) : "memory");
}
__device__ __forceinline__ void bar_sync(int id, int n) { asm volatile("bar.sync %0, %1;" ::"r"(id), "r"(n) : "memory"); }
__device__ __forceinline__ uint32_t pack_bf16(float lo, float hi) {
  uint32_t r;
  asm("cvt.rn.bf16x2.f32 %0, %1, %2;" : "=r"(r) : "f"(hi), "f"(lo));
  return r;
}
__device__ __forceinline__ float ex2(float x) {
  float y;
  asm("ex2.approx.ftz.f32 %0, %1;" : "=f"(y) : "f"(x));
  return y;
}
__device__ __forceinline__ float fadd(float a, float b) {
  float y;
  asm("add.f32 %0, %1, %2;" : "=f"(y) : "f"(a), "f"(b));
  return y;
}
__device__ __forceinline__ float rcp(float x) {
  float y;
  asm("rcp.approx.ftz.f32 %0, %1;" : "=f"(y) : "f"(x));
  return y;
}
__device__ __forceinline__ void stsm4(uint32_t addr, uint32_t a, uint32_t b, uint32_t c, uint32_t d) {
  asm volatile("stmatrix.sync.aligned.m8n8.x4.shared.b16 [%0], {%1, %2, %3, %4};" ::"r"(addr), "r"(a), "r"(b), "r"(c), "r"(d) : "memory");
}

__device__ __forceinline__ void tma4d_mc_hint(uint32_t dst, const CUtensorMap* m, uint32_t bar, int c3, uint64_t pol) {
  asm volatile("cp.async.bulk.tensor.4d.shared::cluster.global.mbarrier::complete_tx::bytes.multicast::cluster.L2::cache_hint"
               " [%0], [%1, {%3, %3, %3, %4}], [%2], %5, %6;"
               ::"r"(dst), "l"(m), "r"(bar), "r"(0), "r"(c3), "h"((uint16_t)3), "l"(pol) : "memory");
}
__device__ __forceinline__ void tma5d_mc(uint32_t dst, const CUtensorMap* m, uint32_t bar, int c2, int c4) {
  asm volatile("cp.async.bulk.tensor.5d.shared::cluster.global.mbarrier::complete_tx::bytes.multicast::cluster"
               " [%0], [%1, {%3, %3, %4, %3, %5}], [%2], %6;"
               ::"r"(dst), "l"(m), "r"(bar), "r"(0), "r"(c2), "r"(c4), "h"((uint16_t)3) : "memory");
}
__device__ __forceinline__ void bulk_load_hint(uint32_t dst, const void* src, uint32_t bytes, uint32_t bar, uint64_t pol) {
  asm volatile("cp.async.bulk.shared::cluster.global.mbarrier::complete_tx::bytes.L2::cache_hint [%0], [%1], %2, [%3], %4;"
               ::"r"(dst), "l"(src), "r"(bytes), "r"(bar), "l"(pol) : "memory");
}
__device__ __forceinline__ void stg2_if(bool on, void* p, uint32_t a, uint32_t b, uint32_t c, uint32_t d, uint32_t e, uint32_t f,
                                        uint32_t g, uint32_t h, uint64_t pol) {
  asm volatile("{\n.reg .pred p;\nsetp.ne.b32 p, %10, 0;\n"
               "@p st.global.L2::cache_hint.v4.b32 [%0], {%1, %2, %3, %4}, %9;\n"
               "@p st.global.L2::cache_hint.v4.b32 [%0 + 512], {%5, %6, %7, %8}, %9;\n}\n"
               ::"l"(p), "r"(a), "r"(b), "r"(c), "r"(d), "r"(e), "r"(f), "r"(g), "r"(h), "l"(pol), "r"((int)on) : "memory");
}
__device__ __forceinline__ uint64_t evict_first() {
  uint64_t p;
  asm("createpolicy.fractional.L2::evict_first.b64 %0, 1.0;" : "=l"(p));
  return p;
}
__device__ __forceinline__ bool elect() {
  uint32_t ok;
  asm volatile("{\n.reg .pred p;\nelect.sync _|p, 0xffffffff;\nselp.u32 %0, 1, 0, p;\n}\n" : "=r"(ok));
  return ok;
}
__device__ __forceinline__ void mbar_arrive(uint32_t bar) {
  asm volatile("mbarrier.arrive.shared::cta.b64 _, [%0];" ::"r"(bar) : "memory");
}
__device__ __forceinline__ void lds128(uint32_t p, uint32_t& a, uint32_t& b, uint32_t& c, uint32_t& d) {
  asm volatile("ld.shared.v4.b32 {%0, %1, %2, %3}, [%4];" : "=r"(a), "=r"(b), "=r"(c), "=r"(d) : "r"(p) : "memory");
}
__device__ __forceinline__ void wait_count(const unsigned int* p, uint32_t target) {
  asm volatile("{\n.reg .pred p;\n.reg .u32 n, v;\nmov.u32 n, 0;\n"
               "LOOP:\nld.acquire.gpu.global.u32 v, [%0];\nsetp.ge.u32 p, v, %1;\n@p bra DONE;\n"
               "nanosleep.u32 %2;\nadd.u32 n, n, 1;\nsetp.lt.u32 p, n, 0x400000;\n@p bra LOOP;\ntrap;\n"
               "DONE:\n}\n" ::"l"(p), "r"(target), "n"(200) : "memory");
}

__device__ __forceinline__ int o_wave(int a, int b, int i) {
  const int p = min(3, b - a - 1);
  return i < p ? b - 2 - i : i == p ? b - 1 : b - 1 - i;
}

struct Cursor {
  uint32_t n;
  __device__ __forceinline__ uint32_t off() const { return n & (8 * NBAR - 8); }
  __device__ __forceinline__ uint32_t ph() const { return (n / (8 * NBAR)) & 1; }
  __device__ __forceinline__ void next() { n += 8; }
};

constexpr float kScaleLog2 = 0.07216878364870322f * 1.4426950408889634f;
constexpr float kSumLimit = 1048576.0f;
constexpr float kMaxLag = 8.0f;

__global__ void __cluster_dims__(2, 1, 1) __launch_bounds__(384, 1)
fused_kernel(const __grid_constant__ Params P) {
  extern __shared__ uint8_t smem_raw[];
  const uint32_t sbase = (smem_u32(smem_raw) + 1023) & ~1023u;
  const uint32_t full0 = sbase + RING, empty0 = full0 + 8 * NBAR, odone = empty0 + 8 * NBAR, oready0 = odone + 8;
  const uint32_t fenced = oready0 + 64, hready0 = fenced + 8;
  const uint32_t rank = blockIdx.x & 1;
  const int role = blockIdx.x >> 1;
  const bool helper = role >= N_CL;
  const int team = helper ? 0 : role >> 2, nt = role & 3, blk = team >> 3;
  const uint32_t* prog = P.ops[helper ? N_TEAM + 2 * (role - N_CL) : team];
  auto q_role = [&](uint32_t op) { return helper ? (int)(((op >> 3) & 60) | ((op >> 12) & 3)) : role; };
  auto o_role = [&](uint32_t op) { return helper ? (int)(((op >> 26) & 56) | ((op >> 9) & 7)) : role; };
  const int wid = __shfl_sync(0xffffffffu, (int)(threadIdx.x >> 5), 0);
  const int wg = wid >> 2;

  const uint32_t op0 = P.first[helper ? N_TEAM + role - N_CL : team];
  if (__builtin_expect(wid == 8, 1)) {
    if (elect()) {
#pragma unroll
      for (int k = 0; k < EARLY; k++) mbar_init(full0 + 8 * k, 1);
      asm volatile("fence.mbarrier_init.release.cluster;" ::: "memory");
      if ((op0 & 3) == OP_Q) {
        const int qr = q_role(op0);
#pragma unroll
        for (int k = 0; k < EARLY; k++) {
          mbar_expect(full0 + 8 * k, SZ_WQ + SZ_A);
          tma2d(sbase + k * (SZ_WQ + SZ_A) + SZ_WQ, &P.x[qr >> 5], full0 + 8 * k, 64 * k, ((qr >> 2) & 7) * kSq + rank * 128);
          tma3d(sbase + k * (SZ_WQ + SZ_A), &P.wq[qr >> 5], full0 + 8 * k, 0, 64 * k, 3 * (4 * ((op0 >> 2) & 7) + (qr & 3)));
          tma3d(sbase + k * (SZ_WQ + SZ_A) + SZ_WQ / 2, &P.wq[qr >> 5], full0 + 8 * k, 0, 64 * k + 32, 3 * (4 * ((op0 >> 2) & 7) + (qr & 3)));
        }
      }
      asm volatile("prefetch.tensormap [%0];" ::"l"(&P.k[blk]) : "memory");
      asm volatile("prefetch.tensormap [%0];" ::"l"(&P.v[blk]) : "memory");
    }
  } else if (threadIdx.x == 0) {
#pragma unroll
    for (int i = EARLY; i < 2 * NBAR + 10 + MAX_PARK; i++) mbar_init(full0 + 8 * i, i >= NBAR && i <= 2 * NBAR ? 16 : 1);
    asm volatile("fence.mbarrier_init.release.cluster;" ::: "memory");
  }
  __syncwarp();
  asm volatile("barrier.cluster.arrive.relaxed.aligned;\nbarrier.cluster.wait.aligned;" ::: "memory");

  if (wg == 2) {
    asm volatile("setmaxnreg.dec.sync.aligned.u32 24;");
    if (wid == 8) {
      Cursor tail{0}, head{0};
      int sh = 0;
      uint32_t cur = 0, used = 0;
      uint64_t fifo = 0;
      uint32_t dst, bar, oready = oready0;
      const uint64_t pol = evict_first();
      auto acquire = [&](uint32_t bytes, int part = 0) {
        uint32_t fp = bytes >> 12;
        if (cur + fp > (RING >> 12)) { fp += (RING >> 12) - cur; cur = 0; }
        used += fp;
        bool more = false;
        uint32_t wbar, wph;
        while (used > (RING >> 12) || (part != 2 && sh == 5 * NFLIGHT)) {
          if (more) mbar_wait(wbar, wph);
          more = true;
          wbar = empty0 + tail.off(); wph = tail.ph();
          tail.next();
          used -= (uint32_t)fifo & 31;
          fifo >>= 5;
          sh -= 5;
        }
        fifo += (uint64_t)fp << sh;
        dst = sbase + (cur << 12);
        bar = full0 + head.off();
        cur += bytes >> 12;
        if (part != 1) {
          sh += 5;
          head.next();
        }
        if (more) mbar_wait(wbar, wph);
      };
      auto scratch = [&](const uint4* src, uint32_t bytes, int n) {
        asm volatile("fence.proxy.async.global;" ::: "memory");
#pragma unroll 1
        for (int i = 0; i < n; i++) {
          acquire(bytes);
          if (elect()) {
            bulk_load_hint(dst, src + i * (bytes / 16), bytes, bar, pol);
            mbar_expect(bar, bytes);
          }
        }
      };
      for (int pc = 0;; pc++) {
        const uint32_t op = prog[pc];
        const int type = op & 3, a = (op >> 2) & 7;
        if (type == OP_END) break;
        if (type == OP_Q) {
          const int qr = q_role(op);
#pragma unroll 1
          for (int k = 0; k < 10; k++) {
            acquire(SZ_WQ, 1);
            if ((pc > 0 || k >= EARLY) && elect()) tma3d_mc(dst + rank * (SZ_WQ / 2), &P.wq[qr >> 5], bar, 0, 64 * k + 32 * rank, 3 * (4 * a + (qr & 3)));
            acquire(SZ_A, 2);
            if ((pc > 0 || k >= EARLY) && elect()) {
              tma2d(dst, &P.x[qr >> 5], bar, 64 * k, ((qr >> 2) & 7) * kSq + rank * 128);
              mbar_expect(bar, SZ_WQ + SZ_A);
            }
          }
        } else if (type == OP_A) {
          const uint32_t nop = prog[pc + 1];
#pragma unroll 1
          for (int t = (op & F_PARK) ? 1 : 0; t < 33; t++) {
            int wave = a;
            if (t == 31 && (nop & 3) != OP_A) t++;
            if (t == 31) {
              wave = (nop >> 2) & 7;
              mbar_wait((nop & F_HELP) ? hready0 + 8 * ((nop >> 10) & 3) : fenced, 0);
              scratch(&g_o[((team * 2 + rank) * 96 + 3 * (4 * wave + nt)) * 1024], SZ_PARK, 2);
            }
            const int isv = t ? ~t & 1 : 0, j = (isv ? (t - 1) >> 1 : (t + 1) >> 1) & 15;
            const int row0 = ((team & 7) * kH + 4 * wave + nt) * kSk;
            acquire(SZ_KV);
            if (t >= KV_TRANSIT) {
              const Cursor c{head.n - 8 * (KV_TRANSIT + 1)};
              mbar_wait(full0 + c.off(), c.ph());
            }
            if (elect()) {
              tma4d_mc_hint(dst + rank * (SZ_KV / 2), isv ? &P.v[blk] : &P.k[blk], bar, row0 / 8 + 8 * j + 4 * rank, pol);
              mbar_expect(bar, SZ_KV);
            }
          }
        } else {
          const int b = (op >> 5) & 15, ro = o_role(op);
#pragma unroll 1
          for (int i = 0; i < b - a; i++) {
            const int w = o_wave(a, b, i);
            mbar_wait(oready, 0);
            oready += 8;
            asm volatile("fence.proxy.async.global;" ::: "memory");
#pragma unroll 1
            for (int k = 12 * w; k < 12 * w + 12; k++) {
              acquire(SZ_A, 1);
              if (elect()) bulk_load_hint(dst, &g_o[(((ro >> 2) * 2 + rank) * 96 + k) * 1024], SZ_A, bar, pol);
              acquire(SZ_WO, 2);
              if (elect()) {
                tma5d_mc(dst + rank * 10240, &P.wo[ro >> 5], bar, 8 * k + 4 * rank, 5 * (ro & 3));
                mbar_expect(bar, SZ_WO + SZ_A);
              }
            }
          }
          if (op & F_LD) {
            if (op & F_PARK) mbar_wait(hready0 + 8 * (MAX_PARK - 1), 0);
            scratch(&g_part[(role * 2 + rank) * 5120], SZ_PART, 5);
          }
          if (!(op & F_ST)) {
            acquire(SZ_OUT);
            if (elect()) mbar_arrive(bar);
            __syncwarp();
            sh -= 5;
          }
        }
      }
      for (; sh > 0; sh -= 5) {
        mbar_wait(empty0 + tail.off(), tail.ph());
        tail.next();
      }
    } else if (threadIdx.x == 288) {
      uint32_t ph = 0;
      bool first = true;
      for (int pc = 0;; pc++) {
        const uint32_t op = prog[pc];
        if ((op & 3) == OP_END) break;
        if ((op & 3) != OP_A && !helper) continue;
        mbar_wait_slow<400>(odone, ph);
        ph ^= 1;
        unsigned int* flag = !helper ? &g_done[(team * 2 + rank) * 8 + ((op >> 2) & 7)]
                             : (op & 3) == OP_Q ? &g_help[(q_role(op) * 2 + rank) * MAX_PARK + ((op >> 10) & 3)]
                                                : &g_help[(o_role(op) * 2 + rank) * MAX_PARK + MAX_PARK - 1];
        asm volatile("red.release.gpu.global.add.u32 [%0], 1;" ::"l"(flag) : "memory");
        if (first) mbar_arrive(fenced);
        first = false;
      }
    } else if (threadIdx.x == 320) {
      uint32_t oready = oready0;
      for (int pc = 0;; pc++) {
        const uint32_t op = prog[pc];
        if ((op & 3) == OP_END) break;
        if ((op & 3) == OP_O) {
          const int a = (op >> 2) & 7, b = (op >> 5) & 15;
#pragma unroll 1
          for (int i = 0; i < b - a; i++) {
            const int ci = ((o_role(op) >> 2) * 2 + rank) * 8 + o_wave(a, b, i);
            wait_count(&g_done[ci], 4);
            mbar_arrive(oready);
            oready += 8;
            if (atomicAdd(&g_seen[ci], 1u) == 3u) { g_seen[ci] = 0; g_done[ci] = 0; }
          }
        }
        if ((op & 3) != OP_Q && (op & F_HELP) && (op & F_PARK)) {
          unsigned int* flag = &g_help[(role * 2 + rank) * MAX_PARK + ((op >> 10) & 3)];
          wait_count(flag, 1);
          mbar_arrive(hready0 + 8 * ((op >> 10) & 3));
          *flag = 0;
        }
      }
    }
  } else {
    asm volatile("setmaxnreg.inc.sync.aligned.u32 240;");
    const int lane = threadIdx.x & 31, warp = wid & 3;
    uint32_t empty_rem;
    asm volatile("mapa.shared::cluster.u32 %0, %1, %2;" : "=r"(empty_rem) : "r"(empty0), "r"(lane & 1));
    auto release = [&](int slot) { mbar_arrive_cluster_if(lane < 2, empty_rem + slot); };
    Cursor r{0};
    const uint32_t ring16 = (sbase & 0x3FFFF) >> 4;
    uint32_t cur = ring16;
    bool rdy0 = false, rdy1 = false;
    auto probe1 = [&]() { rdy0 = mbar_test(full0 + r.off(), r.ph()); };
    auto probe2 = [&]() {
      Cursor n = r;
      rdy0 = mbar_test(full0 + n.off(), n.ph());
      n.next();
      rdy1 = mbar_test(full0 + n.off(), n.ph());
    };
    auto take = [&](bool rdy, uint32_t bytes, uint32_t& addr) {
      const int bi = r.off();
      if (!__all_sync(0xffffffffu, rdy)) mbar_wait(full0 + r.off(), r.ph());
      r.next();
      if (cur > ring16 + ((RING - bytes) >> 4)) cur = ring16;
      addr = cur;
      cur += bytes >> 4;
      return bi;
    };
    auto second = [&](uint32_t bytes) {
      if (cur > ring16 + ((RING - bytes) >> 4)) cur = ring16;
      cur += bytes >> 4;
      return cur - (bytes >> 4);
    };
    const int row = wg * 64 + warp * 16 + (lane >> 2);
    int img0 = row * 4 + ((lane & 3) ^ ((row >> 1) & 3));
    uint4* pend = nullptr;
    const uint64_t spol = evict_first();
    int pc = 0;
    uint32_t op = prog[0];
    auto enter = [&]() {
      r.n = op >> 12; cur = ring16 + (((op >> 20) & 63) << 8);
    };
    auto drain = [&](uint32_t (&t)[48], uint32_t c) {
      if (!(op & (3u << 26)) || c >= 6) return;
#pragma unroll
      for (int i = 0; i < 6; i++)
        stg2_if(c == i, pend + i * 512, t[8 * i], t[8 * i + 1], t[8 * i + 2], t[8 * i + 3],
                t[8 * i + 4], t[8 * i + 5], t[8 * i + 6], t[8 * i + 7], spol);
      if ((op & (1u << 26)) && c == 5) {
        __syncwarp();
        mbar_arrive_if(lane < 2, odone);
      }
    };
    float s[32], o[96], c[80];
    uint32_t q[48], pa[16], pb[16];
    float mc0, mc1, l0, l1;
    bool gen;
    auto soft = [&](float (&s)[32], uint32_t (&pout)[16], bool first) {
      if (first) { gen = false; mc0 = 0.f; mc1 = 0.f; }
      float b0, b1;
      for (;;) {
        if (gen) {
          float m0 = fmaxf(s[0], s[1]), m1 = fmaxf(s[2], s[3]);
#pragma unroll
          for (int i = 1; i < 8; i++) { m0 = fmaxf(m0, fmaxf(s[4 * i], s[4 * i + 1])); m1 = fmaxf(m1, fmaxf(s[4 * i + 2], s[4 * i + 3])); }
          m0 = fmaxf(m0, __shfl_xor_sync(0xffffffffu, m0, 1)); m1 = fmaxf(m1, __shfl_xor_sync(0xffffffffu, m1, 1));
          m0 = fmaxf(m0, __shfl_xor_sync(0xffffffffu, m0, 2)); m1 = fmaxf(m1, __shfl_xor_sync(0xffffffffu, m1, 2));
          if (first) {
            mc0 = m0; mc1 = m1;
          } else if (__any_sync(0xffffffffu, !(m0 <= mc0 + kMaxLag && m1 <= mc1 + kMaxLag))) {
            m0 = fmaxf(mc0, m0); m1 = fmaxf(mc1, m1);
            const float a0 = ex2(mc0 - m0), a1 = ex2(mc1 - m1);
            mc0 = m0; mc1 = m1;
            l0 *= a0; l1 *= a1;
            wg_wait<0>();
            fence_regs(o);
#pragma unroll
            for (int i = 0; i < 96; i++) o[i] *= i & 2 ? a1 : a0;
          }
#pragma unroll
          for (int i = 0; i < 32; i++) s[i] -= i & 2 ? mc1 : mc0;
        }
#pragma unroll
        for (int i = 0; i < 8; i++) {
          const float e1 = ex2(s[4 * i + 1]), e0 = ex2(s[4 * i]), e3 = ex2(s[4 * i + 3]), e2 = ex2(s[4 * i + 2]);
          pout[2 * i] = pack_bf16(e0, e1);
          b0 = i ? b0 + fadd(e1, e0) : fadd(e1, e0);
          pout[2 * i + 1] = pack_bf16(e2, e3);
          b1 = i ? b1 + fadd(e3, e2) : fadd(e3, e2);
        }
        if (!__any_sync(0xffffffffu, !gen && !(fmaxf(b0, b1) <= kSumLimit && (!first || fminf(b0, b1) >= 1.0f / kSumLimit)))) break;
        gen = __any_sync(0xffffffffu, true);
      }
      l0 = first ? b0 : l0 + b0;
      l1 = first ? b1 : l1 + b1;
    };
    auto qk = [&](float (&s)[32], uint32_t ak, int k0, int k1) {
#pragma unroll
      for (int kk = k0; kk < k1; kk++)
        wgmma_rs_n64<0>(s, q[4 * kk], q[4 * kk + 1], q[4 * kk + 2], q[4 * kk + 3], mk_desc(ak, 16, KV_SBO, 1, (kk >> 2) * KV_CH + (kk & 3) * 2), kk != 0);
      wg_commit();
    };
    auto pv = [&](uint32_t (&pin)[16], uint32_t av, int acc) {
#pragma unroll
      for (int kk = 0; kk < 4; kk++)
        wgmma_rs_n192<1>(o, pin[4 * kk], pin[4 * kk + 1], pin[4 * kk + 2], pin[4 * kk + 3], mk_desc(av, KV_CH * 16, KV_SBO, 1, kk * (KV_SBO / 8)), acc || (kk != 0));
      wg_commit();
    };
    auto xw = [&](uint32_t ad, int acc) {
      const uint32_t da = second(SZ_A) + wg * 512;
      wg_fence();
#pragma unroll
      for (int kk = 0; kk < 4; kk++)
        wgmma_ss_n192<1>(o, mk_desc(da, 16, 1024, 1, kk * 2), mk_desc(ad, 4096, 1024, 1, (kk & 1) * 128 + (kk >> 1) * 768), acc || kk != 0);
      wg_commit();
    };
    auto ow = [&](int acc, int prev) {
      uint32_t da;
      const int bi = take(rdy0, SZ_A, da);
      const uint32_t db = second(SZ_WO);
      da += wg * 256;
      wg_fence();
      wgmma_ss_n160<1>(c, mk_desc(da, 16, 512, 2), mk_desc(db, 2048, 512, 2), acc);
      wgmma_ss_n160<1>(c, mk_desc(da, 16, 512, 2, 2), mk_desc(db, 2048, 512, 2, 64), 1);
      wg_commit();
      if (acc == 1) { wg_wait<1>(); release(prev); }
      wgmma_ss_n160<1>(c, mk_desc(da, 16, 512, 2, 512), mk_desc(db, 2048, 512, 2, 640), 1);
      wgmma_ss_n160<1>(c, mk_desc(da, 16, 512, 2, 514), mk_desc(db, 2048, 512, 2, 704), 1);
      wg_commit();
      return bi;
    };
    auto st_part = [&](int i) {
      stg2_if(true, pend + i * 512, __float_as_uint(c[8 * i]), __float_as_uint(c[8 * i + 1]), __float_as_uint(c[8 * i + 2]), __float_as_uint(c[8 * i + 3]),
              __float_as_uint(c[8 * i + 4]), __float_as_uint(c[8 * i + 5]), __float_as_uint(c[8 * i + 6]), __float_as_uint(c[8 * i + 7]), spol);
    };
#pragma unroll
    for (int i = 0; i < 48; i++) q[i] = 0;
    enter();

    if ((op & 3) == OP_Q) {
      uint32_t ad;
      int bi0 = take(false, SZ_WQ, ad), k = 0, lag = 0;
      xw(ad, 0);
      for (;;) {
#pragma unroll 1
        for (;;) {
          drain(q, k - lag);
          probe1();
          wg_wait<0>();
          release(bi0);
          bi0 = take(rdy0, SZ_WQ, ad);
          if (++k == 8) break;
          xw(ad, 1);
        }
        if (wg) bar_sync(2, 256);
        xw(ad, 1);
        const int bi9 = take(false, SZ_WQ, ad);
        xw(ad, 1);
        if (!wg) asm volatile("bar.arrive 2, 256;" ::: "memory");
        k = 0; lag = 0;
        uint32_t nop = prog[++pc];
        wg_wait<1>();
        release(bi0);
        probe2();
        wg_wait<0>();
        fence_regs(o);
        release(bi9);
#pragma unroll
        for (int i = 0; i < 48; i++) q[i] = pack_bf16(o[2 * i] * kScaleLog2, o[2 * i + 1] * kScaleLog2);
        fence_regs(q);
        if (op & F_PARK) {
          const int qt = helper ? (op >> 5) & 15 : team, qm = helper ? (op >> 12) & 3 : nt;
          pend = &g_o[((qt * 2 + rank) * 96 + 3 * (4 * ((op >> 2) & 7) + qm)) * 1024 + img0];
          op = nop;
          enter();
          if ((op & 3) != OP_Q) break;
          bi0 = take(rdy0, SZ_WQ, ad);
          xw(ad, 0);
          continue;
        }
        int wave = (op >> 2) & 7, sk1;
        uint32_t ak1;
        {
          float s0[32];
          const int sk0 = take(rdy0, SZ_KV, ad);
          wg_fence();
          qk(s0, ad, 0, 12);
          sk1 = take(rdy1, SZ_KV, ak1);
          wg_fence();
          qk(s, ak1, 0, S1A);
          probe1();
          wg_wait<1>();
          fence_regs(s0);
          release(sk0);
          soft(s0, pa, true);
        }
        float i0, i1;
        auto sums = [&]() {
          l0 += __shfl_xor_sync(0xffffffffu, l0, 1); l1 += __shfl_xor_sync(0xffffffffu, l1, 1);
          l0 += __shfl_xor_sync(0xffffffffu, l0, 2); l1 += __shfl_xor_sync(0xffffffffu, l1, 2);
          i0 = rcp(l0); i1 = rcp(l1);
          asm volatile("" : "+f"(i0), "+f"(i1));
        };
        auto target = [&]() {
          pend = &g_o[((team * 2 + rank) * 96 + 3 * (4 * wave + nt)) * 1024 + img0];
          asm volatile("" : "+l"(pend));
        };
        bool late = false;
#pragma unroll
        for (int i = 0; i < 16; i++) pb[i] = 0;
        for (;;) {
          nop = prog[++pc];
          {
            uint32_t av;
            const int sv = take(rdy0, SZ_KV, av);
            wg_fence();
            qk(s, ak1, S1A, 12);
            pv(pa, av, 0);
            if (late) {
              stg2_if(true, pend + 4 * 512, pb[0], pb[1], pb[2], pb[3], pb[4], pb[5], pb[6], pb[7], spol);
              stg2_if(true, pend + 5 * 512, pb[8], pb[9], pb[10], pb[11], pb[12], pb[13], pb[14], pb[15], spol);
              __syncwarp();
              mbar_arrive_if(lane < 2, odone);
            }
            probe2();
            wg_wait<1>();
            fence_regs(s);
            release(sk1);
            soft(s, pb, false);
            wg_wait<0>();
            fence_regs(o);
            release(sv);
          }
          auto step = [&](uint32_t (&pin)[16], uint32_t (&pout)[16]) {
            uint32_t ak, av;
            const int sk = take(rdy0, SZ_KV, ak), sv = take(rdy1, SZ_KV, av);
            wg_fence();
            qk(s, ak, 0, 12);
            pv(pin, av, 1);
            probe2();
            wg_wait<1>();
            fence_regs(s);
            release(sk);
            soft(s, pout, false);
            wg_wait<0>();
            fence_regs(o);
            release(sv);
          };
#pragma unroll 1
          for (int jj = 0; jj < 7; jj++) {
            step(pb, pa);
            step(pa, pb);
          }
          if ((nop & 3) != OP_A) break;
          uint32_t ak, av;
          {
            const int b0 = take(rdy0, SZ_PARK, ak), b1 = take(rdy1, SZ_PARK, av);
            const uint32_t ad0 = ak, ad1 = av;
            probe2();
#pragma unroll
            for (int i = 0; i < 12; i++)
              lds128(sbase + ((i < 6 ? ad0 : ad1) - ring16 + img0) * 16 + ((i % 6) >> 1) * 8192 + (i & 1) * 512, q[4 * i], q[4 * i + 1], q[4 * i + 2], q[4 * i + 3]);
            release(b0); release(b1);
          }
          const int sk0 = take(rdy0, SZ_KV, ak), sv = take(rdy1, SZ_KV, av);
          wg_fence();
          qk(s, ak, 0, 8);
          sched_fence(img0, P.zero);
          sums();
          sched_fence(img0, P.zero);
          qk(s, ak, 8, 12);
          pv(pb, av, 1);
          probe2();
          wg_wait<1>();
          fence_regs(s);
          release(sk0);
          soft(s, pa, true);
          sk1 = take(rdy0, SZ_KV, ak1);
          rdy0 = rdy1;
          wg_wait<0>();
          target();
          fence_regs(o);
          release(sv);
          uint32_t t[48];
#pragma unroll
          for (int j = 0; j < 6; j++) {
#pragma unroll
            for (int i = 0; i < 4; i++) {
              t[8 * j + i] = pack_bf16(o[16 * j + 4 * i] * i0, o[16 * j + 4 * i + 1] * i0);
              t[8 * j + i + 4] = pack_bf16(o[16 * j + 4 * i + 2] * i1, o[16 * j + 4 * i + 3] * i1);
            }
            if (j < 4)
            stg2_if(true, pend + j * 512, t[8 * j], t[8 * j + 1], t[8 * j + 2], t[8 * j + 3], t[8 * j + 4], t[8 * j + 5], t[8 * j + 6], t[8 * j + 7], spol);
            if (j == 3) { wg_fence(); qk(s, ak1, 0, 4); }
            if (j == 5) { wg_fence(); qk(s, ak1, 4, S1A); }
            sched_fence(img0, P.zero);
          }
          if (P.zero) {
#pragma unroll
            for (int j = 0; j < 4; j++)
              stg2_if(true, pend, t[8 * j], t[8 * j + 1], t[8 * j + 2], t[8 * j + 3], t[8 * j + 4], t[8 * j + 5], t[8 * j + 6], t[8 * j + 7], spol);
          }
          late = true;
#pragma unroll
          for (int i = 0; i < 16; i++) pb[i] = t[32 + i];
          wave = (nop >> 2) & 7;
        }
        const int sv = take(rdy0, SZ_KV, ad);
        wg_fence();
        pv(pb, ad, 1);
        sums();
        target();
        op = nop;
        enter();
        rdy0 = rdy1;
        auto convert = [&](float (&u)[96], int j0, int j1) {
#pragma unroll
          for (int i = 4 * j0; i < 4 * j1; i++) {
            q[8 * (i >> 2) + (i & 3)] = pack_bf16(u[4 * i], u[4 * i + 1]);
            q[8 * (i >> 2) + (i & 3) + 4] = pack_bf16(u[4 * i + 2], u[4 * i + 3]);
          }
        };
        if ((op & 3) != OP_O) {
          if ((op & 3) == OP_Q) bi0 = take(rdy0, SZ_WQ, ad);
          wg_wait<0>();
          fence_regs(o);
          release(sv);
          float u[96];
#pragma unroll
          for (int i = 0; i < 96; i++) u[i] = o[i] * (i & 2 ? i1 : i0);
          if ((op & 3) != OP_Q) { convert(u, 0, 6); break; }
          fence_regs(u);
          xw(ad, 0);
          sched_fence(img0, P.zero);
          fence_regs(u);
          convert(u, 0, 1);
          stg2_if(true, pend, q[0], q[1], q[2], q[3], q[4], q[5], q[6], q[7], spol);
          probe1();
          wg_wait<0>();
          release(bi0);
          bi0 = take(rdy0, SZ_WQ, ad);
          xw(ad, 1);
          sched_fence(img0, P.zero);
          fence_regs(u);
          convert(u, 1, 6);
          k = 1;
          continue;
        }
        int bi = ow(0, 0);
        wg_wait<2>();
        fence_regs(o);
        release(sv);
#pragma unroll
        for (int j = 0; j < 6; j++) {
          uint32_t t[8];
#pragma unroll
          for (int i = 0; i < 4; i++) {
            t[i] = pack_bf16(o[16 * j + 4 * i] * i0, o[16 * j + 4 * i + 1] * i0);
            t[i + 4] = pack_bf16(o[16 * j + 4 * i + 2] * i1, o[16 * j + 4 * i + 3] * i1);
          }
          stg2_if(true, pend + j * 512, t[0], t[1], t[2], t[3], t[4], t[5], t[6], t[7], spol);
          if (j == 5) {
            __syncwarp();
            mbar_arrive_if(lane < 2, odone);
          }
          probe1();
          wg_wait<1>();
          bi = ow(1, bi);
          fence_regs(o);
        }
        {
          const int nk = 12 * (((op >> 5) & 15) - ((op >> 2) & 7)) - ((op & F_ST) ? 0 : 2);
#pragma unroll 1
          for (int k = 7; k < nk; k++) {
            probe1();
            wg_wait<1>();
            bi = ow(1, bi);
          }
        }
        if (!(op & F_ST)) {
          probe2();
          wg_wait<1>();
          if (wg) {
            wg_wait<0>();
            release(bi);
            bar_sync(2, 256);
          }
          bi0 = ow(2, 0);
          rdy0 = rdy1;
          const int b = ow(2, 0);
          if (!wg) asm volatile("bar.arrive 2, 256;" ::: "memory");
          wg_wait<4>();
          mbar_arrive_cluster_if(lane < 2 && !wg, empty_rem + bi);
          bi = b;
        }
        probe1();
        nop = prog[++pc];
        if (op & F_LD) {
          uint32_t t[80];
#pragma unroll
          for (int j = 0; j < 5; j++) {
            const int b = take(rdy0, SZ_PART, ad);
            probe1();
#pragma unroll
            for (int i = 4 * j; i < 4 * j + 4; i++)
              lds128(sbase + (ad - ring16 + img0) * 16 + ((i >> 1) & 1) * 8192 + (i & 1) * 512, t[4 * i], t[4 * i + 1], t[4 * i + 2], t[4 * i + 3]);
            release(b);
          }
          wg_wait<0>();
          fence_regs(c);
#pragma unroll
          for (int i = 0; i < 80; i++) c[i] += __uint_as_float(t[i]);
        }
        if (!(op & F_ST)) {
          wg_wait<0>();
          fence_regs(c);
          release(bi0);
          release(bi);
          goto finish;
        }
        op = nop;
        enter();
        bi0 = take(rdy0, SZ_WQ, ad);
        xw(ad, 0);
        pend = &g_part[((team * 4 + nt) * 2 + rank) * 5120 + img0];
        probe1();
        wg_wait<1>();
        fence_regs(c);
        release(bi);
        st_part(0); st_part(1);
        wg_wait<0>();
        release(bi0);
        bi0 = take(rdy0, SZ_WQ, ad);
        xw(ad, 1);
        st_part(2); st_part(3);
#pragma unroll
        for (int i = 0; i < 48; i++) q[i] = __float_as_uint(c[32 + i]);
        pend += 4 * 512;
        k = 1; lag = 2;
      }
    }
    rdy0 = false;
    {
      uint32_t t[48];
#pragma unroll
      for (int i = 0; i < 48; i++) t[i] = q[i] ^ P.zero;
      while ((op & 3) == OP_O) {
        int bi = ow(0, 0);
#pragma unroll 1
        for (int k = 1; k < 12 * (int)(((op >> 5) & 15) - ((op >> 2) & 7)); k++) {
          drain(t, k - 1);
          probe1();
          wg_wait<1>();
          bi = ow(1, bi);
        }
        rdy0 = false;
        wg_wait<0>();
        fence_regs(c);
        pc++;
        release(bi);
        if (!(op & F_ST)) goto finish;
        pend = &g_part[((((op >> 26) & 56) | ((op >> 9) & 7)) * 2 + rank) * 5120 + img0];
#pragma unroll
        for (int i = 6; i < 10; i++) st_part(i);
#pragma unroll
        for (int i = 0; i < 48; i++) t[i] = __float_as_uint(c[i]) ^ P.zero;
        op = prog[pc];
        enter();
      }
      for (int i = 0; i < 6; i++) drain(t, i);
    }
    if (false) {
    finish:
      uint32_t ad;
      take(rdy0, SZ_OUT, ad);
      const uint32_t wstage = sbase + (ad - ring16) * 16 + (wg * 4 + warp) * 5120;
      const uint32_t sa = wstage + (lane & 15) * 64;
#pragma unroll
      for (int i = 0; i < 10; i++) {
        const int u = (i & 1) * 2 + (lane >> 4);
        stsm4(sa + (i >> 1) * 1024 + ((u ^ ((lane >> 1) & 3)) << 4), pack_bf16(c[8 * i], c[8 * i + 1]), pack_bf16(c[8 * i + 2], c[8 * i + 3]),
              pack_bf16(c[8 * i + 4], c[8 * i + 5]), pack_bf16(c[8 * i + 6], c[8 * i + 7]));
      }
      asm volatile("fence.proxy.async.shared::cta;" ::: "memory");
      __syncwarp();
      if (lane == 0) {
        tma3d_store(&P.out, wstage, 0, (team & 7) * kSq + rank * 128 + wg * 64 + warp * 16, blk * 20 + nt * 5);
        asm volatile("cp.async.bulk.commit_group;\ncp.async.bulk.wait_group.read 0;" ::: "memory");
      }
    }
  }
}

typedef CUresult (*EncodeFn)(CUtensorMap*, CUtensorMapDataType, cuuint32_t, void*, const cuuint64_t*, const cuuint64_t*,
                             const cuuint32_t*, const cuuint32_t*, CUtensorMapInterleave, CUtensorMapSwizzle,
                             CUtensorMapL2promotion, CUtensorMapFloatOOBfill);

void encode(EncodeFn fn, CUtensorMap* m, const void* ptr, int rank, const cuuint64_t* dims, const cuuint64_t* strides,
            const cuuint32_t* box, CUtensorMapSwizzle swz) {
  const cuuint32_t es[5] = {1, 1, 1, 1, 1};
  CUresult r = fn(m, CU_TENSOR_MAP_DATA_TYPE_BFLOAT16, rank, const_cast<void*>(ptr), dims, strides, box, es,
                  CU_TENSOR_MAP_INTERLEAVE_NONE, swz, CU_TENSOR_MAP_L2_PROMOTION_L2_128B, CU_TENSOR_MAP_FLOAT_OOB_FILL_NONE);
  if (r != CUDA_SUCCESS) fprintf(stderr, "cuTensorMapEncodeTiled failed: %d\n", (int)r);
}

void annotate(uint32_t* ops, int n, bool helper) {
  uint32_t items = 0, cur = 0, pend = 0;
  auto item = [&](uint32_t bytes, int count, uint32_t bytes2 = 0) {
    for (int i = 0; i < count; i++) {
      if (cur + bytes > RING) cur = 0;
      cur += bytes;
      if (cur + bytes2 > RING) cur = 0;
      cur += bytes2;
      items++;
    }
  };
  for (int i = 0; i <= n; i++) {
    const uint32_t op = ops[i];
    ops[i] |= (items % (2 * NBAR)) << 15 | (cur >> 12) << 20 | pend << 26;
    if ((op & 3) == OP_Q) { item(SZ_WQ, 10, SZ_A); pend = (op & F_PARK) ? (helper ? 1 : 2) : 0; }
    if ((op & 3) == OP_A) {
      item(SZ_KV, (op & F_PARK) ? 30 : 31);
      if ((ops[i + 1] & 3) == OP_A) { item(SZ_PARK, 2); item(SZ_KV, 1); }
      item(SZ_KV, 1);
      pend = 1;
    }
    if ((op & 3) == OP_O) {
      item(SZ_A, 12 * (((op >> 5) & 15) - ((op >> 2) & 7)), SZ_WO);
      if (op & F_LD) item(SZ_PART, 5);
      pend = (op & F_ST) ? (helper ? 1 : 2) : 0;
    }
  }
}

void compile_programs(const char* const* text, bool helpers, Params& P) {
  struct Req { int when, team, wave, slot; } req[N_TEAM * MAX_PARK];
  int n_req = 0;
  for (int t = 0; t < N_TEAM; t++) {
    uint32_t* ops = P.ops[t];
    int n = 0, flags[8] = {0, 0, 0, 0, 0, 0, 0, 0}, n_park = 0, last_o = -1, when = 0, given = 0;
    for (const char* s = text[t]; *s; s++) {
      const int a = s[1] - '0';
      if (*s == 'Q' || (*s == 'H' && !helpers)) { ops[n++] = OP_Q | a << 2; when += 10; }
      else if (*s == 'P') { flags[a] = F_PARK; ops[n++] = OP_Q | a << 2 | flags[a]; when += 10; }
      else if (*s == 'H') { req[n_req++] = {when, t, a, n_park}; flags[a] = F_PARK | F_HELP | n_park++ << 10; }
      else if (*s == 'A') { ops[n++] = OP_A | a << 2 | flags[a]; when += 32; }
      else if (*s == 'G') { given = a; if (helpers) req[n_req++] = {1000, t, 0, -a}; }
      else if (*s == 'O') {
        ops[n] = OP_O | a << 2 | (s[2] - '0') << 5;
        if (given) ops[n] = helpers ? ops[n] | F_LD | F_PARK | (MAX_PARK - 1) << 10 : ops[n] & ~(7u << 2);
        if (last_o >= 0) { ops[last_o] |= F_ST; ops[n] |= F_LD; }
        last_o = n++;
        when += 10 * (s[2] - s[1]);
      }
    }
    for (int i = n; i < MAX_OPS; i++) ops[i] = OP_END;
    annotate(ops, n, false);
  }
  for (int i = 1; i < n_req; i++)
    for (int j = i; j > 0 && req[j].when < req[j - 1].when; j--) { Req r = req[j]; req[j] = req[j - 1]; req[j - 1] = r; }
  for (int h = 0; h < N_HELP; h++) {
    uint32_t* ops = P.ops[N_TEAM + 2 * h];
    int n = 0;
    for (int i = 0; i < n_req; i++)
      for (int m = h; m < 4; m += N_HELP) {
        const uint32_t ro = 4 * req[i].team + m;
        ops[n++] = req[i].slot >= 0 ? OP_Q | req[i].wave << 2 | req[i].team << 5 | F_PARK | req[i].slot << 10 | m << 12
                                    : OP_O | -req[i].slot << 5 | F_ST | (ro & 7) << 9 | (ro >> 3) << 29;
      }
    for (int i = n; i < 2 * MAX_OPS; i++) ops[i] = OP_END;
    annotate(ops, n, true);
  }
  for (int i = 0; i < 32; i++) P.first[i] = i < N_TEAM ? P.ops[i][0] : i < N_TEAM + N_HELP ? P.ops[2 * i - N_TEAM][0] : 0;
}

const char* const kPrograms[N_TEAM] = {
  "Q0A0Q1A1H2A2O03Q3A3Q4A4Q5A5Q6A6Q7A7O38",
  "Q0A0Q1A1Q2A2Q3A3O04Q4A4Q5A5Q6A6H7A7O48",
  "Q0A0H1A1Q2A2Q3A3Q4A4O05Q5A5Q6A6Q7A7O58",
  "Q0A0Q1A1Q2A2O03Q3A3Q4A4Q5A5Q6A6H7A7O38",
  "Q0A0Q1A1Q2A2O03Q3A3H4A4Q5A5Q6A6Q7A7O38",
  "Q0A0Q1A1H2A2Q3A3Q4A4O05Q5A5Q6A6Q7A7O58",
  "Q0A0Q1A1Q2A2Q3A3O03Q4A4H5A5Q6A6Q7A7O38",
  "Q0A0Q1A1Q2A2Q3A3Q4A4O05Q5A5Q6A6H7A7O58",
  "P3Q0A0Q1A1Q2A2A3H4A4Q5A5Q6A6Q7A7O08",
  "P5P7Q0A0Q1A1Q2A2H3A3Q4A4A5Q6A6A7G1O18",
  "Q0A0Q1A1Q2A2O02Q3A3H4A4Q5A5Q6A6Q7A7O28",
  "P3P5Q0A0Q1A1Q2A2A3Q4A4A5Q6A6H7A7O08",
  "Q0A0Q1A1Q2A2O02Q3A3Q4A4H5A5Q6A6Q7A7O28",
  "P7Q0A0Q1A1Q2A2Q3A3Q4A4Q5A5Q6A6A7G1O18",
  "P5Q0A0Q1A1Q2A2Q3A3Q4A4A5Q6A6H7A7O08",
  "Q0A0Q1A1Q2A2H3A3Q4A4Q5A5Q6A6Q7A7O08",
};

const char* const* bench_programs() {
  return kPrograms;
}

}

extern "C" void kernel_launch(void* const* d_in, const int* in_sizes, int n_in, void* d_out, int out_size) {
  (void)in_sizes; (void)n_in; (void)out_size;
  static EncodeFn fn = nullptr;
  static int n_clusters = 0;
  if (!fn) {
    cudaDriverEntryPointQueryResult qr;
    void* f = nullptr;
    cudaGetDriverEntryPoint("cuTensorMapEncodeTiled", &f, cudaEnableDefault, &qr);
    fn = (EncodeFn)f;
    cudaFuncSetAttribute(fused_kernel, cudaFuncAttributeMaxDynamicSharedMemorySize, SMEM_BYTES);
    cudaLaunchConfig_t cfg = {};
    cfg.gridDim = dim3(132); cfg.blockDim = dim3(384); cfg.dynamicSmemBytes = SMEM_BYTES;
    cudaLaunchAttribute at[1];
    at[0].id = cudaLaunchAttributeClusterDimension; at[0].val.clusterDim.x = 2; at[0].val.clusterDim.y = 1; at[0].val.clusterDim.z = 1;
    cfg.attrs = at; cfg.numAttrs = 1;
    if (cudaOccupancyMaxActiveClusters(&n_clusters, fused_kernel, &cfg) != cudaSuccess || n_clusters < 1) n_clusters = 1;
    (void)cudaGetLastError();
  }
  Params P;
  const CUtensorMapSwizzle S128 = CU_TENSOR_MAP_SWIZZLE_128B, S64 = CU_TENSOR_MAP_SWIZZLE_64B;
  for (int blk = 0; blk < 2; blk++) {
    void* const* in = d_in + 5 * blk;
    { const cuuint64_t d[] = {kD, kB * kSq}, s[] = {kD * 2}; const cuuint32_t b[] = {64, 128};
      encode(fn, &P.x[blk], in[0], 2, d, s, b, S128); }
    { const cuuint64_t d[] = {64, 8, 3, (cuuint64_t)kB * kH * kSk / 8}, s[] = {kDh * 2, 128, 8 * kDh * 2}; const cuuint32_t b[] = {64, 8, 3, 4};
      encode(fn, &P.k[blk], in[1], 4, d, s, b, S128);
      encode(fn, &P.v[blk], in[2], 4, d, s, b, S128); }
    { const cuuint64_t d[] = {64, kD, kHD / 64}, s[] = {kHD * 2, 128}; const cuuint32_t b[] = {64, 32, 3};
      encode(fn, &P.wq[blk], in[3], 3, d, s, b, S128); }
    { const cuuint64_t d[] = {32, 2, kHD / 8, 4, kD / 32}, s[] = {kD * 2, 8 * kD * 2, 2 * kD * 2, 64}; const cuuint32_t b[] = {32, 2, 4, 4, 5};
      encode(fn, &P.wo[blk], in[4], 5, d, s, b, S64); }
  }
  { const cuuint64_t d[] = {32, kB * kSq, 2 * kD / 32}, s[] = {2 * kD * 2, 64}; const cuuint32_t b[] = {32, 16, 5};
    encode(fn, &P.out, d_out, 3, d, s, b, S64); }

  P.zero = 0;
  if (n_clusters >= N_CL) {
    const bool helpers = n_clusters >= N_CL + N_HELP;
    compile_programs(bench_programs(), helpers, P);
    fused_kernel<<<2 * (N_CL + (helpers ? N_HELP : 0)), 384, SMEM_BYTES>>>(P);
  } else {
    for (int phase = 0; phase < 2; phase++) {
      const char* text[N_TEAM];
      for (int t = 0; t < N_TEAM; t++) text[t] = phase ? "O08" : "Q0A0Q1A1Q2A2Q3A3Q4A4Q5A5Q6A6Q7A7";
      compile_programs(text, false, P);
      fused_kernel<<<2 * N_CL, 384, SMEM_BYTES>>>(P);
    }
  }
}
```

```cpp
#include <cuda_runtime.h>
#include <cuda_bf16.h>
#include <cuda.h>
#include <stdint.h>
#include <stdio.h>

namespace {

constexpr int kB = 8, kSq = 256, kD = 640, kH = 32, kSk = 1024, kDh = 192;
constexpr int kHD = kH * kDh;
constexpr uint32_t RING = 224 * 1024;
constexpr uint32_t SZ_KV = 24576;
constexpr uint32_t SZ_WQ = 24576, SZ_WO = 20480, SZ_A = 16384;
constexpr uint32_t SZ_OUT = 40960;
constexpr uint32_t SZ_PARK = 24576;
constexpr uint32_t SZ_PART = 16384;
constexpr int NBAR = 16, NFLIGHT = 12;
constexpr int KV_TRANSIT = 4;
constexpr int EARLY = 3;
constexpr int S1A = 7;
constexpr uint32_t KV_CH = 64, KV_SBO = 3072;
constexpr int SMEM_BYTES = RING + 512 + 1024;
constexpr int N_TEAM = 16, N_CL = 64, N_HELP = 2, MAX_OPS = 24, MAX_PARK = 4;
enum { OP_END = 0, OP_Q = 1, OP_A = 2, OP_O = 3, F_PARK = 1 << 9, F_LD = 1 << 12, F_ST = 1 << 13, F_HELP = 1 << 12 };

struct alignas(64) Params {
  uint32_t first[32];
  CUtensorMap x[2], wq[2], k[2], v[2], wo[2], out;
  uint32_t ops[N_TEAM + 2 * N_HELP][MAX_OPS];
  uint32_t zero;
};

__device__ uint4 g_o[N_TEAM * 2 * 96 * 1024];
__device__ uint4 g_part[N_CL * 2 * 5 * 1024];
__device__ unsigned int g_done[N_TEAM * 2 * 8];
__device__ unsigned int g_help[N_CL * 2 * MAX_PARK];
__device__ unsigned int g_seen[N_TEAM * 2 * 8];

template <int TB>
__device__ __forceinline__ void wgmma_rs_n64(float (&d)[32], uint32_t a0, uint32_t a1, uint32_t a2, uint32_t a3, uint64_t db, int scale_d) {
  asm volatile("{\n.reg .pred p;\nsetp.ne.b32 p, %37, 0;\n"
    "wgmma.mma_async.sync.aligned.m64n64k16.f32.bf16.bf16 {%0, %1, %2, %3, %4, %5, %6, %7, %8, %9, %10, %11, %12, %13, %14, %15, %16, %17, %18, %19, %20, %21, %22, %23, %24, %25, %26, %27, %28, %29, %30, %31}, {%32, %33, %34, %35}, %36, p, 1, 1, %38;\n}\n"
    : "+f"(d[0]), "+f"(d[1]), "+f"(d[2]), "+f"(d[3]), "+f"(d[4]), "+f"(d[5]), "+f"(d[6]), "+f"(d[7]), "+f"(d[8]), "+f"(d[9]), "+f"(d[10]), "+f"(d[11]), "+f"(d[12]), "+f"(d[13]), "+f"(d[14]), "+f"(d[15]), "+f"(d[16]), "+f"(d[17]), "+f"(d[18]), "+f"(d[19]), "+f"(d[20]), "+f"(d[21]), "+f"(d[22]), "+f"(d[23]), "+f"(d[24]), "+f"(d[25]), "+f"(d[26]), "+f"(d[27]), "+f"(d[28]), "+f"(d[29]), "+f"(d[30]), "+f"(d[31])
    : "r"(a0), "r"(a1), "r"(a2), "r"(a3), "l"(db), "r"(scale_d), "n"(TB));
}
template <int TB, int TA = 0>
__device__ __forceinline__ void wgmma_ss_n160(float (&d)[80], uint64_t da, uint64_t db, int scale_d) {
  asm volatile("{\n.reg .pred p;\nsetp.ne.b32 p, %82, 0;\n"
    "wgmma.mma_async.sync.aligned.m64n160k16.f32.bf16.bf16 {%0, %1, %2, %3, %4, %5, %6, %7, %8, %9, %10, %11, %12, %13, %14, %15, %16, %17, %18, %19, %20, %21, %22, %23, %24, %25, %26, %27, %28, %29, %30, %31, %32, %33, %34, %35, %36, %37, %38, %39, %40, %41, %42, %43, %44, %45, %46, %47, %48, %49, %50, %51, %52, %53, %54, %55, %56, %57, %58, %59, %60, %61, %62, %63, %64, %65, %66, %67, %68, %69, %70, %71, %72, %73, %74, %75, %76, %77, %78, %79}, %80, %81, p, 1, 1, %83, %84;\n}\n"
    : "+f"(d[0]), "+f"(d[1]), "+f"(d[2]), "+f"(d[3]), "+f"(d[4]), "+f"(d[5]), "+f"(d[6]), "+f"(d[7]), "+f"(d[8]), "+f"(d[9]), "+f"(d[10]), "+f"(d[11]), "+f"(d[12]), "+f"(d[13]), "+f"(d[14]), "+f"(d[15]), "+f"(d[16]), "+f"(d[17]), "+f"(d[18]), "+f"(d[19]), "+f"(d[20]), "+f"(d[21]), "+f"(d[22]), "+f"(d[23]), "+f"(d[24]), "+f"(d[25]), "+f"(d[26]), "+f"(d[27]), "+f"(d[28]), "+f"(d[29]), "+f"(d[30]), "+f"(d[31]), "+f"(d[32]), "+f"(d[33]), "+f"(d[34]), "+f"(d[35]), "+f"(d[36]), "+f"(d[37]), "+f"(d[38]), "+f"(d[39]), "+f"(d[40]), "+f"(d[41]), "+f"(d[42]), "+f"(d[43]), "+f"(d[44]), "+f"(d[45]), "+f"(d[46]), "+f"(d[47]), "+f"(d[48]), "+f"(d[49]), "+f"(d[50]), "+f"(d[51]), "+f"(d[52]), "+f"(d[53]), "+f"(d[54]), "+f"(d[55]), "+f"(d[56]), "+f"(d[57]), "+f"(d[58]), "+f"(d[59]), "+f"(d[60]), "+f"(d[61]), "+f"(d[62]), "+f"(d[63]), "+f"(d[64]), "+f"(d[65]), "+f"(d[66]), "+f"(d[67]), "+f"(d[68]), "+f"(d[69]), "+f"(d[70]), "+f"(d[71]), "+f"(d[72]), "+f"(d[73]), "+f"(d[74]), "+f"(d[75]), "+f"(d[76]), "+f"(d[77]), "+f"(d[78]), "+f"(d[79])
    : "l"(da), "l"(db), "r"(scale_d), "n"(TA), "n"(TB));
}
template <int TB, int TA = 0>
__device__ __forceinline__ void wgmma_ss_n192(float (&d)[96], uint64_t da, uint64_t db, int scale_d) {
  asm volatile("{\n.reg .pred p;\nsetp.ne.b32 p, %98, 0;\n"
    "wgmma.mma_async.sync.aligned.m64n192k16.f32.bf16.bf16 {%0, %1, %2, %3, %4, %5, %6, %7, %8, %9, %10, %11, %12, %13, %14, %15, %16, %17, %18, %19, %20, %21, %22, %23, %24, %25, %26, %27, %28, %29, %30, %31, %32, %33, %34, %35, %36, %37, %38, %39, %40, %41, %42, %43, %44, %45, %46, %47, %48, %49, %50, %51, %52, %53, %54, %55, %56, %57, %58, %59, %60, %61, %62, %63, %64, %65, %66, %67, %68, %69, %70, %71, %72, %73, %74, %75, %76, %77, %78, %79, %80, %81, %82, %83, %84, %85, %86, %87, %88, %89, %90, %91, %92, %93, %94, %95}, %96, %97, p, 1, 1, %99, %100;\n}\n"
    : "+f"(d[0]), "+f"(d[1]), "+f"(d[2]), "+f"(d[3]), "+f"(d[4]), "+f"(d[5]), "+f"(d[6]), "+f"(d[7]), "+f"(d[8]), "+f"(d[9]), "+f"(d[10]), "+f"(d[11]), "+f"(d[12]), "+f"(d[13]), "+f"(d[14]), "+f"(d[15]), "+f"(d[16]), "+f"(d[17]), "+f"(d[18]), "+f"(d[19]), "+f"(d[20]), "+f"(d[21]), "+f"(d[22]), "+f"(d[23]), "+f"(d[24]), "+f"(d[25]), "+f"(d[26]), "+f"(d[27]), "+f"(d[28]), "+f"(d[29]), "+f"(d[30]), "+f"(d[31]), "+f"(d[32]), "+f"(d[33]), "+f"(d[34]), "+f"(d[35]), "+f"(d[36]), "+f"(d[37]), "+f"(d[38]), "+f"(d[39]), "+f"(d[40]), "+f"(d[41]), "+f"(d[42]), "+f"(d[43]), "+f"(d[44]), "+f"(d[45]), "+f"(d[46]), "+f"(d[47]), "+f"(d[48]), "+f"(d[49]), "+f"(d[50]), "+f"(d[51]), "+f"(d[52]), "+f"(d[53]), "+f"(d[54]), "+f"(d[55]), "+f"(d[56]), "+f"(d[57]), "+f"(d[58]), "+f"(d[59]), "+f"(d[60]), "+f"(d[61]), "+f"(d[62]), "+f"(d[63]), "+f"(d[64]), "+f"(d[65]), "+f"(d[66]), "+f"(d[67]), "+f"(d[68]), "+f"(d[69]), "+f"(d[70]), "+f"(d[71]), "+f"(d[72]), "+f"(d[73]), "+f"(d[74]), "+f"(d[75]), "+f"(d[76]), "+f"(d[77]), "+f"(d[78]), "+f"(d[79]), "+f"(d[80]), "+f"(d[81]), "+f"(d[82]), "+f"(d[83]), "+f"(d[84]), "+f"(d[85]), "+f"(d[86]), "+f"(d[87]), "+f"(d[88]), "+f"(d[89]), "+f"(d[90]), "+f"(d[91]), "+f"(d[92]), "+f"(d[93]), "+f"(d[94]), "+f"(d[95])
    : "l"(da), "l"(db), "r"(scale_d), "n"(TA), "n"(TB));
}
template <int TB>
__device__ __forceinline__ void wgmma_rs_n192(float (&d)[96], uint32_t a0, uint32_t a1, uint32_t a2, uint32_t a3, uint64_t db, int scale_d) {
  asm volatile("{\n.reg .pred p;\nsetp.ne.b32 p, %101, 0;\n"
    "wgmma.mma_async.sync.aligned.m64n192k16.f32.bf16.bf16 {%0, %1, %2, %3, %4, %5, %6, %7, %8, %9, %10, %11, %12, %13, %14, %15, %16, %17, %18, %19, %20, %21, %22, %23, %24, %25, %26, %27, %28, %29, %30, %31, %32, %33, %34, %35, %36, %37, %38, %39, %40, %41, %42, %43, %44, %45, %46, %47, %48, %49, %50, %51, %52, %53, %54, %55, %56, %57, %58, %59, %60, %61, %62, %63, %64, %65, %66, %67, %68, %69, %70, %71, %72, %73, %74, %75, %76, %77, %78, %79, %80, %81, %82, %83, %84, %85, %86, %87, %88, %89, %90, %91, %92, %93, %94, %95}, {%96, %97, %98, %99}, %100, p, 1, 1, %102;\n}\n"
    : "+f"(d[0]), "+f"(d[1]), "+f"(d[2]), "+f"(d[3]), "+f"(d[4]), "+f"(d[5]), "+f"(d[6]), "+f"(d[7]), "+f"(d[8]), "+f"(d[9]), "+f"(d[10]), "+f"(d[11]), "+f"(d[12]), "+f"(d[13]), "+f"(d[14]), "+f"(d[15]), "+f"(d[16]), "+f"(d[17]), "+f"(d[18]), "+f"(d[19]), "+f"(d[20]), "+f"(d[21]), "+f"(d[22]), "+f"(d[23]), "+f"(d[24]), "+f"(d[25]), "+f"(d[26]), "+f"(d[27]), "+f"(d[28]), "+f"(d[29]), "+f"(d[30]), "+f"(d[31]), "+f"(d[32]), "+f"(d[33]), "+f"(d[34]), "+f"(d[35]), "+f"(d[36]), "+f"(d[37]), "+f"(d[38]), "+f"(d[39]), "+f"(d[40]), "+f"(d[41]), "+f"(d[42]), "+f"(d[43]), "+f"(d[44]), "+f"(d[45]), "+f"(d[46]), "+f"(d[47]), "+f"(d[48]), "+f"(d[49]), "+f"(d[50]), "+f"(d[51]), "+f"(d[52]), "+f"(d[53]), "+f"(d[54]), "+f"(d[55]), "+f"(d[56]), "+f"(d[57]), "+f"(d[58]), "+f"(d[59]), "+f"(d[60]), "+f"(d[61]), "+f"(d[62]), "+f"(d[63]), "+f"(d[64]), "+f"(d[65]), "+f"(d[66]), "+f"(d[67]), "+f"(d[68]), "+f"(d[69]), "+f"(d[70]), "+f"(d[71]), "+f"(d[72]), "+f"(d[73]), "+f"(d[74]), "+f"(d[75]), "+f"(d[76]), "+f"(d[77]), "+f"(d[78]), "+f"(d[79]), "+f"(d[80]), "+f"(d[81]), "+f"(d[82]), "+f"(d[83]), "+f"(d[84]), "+f"(d[85]), "+f"(d[86]), "+f"(d[87]), "+f"(d[88]), "+f"(d[89]), "+f"(d[90]), "+f"(d[91]), "+f"(d[92]), "+f"(d[93]), "+f"(d[94]), "+f"(d[95])
    : "r"(a0), "r"(a1), "r"(a2), "r"(a3), "l"(db), "r"(scale_d), "n"(TB));
}

__device__ __forceinline__ uint32_t smem_u32(const void* p) { return (uint32_t)__cvta_generic_to_shared(p); }
__device__ __forceinline__ void wg_fence() { asm volatile("wgmma.fence.sync.aligned;" ::: "memory"); }
__device__ __forceinline__ void wg_commit() { asm volatile("wgmma.commit_group.sync.aligned;" ::: "memory"); }
template <int N> __device__ __forceinline__ void wg_wait() { asm volatile("wgmma.wait_group.sync.aligned %0;" ::"n"(N) : "memory"); }
__device__ __forceinline__ void sched_fence(int& keep, uint32_t zero) {
  asm volatile("{\n.reg .u32 c;\nmov.u32 c, %%clock;\nand.b32 c, c, %1;\nxor.b32 %0, %0, c;\n}\n" : "+r"(keep) : "r"(zero) : "memory");
}
template <int N> __device__ __forceinline__ void fence_regs(float (&r)[N]) {
#pragma unroll
  for (int i = 0; i < N; i++) asm volatile("" : "+f"(r[i])::"memory");
}
template <int N> __device__ __forceinline__ void fence_regs(uint32_t (&r)[N]) {
#pragma unroll
  for (int i = 0; i < N; i++) asm volatile("" : "+r"(r[i])::"memory");
}
__device__ __forceinline__ uint64_t mk_desc(uint32_t a16, uint32_t lbo, uint32_t sbo, uint32_t swz, uint32_t off = 0) {
  uint64_t d;
  asm("mov.b64 %0, {%1, %2};" : "=l"(d) : "r"(a16), "r"((sbo >> 4) | (swz << 30)));
  return d + (off + ((lbo >> 4) << 16));
}
__device__ __forceinline__ void mbar_init(uint32_t bar, uint32_t cnt) {
  asm volatile("mbarrier.init.shared::cta.b64 [%0], %1;" ::"r"(bar), "r"(cnt) : "memory");
}
__device__ __forceinline__ void mbar_expect(uint32_t bar, uint32_t tx) {
  asm volatile("mbarrier.arrive.expect_tx.shared::cta.b64 _, [%0], %1;" ::"r"(bar), "r"(tx) : "memory");
}
__device__ __forceinline__ bool mbar_test(uint32_t bar, uint32_t ph) {
  uint32_t ok;
  asm volatile("{\n.reg .pred p;\nmbarrier.test_wait.parity.shared::cta.b64 p, [%1], %2;\nselp.u32 %0, 1, 0, p;\n}\n"
               : "=r"(ok) : "r"(bar), "r"(ph) : "memory");
  return ok;
}
__device__ __forceinline__ void mbar_wait(uint32_t bar, uint32_t ph) {
  asm volatile("{\n.reg .pred p;\n.reg .u32 n;\nmov.u32 n, 0;\n"
               "LOOP:\nadd.u32 n, n, 1;\nmbarrier.try_wait.parity.shared::cta.b64 p, [%0], %1;\n@p bra DONE;\n"
               "setp.lt.u32 p, n, 0x1000000;\n@p bra LOOP;\ntrap;\n"
               "DONE:\n}\n" ::"r"(bar), "r"(ph) : "memory");
}
__device__ __forceinline__ void mbar_wait_long(uint32_t bar, uint32_t ph) {
  asm volatile("{\n.reg .pred p;\n.reg .u32 n;\nmov.u32 n, 0;\n"
               "LOOP:\nmbarrier.try_wait.parity.shared::cta.b64 p, [%0], %1, %2;\n@p bra DONE;\n"
               "add.u32 n, n, 1;\nsetp.lt.u32 p, n, 0x40000;\n@p bra LOOP;\ntrap;\n"
               "DONE:\n}\n" ::"r"(bar), "r"(ph), "r"(20000) : "memory");
}
__device__ __forceinline__ void mbar_arrive_cluster_if(bool on, uint32_t addr) {
  asm volatile("{\n.reg .pred p;\nsetp.ne.b32 p, %1, 0;\n@p mbarrier.arrive.shared::cluster.b64 _, [%0];\n}\n" ::"r"(addr), "r"((int)on) : "memory");
}
__device__ __forceinline__ void mbar_arrive_if(bool on, uint32_t addr) {
  asm volatile("{\n.reg .pred p;\nsetp.ne.b32 p, %1, 0;\n@p mbarrier.arrive.shared::cta.b64 _, [%0];\n}\n" ::"r"(addr), "r"((int)on) : "memory");
}
__device__ __forceinline__ void tma2d(uint32_t dst, const CUtensorMap* m, uint32_t bar, int c0, int c1) {
  asm volatile("cp.async.bulk.tensor.2d.shared::cluster.global.mbarrier::complete_tx::bytes [%0], [%1, {%3, %4}], [%2];"
               ::"r"(dst), "l"(m), "r"(bar), "r"(c0), "r"(c1) : "memory");
}
__device__ __forceinline__ void tma3d(uint32_t dst, const CUtensorMap* m, uint32_t bar, int c0, int c1, int c2) {
  asm volatile("cp.async.bulk.tensor.3d.shared::cluster.global.mbarrier::complete_tx::bytes [%0], [%1, {%3, %4, %5}], [%2];"
               ::"r"(dst), "l"(m), "r"(bar), "r"(c0), "r"(c1), "r"(c2) : "memory");
}
__device__ __forceinline__ void tma3d_mc(uint32_t dst, const CUtensorMap* m, uint32_t bar, int c0, int c1, int c2) {
  asm volatile("cp.async.bulk.tensor.3d.shared::cluster.global.mbarrier::complete_tx::bytes.multicast::cluster"
               " [%0], [%1, {%3, %4, %5}], [%2], %6;"
               ::"r"(dst), "l"(m), "r"(bar), "r"(c0), "r"(c1), "r"(c2), "h"((uint16_t)3) : "memory");
}
__device__ __forceinline__ void tma3d_store(const CUtensorMap* m, uint32_t src, int c0, int c1, int c2) {
  asm volatile("cp.async.bulk.tensor.3d.global.shared::cta.bulk_group [%0, {%2, %3, %4}], [%1];"
               ::"l"(m), "r"(src), "r"(c0), "r"(c1), "r"(c2) : "memory");
}
__device__ __forceinline__ void bar_sync(int id, int n) { asm volatile("bar.sync %0, %1;" ::"r"(id), "r"(n) : "memory"); }
__device__ __forceinline__ uint32_t pack_bf16(float lo, float hi) {
  uint32_t r;
  asm("cvt.rn.bf16x2.f32 %0, %1, %2;" : "=r"(r) : "f"(hi), "f"(lo));
  return r;
}
__device__ __forceinline__ float ex2(float x) {
  float y;
  asm("ex2.approx.ftz.f32 %0, %1;" : "=f"(y) : "f"(x));
  return y;
}
__device__ __forceinline__ float fadd(float a, float b) {
  float y;
  asm("add.f32 %0, %1, %2;" : "=f"(y) : "f"(a), "f"(b));
  return y;
}
__device__ __forceinline__ float rcp(float x) {
  float y;
  asm("rcp.approx.ftz.f32 %0, %1;" : "=f"(y) : "f"(x));
  return y;
}
__device__ __forceinline__ void stsm4(uint32_t addr, uint32_t a, uint32_t b, uint32_t c, uint32_t d) {
  asm volatile("stmatrix.sync.aligned.m8n8.x4.shared.b16 [%0], {%1, %2, %3, %4};" ::"r"(addr), "r"(a), "r"(b), "r"(c), "r"(d) : "memory");
}

__device__ __forceinline__ void tma4d_mc_hint(uint32_t dst, const CUtensorMap* m, uint32_t bar, int c3, uint64_t pol) {
  asm volatile("cp.async.bulk.tensor.4d.shared::cluster.global.mbarrier::complete_tx::bytes.multicast::cluster.L2::cache_hint"
               " [%0], [%1, {%3, %3, %3, %4}], [%2], %5, %6;"
               ::"r"(dst), "l"(m), "r"(bar), "r"(0), "r"(c3), "h"((uint16_t)3), "l"(pol) : "memory");
}
__device__ __forceinline__ void tma5d_mc(uint32_t dst, const CUtensorMap* m, uint32_t bar, int c2, int c4) {
  asm volatile("cp.async.bulk.tensor.5d.shared::cluster.global.mbarrier::complete_tx::bytes.multicast::cluster"
               " [%0], [%1, {%3, %3, %4, %3, %5}], [%2], %6;"
               ::"r"(dst), "l"(m), "r"(bar), "r"(0), "r"(c2), "r"(c4), "h"((uint16_t)3) : "memory");
}
__device__ __forceinline__ void bulk_load_hint(uint32_t dst, const void* src, uint32_t bytes, uint32_t bar, uint64_t pol) {
  asm volatile("cp.async.bulk.shared::cluster.global.mbarrier::complete_tx::bytes.L2::cache_hint [%0], [%1], %2, [%3], %4;"
               ::"r"(dst), "l"(src), "r"(bytes), "r"(bar), "l"(pol) : "memory");
}
__device__ __forceinline__ void stg2_if(bool on, void* p, uint32_t a, uint32_t b, uint32_t c, uint32_t d, uint32_t e, uint32_t f,
                                        uint32_t g, uint32_t h, uint64_t pol) {
  asm volatile("{\n.reg .pred p;\nsetp.ne.b32 p, %10, 0;\n"
               "@p st.global.L2::cache_hint.v4.b32 [%0], {%1, %2, %3, %4}, %9;\n"
               "@p st.global.L2::cache_hint.v4.b32 [%0 + 512], {%5, %6, %7, %8}, %9;\n}\n"
               ::"l"(p), "r"(a), "r"(b), "r"(c), "r"(d), "r"(e), "r"(f), "r"(g), "r"(h), "l"(pol), "r"((int)on) : "memory");
}
__device__ __forceinline__ uint64_t evict_first() {
  uint64_t p;
  asm("createpolicy.fractional.L2::evict_first.b64 %0, 1.0;" : "=l"(p));
  return p;
}
__device__ __forceinline__ bool elect() {
  uint32_t ok;
  asm volatile("{\n.reg .pred p;\nelect.sync _|p, 0xffffffff;\nselp.u32 %0, 1, 0, p;\n}\n" : "=r"(ok));
  return ok;
}
__device__ __forceinline__ void mbar_arrive(uint32_t bar) {
  asm volatile("mbarrier.arrive.shared::cta.b64 _, [%0];" ::"r"(bar) : "memory");
}
__device__ __forceinline__ void lds128(uint32_t p, uint32_t& a, uint32_t& b, uint32_t& c, uint32_t& d) {
  asm volatile("ld.shared.v4.b32 {%0, %1, %2, %3}, [%4];" : "=r"(a), "=r"(b), "=r"(c), "=r"(d) : "r"(p) : "memory");
}
__device__ __forceinline__ void wait_count(const unsigned int* p, uint32_t target) {
  asm volatile("{\n.reg .pred p;\n.reg .u32 n, v;\nmov.u32 n, 0;\n"
               "LOOP:\nld.acquire.gpu.global.u32 v, [%0];\nsetp.ge.u32 p, v, %1;\n@p bra DONE;\n"
               "nanosleep.u32 %2;\nadd.u32 n, n, 1;\nsetp.lt.u32 p, n, 0x400000;\n@p bra LOOP;\ntrap;\n"
               "DONE:\n}\n" ::"l"(p), "r"(target), "n"(300) : "memory");
}

__device__ __forceinline__ int o_wave(int a, int b, int i) {
  const int p = min(3, b - a - 1);
  return i < p ? b - 2 - i : i == p ? b - 1 : b - 1 - i;
}

struct Cursor {
  uint32_t n;
  __device__ __forceinline__ uint32_t off() const { return n & (8 * NBAR - 8); }
  __device__ __forceinline__ uint32_t ph() const { return (n / (8 * NBAR)) & 1; }
  __device__ __forceinline__ void next() { n += 8; }
};

constexpr float kScaleLog2 = 0.07216878364870322f * 1.4426950408889634f;
constexpr float kSumLimit = 1048576.0f;
constexpr float kMaxLag = 8.0f;

__global__ void __cluster_dims__(2, 1, 1) __launch_bounds__(384, 1)
fused_kernel(const __grid_constant__ Params P) {
  extern __shared__ uint8_t smem_raw[];
  const uint32_t sbase = (smem_u32(smem_raw) + 1023) & ~1023u;
  const uint32_t full0 = sbase + RING, empty0 = full0 + 8 * NBAR, odone = empty0 + 8 * NBAR, oready0 = odone + 8;
  const uint32_t fenced = oready0 + 64, hready0 = fenced + 8;
  const uint32_t rank = blockIdx.x & 1;
  const int role = blockIdx.x >> 1;
  const bool helper = role >= N_CL;
  const int team = helper ? 0 : role >> 2, nt = role & 3, blk = team >> 3;
  const uint32_t* prog = P.ops[helper ? N_TEAM + 2 * (role - N_CL) : team];
  auto q_role = [&](uint32_t op) { return helper ? (int)(((op >> 3) & 60) | ((op >> 12) & 3)) : role; };
  auto o_role = [&](uint32_t op) { return helper ? (int)(((op >> 26) & 56) | ((op >> 9) & 7)) : role; };
  const int wid = __shfl_sync(0xffffffffu, (int)(threadIdx.x >> 5), 0);
  const int wg = wid >> 2;

  const uint32_t op0 = P.first[helper ? N_TEAM + role - N_CL : team];
  if (__builtin_expect(wid == 8, 1)) {
    if (elect()) {
#pragma unroll
      for (int k = 0; k < EARLY; k++) mbar_init(full0 + 8 * k, 1);
      asm volatile("fence.mbarrier_init.release.cluster;" ::: "memory");
      if ((op0 & 3) == OP_Q) {
        const int qr = q_role(op0);
#pragma unroll
        for (int k = 0; k < EARLY; k++) {
          mbar_expect(full0 + 8 * k, SZ_WQ + SZ_A);
          tma2d(sbase + k * (SZ_WQ + SZ_A) + SZ_WQ, &P.x[qr >> 5], full0 + 8 * k, 64 * k, ((qr >> 2) & 7) * kSq + rank * 128);
          tma3d(sbase + k * (SZ_WQ + SZ_A), &P.wq[qr >> 5], full0 + 8 * k, 0, 64 * k, 3 * (4 * ((op0 >> 2) & 7) + (qr & 3)));
          tma3d(sbase + k * (SZ_WQ + SZ_A) + SZ_WQ / 2, &P.wq[qr >> 5], full0 + 8 * k, 0, 64 * k + 32, 3 * (4 * ((op0 >> 2) & 7) + (qr & 3)));
        }
      }
      asm volatile("prefetch.tensormap [%0];" ::"l"(&P.k[blk]) : "memory");
      asm volatile("prefetch.tensormap [%0];" ::"l"(&P.v[blk]) : "memory");
    }
  } else if (threadIdx.x == 0) {
#pragma unroll
    for (int i = EARLY; i < 2 * NBAR + 10 + MAX_PARK; i++) mbar_init(full0 + 8 * i, i >= NBAR && i <= 2 * NBAR ? 16 : 1);
    asm volatile("fence.mbarrier_init.release.cluster;" ::: "memory");
  }
  __syncwarp();
  asm volatile("barrier.cluster.arrive.relaxed.aligned;\nbarrier.cluster.wait.aligned;" ::: "memory");

  if (wg == 2) {
    asm volatile("setmaxnreg.dec.sync.aligned.u32 24;");
    if (wid == 8) {
      Cursor tail{0}, head{0};
      int sh = 0;
      uint32_t cur = 0, used = 0;
      uint64_t fifo = 0;
      uint32_t dst, bar, oready = oready0;
      const uint64_t pol = evict_first();
      auto acquire = [&](uint32_t bytes, int part = 0) {
        uint32_t fp = bytes >> 12;
        if (cur + fp > (RING >> 12)) { fp += (RING >> 12) - cur; cur = 0; }
        used += fp;
        bool more = false;
        uint32_t wbar, wph;
        while (used > (RING >> 12) || (part != 2 && sh == 5 * NFLIGHT)) {
          if (more) mbar_wait(wbar, wph);
          more = true;
          wbar = empty0 + tail.off(); wph = tail.ph();
          tail.next();
          used -= (uint32_t)fifo & 31;
          fifo >>= 5;
          sh -= 5;
        }
        fifo += (uint64_t)fp << sh;
        dst = sbase + (cur << 12);
        bar = full0 + head.off();
        cur += bytes >> 12;
        if (part != 1) {
          sh += 5;
          head.next();
        }
        if (more) mbar_wait(wbar, wph);
      };
      auto scratch = [&](const uint4* src, uint32_t bytes, int n) {
        asm volatile("fence.proxy.async.global;" ::: "memory");
#pragma unroll 1
        for (int i = 0; i < n; i++) {
          acquire(bytes);
          if (elect()) {
            bulk_load_hint(dst, src + i * (bytes / 16), bytes, bar, pol);
            mbar_expect(bar, bytes);
          }
        }
      };
      for (int pc = 0;; pc++) {
        const uint32_t op = prog[pc];
        const int type = op & 3, a = (op >> 2) & 7;
        if (type == OP_END) break;
        if (type == OP_Q) {
          const int qr = q_role(op);
#pragma unroll 1
          for (int k = 0; k < 10; k++) {
            acquire(SZ_WQ, 1);
            if ((pc > 0 || k >= EARLY) && elect()) tma3d_mc(dst + rank * (SZ_WQ / 2), &P.wq[qr >> 5], bar, 0, 64 * k + 32 * rank, 3 * (4 * a + (qr & 3)));
            acquire(SZ_A, 2);
            if ((pc > 0 || k >= EARLY) && elect()) {
              tma2d(dst, &P.x[qr >> 5], bar, 64 * k, ((qr >> 2) & 7) * kSq + rank * 128);
              mbar_expect(bar, SZ_WQ + SZ_A);
            }
          }
        } else if (type == OP_A) {
          const uint32_t nop = prog[pc + 1];
#pragma unroll 1
          for (int t = (op & F_PARK) ? 1 : 0; t < 33; t++) {
            int wave = a;
            if (t == 31 && (nop & 3) != OP_A) t++;
            if (t == 31) {
              wave = (nop >> 2) & 7;
              mbar_wait((nop & F_HELP) ? hready0 + 8 * ((nop >> 10) & 3) : fenced, 0);
              scratch(&g_o[((team * 2 + rank) * 96 + 3 * (4 * wave + nt)) * 1024], SZ_PARK, 2);
            }
            const int isv = t ? ~t & 1 : 0, j = (isv ? (t - 1) >> 1 : (t + 1) >> 1) & 15;
            const int row0 = ((team & 7) * kH + 4 * wave + nt) * kSk;
            if (t >= KV_TRANSIT) {
              const Cursor c{head.n - 8 * KV_TRANSIT};
              mbar_wait(full0 + c.off(), c.ph());
            }
            acquire(SZ_KV);
            if (elect()) {
              tma4d_mc_hint(dst + rank * (SZ_KV / 2), isv ? &P.v[blk] : &P.k[blk], bar, row0 / 8 + 8 * j + 4 * rank, pol);
              mbar_expect(bar, SZ_KV);
            }
          }
        } else {
          const int b = (op >> 5) & 15, ro = o_role(op);
#pragma unroll 1
          for (int i = 0; i < b - a; i++) {
            const int w = o_wave(a, b, i);
            mbar_wait(oready, 0);
            oready += 8;
            asm volatile("fence.proxy.async.global;" ::: "memory");
#pragma unroll 1
            for (int k = 12 * w; k < 12 * w + 12; k++) {
              acquire(SZ_A, 1);
              if (elect()) bulk_load_hint(dst, &g_o[(((ro >> 2) * 2 + rank) * 96 + k) * 1024], SZ_A, bar, pol);
              acquire(SZ_WO, 2);
              if (elect()) {
                tma5d_mc(dst + rank * 10240, &P.wo[ro >> 5], bar, 8 * k + 4 * rank, 5 * (ro & 3));
                mbar_expect(bar, SZ_WO + SZ_A);
              }
            }
          }
          if (op & F_LD) {
            if (op & F_PARK) mbar_wait(hready0 + 8 * (MAX_PARK - 1), 0);
            scratch(&g_part[(role * 2 + rank) * 5120], SZ_PART, 5);
          }
          if (!(op & F_ST)) {
            acquire(SZ_OUT);
            if (elect()) mbar_arrive(bar);
            __syncwarp();
            sh -= 5;
          }
        }
      }
      for (; sh > 0; sh -= 5) {
        mbar_wait(empty0 + tail.off(), tail.ph());
        tail.next();
      }
    } else if (threadIdx.x == 288) {
      uint32_t ph = 0;
      bool first = true;
      for (int pc = 0;; pc++) {
        const uint32_t op = prog[pc];
        if ((op & 3) == OP_END) break;
        if ((op & 3) != OP_A && !helper) continue;
        mbar_wait_long(odone, ph);
        ph ^= 1;
        unsigned int* flag = !helper ? &g_done[(team * 2 + rank) * 8 + ((op >> 2) & 7)]
                             : (op & 3) == OP_Q ? &g_help[(q_role(op) * 2 + rank) * MAX_PARK + ((op >> 10) & 3)]
                                                : &g_help[(o_role(op) * 2 + rank) * MAX_PARK + MAX_PARK - 1];
        asm volatile("red.release.gpu.global.add.u32 [%0], 1;" ::"l"(flag) : "memory");
        if (first) mbar_arrive(fenced);
        first = false;
      }
    } else if (threadIdx.x == 320) {
      uint32_t oready = oready0;
      for (int pc = 0;; pc++) {
        const uint32_t op = prog[pc];
        if ((op & 3) == OP_END) break;
        if ((op & 3) == OP_O) {
          const int a = (op >> 2) & 7, b = (op >> 5) & 15;
#pragma unroll 1
          for (int i = 0; i < b - a; i++) {
            const int ci = ((o_role(op) >> 2) * 2 + rank) * 8 + o_wave(a, b, i);
            wait_count(&g_done[ci], 4);
            mbar_arrive(oready);
            oready += 8;
            if (atomicAdd(&g_seen[ci], 1u) == 3u) { g_seen[ci] = 0; g_done[ci] = 0; }
          }
        }
        if ((op & 3) != OP_Q && (op & F_HELP) && (op & F_PARK)) {
          unsigned int* flag = &g_help[(role * 2 + rank) * MAX_PARK + ((op >> 10) & 3)];
          wait_count(flag, 1);
          mbar_arrive(hready0 + 8 * ((op >> 10) & 3));
          *flag = 0;
        }
      }
    }
  } else {
    asm volatile("setmaxnreg.inc.sync.aligned.u32 240;");
    const int lane = threadIdx.x & 31, warp = wid & 3;
    uint32_t empty_rem;
    asm volatile("mapa.shared::cluster.u32 %0, %1, %2;" : "=r"(empty_rem) : "r"(empty0), "r"(lane & 1));
    auto release = [&](int slot) { mbar_arrive_cluster_if(lane < 2, empty_rem + slot); };
    Cursor r{0};
    const uint32_t ring16 = (sbase & 0x3FFFF) >> 4;
    uint32_t cur = ring16;
    bool rdy0 = false, rdy1 = false;
    auto probe1 = [&]() { rdy0 = mbar_test(full0 + r.off(), r.ph()); };
    auto probe2 = [&]() {
      Cursor n = r;
      rdy0 = mbar_test(full0 + n.off(), n.ph());
      n.next();
      rdy1 = mbar_test(full0 + n.off(), n.ph());
    };
    auto take = [&](bool rdy, uint32_t bytes, uint32_t& addr) {
      const int bi = r.off();
      if (!__all_sync(0xffffffffu, rdy)) mbar_wait(full0 + r.off(), r.ph());
      r.next();
      if (cur > ring16 + ((RING - bytes) >> 4)) cur = ring16;
      addr = cur;
      cur += bytes >> 4;
      return bi;
    };
    auto second = [&](uint32_t bytes) {
      if (cur > ring16 + ((RING - bytes) >> 4)) cur = ring16;
      cur += bytes >> 4;
      return cur - (bytes >> 4);
    };
    const int row = wg * 64 + warp * 16 + (lane >> 2);
    int img0 = row * 4 + ((lane & 3) ^ ((row >> 1) & 3));
    uint4* pend = nullptr;
    const uint64_t spol = evict_first();
    int pc = 0;
    uint32_t op = prog[0];
    auto enter = [&]() {
      r.n = op >> 12; cur = ring16 + (((op >> 20) & 63) << 8);
    };
    auto drain = [&](uint32_t (&t)[48], uint32_t c) {
      if (!(op & (3u << 26)) || c >= 6) return;
#pragma unroll
      for (int i = 0; i < 6; i++)
        stg2_if(c == i, pend + i * 512, t[8 * i], t[8 * i + 1], t[8 * i + 2], t[8 * i + 3],
                t[8 * i + 4], t[8 * i + 5], t[8 * i + 6], t[8 * i + 7], spol);
      if ((op & (1u << 26)) && c == 5) {
        __syncwarp();
        mbar_arrive_if(lane < 2, odone);
      }
    };
    float s[32], o[96], c[80];
    uint32_t q[48], pa[16], pb[16];
    float mc0, mc1, l0, l1;
    bool gen;
    auto soft = [&](float (&s)[32], uint32_t (&pout)[16], bool first) {
      if (first) { gen = false; mc0 = 0.f; mc1 = 0.f; }
      float b0, b1;
      for (;;) {
        if (gen) {
          float m0 = fmaxf(s[0], s[1]), m1 = fmaxf(s[2], s[3]);
#pragma unroll
          for (int i = 1; i < 8; i++) { m0 = fmaxf(m0, fmaxf(s[4 * i], s[4 * i + 1])); m1 = fmaxf(m1, fmaxf(s[4 * i + 2], s[4 * i + 3])); }
          m0 = fmaxf(m0, __shfl_xor_sync(0xffffffffu, m0, 1)); m1 = fmaxf(m1, __shfl_xor_sync(0xffffffffu, m1, 1));
          m0 = fmaxf(m0, __shfl_xor_sync(0xffffffffu, m0, 2)); m1 = fmaxf(m1, __shfl_xor_sync(0xffffffffu, m1, 2));
          if (first) {
            mc0 = m0; mc1 = m1;
          } else if (__any_sync(0xffffffffu, !(m0 <= mc0 + kMaxLag && m1 <= mc1 + kMaxLag))) {
            m0 = fmaxf(mc0, m0); m1 = fmaxf(mc1, m1);
            const float a0 = ex2(mc0 - m0), a1 = ex2(mc1 - m1);
            mc0 = m0; mc1 = m1;
            l0 *= a0; l1 *= a1;
            wg_wait<0>();
            fence_regs(o);
#pragma unroll
            for (int i = 0; i < 96; i++) o[i] *= i & 2 ? a1 : a0;
          }
#pragma unroll
          for (int i = 0; i < 32; i++) s[i] -= i & 2 ? mc1 : mc0;
        }
#pragma unroll
        for (int i = 0; i < 8; i++) {
          const float e1 = ex2(s[4 * i + 1]), e0 = ex2(s[4 * i]), e3 = ex2(s[4 * i + 3]), e2 = ex2(s[4 * i + 2]);
          pout[2 * i] = pack_bf16(e0, e1);
          b0 = i ? b0 + fadd(e1, e0) : fadd(e1, e0);
          pout[2 * i + 1] = pack_bf16(e2, e3);
          b1 = i ? b1 + fadd(e3, e2) : fadd(e3, e2);
        }
        if (!__any_sync(0xffffffffu, !gen && !(fmaxf(b0, b1) <= kSumLimit && (!first || fminf(b0, b1) >= 1.0f / kSumLimit)))) break;
        gen = __any_sync(0xffffffffu, true);
      }
      l0 = first ? b0 : l0 + b0;
      l1 = first ? b1 : l1 + b1;
    };
    auto qk = [&](float (&s)[32], uint32_t ak, int k0, int k1) {
#pragma unroll
      for (int kk = k0; kk < k1; kk++)
        wgmma_rs_n64<0>(s, q[4 * kk], q[4 * kk + 1], q[4 * kk + 2], q[4 * kk + 3], mk_desc(ak, 16, KV_SBO, 1, (kk >> 2) * KV_CH + (kk & 3) * 2), kk != 0);
      wg_commit();
    };
    auto pv = [&](uint32_t (&pin)[16], uint32_t av, int acc) {
#pragma unroll
      for (int kk = 0; kk < 4; kk++)
        wgmma_rs_n192<1>(o, pin[4 * kk], pin[4 * kk + 1], pin[4 * kk + 2], pin[4 * kk + 3], mk_desc(av, KV_CH * 16, KV_SBO, 1, kk * (KV_SBO / 8)), acc || (kk != 0));
      wg_commit();
    };
    auto xw = [&](uint32_t ad, int acc) {
      const uint32_t da = second(SZ_A) + wg * 512;
      wg_fence();
#pragma unroll
      for (int kk = 0; kk < 4; kk++)
        wgmma_ss_n192<1>(o, mk_desc(da, 16, 1024, 1, kk * 2), mk_desc(ad, 4096, 1024, 1, (kk & 1) * 128 + (kk >> 1) * 768), acc || kk != 0);
      wg_commit();
    };
    auto ow = [&](int acc, int prev) {
      uint32_t da;
      const int bi = take(rdy0, SZ_A, da);
      const uint32_t db = second(SZ_WO);
      da += wg * 256;
      wg_fence();
      wgmma_ss_n160<1>(c, mk_desc(da, 16, 512, 2), mk_desc(db, 2048, 512, 2), acc);
      wgmma_ss_n160<1>(c, mk_desc(da, 16, 512, 2, 2), mk_desc(db, 2048, 512, 2, 64), 1);
      wg_commit();
      if (acc == 1) { wg_wait<1>(); release(prev); }
      wgmma_ss_n160<1>(c, mk_desc(da, 16, 512, 2, 512), mk_desc(db, 2048, 512, 2, 640), 1);
      wgmma_ss_n160<1>(c, mk_desc(da, 16, 512, 2, 514), mk_desc(db, 2048, 512, 2, 704), 1);
      wg_commit();
      return bi;
    };
    auto st_part = [&](int i) {
      stg2_if(true, pend + i * 512, __float_as_uint(c[8 * i]), __float_as_uint(c[8 * i + 1]), __float_as_uint(c[8 * i + 2]), __float_as_uint(c[8 * i + 3]),
              __float_as_uint(c[8 * i + 4]), __float_as_uint(c[8 * i + 5]), __float_as_uint(c[8 * i + 6]), __float_as_uint(c[8 * i + 7]), spol);
    };
#pragma unroll
    for (int i = 0; i < 48; i++) q[i] = 0;
    enter();

    if ((op & 3) == OP_Q) {
      uint32_t ad;
      int bi0 = take(false, SZ_WQ, ad), k = 0, lag = 0;
      xw(ad, 0);
      for (;;) {
#pragma unroll 1
        for (;;) {
          drain(q, k - lag);
          probe1();
          wg_wait<0>();
          release(bi0);
          bi0 = take(rdy0, SZ_WQ, ad);
          if (++k == 8) break;
          xw(ad, 1);
        }
        if (wg) bar_sync(2, 256);
        xw(ad, 1);
        const int bi9 = take(false, SZ_WQ, ad);
        xw(ad, 1);
        if (!wg) asm volatile("bar.arrive 2, 256;" ::: "memory");
        k = 0; lag = 0;
        uint32_t nop = prog[++pc];
        wg_wait<1>();
        release(bi0);
        probe2();
        wg_wait<0>();
        fence_regs(o);
        release(bi9);
#pragma unroll
        for (int i = 0; i < 48; i++) q[i] = pack_bf16(o[2 * i] * kScaleLog2, o[2 * i + 1] * kScaleLog2);
        fence_regs(q);
        if (op & F_PARK) {
          const int qt = helper ? (op >> 5) & 15 : team, qm = helper ? (op >> 12) & 3 : nt;
          pend = &g_o[((qt * 2 + rank) * 96 + 3 * (4 * ((op >> 2) & 7) + qm)) * 1024 + img0];
          op = nop;
          enter();
          if ((op & 3) != OP_Q) break;
          bi0 = take(rdy0, SZ_WQ, ad);
          xw(ad, 0);
          continue;
        }
        int wave = (op >> 2) & 7, sk1;
        uint32_t ak1;
        {
          float s0[32];
          const int sk0 = take(rdy0, SZ_KV, ad);
          wg_fence();
          qk(s0, ad, 0, 12);
          sk1 = take(rdy1, SZ_KV, ak1);
          wg_fence();
          qk(s, ak1, 0, S1A);
          probe1();
          wg_wait<1>();
          fence_regs(s0);
          release(sk0);
          soft(s0, pa, true);
        }
        float i0, i1;
        auto sums = [&]() {
          l0 += __shfl_xor_sync(0xffffffffu, l0, 1); l1 += __shfl_xor_sync(0xffffffffu, l1, 1);
          l0 += __shfl_xor_sync(0xffffffffu, l0, 2); l1 += __shfl_xor_sync(0xffffffffu, l1, 2);
          i0 = rcp(l0); i1 = rcp(l1);
          asm volatile("" : "+f"(i0), "+f"(i1));
        };
        auto target = [&]() {
          pend = &g_o[((team * 2 + rank) * 96 + 3 * (4 * wave + nt)) * 1024 + img0];
          asm volatile("" : "+l"(pend));
        };
        bool late = false;
#pragma unroll
        for (int i = 0; i < 16; i++) pb[i] = 0;
        for (;;) {
          nop = prog[++pc];
          {
            uint32_t av;
            const int sv = take(rdy0, SZ_KV, av);
            wg_fence();
            qk(s, ak1, S1A, 12);
            pv(pa, av, 0);
            if (late) {
              stg2_if(true, pend + 4 * 512, pb[0], pb[1], pb[2], pb[3], pb[4], pb[5], pb[6], pb[7], spol);
              stg2_if(true, pend + 5 * 512, pb[8], pb[9], pb[10], pb[11], pb[12], pb[13], pb[14], pb[15], spol);
              __syncwarp();
              mbar_arrive_if(lane < 2, odone);
            }
            probe2();
            wg_wait<1>();
            fence_regs(s);
            release(sk1);
            soft(s, pb, false);
            wg_wait<0>();
            fence_regs(o);
            release(sv);
          }
          auto step = [&](uint32_t (&pin)[16], uint32_t (&pout)[16]) {
            uint32_t ak, av;
            const int sk = take(rdy0, SZ_KV, ak), sv = take(rdy1, SZ_KV, av);
            wg_fence();
            qk(s, ak, 0, 12);
            pv(pin, av, 1);
            probe2();
            wg_wait<1>();
            fence_regs(s);
            release(sk);
            soft(s, pout, false);
            wg_wait<0>();
            fence_regs(o);
            release(sv);
          };
#pragma unroll 1
          for (int jj = 0; jj < 7; jj++) {
            step(pb, pa);
            step(pa, pb);
          }
          if ((nop & 3) != OP_A) break;
          uint32_t ak, av;
          {
            const int b0 = take(rdy0, SZ_PARK, ak), b1 = take(rdy1, SZ_PARK, av);
            const uint32_t ad0 = ak, ad1 = av;
            probe2();
#pragma unroll
            for (int i = 0; i < 12; i++)
              lds128(sbase + ((i < 6 ? ad0 : ad1) - ring16 + img0) * 16 + ((i % 6) >> 1) * 8192 + (i & 1) * 512, q[4 * i], q[4 * i + 1], q[4 * i + 2], q[4 * i + 3]);
            release(b0); release(b1);
          }
          const int sk0 = take(rdy0, SZ_KV, ak), sv = take(rdy1, SZ_KV, av);
          wg_fence();
          qk(s, ak, 0, 8);
          sched_fence(img0, P.zero);
          sums();
          sched_fence(img0, P.zero);
          qk(s, ak, 8, 12);
          pv(pb, av, 1);
          probe2();
          wg_wait<1>();
          fence_regs(s);
          release(sk0);
          soft(s, pa, true);
          sk1 = take(rdy0, SZ_KV, ak1);
          rdy0 = rdy1;
          wg_wait<0>();
          target();
          fence_regs(o);
          release(sv);
          uint32_t t[48];
#pragma unroll
          for (int j = 0; j < 6; j++) {
#pragma unroll
            for (int i = 0; i < 4; i++) {
              t[8 * j + i] = pack_bf16(o[16 * j + 4 * i] * i0, o[16 * j + 4 * i + 1] * i0);
              t[8 * j + i + 4] = pack_bf16(o[16 * j + 4 * i + 2] * i1, o[16 * j + 4 * i + 3] * i1);
            }
            if (j < 4)
            stg2_if(true, pend + j * 512, t[8 * j], t[8 * j + 1], t[8 * j + 2], t[8 * j + 3], t[8 * j + 4], t[8 * j + 5], t[8 * j + 6], t[8 * j + 7], spol);
            if (j == 3) { wg_fence(); qk(s, ak1, 0, 4); }
            if (j == 5) { wg_fence(); qk(s, ak1, 4, S1A); }
            sched_fence(img0, P.zero);
          }
          if (P.zero) {
#pragma unroll
            for (int j = 0; j < 4; j++)
              stg2_if(true, pend, t[8 * j], t[8 * j + 1], t[8 * j + 2], t[8 * j + 3], t[8 * j + 4], t[8 * j + 5], t[8 * j + 6], t[8 * j + 7], spol);
          }
          late = true;
#pragma unroll
          for (int i = 0; i < 16; i++) pb[i] = t[32 + i];
          wave = (nop >> 2) & 7;
        }
        const int sv = take(rdy0, SZ_KV, ad);
        wg_fence();
        pv(pb, ad, 1);
        sums();
        target();
        op = nop;
        enter();
        rdy0 = rdy1;
        auto convert = [&](float (&u)[96], int j0, int j1) {
#pragma unroll
          for (int i = 4 * j0; i < 4 * j1; i++) {
            q[8 * (i >> 2) + (i & 3)] = pack_bf16(u[4 * i], u[4 * i + 1]);
            q[8 * (i >> 2) + (i & 3) + 4] = pack_bf16(u[4 * i + 2], u[4 * i + 3]);
          }
        };
        if ((op & 3) != OP_O) {
          if ((op & 3) == OP_Q) bi0 = take(rdy0, SZ_WQ, ad);
          wg_wait<0>();
          fence_regs(o);
          release(sv);
          float u[96];
#pragma unroll
          for (int i = 0; i < 96; i++) u[i] = o[i] * (i & 2 ? i1 : i0);
          if ((op & 3) != OP_Q) { convert(u, 0, 6); break; }
          fence_regs(u);
          xw(ad, 0);
          sched_fence(img0, P.zero);
          fence_regs(u);
          convert(u, 0, 1);
          stg2_if(true, pend, q[0], q[1], q[2], q[3], q[4], q[5], q[6], q[7], spol);
          probe1();
          wg_wait<0>();
          release(bi0);
          bi0 = take(rdy0, SZ_WQ, ad);
          xw(ad, 1);
          sched_fence(img0, P.zero);
          fence_regs(u);
          convert(u, 1, 6);
          k = 1;
          continue;
        }
        int bi = ow(0, 0);
        wg_wait<2>();
        fence_regs(o);
        release(sv);
#pragma unroll
        for (int j = 0; j < 6; j++) {
          uint32_t t[8];
#pragma unroll
          for (int i = 0; i < 4; i++) {
            t[i] = pack_bf16(o[16 * j + 4 * i] * i0, o[16 * j + 4 * i + 1] * i0);
            t[i + 4] = pack_bf16(o[16 * j + 4 * i + 2] * i1, o[16 * j + 4 * i + 3] * i1);
          }
          stg2_if(true, pend + j * 512, t[0], t[1], t[2], t[3], t[4], t[5], t[6], t[7], spol);
          if (j == 5) {
            __syncwarp();
            mbar_arrive_if(lane < 2, odone);
          }
          probe1();
          wg_wait<1>();
          bi = ow(1, bi);
          fence_regs(o);
        }
        {
          const int nk = 12 * (((op >> 5) & 15) - ((op >> 2) & 7)) - ((op & F_ST) ? 0 : 2);
#pragma unroll 1
          for (int k = 7; k < nk; k++) {
            probe1();
            wg_wait<1>();
            bi = ow(1, bi);
          }
        }
        if (!(op & F_ST)) {
          probe2();
          wg_wait<1>();
          if (wg) {
            wg_wait<0>();
            release(bi);
            bar_sync(2, 256);
          }
          bi0 = ow(2, 0);
          rdy0 = rdy1;
          const int b = ow(2, 0);
          if (!wg) asm volatile("bar.arrive 2, 256;" ::: "memory");
          wg_wait<4>();
          mbar_arrive_cluster_if(lane < 2 && !wg, empty_rem + bi);
          bi = b;
        }
        probe1();
        nop = prog[++pc];
        if (op & F_LD) {
          uint32_t t[80];
#pragma unroll
          for (int j = 0; j < 5; j++) {
            const int b = take(rdy0, SZ_PART, ad);
            probe1();
#pragma unroll
            for (int i = 4 * j; i < 4 * j + 4; i++)
              lds128(sbase + (ad - ring16 + img0) * 16 + ((i >> 1) & 1) * 8192 + (i & 1) * 512, t[4 * i], t[4 * i + 1], t[4 * i + 2], t[4 * i + 3]);
            release(b);
          }
          wg_wait<0>();
          fence_regs(c);
#pragma unroll
          for (int i = 0; i < 80; i++) c[i] += __uint_as_float(t[i]);
        }
        if (!(op & F_ST)) {
          wg_wait<0>();
          fence_regs(c);
          release(bi0);
          release(bi);
          goto finish;
        }
        op = nop;
        enter();
        bi0 = take(rdy0, SZ_WQ, ad);
        xw(ad, 0);
        pend = &g_part[((team * 4 + nt) * 2 + rank) * 5120 + img0];
        probe1();
        wg_wait<1>();
        fence_regs(c);
        release(bi);
        st_part(0); st_part(1);
        wg_wait<0>();
        release(bi0);
        bi0 = take(rdy0, SZ_WQ, ad);
        xw(ad, 1);
        st_part(2); st_part(3);
#pragma unroll
        for (int i = 0; i < 48; i++) q[i] = __float_as_uint(c[32 + i]);
        pend += 4 * 512;
        k = 1; lag = 2;
      }
    }
    rdy0 = false;
    {
      uint32_t t[48];
#pragma unroll
      for (int i = 0; i < 48; i++) t[i] = q[i] ^ P.zero;
      while ((op & 3) == OP_O) {
        int bi = ow(0, 0);
#pragma unroll 1
        for (int k = 1; k < 12 * (int)(((op >> 5) & 15) - ((op >> 2) & 7)); k++) {
          drain(t, k - 1);
          probe1();
          wg_wait<1>();
          bi = ow(1, bi);
        }
        rdy0 = false;
        wg_wait<0>();
        fence_regs(c);
        pc++;
        release(bi);
        if (!(op & F_ST)) goto finish;
        pend = &g_part[((((op >> 26) & 56) | ((op >> 9) & 7)) * 2 + rank) * 5120 + img0];
#pragma unroll
        for (int i = 6; i < 10; i++) st_part(i);
#pragma unroll
        for (int i = 0; i < 48; i++) t[i] = __float_as_uint(c[i]) ^ P.zero;
        op = prog[pc];
        enter();
      }
      for (int i = 0; i < 6; i++) drain(t, i);
    }
    if (false) {
    finish:
      uint32_t ad;
      take(rdy0, SZ_OUT, ad);
      const uint32_t wstage = sbase + (ad - ring16) * 16 + (wg * 4 + warp) * 5120;
      const uint32_t sa = wstage + (lane & 15) * 64;
#pragma unroll
      for (int i = 0; i < 10; i++) {
        const int u = (i & 1) * 2 + (lane >> 4);
        stsm4(sa + (i >> 1) * 1024 + ((u ^ ((lane >> 1) & 3)) << 4), pack_bf16(c[8 * i], c[8 * i + 1]), pack_bf16(c[8 * i + 2], c[8 * i + 3]),
              pack_bf16(c[8 * i + 4], c[8 * i + 5]), pack_bf16(c[8 * i + 6], c[8 * i + 7]));
      }
      asm volatile("fence.proxy.async.shared::cta;" ::: "memory");
      __syncwarp();
      if (lane == 0) {
        tma3d_store(&P.out, wstage, 0, (team & 7) * kSq + rank * 128 + wg * 64 + warp * 16, blk * 20 + nt * 5);
        asm volatile("cp.async.bulk.commit_group;\ncp.async.bulk.wait_group.read 0;" ::: "memory");
      }
    }
  }
}

typedef CUresult (*EncodeFn)(CUtensorMap*, CUtensorMapDataType, cuuint32_t, void*, const cuuint64_t*, const cuuint64_t*,
                             const cuuint32_t*, const cuuint32_t*, CUtensorMapInterleave, CUtensorMapSwizzle,
                             CUtensorMapL2promotion, CUtensorMapFloatOOBfill);

void encode(EncodeFn fn, CUtensorMap* m, const void* ptr, int rank, const cuuint64_t* dims, const cuuint64_t* strides,
            const cuuint32_t* box, CUtensorMapSwizzle swz) {
  const cuuint32_t es[5] = {1, 1, 1, 1, 1};
  CUresult r = fn(m, CU_TENSOR_MAP_DATA_TYPE_BFLOAT16, rank, const_cast<void*>(ptr), dims, strides, box, es,
                  CU_TENSOR_MAP_INTERLEAVE_NONE, swz, CU_TENSOR_MAP_L2_PROMOTION_L2_128B, CU_TENSOR_MAP_FLOAT_OOB_FILL_NONE);
  if (r != CUDA_SUCCESS) fprintf(stderr, "cuTensorMapEncodeTiled failed: %d\n", (int)r);
}

void annotate(uint32_t* ops, int n, bool helper) {
  uint32_t items = 0, cur = 0, pend = 0;
  auto item = [&](uint32_t bytes, int count, uint32_t bytes2 = 0) {
    for (int i = 0; i < count; i++) {
      if (cur + bytes > RING) cur = 0;
      cur += bytes;
      if (cur + bytes2 > RING) cur = 0;
      cur += bytes2;
      items++;
    }
  };
  for (int i = 0; i <= n; i++) {
    const uint32_t op = ops[i];
    ops[i] |= (items % (2 * NBAR)) << 15 | (cur >> 12) << 20 | pend << 26;
    if ((op & 3) == OP_Q) { item(SZ_WQ, 10, SZ_A); pend = (op & F_PARK) ? (helper ? 1 : 2) : 0; }
    if ((op & 3) == OP_A) {
      item(SZ_KV, (op & F_PARK) ? 30 : 31);
      if ((ops[i + 1] & 3) == OP_A) { item(SZ_PARK, 2); item(SZ_KV, 1); }
      item(SZ_KV, 1);
      pend = 1;
    }
    if ((op & 3) == OP_O) {
      item(SZ_A, 12 * (((op >> 5) & 15) - ((op >> 2) & 7)), SZ_WO);
      if (op & F_LD) item(SZ_PART, 5);
      pend = (op & F_ST) ? (helper ? 1 : 2) : 0;
    }
  }
}

void compile_programs(const char* const* text, bool helpers, Params& P) {
  struct Req { int when, team, wave, slot; } req[N_TEAM * MAX_PARK];
  int n_req = 0;
  for (int t = 0; t < N_TEAM; t++) {
    uint32_t* ops = P.ops[t];
    int n = 0, flags[8] = {0, 0, 0, 0, 0, 0, 0, 0}, n_park = 0, last_o = -1, when = 0, given = 0;
    for (const char* s = text[t]; *s; s++) {
      const int a = s[1] - '0';
      if (*s == 'Q' || (*s == 'H' && !helpers)) { ops[n++] = OP_Q | a << 2; when += 10; }
      else if (*s == 'P') { flags[a] = F_PARK; ops[n++] = OP_Q | a << 2 | flags[a]; when += 10; }
      else if (*s == 'H') { req[n_req++] = {when, t, a, n_park}; flags[a] = F_PARK | F_HELP | n_park++ << 10; }
      else if (*s == 'A') { ops[n++] = OP_A | a << 2 | flags[a]; when += 32; }
      else if (*s == 'G') { given = a; if (helpers) req[n_req++] = {1000, t, 0, -a}; }
      else if (*s == 'O') {
        ops[n] = OP_O | a << 2 | (s[2] - '0') << 5;
        if (given) ops[n] = helpers ? ops[n] | F_LD | F_PARK | (MAX_PARK - 1) << 10 : ops[n] & ~(7u << 2);
        if (last_o >= 0) { ops[last_o] |= F_ST; ops[n] |= F_LD; }
        last_o = n++;
        when += 10 * (s[2] - s[1]);
      }
    }
    for (int i = n; i < MAX_OPS; i++) ops[i] = OP_END;
    annotate(ops, n, false);
  }
  for (int i = 1; i < n_req; i++)
    for (int j = i; j > 0 && req[j].when < req[j - 1].when; j--) { Req r = req[j]; req[j] = req[j - 1]; req[j - 1] = r; }
  for (int h = 0; h < N_HELP; h++) {
    uint32_t* ops = P.ops[N_TEAM + 2 * h];
    int n = 0;
    for (int i = 0; i < n_req; i++)
      for (int m = h; m < 4; m += N_HELP) {
        const uint32_t ro = 4 * req[i].team + m;
        ops[n++] = req[i].slot >= 0 ? OP_Q | req[i].wave << 2 | req[i].team << 5 | F_PARK | req[i].slot << 10 | m << 12
                                    : OP_O | -req[i].slot << 5 | F_ST | (ro & 7) << 9 | (ro >> 3) << 29;
      }
    for (int i = n; i < 2 * MAX_OPS; i++) ops[i] = OP_END;
    annotate(ops, n, true);
  }
  for (int i = 0; i < 32; i++) P.first[i] = i < N_TEAM ? P.ops[i][0] : i < N_TEAM + N_HELP ? P.ops[2 * i - N_TEAM][0] : 0;
}

const char* const kPrograms[N_TEAM] = {
  "Q0A0Q1A1H2A2O03Q3A3Q4A4Q5A5Q6A6Q7A7O38",
  "Q0A0Q1A1Q2A2Q3A3O04Q4A4Q5A5Q6A6H7A7O48",
  "Q0A0H1A1Q2A2Q3A3Q4A4O05Q5A5Q6A6Q7A7O58",
  "Q0A0Q1A1Q2A2O03Q3A3Q4A4Q5A5Q6A6H7A7O38",
  "Q0A0Q1A1Q2A2O03Q3A3H4A4Q5A5Q6A6Q7A7O38",
  "Q0A0Q1A1H2A2Q3A3Q4A4O05Q5A5Q6A6Q7A7O58",
  "Q0A0Q1A1Q2A2Q3A3O03Q4A4H5A5Q6A6Q7A7O38",
  "Q0A0Q1A1Q2A2Q3A3Q4A4O05Q5A5Q6A6H7A7O58",
  "P3Q0A0Q1A1Q2A2A3H4A4Q5A5Q6A6Q7A7O08",
  "P5P7Q0A0Q1A1Q2A2H3A3Q4A4A5Q6A6A7G1O18",
  "Q0A0Q1A1Q2A2O02Q3A3H4A4Q5A5Q6A6Q7A7O28",
  "P3P5Q0A0Q1A1Q2A2A3Q4A4A5Q6A6H7A7O08",
  "Q0A0Q1A1Q2A2O02Q3A3Q4A4H5A5Q6A6Q7A7O28",
  "P7Q0A0Q1A1Q2A2Q3A3Q4A4Q5A5Q6A6A7G1O18",
  "P5Q0A0Q1A1Q2A2Q3A3Q4A4A5Q6A6H7A7O08",
  "Q0A0Q1A1Q2A2H3A3Q4A4Q5A5Q6A6Q7A7O08",
};

const char* const* bench_programs() {
  return kPrograms;
}

}

extern "C" void kernel_launch(void* const* d_in, const int* in_sizes, int n_in, void* d_out, int out_size) {
  (void)in_sizes; (void)n_in; (void)out_size;
  static EncodeFn fn = nullptr;
  static int n_clusters = 0;
  if (!fn) {
    cudaDriverEntryPointQueryResult qr;
    void* f = nullptr;
    cudaGetDriverEntryPoint("cuTensorMapEncodeTiled", &f, cudaEnableDefault, &qr);
    fn = (EncodeFn)f;
    cudaFuncSetAttribute(fused_kernel, cudaFuncAttributeMaxDynamicSharedMemorySize, SMEM_BYTES);
    cudaLaunchConfig_t cfg = {};
    cfg.gridDim = dim3(132); cfg.blockDim = dim3(384); cfg.dynamicSmemBytes = SMEM_BYTES;
    cudaLaunchAttribute at[1];
    at[0].id = cudaLaunchAttributeClusterDimension; at[0].val.clusterDim.x = 2; at[0].val.clusterDim.y = 1; at[0].val.clusterDim.z = 1;
    cfg.attrs = at; cfg.numAttrs = 1;
    if (cudaOccupancyMaxActiveClusters(&n_clusters, fused_kernel, &cfg) != cudaSuccess || n_clusters < 1) n_clusters = 1;
    (void)cudaGetLastError();
  }
  Params P;
  const CUtensorMapSwizzle S128 = CU_TENSOR_MAP_SWIZZLE_128B, S64 = CU_TENSOR_MAP_SWIZZLE_64B;
  for (int blk = 0; blk < 2; blk++) {
    void* const* in = d_in + 5 * blk;
    { const cuuint64_t d[] = {kD, kB * kSq}, s[] = {kD * 2}; const cuuint32_t b[] = {64, 128};
      encode(fn, &P.x[blk], in[0], 2, d, s, b, S128); }
    { const cuuint64_t d[] = {64, 8, 3, (cuuint64_t)kB * kH * kSk / 8}, s[] = {kDh * 2, 128, 8 * kDh * 2}; const cuuint32_t b[] = {64, 8, 3, 4};
      encode(fn, &P.k[blk], in[1], 4, d, s, b, S128);
      encode(fn, &P.v[blk], in[2], 4, d, s, b, S128); }
    { const cuuint64_t d[] = {64, kD, kHD / 64}, s[] = {kHD * 2, 128}; const cuuint32_t b[] = {64, 32, 3};
      encode(fn, &P.wq[blk], in[3], 3, d, s, b, S128); }
    { const cuuint64_t d[] = {32, 2, kHD / 8, 4, kD / 32}, s[] = {kD * 2, 8 * kD * 2, 2 * kD * 2, 64}; const cuuint32_t b[] = {32, 2, 4, 4, 5};
      encode(fn, &P.wo[blk], in[4], 5, d, s, b, S64); }
  }
  { const cuuint64_t d[] = {32, kB * kSq, 2 * kD / 32}, s[] = {2 * kD * 2, 64}; const cuuint32_t b[] = {32, 16, 5};
    encode(fn, &P.out, d_out, 3, d, s, b, S64); }

  P.zero = 0;
  if (n_clusters >= N_CL) {
    const bool helpers = n_clusters >= N_CL + N_HELP;
    compile_programs(bench_programs(), helpers, P);
    fused_kernel<<<2 * (N_CL + (helpers ? N_HELP : 0)), 384, SMEM_BYTES>>>(P);
  } else {
    for (int phase = 0; phase < 2; phase++) {
      const char* text[N_TEAM];
      for (int t = 0; t < N_TEAM; t++) text[t] = phase ? "O08" : "Q0A0Q1A1Q2A2Q3A3Q4A4Q5A5Q6A6Q7A7";
      compile_programs(text, false, P);
      fused_kernel<<<2 * N_CL, 384, SMEM_BYTES>>>(P);
    }
  }
}
```

```cpp
#include <cuda_runtime.h>
#include <cuda_bf16.h>
#include <cuda.h>
#include <stdint.h>
#include <stdio.h>

namespace {

constexpr int kB = 8, kSq = 256, kD = 640, kH = 32, kSk = 1024, kDh = 192;
constexpr int kHD = kH * kDh;
constexpr uint32_t RING = 224 * 1024;
constexpr uint32_t SZ_KV = 24576;
constexpr uint32_t SZ_WQ = 24576, SZ_WO = 20480, SZ_A = 16384;
constexpr uint32_t SZ_OUT = 40960;
constexpr uint32_t SZ_PARK = 24576;
constexpr uint32_t SZ_PART = 16384;
constexpr int NBAR = 16, NFLIGHT = 12;
constexpr int KV_TRANSIT = 4;
constexpr int EARLY = 3;
constexpr int S1A = 7;
constexpr uint32_t KV_CH = 64, KV_SBO = 3072;
constexpr int SMEM_BYTES = RING + 512 + 1024;
constexpr int N_TEAM = 16, N_CL = 64, N_HELP = 2, MAX_OPS = 24, MAX_PARK = 4;
enum { OP_END = 0, OP_Q = 1, OP_A = 2, OP_O = 3, F_PARK = 1 << 9, F_LD = 1 << 12, F_ST = 1 << 13, F_HELP = 1 << 12 };

struct alignas(64) Params {
  uint32_t first[32];
  CUtensorMap x[2], wq[2], k[2], v[2], wo[2], out;
  uint32_t ops[N_TEAM + 2 * N_HELP][MAX_OPS];
  uint32_t zero;
};

__device__ uint4 g_o[N_TEAM * 2 * 96 * 1024];
__device__ uint4 g_part[N_CL * 2 * 5 * 1024];
__device__ unsigned int g_done[N_TEAM * 2 * 8];
__device__ unsigned int g_help[N_CL * 2 * MAX_PARK];
__device__ unsigned int g_seen[N_TEAM * 2 * 8];

template <int TB>
__device__ __forceinline__ void wgmma_rs_n64(float (&d)[32], uint32_t a0, uint32_t a1, uint32_t a2, uint32_t a3, uint64_t db, int scale_d) {
  asm volatile("{\n.reg .pred p;\nsetp.ne.b32 p, %37, 0;\n"
    "wgmma.mma_async.sync.aligned.m64n64k16.f32.bf16.bf16 {%0, %1, %2, %3, %4, %5, %6, %7, %8, %9, %10, %11, %12, %13, %14, %15, %16, %17, %18, %19, %20, %21, %22, %23, %24, %25, %26, %27, %28, %29, %30, %31}, {%32, %33, %34, %35}, %36, p, 1, 1, %38;\n}\n"
    : "+f"(d[0]), "+f"(d[1]), "+f"(d[2]), "+f"(d[3]), "+f"(d[4]), "+f"(d[5]), "+f"(d[6]), "+f"(d[7]), "+f"(d[8]), "+f"(d[9]), "+f"(d[10]), "+f"(d[11]), "+f"(d[12]), "+f"(d[13]), "+f"(d[14]), "+f"(d[15]), "+f"(d[16]), "+f"(d[17]), "+f"(d[18]), "+f"(d[19]), "+f"(d[20]), "+f"(d[21]), "+f"(d[22]), "+f"(d[23]), "+f"(d[24]), "+f"(d[25]), "+f"(d[26]), "+f"(d[27]), "+f"(d[28]), "+f"(d[29]), "+f"(d[30]), "+f"(d[31])
    : "r"(a0), "r"(a1), "r"(a2), "r"(a3), "l"(db), "r"(scale_d), "n"(TB));
}
template <int TB, int TA = 0>
__device__ __forceinline__ void wgmma_ss_n160(float (&d)[80], uint64_t da, uint64_t db, int scale_d) {
  asm volatile("{\n.reg .pred p;\nsetp.ne.b32 p, %82, 0;\n"
    "wgmma.mma_async.sync.aligned.m64n160k16.f32.bf16.bf16 {%0, %1, %2, %3, %4, %5, %6, %7, %8, %9, %10, %11, %12, %13, %14, %15, %16, %17, %18, %19, %20, %21, %22, %23, %24, %25, %26, %27, %28, %29, %30, %31, %32, %33, %34, %35, %36, %37, %38, %39, %40, %41, %42, %43, %44, %45, %46, %47, %48, %49, %50, %51, %52, %53, %54, %55, %56, %57, %58, %59, %60, %61, %62, %63, %64, %65, %66, %67, %68, %69, %70, %71, %72, %73, %74, %75, %76, %77, %78, %79}, %80, %81, p, 1, 1, %83, %84;\n}\n"
    : "+f"(d[0]), "+f"(d[1]), "+f"(d[2]), "+f"(d[3]), "+f"(d[4]), "+f"(d[5]), "+f"(d[6]), "+f"(d[7]), "+f"(d[8]), "+f"(d[9]), "+f"(d[10]), "+f"(d[11]), "+f"(d[12]), "+f"(d[13]), "+f"(d[14]), "+f"(d[15]), "+f"(d[16]), "+f"(d[17]), "+f"(d[18]), "+f"(d[19]), "+f"(d[20]), "+f"(d[21]), "+f"(d[22]), "+f"(d[23]), "+f"(d[24]), "+f"(d[25]), "+f"(d[26]), "+f"(d[27]), "+f"(d[28]), "+f"(d[29]), "+f"(d[30]), "+f"(d[31]), "+f"(d[32]), "+f"(d[33]), "+f"(d[34]), "+f"(d[35]), "+f"(d[36]), "+f"(d[37]), "+f"(d[38]), "+f"(d[39]), "+f"(d[40]), "+f"(d[41]), "+f"(d[42]), "+f"(d[43]), "+f"(d[44]), "+f"(d[45]), "+f"(d[46]), "+f"(d[47]), "+f"(d[48]), "+f"(d[49]), "+f"(d[50]), "+f"(d[51]), "+f"(d[52]), "+f"(d[53]), "+f"(d[54]), "+f"(d[55]), "+f"(d[56]), "+f"(d[57]), "+f"(d[58]), "+f"(d[59]), "+f"(d[60]), "+f"(d[61]), "+f"(d[62]), "+f"(d[63]), "+f"(d[64]), "+f"(d[65]), "+f"(d[66]), "+f"(d[67]), "+f"(d[68]), "+f"(d[69]), "+f"(d[70]), "+f"(d[71]), "+f"(d[72]), "+f"(d[73]), "+f"(d[74]), "+f"(d[75]), "+f"(d[76]), "+f"(d[77]), "+f"(d[78]), "+f"(d[79])
    : "l"(da), "l"(db), "r"(scale_d), "n"(TA), "n"(TB));
}
template <int TB, int TA = 0>
__device__ __forceinline__ void wgmma_ss_n192(float (&d)[96], uint64_t da, uint64_t db, int scale_d) {
  asm volatile("{\n.reg .pred p;\nsetp.ne.b32 p, %98, 0;\n"
    "wgmma.mma_async.sync.aligned.m64n192k16.f32.bf16.bf16 {%0, %1, %2, %3, %4, %5, %6, %7, %8, %9, %10, %11, %12, %13, %14, %15, %16, %17, %18, %19, %20, %21, %22, %23, %24, %25, %26, %27, %28, %29, %30, %31, %32, %33, %34, %35, %36, %37, %38, %39, %40, %41, %42, %43, %44, %45, %46, %47, %48, %49, %50, %51, %52, %53, %54, %55, %56, %57, %58, %59, %60, %61, %62, %63, %64, %65, %66, %67, %68, %69, %70, %71, %72, %73, %74, %75, %76, %77, %78, %79, %80, %81, %82, %83, %84, %85, %86, %87, %88, %89, %90, %91, %92, %93, %94, %95}, %96, %97, p, 1, 1, %99, %100;\n}\n"
    : "+f"(d[0]), "+f"(d[1]), "+f"(d[2]), "+f"(d[3]), "+f"(d[4]), "+f"(d[5]), "+f"(d[6]), "+f"(d[7]), "+f"(d[8]), "+f"(d[9]), "+f"(d[10]), "+f"(d[11]), "+f"(d[12]), "+f"(d[13]), "+f"(d[14]), "+f"(d[15]), "+f"(d[16]), "+f"(d[17]), "+f"(d[18]), "+f"(d[19]), "+f"(d[20]), "+f"(d[21]), "+f"(d[22]), "+f"(d[23]), "+f"(d[24]), "+f"(d[25]), "+f"(d[26]), "+f"(d[27]), "+f"(d[28]), "+f"(d[29]), "+f"(d[30]), "+f"(d[31]), "+f"(d[32]), "+f"(d[33]), "+f"(d[34]), "+f"(d[35]), "+f"(d[36]), "+f"(d[37]), "+f"(d[38]), "+f"(d[39]), "+f"(d[40]), "+f"(d[41]), "+f"(d[42]), "+f"(d[43]), "+f"(d[44]), "+f"(d[45]), "+f"(d[46]), "+f"(d[47]), "+f"(d[48]), "+f"(d[49]), "+f"(d[50]), "+f"(d[51]), "+f"(d[52]), "+f"(d[53]), "+f"(d[54]), "+f"(d[55]), "+f"(d[56]), "+f"(d[57]), "+f"(d[58]), "+f"(d[59]), "+f"(d[60]), "+f"(d[61]), "+f"(d[62]), "+f"(d[63]), "+f"(d[64]), "+f"(d[65]), "+f"(d[66]), "+f"(d[67]), "+f"(d[68]), "+f"(d[69]), "+f"(d[70]), "+f"(d[71]), "+f"(d[72]), "+f"(d[73]), "+f"(d[74]), "+f"(d[75]), "+f"(d[76]), "+f"(d[77]), "+f"(d[78]), "+f"(d[79]), "+f"(d[80]), "+f"(d[81]), "+f"(d[82]), "+f"(d[83]), "+f"(d[84]), "+f"(d[85]), "+f"(d[86]), "+f"(d[87]), "+f"(d[88]), "+f"(d[89]), "+f"(d[90]), "+f"(d[91]), "+f"(d[92]), "+f"(d[93]), "+f"(d[94]), "+f"(d[95])
    : "l"(da), "l"(db), "r"(scale_d), "n"(TA), "n"(TB));
}
template <int TB>
__device__ __forceinline__ void wgmma_rs_n192(float (&d)[96], uint32_t a0, uint32_t a1, uint32_t a2, uint32_t a3, uint64_t db, int scale_d) {
  asm volatile("{\n.reg .pred p;\nsetp.ne.b32 p, %101, 0;\n"
    "wgmma.mma_async.sync.aligned.m64n192k16.f32.bf16.bf16 {%0, %1, %2, %3, %4, %5, %6, %7, %8, %9, %10, %11, %12, %13, %14, %15, %16, %17, %18, %19, %20, %21, %22, %23, %24, %25, %26, %27, %28, %29, %30, %31, %32, %33, %34, %35, %36, %37, %38, %39, %40, %41, %42, %43, %44, %45, %46, %47, %48, %49, %50, %51, %52, %53, %54, %55, %56, %57, %58, %59, %60, %61, %62, %63, %64, %65, %66, %67, %68, %69, %70, %71, %72, %73, %74, %75, %76, %77, %78, %79, %80, %81, %82, %83, %84, %85, %86, %87, %88, %89, %90, %91, %92, %93, %94, %95}, {%96, %97, %98, %99}, %100, p, 1, 1, %102;\n}\n"
    : "+f"(d[0]), "+f"(d[1]), "+f"(d[2]), "+f"(d[3]), "+f"(d[4]), "+f"(d[5]), "+f"(d[6]), "+f"(d[7]), "+f"(d[8]), "+f"(d[9]), "+f"(d[10]), "+f"(d[11]), "+f"(d[12]), "+f"(d[13]), "+f"(d[14]), "+f"(d[15]), "+f"(d[16]), "+f"(d[17]), "+f"(d[18]), "+f"(d[19]), "+f"(d[20]), "+f"(d[21]), "+f"(d[22]), "+f"(d[23]), "+f"(d[24]), "+f"(d[25]), "+f"(d[26]), "+f"(d[27]), "+f"(d[28]), "+f"(d[29]), "+f"(d[30]), "+f"(d[31]), "+f"(d[32]), "+f"(d[33]), "+f"(d[34]), "+f"(d[35]), "+f"(d[36]), "+f"(d[37]), "+f"(d[38]), "+f"(d[39]), "+f"(d[40]), "+f"(d[41]), "+f"(d[42]), "+f"(d[43]), "+f"(d[44]), "+f"(d[45]), "+f"(d[46]), "+f"(d[47]), "+f"(d[48]), "+f"(d[49]), "+f"(d[50]), "+f"(d[51]), "+f"(d[52]), "+f"(d[53]), "+f"(d[54]), "+f"(d[55]), "+f"(d[56]), "+f"(d[57]), "+f"(d[58]), "+f"(d[59]), "+f"(d[60]), "+f"(d[61]), "+f"(d[62]), "+f"(d[63]), "+f"(d[64]), "+f"(d[65]), "+f"(d[66]), "+f"(d[67]), "+f"(d[68]), "+f"(d[69]), "+f"(d[70]), "+f"(d[71]), "+f"(d[72]), "+f"(d[73]), "+f"(d[74]), "+f"(d[75]), "+f"(d[76]), "+f"(d[77]), "+f"(d[78]), "+f"(d[79]), "+f"(d[80]), "+f"(d[81]), "+f"(d[82]), "+f"(d[83]), "+f"(d[84]), "+f"(d[85]), "+f"(d[86]), "+f"(d[87]), "+f"(d[88]), "+f"(d[89]), "+f"(d[90]), "+f"(d[91]), "+f"(d[92]), "+f"(d[93]), "+f"(d[94]), "+f"(d[95])
    : "r"(a0), "r"(a1), "r"(a2), "r"(a3), "l"(db), "r"(scale_d), "n"(TB));
}

__device__ __forceinline__ uint32_t smem_u32(const void* p) { return (uint32_t)__cvta_generic_to_shared(p); }
__device__ __forceinline__ void wg_fence() { asm volatile("wgmma.fence.sync.aligned;" ::: "memory"); }
__device__ __forceinline__ void wg_commit() { asm volatile("wgmma.commit_group.sync.aligned;" ::: "memory"); }
template <int N> __device__ __forceinline__ void wg_wait() { asm volatile("wgmma.wait_group.sync.aligned %0;" ::"n"(N) : "memory"); }
__device__ __forceinline__ void sched_fence(int& keep, uint32_t zero) {
  asm volatile("{\n.reg .u32 c;\nmov.u32 c, %%clock;\nand.b32 c, c, %1;\nxor.b32 %0, %0, c;\n}\n" : "+r"(keep) : "r"(zero) : "memory");
}
template <int N> __device__ __forceinline__ void fence_regs(float (&r)[N]) {
#pragma unroll
  for (int i = 0; i < N; i++) asm volatile("" : "+f"(r[i])::"memory");
}
template <int N> __device__ __forceinline__ void fence_regs(uint32_t (&r)[N]) {
#pragma unroll
  for (int i = 0; i < N; i++) asm volatile("" : "+r"(r[i])::"memory");
}
__device__ __forceinline__ uint64_t mk_desc(uint32_t a16, uint32_t lbo, uint32_t sbo, uint32_t swz, uint32_t off = 0) {
  uint64_t d;
  asm("mov.b64 %0, {%1, %2};" : "=l"(d) : "r"(a16), "r"((sbo >> 4) | (swz << 30)));
  return d + (off + ((lbo >> 4) << 16));
}
__device__ __forceinline__ void mbar_init(uint32_t bar, uint32_t cnt) {
  asm volatile("mbarrier.init.shared::cta.b64 [%0], %1;" ::"r"(bar), "r"(cnt) : "memory");
}
__device__ __forceinline__ void mbar_expect(uint32_t bar, uint32_t tx) {
  asm volatile("mbarrier.arrive.expect_tx.shared::cta.b64 _, [%0], %1;" ::"r"(bar), "r"(tx) : "memory");
}
__device__ __forceinline__ bool mbar_test(uint32_t bar, uint32_t ph) {
  uint32_t ok;
  asm volatile("{\n.reg .pred p;\nmbarrier.test_wait.parity.shared::cta.b64 p, [%1], %2;\nselp.u32 %0, 1, 0, p;\n}\n"
               : "=r"(ok) : "r"(bar), "r"(ph) : "memory");
  return ok;
}
__device__ __forceinline__ void mbar_wait(uint32_t bar, uint32_t ph) {
  asm volatile("{\n.reg .pred p;\n.reg .u32 n;\nmov.u32 n, 0;\n"
               "LOOP:\nadd.u32 n, n, 1;\nmbarrier.try_wait.parity.shared::cta.b64 p, [%0], %1;\n@p bra DONE;\n"
               "setp.lt.u32 p, n, 0x1000000;\n@p bra LOOP;\ntrap;\n"
               "DONE:\n}\n" ::"r"(bar), "r"(ph) : "memory");
}
__device__ __forceinline__ void mbar_wait_long(uint32_t bar, uint32_t ph) {
  asm volatile("{\n.reg .pred p;\n.reg .u32 n;\nmov.u32 n, 0;\n"
               "LOOP:\nmbarrier.try_wait.parity.shared::cta.b64 p, [%0], %1, %2;\n@p bra DONE;\n"
               "add.u32 n, n, 1;\nsetp.lt.u32 p, n, 0x40000;\n@p bra LOOP;\ntrap;\n"
               "DONE:\n}\n" ::"r"(bar), "r"(ph), "r"(20000) : "memory");
}
__device__ __forceinline__ void mbar_arrive_cluster_if(bool on, uint32_t addr) {
  asm volatile("{\n.reg .pred p;\nsetp.ne.b32 p, %1, 0;\n@p mbarrier.arrive.shared::cluster.b64 _, [%0];\n}\n" ::"r"(addr), "r"((int)on) : "memory");
}
__device__ __forceinline__ void mbar_arrive_if(bool on, uint32_t addr) {
  asm volatile("{\n.reg .pred p;\nsetp.ne.b32 p, %1, 0;\n@p mbarrier.arrive.shared::cta.b64 _, [%0];\n}\n" ::"r"(addr), "r"((int)on) : "memory");
}
__device__ __forceinline__ void tma2d(uint32_t dst, const CUtensorMap* m, uint32_t bar, int c0, int c1) {
  asm volatile("cp.async.bulk.tensor.2d.shared::cluster.global.mbarrier::complete_tx::bytes [%0], [%1, {%3, %4}], [%2];"
               ::"r"(dst), "l"(m), "r"(bar), "r"(c0), "r"(c1) : "memory");
}
__device__ __forceinline__ void tma3d(uint32_t dst, const CUtensorMap* m, uint32_t bar, int c0, int c1, int c2) {
  asm volatile("cp.async.bulk.tensor.3d.shared::cluster.global.mbarrier::complete_tx::bytes [%0], [%1, {%3, %4, %5}], [%2];"
               ::"r"(dst), "l"(m), "r"(bar), "r"(c0), "r"(c1), "r"(c2) : "memory");
}
__device__ __forceinline__ void tma3d_mc(uint32_t dst, const CUtensorMap* m, uint32_t bar, int c0, int c1, int c2) {
  asm volatile("cp.async.bulk.tensor.3d.shared::cluster.global.mbarrier::complete_tx::bytes.multicast::cluster"
               " [%0], [%1, {%3, %4, %5}], [%2], %6;"
               ::"r"(dst), "l"(m), "r"(bar), "r"(c0), "r"(c1), "r"(c2), "h"((uint16_t)3) : "memory");
}
__device__ __forceinline__ void tma3d_store(const CUtensorMap* m, uint32_t src, int c0, int c1, int c2) {
  asm volatile("cp.async.bulk.tensor.3d.global.shared::cta.bulk_group [%0, {%2, %3, %4}], [%1];"
               ::"l"(m), "r"(src), "r"(c0), "r"(c1), "r"(c2) : "memory");
}
__device__ __forceinline__ void bar_sync(int id, int n) { asm volatile("bar.sync %0, %1;" ::"r"(id), "r"(n) : "memory"); }
__device__ __forceinline__ uint32_t pack_bf16(float lo, float hi) {
  uint32_t r;
  asm("cvt.rn.bf16x2.f32 %0, %1, %2;" : "=r"(r) : "f"(hi), "f"(lo));
  return r;
}
__device__ __forceinline__ float ex2(float x) {
  float y;
  asm("ex2.approx.ftz.f32 %0, %1;" : "=f"(y) : "f"(x));
  return y;
}
__device__ __forceinline__ float fadd(float a, float b) {
  float y;
  asm("add.f32 %0, %1, %2;" : "=f"(y) : "f"(a), "f"(b));
  return y;
}
__device__ __forceinline__ float rcp(float x) {
  float y;
  asm("rcp.approx.ftz.f32 %0, %1;" : "=f"(y) : "f"(x));
  return y;
}
__device__ __forceinline__ void stsm4(uint32_t addr, uint32_t a, uint32_t b, uint32_t c, uint32_t d) {
  asm volatile("stmatrix.sync.aligned.m8n8.x4.shared.b16 [%0], {%1, %2, %3, %4};" ::"r"(addr), "r"(a), "r"(b), "r"(c), "r"(d) : "memory");
}

__device__ __forceinline__ void tma4d_mc_hint(uint32_t dst, const CUtensorMap* m, uint32_t bar, int c3, uint64_t pol) {
  asm volatile("cp.async.bulk.tensor.4d.shared::cluster.global.mbarrier::complete_tx::bytes.multicast::cluster.L2::cache_hint"
               " [%0], [%1, {%3, %3, %3, %4}], [%2], %5, %6;"
               ::"r"(dst), "l"(m), "r"(bar), "r"(0), "r"(c3), "h"((uint16_t)3), "l"(pol) : "memory");
}
__device__ __forceinline__ void tma5d_mc(uint32_t dst, const CUtensorMap* m, uint32_t bar, int c2, int c4) {
  asm volatile("cp.async.bulk.tensor.5d.shared::cluster.global.mbarrier::complete_tx::bytes.multicast::cluster"
               " [%0], [%1, {%3, %3, %4, %3, %5}], [%2], %6;"
               ::"r"(dst), "l"(m), "r"(bar), "r"(0), "r"(c2), "r"(c4), "h"((uint16_t)3) : "memory");
}
__device__ __forceinline__ void bulk_load_hint(uint32_t dst, const void* src, uint32_t bytes, uint32_t bar, uint64_t pol) {
  asm volatile("cp.async.bulk.shared::cluster.global.mbarrier::complete_tx::bytes.L2::cache_hint [%0], [%1], %2, [%3], %4;"
               ::"r"(dst), "l"(src), "r"(bytes), "r"(bar), "l"(pol) : "memory");
}
__device__ __forceinline__ void stg2_if(bool on, void* p, uint32_t a, uint32_t b, uint32_t c, uint32_t d, uint32_t e, uint32_t f,
                                        uint32_t g, uint32_t h, uint64_t pol) {
  asm volatile("{\n.reg .pred p;\nsetp.ne.b32 p, %10, 0;\n"
               "@p st.global.L2::cache_hint.v4.b32 [%0], {%1, %2, %3, %4}, %9;\n"
               "@p st.global.L2::cache_hint.v4.b32 [%0 + 512], {%5, %6, %7, %8}, %9;\n}\n"
               ::"l"(p), "r"(a), "r"(b), "r"(c), "r"(d), "r"(e), "r"(f), "r"(g), "r"(h), "l"(pol), "r"((int)on) : "memory");
}
__device__ __forceinline__ uint64_t evict_first() {
  uint64_t p;
  asm("createpolicy.fractional.L2::evict_first.b64 %0, 1.0;" : "=l"(p));
  return p;
}
__device__ __forceinline__ bool elect() {
  uint32_t ok;
  asm volatile("{\n.reg .pred p;\nelect.sync _|p, 0xffffffff;\nselp.u32 %0, 1, 0, p;\n}\n" : "=r"(ok));
  return ok;
}
__device__ __forceinline__ void mbar_arrive(uint32_t bar) {
  asm volatile("mbarrier.arrive.shared::cta.b64 _, [%0];" ::"r"(bar) : "memory");
}
__device__ __forceinline__ void lds128(uint32_t p, uint32_t& a, uint32_t& b, uint32_t& c, uint32_t& d) {
  asm volatile("ld.shared.v4.b32 {%0, %1, %2, %3}, [%4];" : "=r"(a), "=r"(b), "=r"(c), "=r"(d) : "r"(p) : "memory");
}
__device__ __forceinline__ void wait_count(const unsigned int* p, uint32_t target) {
  asm volatile("{\n.reg .pred p;\n.reg .u32 n, v;\nmov.u32 n, 0;\n"
               "LOOP:\nld.acquire.gpu.global.u32 v, [%0];\nsetp.ge.u32 p, v, %1;\n@p bra DONE;\n"
               "nanosleep.u32 %2;\nadd.u32 n, n, 1;\nsetp.lt.u32 p, n, 0x400000;\n@p bra LOOP;\ntrap;\n"
               "DONE:\n}\n" ::"l"(p), "r"(target), "n"(300) : "memory");
}

__device__ __forceinline__ int o_wave(int a, int b, int i) {
  const int p = min(3, b - a - 1);
  return i < p ? b - 2 - i : i == p ? b - 1 : b - 1 - i;
}

struct Cursor {
  uint32_t n;
  __device__ __forceinline__ uint32_t off() const { return n & (8 * NBAR - 8); }
  __device__ __forceinline__ uint32_t ph() const { return (n / (8 * NBAR)) & 1; }
  __device__ __forceinline__ void next() { n += 8; }
};

constexpr float kScaleLog2 = 0.07216878364870322f * 1.4426950408889634f;
constexpr float kSumLimit = 1048576.0f;
constexpr float kMaxLag = 8.0f;

__global__ void __cluster_dims__(2, 1, 1) __launch_bounds__(384, 1)
fused_kernel(const __grid_constant__ Params P) {
  extern __shared__ uint8_t smem_raw[];
  const uint32_t sbase = (smem_u32(smem_raw) + 1023) & ~1023u;
  const uint32_t full0 = sbase + RING, empty0 = full0 + 8 * NBAR, odone = empty0 + 8 * NBAR, oready0 = odone + 8;
  const uint32_t fenced = oready0 + 64, hready0 = fenced + 8;
  const uint32_t rank = blockIdx.x & 1;
  const int role = blockIdx.x >> 1;
  const bool helper = role >= N_CL;
  const int team = helper ? 0 : role >> 2, nt = role & 3, blk = team >> 3;
  const uint32_t* prog = P.ops[helper ? N_TEAM + 2 * (role - N_CL) : team];
  auto q_role = [&](uint32_t op) { return helper ? (int)(((op >> 3) & 60) | ((op >> 12) & 3)) : role; };
  auto o_role = [&](uint32_t op) { return helper ? (int)(((op >> 26) & 56) | ((op >> 9) & 7)) : role; };
  const int wid = __shfl_sync(0xffffffffu, (int)(threadIdx.x >> 5), 0);
  const int wg = wid >> 2;

  const uint32_t op0 = P.first[helper ? N_TEAM + role - N_CL : team];
  if (__builtin_expect(wid == 8, 1)) {
    if (elect()) {
#pragma unroll
      for (int k = 0; k < EARLY; k++) mbar_init(full0 + 8 * k, 1);
      asm volatile("fence.mbarrier_init.release.cluster;" ::: "memory");
      if ((op0 & 3) == OP_Q) {
        const int qr = q_role(op0);
#pragma unroll
        for (int k = 0; k < EARLY; k++) {
          mbar_expect(full0 + 8 * k, SZ_WQ + SZ_A);
          tma2d(sbase + k * (SZ_WQ + SZ_A) + SZ_WQ, &P.x[qr >> 5], full0 + 8 * k, 64 * k, ((qr >> 2) & 7) * kSq + rank * 128);
          tma3d(sbase + k * (SZ_WQ + SZ_A), &P.wq[qr >> 5], full0 + 8 * k, 0, 64 * k, 3 * (4 * ((op0 >> 2) & 7) + (qr & 3)));
          tma3d(sbase + k * (SZ_WQ + SZ_A) + SZ_WQ / 2, &P.wq[qr >> 5], full0 + 8 * k, 0, 64 * k + 32, 3 * (4 * ((op0 >> 2) & 7) + (qr & 3)));
        }
      }
      asm volatile("prefetch.tensormap [%0];" ::"l"(&P.k[blk]) : "memory");
      asm volatile("prefetch.tensormap [%0];" ::"l"(&P.v[blk]) : "memory");
    }
  } else if (threadIdx.x == 0) {
#pragma unroll
    for (int i = EARLY; i < 2 * NBAR + 10 + MAX_PARK; i++) mbar_init(full0 + 8 * i, i >= NBAR && i <= 2 * NBAR ? 16 : 1);
    asm volatile("fence.mbarrier_init.release.cluster;" ::: "memory");
  }
  __syncwarp();
  asm volatile("barrier.cluster.arrive.relaxed.aligned;\nbarrier.cluster.wait.aligned;" ::: "memory");

  if (wg == 2) {
    asm volatile("setmaxnreg.dec.sync.aligned.u32 24;");
    if (wid == 8) {
      Cursor tail{0}, head{0};
      int sh = 0;
      uint32_t cur = 0, used = 0;
      uint64_t fifo = 0;
      uint32_t dst, bar, oready = oready0;
      const uint64_t pol = evict_first();
      auto acquire = [&](uint32_t bytes, int part = 0) {
        uint32_t fp = bytes >> 12;
        if (cur + fp > (RING >> 12)) { fp += (RING >> 12) - cur; cur = 0; }
        used += fp;
        bool more = false;
        uint32_t wbar, wph;
        while (used > (RING >> 12) || (part != 2 && sh == 5 * NFLIGHT)) {
          if (more) mbar_wait(wbar, wph);
          more = true;
          wbar = empty0 + tail.off(); wph = tail.ph();
          tail.next();
          used -= (uint32_t)fifo & 31;
          fifo >>= 5;
          sh -= 5;
        }
        fifo += (uint64_t)fp << sh;
        dst = sbase + (cur << 12);
        bar = full0 + head.off();
        cur += bytes >> 12;
        if (part != 1) {
          sh += 5;
          head.next();
        }
        if (more) mbar_wait(wbar, wph);
      };
      auto scratch = [&](const uint4* src, uint32_t bytes, int n) {
        asm volatile("fence.proxy.async.global;" ::: "memory");
#pragma unroll 1
        for (int i = 0; i < n; i++) {
          acquire(bytes);
          if (elect()) {
            bulk_load_hint(dst, src + i * (bytes / 16), bytes, bar, pol);
            mbar_expect(bar, bytes);
          }
        }
      };
      for (int pc = 0;; pc++) {
        const uint32_t op = prog[pc];
        const int type = op & 3, a = (op >> 2) & 7;
        if (type == OP_END) break;
        if (type == OP_Q) {
          const int qr = q_role(op);
#pragma unroll 1
          for (int k = 0; k < 10; k++) {
            acquire(SZ_WQ, 1);
            if ((pc > 0 || k >= EARLY) && elect()) tma3d_mc(dst + rank * (SZ_WQ / 2), &P.wq[qr >> 5], bar, 0, 64 * k + 32 * rank, 3 * (4 * a + (qr & 3)));
            acquire(SZ_A, 2);
            if ((pc > 0 || k >= EARLY) && elect()) {
              tma2d(dst, &P.x[qr >> 5], bar, 64 * k, ((qr >> 2) & 7) * kSq + rank * 128);
              mbar_expect(bar, SZ_WQ + SZ_A);
            }
          }
        } else if (type == OP_A) {
          const uint32_t nop = prog[pc + 1];
#pragma unroll 1
          for (int t = (op & F_PARK) ? 1 : 0; t < 33; t++) {
            int wave = a;
            if (t == 31 && (nop & 3) != OP_A) t++;
            if (t == 31) {
              wave = (nop >> 2) & 7;
              mbar_wait((nop & F_HELP) ? hready0 + 8 * ((nop >> 10) & 3) : fenced, 0);
              scratch(&g_o[((team * 2 + rank) * 96 + 3 * (4 * wave + nt)) * 1024], SZ_PARK, 2);
            }
            const int isv = t ? ~t & 1 : 0, j = (isv ? (t - 1) >> 1 : (t + 1) >> 1) & 15;
            const int row0 = ((team & 7) * kH + 4 * wave + nt) * kSk;
            if (t >= KV_TRANSIT) {
              const Cursor c{head.n - 8 * KV_TRANSIT};
              mbar_wait(full0 + c.off(), c.ph());
            }
            acquire(SZ_KV);
            if (elect()) {
              tma4d_mc_hint(dst + rank * (SZ_KV / 2), isv ? &P.v[blk] : &P.k[blk], bar, row0 / 8 + 8 * j + 4 * rank, pol);
              mbar_expect(bar, SZ_KV);
            }
          }
        } else {
          const int b = (op >> 5) & 15, ro = o_role(op);
#pragma unroll 1
          for (int i = 0; i < b - a; i++) {
            const int w = o_wave(a, b, i);
            mbar_wait(oready, 0);
            oready += 8;
            asm volatile("fence.proxy.async.global;" ::: "memory");
#pragma unroll 1
            for (int k = 12 * w; k < 12 * w + 12; k++) {
              acquire(SZ_A, 1);
              if (elect()) bulk_load_hint(dst, &g_o[(((ro >> 2) * 2 + rank) * 96 + k) * 1024], SZ_A, bar, pol);
              acquire(SZ_WO, 2);
              if (elect()) {
                tma5d_mc(dst + rank * 10240, &P.wo[ro >> 5], bar, 8 * k + 4 * rank, 5 * (ro & 3));
                mbar_expect(bar, SZ_WO + SZ_A);
              }
            }
          }
          if (op & F_LD) {
            if (op & F_PARK) mbar_wait(hready0 + 8 * (MAX_PARK - 1), 0);
            scratch(&g_part[(role * 2 + rank) * 5120], SZ_PART, 5);
          }
          if (!(op & F_ST)) {
            acquire(SZ_OUT);
            if (elect()) mbar_arrive(bar);
            __syncwarp();
            sh -= 5;
          }
        }
      }
      for (; sh > 0; sh -= 5) {
        mbar_wait(empty0 + tail.off(), tail.ph());
        tail.next();
      }
    } else if (threadIdx.x == 288) {
      uint32_t ph = 0;
      bool first = true;
      for (int pc = 0;; pc++) {
        const uint32_t op = prog[pc];
        if ((op & 3) == OP_END) break;
        if ((op & 3) != OP_A && !helper) continue;
        mbar_wait_long(odone, ph);
        ph ^= 1;
        unsigned int* flag = !helper ? &g_done[(team * 2 + rank) * 8 + ((op >> 2) & 7)]
                             : (op & 3) == OP_Q ? &g_help[(q_role(op) * 2 + rank) * MAX_PARK + ((op >> 10) & 3)]
                                                : &g_help[(o_role(op) * 2 + rank) * MAX_PARK + MAX_PARK - 1];
        asm volatile("red.release.gpu.global.add.u32 [%0], 1;" ::"l"(flag) : "memory");
        if (first) mbar_arrive(fenced);
        first = false;
      }
    } else if (threadIdx.x == 320) {
      uint32_t oready = oready0;
      for (int pc = 0;; pc++) {
        const uint32_t op = prog[pc];
        if ((op & 3) == OP_END) break;
        if ((op & 3) == OP_O) {
          const int a = (op >> 2) & 7, b = (op >> 5) & 15;
#pragma unroll 1
          for (int i = 0; i < b - a; i++) {
            const int ci = ((o_role(op) >> 2) * 2 + rank) * 8 + o_wave(a, b, i);
            wait_count(&g_done[ci], 4);
            mbar_arrive(oready);
            oready += 8;
            if (atomicAdd(&g_seen[ci], 1u) == 3u) { g_seen[ci] = 0; g_done[ci] = 0; }
          }
        }
        if ((op & 3) != OP_Q && (op & F_HELP) && (op & F_PARK)) {
          unsigned int* flag = &g_help[(role * 2 + rank) * MAX_PARK + ((op >> 10) & 3)];
          wait_count(flag, 1);
          mbar_arrive(hready0 + 8 * ((op >> 10) & 3));
          *flag = 0;
        }
      }
    }
  } else {
    asm volatile("setmaxnreg.inc.sync.aligned.u32 240;");
    const int lane = threadIdx.x & 31, warp = wid & 3;
    uint32_t empty_rem;
    asm volatile("mapa.shared::cluster.u32 %0, %1, %2;" : "=r"(empty_rem) : "r"(empty0), "r"(lane & 1));
    auto release = [&](int slot) { mbar_arrive_cluster_if(lane < 2, empty_rem + slot); };
    Cursor r{0};
    const uint32_t ring16 = (sbase & 0x3FFFF) >> 4;
    uint32_t cur = ring16;
    bool rdy0 = false, rdy1 = false;
    auto probe1 = [&]() { rdy0 = mbar_test(full0 + r.off(), r.ph()); };
    auto probe2 = [&]() {
      Cursor n = r;
      rdy0 = mbar_test(full0 + n.off(), n.ph());
      n.next();
      rdy1 = mbar_test(full0 + n.off(), n.ph());
    };
    auto take = [&](bool rdy, uint32_t bytes, uint32_t& addr) {
      const int bi = r.off();
      if (!__all_sync(0xffffffffu, rdy)) mbar_wait(full0 + r.off(), r.ph());
      r.next();
      if (cur > ring16 + ((RING - bytes) >> 4)) cur = ring16;
      addr = cur;
      cur += bytes >> 4;
      return bi;
    };
    auto second = [&](uint32_t bytes) {
      if (cur > ring16 + ((RING - bytes) >> 4)) cur = ring16;
      cur += bytes >> 4;
      return cur - (bytes >> 4);
    };
    const int row = wg * 64 + warp * 16 + (lane >> 2);
    int img0 = row * 4 + ((lane & 3) ^ ((row >> 1) & 3));
    uint4* pend = nullptr;
    const uint64_t spol = evict_first();
    int pc = 0;
    uint32_t op = prog[0];
    auto enter = [&]() {
      r.n = op >> 12; cur = ring16 + (((op >> 20) & 63) << 8);
    };
    auto drain = [&](uint32_t (&t)[48], uint32_t c) {
      if (!(op & (3u << 26)) || c >= 6) return;
#pragma unroll
      for (int i = 0; i < 6; i++)
        stg2_if(c == i, pend + i * 512, t[8 * i], t[8 * i + 1], t[8 * i + 2], t[8 * i + 3],
                t[8 * i + 4], t[8 * i + 5], t[8 * i + 6], t[8 * i + 7], spol);
      if ((op & (1u << 26)) && c == 5) {
        __syncwarp();
        mbar_arrive_if(lane < 2, odone);
      }
    };
    float s[32], o[96], c[80];
    uint32_t q[48], pa[16], pb[16];
    float mc0, mc1, l0, l1;
    bool gen;
    auto soft = [&](float (&s)[32], uint32_t (&pout)[16], bool first) {
      if (first) { gen = false; mc0 = 0.f; mc1 = 0.f; }
      float b0, b1;
      for (;;) {
        if (gen) {
          float m0 = fmaxf(s[0], s[1]), m1 = fmaxf(s[2], s[3]);
#pragma unroll
          for (int i = 1; i < 8; i++) { m0 = fmaxf(m0, fmaxf(s[4 * i], s[4 * i + 1])); m1 = fmaxf(m1, fmaxf(s[4 * i + 2], s[4 * i + 3])); }
          m0 = fmaxf(m0, __shfl_xor_sync(0xffffffffu, m0, 1)); m1 = fmaxf(m1, __shfl_xor_sync(0xffffffffu, m1, 1));
          m0 = fmaxf(m0, __shfl_xor_sync(0xffffffffu, m0, 2)); m1 = fmaxf(m1, __shfl_xor_sync(0xffffffffu, m1, 2));
          if (first) {
            mc0 = m0; mc1 = m1;
          } else if (__any_sync(0xffffffffu, !(m0 <= mc0 + kMaxLag && m1 <= mc1 + kMaxLag))) {
            m0 = fmaxf(mc0, m0); m1 = fmaxf(mc1, m1);
            const float a0 = ex2(mc0 - m0), a1 = ex2(mc1 - m1);
            mc0 = m0; mc1 = m1;
            l0 *= a0; l1 *= a1;
            wg_wait<0>();
            fence_regs(o);
#pragma unroll
            for (int i = 0; i < 96; i++) o[i] *= i & 2 ? a1 : a0;
          }
#pragma unroll
          for (int i = 0; i < 32; i++) s[i] -= i & 2 ? mc1 : mc0;
        }
#pragma unroll
        for (int i = 0; i < 8; i++) {
          const float e1 = ex2(s[4 * i + 1]), e0 = ex2(s[4 * i]), e3 = ex2(s[4 * i + 3]), e2 = ex2(s[4 * i + 2]);
          pout[2 * i] = pack_bf16(e0, e1);
          b0 = i ? b0 + fadd(e1, e0) : fadd(e1, e0);
          pout[2 * i + 1] = pack_bf16(e2, e3);
          b1 = i ? b1 + fadd(e3, e2) : fadd(e3, e2);
        }
        if (!__any_sync(0xffffffffu, !gen && !(fmaxf(b0, b1) <= kSumLimit && (!first || fminf(b0, b1) >= 1.0f / kSumLimit)))) break;
        gen = __any_sync(0xffffffffu, true);
      }
      l0 = first ? b0 : l0 + b0;
      l1 = first ? b1 : l1 + b1;
    };
    auto qk = [&](float (&s)[32], uint32_t ak, int k0, int k1) {
#pragma unroll
      for (int kk = k0; kk < k1; kk++)
        wgmma_rs_n64<0>(s, q[4 * kk], q[4 * kk + 1], q[4 * kk + 2], q[4 * kk + 3], mk_desc(ak, 16, KV_SBO, 1, (kk >> 2) * KV_CH + (kk & 3) * 2), kk != 0);
      wg_commit();
    };
    auto pv = [&](uint32_t (&pin)[16], uint32_t av, int acc) {
#pragma unroll
      for (int kk = 0; kk < 4; kk++)
        wgmma_rs_n192<1>(o, pin[4 * kk], pin[4 * kk + 1], pin[4 * kk + 2], pin[4 * kk + 3], mk_desc(av, KV_CH * 16, KV_SBO, 1, kk * (KV_SBO / 8)), acc || (kk != 0));
      wg_commit();
    };
    auto xw = [&](uint32_t ad, int acc) {
      const uint32_t da = second(SZ_A) + wg * 512;
      wg_fence();
#pragma unroll
      for (int kk = 0; kk < 4; kk++)
        wgmma_ss_n192<1>(o, mk_desc(da, 16, 1024, 1, kk * 2), mk_desc(ad, 4096, 1024, 1, (kk & 1) * 128 + (kk >> 1) * 768), acc || kk != 0);
      wg_commit();
    };
    auto ow = [&](int acc, int prev) {
      uint32_t da;
      const int bi = take(rdy0, SZ_A, da);
      const uint32_t db = second(SZ_WO);
      da += wg * 256;
      wg_fence();
      wgmma_ss_n160<1>(c, mk_desc(da, 16, 512, 2), mk_desc(db, 2048, 512, 2), acc);
      wgmma_ss_n160<1>(c, mk_desc(da, 16, 512, 2, 2), mk_desc(db, 2048, 512, 2, 64), 1);
      wg_commit();
      if (acc == 1) { wg_wait<1>(); release(prev); }
      wgmma_ss_n160<1>(c, mk_desc(da, 16, 512, 2, 512), mk_desc(db, 2048, 512, 2, 640), 1);
      wgmma_ss_n160<1>(c, mk_desc(da, 16, 512, 2, 514), mk_desc(db, 2048, 512, 2, 704), 1);
      wg_commit();
      return bi;
    };
    auto st_part = [&](int i) {
      stg2_if(true, pend + i * 512, __float_as_uint(c[8 * i]), __float_as_uint(c[8 * i + 1]), __float_as_uint(c[8 * i + 2]), __float_as_uint(c[8 * i + 3]),
              __float_as_uint(c[8 * i + 4]), __float_as_uint(c[8 * i + 5]), __float_as_uint(c[8 * i + 6]), __float_as_uint(c[8 * i + 7]), spol);
    };
#pragma unroll
    for (int i = 0; i < 48; i++) q[i] = 0;
    enter();

    if ((op & 3) == OP_Q) {
      uint32_t ad;
      int bi0 = take(false, SZ_WQ, ad), k = 0, lag = 0;
      xw(ad, 0);
      for (;;) {
#pragma unroll 1
        for (;;) {
          drain(q, k - lag);
          probe1();
          wg_wait<0>();
          release(bi0);
          bi0 = take(rdy0, SZ_WQ, ad);
          if (++k == 8) break;
          xw(ad, 1);
        }
        if (wg) bar_sync(2, 256);
        xw(ad, 1);
        const int bi9 = take(false, SZ_WQ, ad);
        xw(ad, 1);
        if (!wg) asm volatile("bar.arrive 2, 256;" ::: "memory");
        k = 0; lag = 0;
        uint32_t nop = prog[++pc];
        wg_wait<1>();
        release(bi0);
        probe2();
        wg_wait<0>();
        fence_regs(o);
        release(bi9);
#pragma unroll
        for (int i = 0; i < 48; i++) q[i] = pack_bf16(o[2 * i] * kScaleLog2, o[2 * i + 1] * kScaleLog2);
        fence_regs(q);
        if (op & F_PARK) {
          const int qt = helper ? (op >> 5) & 15 : team, qm = helper ? (op >> 12) & 3 : nt;
          pend = &g_o[((qt * 2 + rank) * 96 + 3 * (4 * ((op >> 2) & 7) + qm)) * 1024 + img0];
          op = nop;
          enter();
          if ((op & 3) != OP_Q) break;
          bi0 = take(rdy0, SZ_WQ, ad);
          xw(ad, 0);
          continue;
        }
        int wave = (op >> 2) & 7, sk1;
        uint32_t ak1;
        {
          float s0[32];
          const int sk0 = take(rdy0, SZ_KV, ad);
          wg_fence();
          qk(s0, ad, 0, 12);
          sk1 = take(rdy1, SZ_KV, ak1);
          wg_fence();
          qk(s, ak1, 0, S1A);
          probe1();
          wg_wait<1>();
          fence_regs(s0);
          release(sk0);
          soft(s0, pa, true);
        }
        float i0, i1;
        auto sums = [&]() {
          l0 += __shfl_xor_sync(0xffffffffu, l0, 1); l1 += __shfl_xor_sync(0xffffffffu, l1, 1);
          l0 += __shfl_xor_sync(0xffffffffu, l0, 2); l1 += __shfl_xor_sync(0xffffffffu, l1, 2);
          i0 = rcp(l0); i1 = rcp(l1);
          asm volatile("" : "+f"(i0), "+f"(i1));
        };
        auto target = [&]() {
          pend = &g_o[((team * 2 + rank) * 96 + 3 * (4 * wave + nt)) * 1024 + img0];
          asm volatile("" : "+l"(pend));
        };
        bool late = false;
#pragma unroll
        for (int i = 0; i < 16; i++) pb[i] = 0;
        for (;;) {
          nop = prog[++pc];
          {
            uint32_t av;
            const int sv = take(rdy0, SZ_KV, av);
            wg_fence();
            qk(s, ak1, S1A, 12);
            pv(pa, av, 0);
            if (late) {
              stg2_if(true, pend + 4 * 512, pb[0], pb[1], pb[2], pb[3], pb[4], pb[5], pb[6], pb[7], spol);
              stg2_if(true, pend + 5 * 512, pb[8], pb[9], pb[10], pb[11], pb[12], pb[13], pb[14], pb[15], spol);
              __syncwarp();
              mbar_arrive_if(lane < 2, odone);
            }
            probe2();
            wg_wait<1>();
            fence_regs(s);
            release(sk1);
            soft(s, pb, false);
            wg_wait<0>();
            fence_regs(o);
            release(sv);
          }
          auto step = [&](uint32_t (&pin)[16], uint32_t (&pout)[16]) {
            uint32_t ak, av;
            const int sk = take(rdy0, SZ_KV, ak), sv = take(rdy1, SZ_KV, av);
            wg_fence();
            qk(s, ak, 0, 12);
            pv(pin, av, 1);
            probe2();
            wg_wait<1>();
            fence_regs(s);
            release(sk);
            soft(s, pout, false);
            wg_wait<0>();
            fence_regs(o);
            release(sv);
          };
#pragma unroll 1
          for (int jj = 0; jj < 7; jj++) {
            step(pb, pa);
            step(pa, pb);
          }
          if ((nop & 3) != OP_A) break;
          uint32_t ak, av;
          {
            const int b0 = take(rdy0, SZ_PARK, ak), b1 = take(rdy1, SZ_PARK, av);
            const uint32_t ad0 = ak, ad1 = av;
            probe2();
#pragma unroll
            for (int i = 0; i < 12; i++)
              lds128(sbase + ((i < 6 ? ad0 : ad1) - ring16 + img0) * 16 + ((i % 6) >> 1) * 8192 + (i & 1) * 512, q[4 * i], q[4 * i + 1], q[4 * i + 2], q[4 * i + 3]);
            release(b0); release(b1);
          }
          const int sk0 = take(rdy0, SZ_KV, ak), sv = take(rdy1, SZ_KV, av);
          wg_fence();
          qk(s, ak, 0, 8);
          sched_fence(img0, P.zero);
          sums();
          sched_fence(img0, P.zero);
          qk(s, ak, 8, 12);
          pv(pb, av, 1);
          probe2();
          wg_wait<1>();
          fence_regs(s);
          release(sk0);
          soft(s, pa, true);
          sk1 = take(rdy0, SZ_KV, ak1);
          rdy0 = rdy1;
          wg_wait<0>();
          target();
          fence_regs(o);
          release(sv);
          uint32_t t[48];
#pragma unroll
          for (int j = 0; j < 6; j++) {
#pragma unroll
            for (int i = 0; i < 4; i++) {
              t[8 * j + i] = pack_bf16(o[16 * j + 4 * i] * i0, o[16 * j + 4 * i + 1] * i0);
              t[8 * j + i + 4] = pack_bf16(o[16 * j + 4 * i + 2] * i1, o[16 * j + 4 * i + 3] * i1);
            }
            if (j < 4)
            stg2_if(true, pend + j * 512, t[8 * j], t[8 * j + 1], t[8 * j + 2], t[8 * j + 3], t[8 * j + 4], t[8 * j + 5], t[8 * j + 6], t[8 * j + 7], spol);
            if (j == 3) { wg_fence(); qk(s, ak1, 0, 4); }
            if (j == 5) { wg_fence(); qk(s, ak1, 4, S1A); }
            sched_fence(img0, P.zero);
          }
          if (P.zero) {
#pragma unroll
            for (int j = 0; j < 4; j++)
              stg2_if(true, pend, t[8 * j], t[8 * j + 1], t[8 * j + 2], t[8 * j + 3], t[8 * j + 4], t[8 * j + 5], t[8 * j + 6], t[8 * j + 7], spol);
          }
          late = true;
#pragma unroll
          for (int i = 0; i < 16; i++) pb[i] = t[32 + i];
          wave = (nop >> 2) & 7;
        }
        const int sv = take(rdy0, SZ_KV, ad);
        wg_fence();
        pv(pb, ad, 1);
        sums();
        target();
        op = nop;
        enter();
        rdy0 = rdy1;
        auto convert = [&](float (&u)[96], int j0, int j1) {
#pragma unroll
          for (int i = 4 * j0; i < 4 * j1; i++) {
            q[8 * (i >> 2) + (i & 3)] = pack_bf16(u[4 * i], u[4 * i + 1]);
            q[8 * (i >> 2) + (i & 3) + 4] = pack_bf16(u[4 * i + 2], u[4 * i + 3]);
          }
        };
        if ((op & 3) != OP_O) {
          if ((op & 3) == OP_Q) bi0 = take(rdy0, SZ_WQ, ad);
          wg_wait<0>();
          fence_regs(o);
          release(sv);
          float u[96];
#pragma unroll
          for (int i = 0; i < 96; i++) u[i] = o[i] * (i & 2 ? i1 : i0);
          if ((op & 3) != OP_Q) { convert(u, 0, 6); break; }
          fence_regs(u);
          xw(ad, 0);
          sched_fence(img0, P.zero);
          fence_regs(u);
          convert(u, 0, 1);
          stg2_if(true, pend, q[0], q[1], q[2], q[3], q[4], q[5], q[6], q[7], spol);
          probe1();
          wg_wait<0>();
          release(bi0);
          bi0 = take(rdy0, SZ_WQ, ad);
          xw(ad, 1);
          sched_fence(img0, P.zero);
          fence_regs(u);
          convert(u, 1, 6);
          k = 1;
          continue;
        }
        int bi = ow(0, 0);
        wg_wait<2>();
        fence_regs(o);
        release(sv);
#pragma unroll
        for (int j = 0; j < 6; j++) {
          uint32_t t[8];
#pragma unroll
          for (int i = 0; i < 4; i++) {
            t[i] = pack_bf16(o[16 * j + 4 * i] * i0, o[16 * j + 4 * i + 1] * i0);
            t[i + 4] = pack_bf16(o[16 * j + 4 * i + 2] * i1, o[16 * j + 4 * i + 3] * i1);
          }
          stg2_if(true, pend + j * 512, t[0], t[1], t[2], t[3], t[4], t[5], t[6], t[7], spol);
          if (j == 5) {
            __syncwarp();
            mbar_arrive_if(lane < 2, odone);
          }
          probe1();
          wg_wait<1>();
          bi = ow(1, bi);
          fence_regs(o);
        }
        {
          const int nk = 12 * (((op >> 5) & 15) - ((op >> 2) & 7)) - ((op & F_ST) ? 0 : 2);
#pragma unroll 1
          for (int k = 7; k < nk; k++) {
            probe1();
            wg_wait<1>();
            bi = ow(1, bi);
          }
        }
        if (!(op & F_ST)) {
          probe2();
          wg_wait<1>();
          if (wg) {
            wg_wait<0>();
            release(bi);
            bar_sync(2, 256);
          }
          bi0 = ow(2, 0);
          rdy0 = rdy1;
          const int b = ow(2, 0);
          if (!wg) asm volatile("bar.arrive 2, 256;" ::: "memory");
          wg_wait<4>();
          mbar_arrive_cluster_if(lane < 2 && !wg, empty_rem + bi);
          bi = b;
        }
        probe1();
        nop = prog[++pc];
        if (op & F_LD) {
          uint32_t t[80];
#pragma unroll
          for (int j = 0; j < 5; j++) {
            const int b = take(rdy0, SZ_PART, ad);
            probe1();
#pragma unroll
            for (int i = 4 * j; i < 4 * j + 4; i++)
              lds128(sbase + (ad - ring16 + img0) * 16 + ((i >> 1) & 1) * 8192 + (i & 1) * 512, t[4 * i], t[4 * i + 1], t[4 * i + 2], t[4 * i + 3]);
            release(b);
          }
          wg_wait<0>();
          fence_regs(c);
#pragma unroll
          for (int i = 0; i < 80; i++) c[i] += __uint_as_float(t[i]);
        }
        if (!(op & F_ST)) {
          wg_wait<0>();
          fence_regs(c);
          release(bi0);
          release(bi);
          goto finish;
        }
        op = nop;
        enter();
        bi0 = take(rdy0, SZ_WQ, ad);
        xw(ad, 0);
        pend = &g_part[((team * 4 + nt) * 2 + rank) * 5120 + img0];
        probe1();
        wg_wait<1>();
        fence_regs(c);
        release(bi);
        st_part(0); st_part(1);
        wg_wait<0>();
        release(bi0);
        bi0 = take(rdy0, SZ_WQ, ad);
        xw(ad, 1);
        st_part(2); st_part(3);
#pragma unroll
        for (int i = 0; i < 48; i++) q[i] = __float_as_uint(c[32 + i]);
        pend += 4 * 512;
        k = 1; lag = 2;
      }
    }
    rdy0 = false;
    {
      uint32_t t[48];
#pragma unroll
      for (int i = 0; i < 48; i++) t[i] = q[i] ^ P.zero;
      while ((op & 3) == OP_O) {
        int bi = ow(0, 0);
#pragma unroll 1
        for (int k = 1; k < 12 * (int)(((op >> 5) & 15) - ((op >> 2) & 7)); k++) {
          drain(t, k - 1);
          probe1();
          wg_wait<1>();
          bi = ow(1, bi);
        }
        rdy0 = false;
        wg_wait<0>();
        fence_regs(c);
        pc++;
        release(bi);
        if (!(op & F_ST)) goto finish;
        pend = &g_part[((((op >> 26) & 56) | ((op >> 9) & 7)) * 2 + rank) * 5120 + img0];
#pragma unroll
        for (int i = 6; i < 10; i++) st_part(i);
#pragma unroll
        for (int i = 0; i < 48; i++) t[i] = __float_as_uint(c[i]) ^ P.zero;
        op = prog[pc];
        enter();
      }
      for (int i = 0; i < 6; i++) drain(t, i);
    }
    if (false) {
    finish:
      uint32_t ad;
      take(rdy0, SZ_OUT, ad);
      const uint32_t wstage = sbase + (ad - ring16) * 16 + (wg * 4 + warp) * 5120;
      const uint32_t sa = wstage + (lane & 15) * 64;
#pragma unroll
      for (int i = 0; i < 10; i++) {
        const int u = (i & 1) * 2 + (lane >> 4);
        stsm4(sa + (i >> 1) * 1024 + ((u ^ ((lane >> 1) & 3)) << 4), pack_bf16(c[8 * i], c[8 * i + 1]), pack_bf16(c[8 * i + 2], c[8 * i + 3]),
              pack_bf16(c[8 * i + 4], c[8 * i + 5]), pack_bf16(c[8 * i + 6], c[8 * i + 7]));
      }
      asm volatile("fence.proxy.async.shared::cta;" ::: "memory");
      __syncwarp();
      if (lane == 0) {
        tma3d_store(&P.out, wstage, 0, (team & 7) * kSq + rank * 128 + wg * 64 + warp * 16, blk * 20 + nt * 5);
        asm volatile("cp.async.bulk.commit_group;\ncp.async.bulk.wait_group.read 0;" ::: "memory");
      }
    }
  }
}

typedef CUresult (*EncodeFn)(CUtensorMap*, CUtensorMapDataType, cuuint32_t, void*, const cuuint64_t*, const cuuint64_t*,
                             const cuuint32_t*, const cuuint32_t*, CUtensorMapInterleave, CUtensorMapSwizzle,
                             CUtensorMapL2promotion, CUtensorMapFloatOOBfill);

void encode(EncodeFn fn, CUtensorMap* m, const void* ptr, int rank, const cuuint64_t* dims, const cuuint64_t* strides,
            const cuuint32_t* box, CUtensorMapSwizzle swz) {
  const cuuint32_t es[5] = {1, 1, 1, 1, 1};
  CUresult r = fn(m, CU_TENSOR_MAP_DATA_TYPE_BFLOAT16, rank, const_cast<void*>(ptr), dims, strides, box, es,
                  CU_TENSOR_MAP_INTERLEAVE_NONE, swz, CU_TENSOR_MAP_L2_PROMOTION_L2_128B, CU_TENSOR_MAP_FLOAT_OOB_FILL_NONE);
  if (r != CUDA_SUCCESS) fprintf(stderr, "cuTensorMapEncodeTiled failed: %d\n", (int)r);
}

void annotate(uint32_t* ops, int n, bool helper) {
  uint32_t items = 0, cur = 0, pend = 0;
  auto item = [&](uint32_t bytes, int count, uint32_t bytes2 = 0) {
    for (int i = 0; i < count; i++) {
      if (cur + bytes > RING) cur = 0;
      cur += bytes;
      if (cur + bytes2 > RING) cur = 0;
      cur += bytes2;
      items++;
    }
  };
  for (int i = 0; i <= n; i++) {
    const uint32_t op = ops[i];
    ops[i] |= (items % (2 * NBAR)) << 15 | (cur >> 12) << 20 | pend << 26;
    if ((op & 3) == OP_Q) { item(SZ_WQ, 10, SZ_A); pend = (op & F_PARK) ? (helper ? 1 : 2) : 0; }
    if ((op & 3) == OP_A) {
      item(SZ_KV, (op & F_PARK) ? 30 : 31);
      if ((ops[i + 1] & 3) == OP_A) { item(SZ_PARK, 2); item(SZ_KV, 1); }
      item(SZ_KV, 1);
      pend = 1;
    }
    if ((op & 3) == OP_O) {
      item(SZ_A, 12 * (((op >> 5) & 15) - ((op >> 2) & 7)), SZ_WO);
      if (op & F_LD) item(SZ_PART, 5);
      pend = (op & F_ST) ? (helper ? 1 : 2) : 0;
    }
  }
}

void compile_programs(const char* const* text, bool helpers, Params& P) {
  struct Req { int when, team, wave, slot; } req[N_TEAM * MAX_PARK];
  int n_req = 0;
  for (int t = 0; t < N_TEAM; t++) {
    uint32_t* ops = P.ops[t];
    int n = 0, flags[8] = {0, 0, 0, 0, 0, 0, 0, 0}, n_park = 0, last_o = -1, when = 0, given = 0;
    for (const char* s = text[t]; *s; s++) {
      const int a = s[1] - '0';
      if (*s == 'Q' || (*s == 'H' && !helpers)) { ops[n++] = OP_Q | a << 2; when += 10; }
      else if (*s == 'P') { flags[a] = F_PARK; ops[n++] = OP_Q | a << 2 | flags[a]; when += 10; }
      else if (*s == 'H') { req[n_req++] = {when, t, a, n_park}; flags[a] = F_PARK | F_HELP | n_park++ << 10; }
      else if (*s == 'A') { ops[n++] = OP_A | a << 2 | flags[a]; when += 32; }
      else if (*s == 'G') { given = a; if (helpers) req[n_req++] = {1000, t, 0, -a}; }
      else if (*s == 'O') {
        ops[n] = OP_O | a << 2 | (s[2] - '0') << 5;
        if (given) ops[n] = helpers ? ops[n] | F_LD | F_PARK | (MAX_PARK - 1) << 10 : ops[n] & ~(7u << 2);
        if (last_o >= 0) { ops[last_o] |= F_ST; ops[n] |= F_LD; }
        last_o = n++;
        when += 10 * (s[2] - s[1]);
      }
    }
    for (int i = n; i < MAX_OPS; i++) ops[i] = OP_END;
    annotate(ops, n, false);
  }
  for (int i = 1; i < n_req; i++)
    for (int j = i; j > 0 && req[j].when < req[j - 1].when; j--) { Req r = req[j]; req[j] = req[j - 1]; req[j - 1] = r; }
  for (int h = 0; h < N_HELP; h++) {
    uint32_t* ops = P.ops[N_TEAM + 2 * h];
    int n = 0;
    for (int i = 0; i < n_req; i++)
      for (int m = h; m < 4; m += N_HELP) {
        const uint32_t ro = 4 * req[i].team + m;
        ops[n++] = req[i].slot >= 0 ? OP_Q | req[i].wave << 2 | req[i].team << 5 | F_PARK | req[i].slot << 10 | m << 12
                                    : OP_O | -req[i].slot << 5 | F_ST | (ro & 7) << 9 | (ro >> 3) << 29;
      }
    for (int i = n; i < 2 * MAX_OPS; i++) ops[i] = OP_END;
    annotate(ops, n, true);
  }
  for (int i = 0; i < 32; i++) P.first[i] = i < N_TEAM ? P.ops[i][0] : i < N_TEAM + N_HELP ? P.ops[2 * i - N_TEAM][0] : 0;
}

const char* const kPrograms[N_TEAM] = {
  "Q0A0Q1A1H2A2Q3A3O03Q4A4Q5A5Q6A6Q7A7O38",
  "Q0A0Q1A1Q2A2Q3A3O04Q4A4Q5A5Q6A6H7A7O48",
  "Q0A0H1A1Q2A2Q3A3Q4A4O05Q5A5Q6A6Q7A7O58",
  "Q0A0Q1A1Q2A2O03Q3A3Q4A4Q5A5H6A6Q7A7O38",
  "Q0A0Q1A1Q2A2Q3A3Q4A4O05Q5A5Q6A6H7A7O58",
  "Q0A0Q1A1H2A2Q3A3Q4A4O05Q5A5Q6A6Q7A7O58",
  "Q0A0Q1A1Q2A2O03Q3A3Q4A4H5A5Q6A6Q7A7O38",
  "Q0A0Q1A1Q2A2O03Q3A3H4A4Q5A5Q6A6Q7A7O38",
  "P3Q0A0Q1A1Q2A2A3H4A4Q5A5Q6A6Q7A7O08",
  "P5P7Q0A0Q1A1Q2A2H3A3Q4A4A5Q6A6A7G1O18",
  "Q0A0Q1A1Q2A2O02Q3A3H4A4Q5A5Q6A6Q7A7O28",
  "P3P5Q0A0Q1A1Q2A2A3Q4A4A5Q6A6H7A7O08",
  "Q0A0Q1A1Q2A2Q3A3Q4A4Q5A5H6A6Q7A7O08",
  "P7Q0A0Q1A1Q2A2Q3A3Q4A4Q5A5Q6A6A7G1O18",
  "Q0A0Q1A1Q2A2H3A3Q4A4Q5A5Q6A6Q7A7O08",
  "P3Q0A0Q1A1Q2A2A3Q4A4Q5A5H6A6Q7A7O08",
};

const char* const* bench_programs() {
  return kPrograms;
}

}

extern "C" void kernel_launch(void* const* d_in, const int* in_sizes, int n_in, void* d_out, int out_size) {
  (void)in_sizes; (void)n_in; (void)out_size;
  static EncodeFn fn = nullptr;
  static int n_clusters = 0;
  if (!fn) {
    cudaDriverEntryPointQueryResult qr;
    void* f = nullptr;
    cudaGetDriverEntryPoint("cuTensorMapEncodeTiled", &f, cudaEnableDefault, &qr);
    fn = (EncodeFn)f;
    cudaFuncSetAttribute(fused_kernel, cudaFuncAttributeMaxDynamicSharedMemorySize, SMEM_BYTES);
    cudaLaunchConfig_t cfg = {};
    cfg.gridDim = dim3(132); cfg.blockDim = dim3(384); cfg.dynamicSmemBytes = SMEM_BYTES;
    cudaLaunchAttribute at[1];
    at[0].id = cudaLaunchAttributeClusterDimension; at[0].val.clusterDim.x = 2; at[0].val.clusterDim.y = 1; at[0].val.clusterDim.z = 1;
    cfg.attrs = at; cfg.numAttrs = 1;
    if (cudaOccupancyMaxActiveClusters(&n_clusters, fused_kernel, &cfg) != cudaSuccess || n_clusters < 1) n_clusters = 1;
    (void)cudaGetLastError();
  }
  Params P;
  const CUtensorMapSwizzle S128 = CU_TENSOR_MAP_SWIZZLE_128B, S64 = CU_TENSOR_MAP_SWIZZLE_64B;
  for (int blk = 0; blk < 2; blk++) {
    void* const* in = d_in + 5 * blk;
    { const cuuint64_t d[] = {kD, kB * kSq}, s[] = {kD * 2}; const cuuint32_t b[] = {64, 128};
      encode(fn, &P.x[blk], in[0], 2, d, s, b, S128); }
    { const cuuint64_t d[] = {64, 8, 3, (cuuint64_t)kB * kH * kSk / 8}, s[] = {kDh * 2, 128, 8 * kDh * 2}; const cuuint32_t b[] = {64, 8, 3, 4};
      encode(fn, &P.k[blk], in[1], 4, d, s, b, S128);
      encode(fn, &P.v[blk], in[2], 4, d, s, b, S128); }
    { const cuuint64_t d[] = {64, kD, kHD / 64}, s[] = {kHD * 2, 128}; const cuuint32_t b[] = {64, 32, 3};
      encode(fn, &P.wq[blk], in[3], 3, d, s, b, S128); }
    { const cuuint64_t d[] = {32, 2, kHD / 8, 4, kD / 32}, s[] = {kD * 2, 8 * kD * 2, 2 * kD * 2, 64}; const cuuint32_t b[] = {32, 2, 4, 4, 5};
      encode(fn, &P.wo[blk], in[4], 5, d, s, b, S64); }
  }
  { const cuuint64_t d[] = {32, kB * kSq, 2 * kD / 32}, s[] = {2 * kD * 2, 64}; const cuuint32_t b[] = {32, 16, 5};
    encode(fn, &P.out, d_out, 3, d, s, b, S64); }

  P.zero = 0;
  if (n_clusters >= N_CL) {
    const bool helpers = n_clusters >= N_CL + N_HELP;
    compile_programs(bench_programs(), helpers, P);
    fused_kernel<<<2 * (N_CL + (helpers ? N_HELP : 0)), 384, SMEM_BYTES>>>(P);
  } else {
    for (int phase = 0; phase < 2; phase++) {
      const char* text[N_TEAM];
      for (int t = 0; t < N_TEAM; t++) text[t] = phase ? "O08" : "Q0A0Q1A1Q2A2Q3A3Q4A4Q5A5Q6A6Q7A7";
      compile_programs(text, false, P);
      fused_kernel<<<2 * N_CL, 384, SMEM_BYTES>>>(P);
    }
  }
}
```

```cpp
#include <cuda_runtime.h>
#include <cuda_bf16.h>
#include <cuda.h>
#include <stdint.h>
#include <stdio.h>

namespace {

constexpr int kB = 8, kSq = 256, kD = 640, kH = 32, kSk = 1024, kDh = 192;
constexpr int kHD = kH * kDh;
constexpr uint32_t RING = 224 * 1024;
constexpr uint32_t SZ_KV = 24576;
constexpr uint32_t SZ_WQ = 24576, SZ_WO = 20480, SZ_A = 16384;
constexpr uint32_t SZ_OUT = 40960;
constexpr uint32_t SZ_PARK = 24576;
constexpr uint32_t SZ_PART = 16384;
constexpr int NBAR = 16, NFLIGHT = 12;
constexpr int KV_TRANSIT = 4;
constexpr int EARLY = 3;
constexpr int S1A = 7;
constexpr uint32_t KV_CH = 64, KV_SBO = 3072;
constexpr int SMEM_BYTES = RING + 512 + 1024;
constexpr int N_TEAM = 16, N_CL = 64, N_HELP = 2, MAX_OPS = 24, MAX_PARK = 4;
enum { OP_END = 0, OP_Q = 1, OP_A = 2, OP_O = 3, F_PARK = 1 << 9, F_LD = 1 << 12, F_ST = 1 << 13, F_HELP = 1 << 12 };

struct alignas(64) Params {
  uint32_t first[32];
  CUtensorMap x[2], wq[2], k[2], v[2], wo[2], out;
  uint32_t ops[N_TEAM + 2 * N_HELP][MAX_OPS];
  uint32_t zero;
};

__device__ uint4 g_o[N_TEAM * 2 * 96 * 1024];
__device__ uint4 g_part[N_CL * 2 * 5 * 1024];
__device__ unsigned int g_done[N_TEAM * 2 * 8];
__device__ unsigned int g_help[N_CL * 2 * MAX_PARK];
__device__ unsigned int g_seen[N_TEAM * 2 * 8];

template <int TB>
__device__ __forceinline__ void wgmma_rs_n64(float (&d)[32], uint32_t a0, uint32_t a1, uint32_t a2, uint32_t a3, uint64_t db, int scale_d) {
  asm volatile("{\n.reg .pred p;\nsetp.ne.b32 p, %37, 0;\n"
    "wgmma.mma_async.sync.aligned.m64n64k16.f32.bf16.bf16 {%0, %1, %2, %3, %4, %5, %6, %7, %8, %9, %10, %11, %12, %13, %14, %15, %16, %17, %18, %19, %20, %21, %22, %23, %24, %25, %26, %27, %28, %29, %30, %31}, {%32, %33, %34, %35}, %36, p, 1, 1, %38;\n}\n"
    : "+f"(d[0]), "+f"(d[1]), "+f"(d[2]), "+f"(d[3]), "+f"(d[4]), "+f"(d[5]), "+f"(d[6]), "+f"(d[7]), "+f"(d[8]), "+f"(d[9]), "+f"(d[10]), "+f"(d[11]), "+f"(d[12]), "+f"(d[13]), "+f"(d[14]), "+f"(d[15]), "+f"(d[16]), "+f"(d[17]), "+f"(d[18]), "+f"(d[19]), "+f"(d[20]), "+f"(d[21]), "+f"(d[22]), "+f"(d[23]), "+f"(d[24]), "+f"(d[25]), "+f"(d[26]), "+f"(d[27]), "+f"(d[28]), "+f"(d[29]), "+f"(d[30]), "+f"(d[31])
    : "r"(a0), "r"(a1), "r"(a2), "r"(a3), "l"(db), "r"(scale_d), "n"(TB));
}
template <int TB, int TA = 0>
__device__ __forceinline__ void wgmma_ss_n160(float (&d)[80], uint64_t da, uint64_t db, int scale_d) {
  asm volatile("{\n.reg .pred p;\nsetp.ne.b32 p, %82, 0;\n"
    "wgmma.mma_async.sync.aligned.m64n160k16.f32.bf16.bf16 {%0, %1, %2, %3, %4, %5, %6, %7, %8, %9, %10, %11, %12, %13, %14, %15, %16, %17, %18, %19, %20, %21, %22, %23, %24, %25, %26, %27, %28, %29, %30, %31, %32, %33, %34, %35, %36, %37, %38, %39, %40, %41, %42, %43, %44, %45, %46, %47, %48, %49, %50, %51, %52, %53, %54, %55, %56, %57, %58, %59, %60, %61, %62, %63, %64, %65, %66, %67, %68, %69, %70, %71, %72, %73, %74, %75, %76, %77, %78, %79}, %80, %81, p, 1, 1, %83, %84;\n}\n"
    : "+f"(d[0]), "+f"(d[1]), "+f"(d[2]), "+f"(d[3]), "+f"(d[4]), "+f"(d[5]), "+f"(d[6]), "+f"(d[7]), "+f"(d[8]), "+f"(d[9]), "+f"(d[10]), "+f"(d[11]), "+f"(d[12]), "+f"(d[13]), "+f"(d[14]), "+f"(d[15]), "+f"(d[16]), "+f"(d[17]), "+f"(d[18]), "+f"(d[19]), "+f"(d[20]), "+f"(d[21]), "+f"(d[22]), "+f"(d[23]), "+f"(d[24]), "+f"(d[25]), "+f"(d[26]), "+f"(d[27]), "+f"(d[28]), "+f"(d[29]), "+f"(d[30]), "+f"(d[31]), "+f"(d[32]), "+f"(d[33]), "+f"(d[34]), "+f"(d[35]), "+f"(d[36]), "+f"(d[37]), "+f"(d[38]), "+f"(d[39]), "+f"(d[40]), "+f"(d[41]), "+f"(d[42]), "+f"(d[43]), "+f"(d[44]), "+f"(d[45]), "+f"(d[46]), "+f"(d[47]), "+f"(d[48]), "+f"(d[49]), "+f"(d[50]), "+f"(d[51]), "+f"(d[52]), "+f"(d[53]), "+f"(d[54]), "+f"(d[55]), "+f"(d[56]), "+f"(d[57]), "+f"(d[58]), "+f"(d[59]), "+f"(d[60]), "+f"(d[61]), "+f"(d[62]), "+f"(d[63]), "+f"(d[64]), "+f"(d[65]), "+f"(d[66]), "+f"(d[67]), "+f"(d[68]), "+f"(d[69]), "+f"(d[70]), "+f"(d[71]), "+f"(d[72]), "+f"(d[73]), "+f"(d[74]), "+f"(d[75]), "+f"(d[76]), "+f"(d[77]), "+f"(d[78]), "+f"(d[79])
    : "l"(da), "l"(db), "r"(scale_d), "n"(TA), "n"(TB));
}
template <int TB, int TA = 0>
__device__ __forceinline__ void wgmma_ss_n192(float (&d)[96], uint64_t da, uint64_t db, int scale_d) {
  asm volatile("{\n.reg .pred p;\nsetp.ne.b32 p, %98, 0;\n"
    "wgmma.mma_async.sync.aligned.m64n192k16.f32.bf16.bf16 {%0, %1, %2, %3, %4, %5, %6, %7, %8, %9, %10, %11, %12, %13, %14, %15, %16, %17, %18, %19, %20, %21, %22, %23, %24, %25, %26, %27, %28, %29, %30, %31, %32, %33, %34, %35, %36, %37, %38, %39, %40, %41, %42, %43, %44, %45, %46, %47, %48, %49, %50, %51, %52, %53, %54, %55, %56, %57, %58, %59, %60, %61, %62, %63, %64, %65, %66, %67, %68, %69, %70, %71, %72, %73, %74, %75, %76, %77, %78, %79, %80, %81, %82, %83, %84, %85, %86, %87, %88, %89, %90, %91, %92, %93, %94, %95}, %96, %97, p, 1, 1, %99, %100;\n}\n"
    : "+f"(d[0]), "+f"(d[1]), "+f"(d[2]), "+f"(d[3]), "+f"(d[4]), "+f"(d[5]), "+f"(d[6]), "+f"(d[7]), "+f"(d[8]), "+f"(d[9]), "+f"(d[10]), "+f"(d[11]), "+f"(d[12]), "+f"(d[13]), "+f"(d[14]), "+f"(d[15]), "+f"(d[16]), "+f"(d[17]), "+f"(d[18]), "+f"(d[19]), "+f"(d[20]), "+f"(d[21]), "+f"(d[22]), "+f"(d[23]), "+f"(d[24]), "+f"(d[25]), "+f"(d[26]), "+f"(d[27]), "+f"(d[28]), "+f"(d[29]), "+f"(d[30]), "+f"(d[31]), "+f"(d[32]), "+f"(d[33]), "+f"(d[34]), "+f"(d[35]), "+f"(d[36]), "+f"(d[37]), "+f"(d[38]), "+f"(d[39]), "+f"(d[40]), "+f"(d[41]), "+f"(d[42]), "+f"(d[43]), "+f"(d[44]), "+f"(d[45]), "+f"(d[46]), "+f"(d[47]), "+f"(d[48]), "+f"(d[49]), "+f"(d[50]), "+f"(d[51]), "+f"(d[52]), "+f"(d[53]), "+f"(d[54]), "+f"(d[55]), "+f"(d[56]), "+f"(d[57]), "+f"(d[58]), "+f"(d[59]), "+f"(d[60]), "+f"(d[61]), "+f"(d[62]), "+f"(d[63]), "+f"(d[64]), "+f"(d[65]), "+f"(d[66]), "+f"(d[67]), "+f"(d[68]), "+f"(d[69]), "+f"(d[70]), "+f"(d[71]), "+f"(d[72]), "+f"(d[73]), "+f"(d[74]), "+f"(d[75]), "+f"(d[76]), "+f"(d[77]), "+f"(d[78]), "+f"(d[79]), "+f"(d[80]), "+f"(d[81]), "+f"(d[82]), "+f"(d[83]), "+f"(d[84]), "+f"(d[85]), "+f"(d[86]), "+f"(d[87]), "+f"(d[88]), "+f"(d[89]), "+f"(d[90]), "+f"(d[91]), "+f"(d[92]), "+f"(d[93]), "+f"(d[94]), "+f"(d[95])
    : "l"(da), "l"(db), "r"(scale_d), "n"(TA), "n"(TB));
}
template <int TB>
__device__ __forceinline__ void wgmma_rs_n192(float (&d)[96], uint32_t a0, uint32_t a1, uint32_t a2, uint32_t a3, uint64_t db, int scale_d) {
  asm volatile("{\n.reg .pred p;\nsetp.ne.b32 p, %101, 0;\n"
    "wgmma.mma_async.sync.aligned.m64n192k16.f32.bf16.bf16 {%0, %1, %2, %3, %4, %5, %6, %7, %8, %9, %10, %11, %12, %13, %14, %15, %16, %17, %18, %19, %20, %21, %22, %23, %24, %25, %26, %27, %28, %29, %30, %31, %32, %33, %34, %35, %36, %37, %38, %39, %40, %41, %42, %43, %44, %45, %46, %47, %48, %49, %50, %51, %52, %53, %54, %55, %56, %57, %58, %59, %60, %61, %62, %63, %64, %65, %66, %67, %68, %69, %70, %71, %72, %73, %74, %75, %76, %77, %78, %79, %80, %81, %82, %83, %84, %85, %86, %87, %88, %89, %90, %91, %92, %93, %94, %95}, {%96, %97, %98, %99}, %100, p, 1, 1, %102;\n}\n"
    : "+f"(d[0]), "+f"(d[1]), "+f"(d[2]), "+f"(d[3]), "+f"(d[4]), "+f"(d[5]), "+f"(d[6]), "+f"(d[7]), "+f"(d[8]), "+f"(d[9]), "+f"(d[10]), "+f"(d[11]), "+f"(d[12]), "+f"(d[13]), "+f"(d[14]), "+f"(d[15]), "+f"(d[16]), "+f"(d[17]), "+f"(d[18]), "+f"(d[19]), "+f"(d[20]), "+f"(d[21]), "+f"(d[22]), "+f"(d[23]), "+f"(d[24]), "+f"(d[25]), "+f"(d[26]), "+f"(d[27]), "+f"(d[28]), "+f"(d[29]), "+f"(d[30]), "+f"(d[31]), "+f"(d[32]), "+f"(d[33]), "+f"(d[34]), "+f"(d[35]), "+f"(d[36]), "+f"(d[37]), "+f"(d[38]), "+f"(d[39]), "+f"(d[40]), "+f"(d[41]), "+f"(d[42]), "+f"(d[43]), "+f"(d[44]), "+f"(d[45]), "+f"(d[46]), "+f"(d[47]), "+f"(d[48]), "+f"(d[49]), "+f"(d[50]), "+f"(d[51]), "+f"(d[52]), "+f"(d[53]), "+f"(d[54]), "+f"(d[55]), "+f"(d[56]), "+f"(d[57]), "+f"(d[58]), "+f"(d[59]), "+f"(d[60]), "+f"(d[61]), "+f"(d[62]), "+f"(d[63]), "+f"(d[64]), "+f"(d[65]), "+f"(d[66]), "+f"(d[67]), "+f"(d[68]), "+f"(d[69]), "+f"(d[70]), "+f"(d[71]), "+f"(d[72]), "+f"(d[73]), "+f"(d[74]), "+f"(d[75]), "+f"(d[76]), "+f"(d[77]), "+f"(d[78]), "+f"(d[79]), "+f"(d[80]), "+f"(d[81]), "+f"(d[82]), "+f"(d[83]), "+f"(d[84]), "+f"(d[85]), "+f"(d[86]), "+f"(d[87]), "+f"(d[88]), "+f"(d[89]), "+f"(d[90]), "+f"(d[91]), "+f"(d[92]), "+f"(d[93]), "+f"(d[94]), "+f"(d[95])
    : "r"(a0), "r"(a1), "r"(a2), "r"(a3), "l"(db), "r"(scale_d), "n"(TB));
}

__device__ __forceinline__ uint32_t smem_u32(const void* p) { return (uint32_t)__cvta_generic_to_shared(p); }
__device__ __forceinline__ void wg_fence() { asm volatile("wgmma.fence.sync.aligned;" ::: "memory"); }
__device__ __forceinline__ void wg_commit() { asm volatile("wgmma.commit_group.sync.aligned;" ::: "memory"); }
template <int N> __device__ __forceinline__ void wg_wait() { asm volatile("wgmma.wait_group.sync.aligned %0;" ::"n"(N) : "memory"); }
__device__ __forceinline__ void sched_fence(int& keep, uint32_t zero) {
  asm volatile("{\n.reg .u32 c;\nmov.u32 c, %%clock;\nand.b32 c, c, %1;\nxor.b32 %0, %0, c;\n}\n" : "+r"(keep) : "r"(zero) : "memory");
}
template <int N> __device__ __forceinline__ void fence_regs(float (&r)[N]) {
#pragma unroll
  for (int i = 0; i < N; i++) asm volatile("" : "+f"(r[i])::"memory");
}
template <int N> __device__ __forceinline__ void fence_regs(uint32_t (&r)[N]) {
#pragma unroll
  for (int i = 0; i < N; i++) asm volatile("" : "+r"(r[i])::"memory");
}
__device__ __forceinline__ uint64_t mk_desc(uint32_t a16, uint32_t lbo, uint32_t sbo, uint32_t swz, uint32_t off = 0) {
  uint64_t d;
  asm("mov.b64 %0, {%1, %2};" : "=l"(d) : "r"(a16), "r"((sbo >> 4) | (swz << 30)));
  return d + (off + ((lbo >> 4) << 16));
}
__device__ __forceinline__ void mbar_init(uint32_t bar, uint32_t cnt) {
  asm volatile("mbarrier.init.shared::cta.b64 [%0], %1;" ::"r"(bar), "r"(cnt) : "memory");
}
__device__ __forceinline__ void mbar_expect(uint32_t bar, uint32_t tx) {
  asm volatile("mbarrier.arrive.expect_tx.shared::cta.b64 _, [%0], %1;" ::"r"(bar), "r"(tx) : "memory");
}
__device__ __forceinline__ bool mbar_test(uint32_t bar, uint32_t ph) {
  uint32_t ok;
  asm volatile("{\n.reg .pred p;\nmbarrier.test_wait.parity.shared::cta.b64 p, [%1], %2;\nselp.u32 %0, 1, 0, p;\n}\n"
               : "=r"(ok) : "r"(bar), "r"(ph) : "memory");
  return ok;
}
__device__ __forceinline__ void mbar_wait(uint32_t bar, uint32_t ph) {
  asm volatile("{\n.reg .pred p;\n.reg .u32 n;\nmov.u32 n, 0;\n"
               "LOOP:\nadd.u32 n, n, 1;\nmbarrier.try_wait.parity.shared::cta.b64 p, [%0], %1;\n@p bra DONE;\n"
               "setp.lt.u32 p, n, 0x1000000;\n@p bra LOOP;\ntrap;\n"
               "DONE:\n}\n" ::"r"(bar), "r"(ph) : "memory");
}
__device__ __forceinline__ void mbar_wait_math(uint32_t bar, uint32_t ph) {
  asm volatile("{\n.reg .pred p;\nLOOP:\nmbarrier.try_wait.parity.shared::cta.b64 p, [%0], %1;\n@!p bra LOOP;\n}\n" ::"r"(bar), "r"(ph) : "memory");
}
__device__ __forceinline__ void mbar_wait_long(uint32_t bar, uint32_t ph) {
  asm volatile("{\n.reg .pred p;\n.reg .u32 n;\nmov.u32 n, 0;\n"
               "LOOP:\nmbarrier.try_wait.parity.shared::cta.b64 p, [%0], %1, %2;\n@p bra DONE;\n"
               "add.u32 n, n, 1;\nsetp.lt.u32 p, n, 0x40000;\n@p bra LOOP;\ntrap;\n"
               "DONE:\n}\n" ::"r"(bar), "r"(ph), "r"(20000) : "memory");
}
__device__ __forceinline__ void mbar_arrive_cluster_if(bool on, uint32_t addr) {
  asm volatile("{\n.reg .pred p;\nsetp.ne.b32 p, %1, 0;\n@p mbarrier.arrive.shared::cluster.b64 _, [%0];\n}\n" ::"r"(addr), "r"((int)on) : "memory");
}
__device__ __forceinline__ void mbar_arrive_if(bool on, uint32_t addr) {
  asm volatile("{\n.reg .pred p;\nsetp.ne.b32 p, %1, 0;\n@p mbarrier.arrive.shared::cta.b64 _, [%0];\n}\n" ::"r"(addr), "r"((int)on) : "memory");
}
__device__ __forceinline__ void tma2d(uint32_t dst, const CUtensorMap* m, uint32_t bar, int c0, int c1) {
  asm volatile("cp.async.bulk.tensor.2d.shared::cluster.global.mbarrier::complete_tx::bytes [%0], [%1, {%3, %4}], [%2];"
               ::"r"(dst), "l"(m), "r"(bar), "r"(c0), "r"(c1) : "memory");
}
__device__ __forceinline__ void tma3d(uint32_t dst, const CUtensorMap* m, uint32_t bar, int c0, int c1, int c2) {
  asm volatile("cp.async.bulk.tensor.3d.shared::cluster.global.mbarrier::complete_tx::bytes [%0], [%1, {%3, %4, %5}], [%2];"
               ::"r"(dst), "l"(m), "r"(bar), "r"(c0), "r"(c1), "r"(c2) : "memory");
}
__device__ __forceinline__ void tma3d_mc(uint32_t dst, const CUtensorMap* m, uint32_t bar, int c0, int c1, int c2) {
  asm volatile("cp.async.bulk.tensor.3d.shared::cluster.global.mbarrier::complete_tx::bytes.multicast::cluster"
               " [%0], [%1, {%3, %4, %5}], [%2], %6;"
               ::"r"(dst), "l"(m), "r"(bar), "r"(c0), "r"(c1), "r"(c2), "h"((uint16_t)3) : "memory");
}
__device__ __forceinline__ void tma3d_store(const CUtensorMap* m, uint32_t src, int c0, int c1, int c2) {
  asm volatile("cp.async.bulk.tensor.3d.global.shared::cta.bulk_group [%0, {%2, %3, %4}], [%1];"
               ::"l"(m), "r"(src), "r"(c0), "r"(c1), "r"(c2) : "memory");
}
__device__ __forceinline__ void bar_sync(int id, int n) { asm volatile("bar.sync %0, %1;" ::"r"(id), "r"(n) : "memory"); }
__device__ __forceinline__ uint32_t pack_bf16(float lo, float hi) {
  uint32_t r;
  asm("cvt.rn.bf16x2.f32 %0, %1, %2;" : "=r"(r) : "f"(hi), "f"(lo));
  return r;
}
__device__ __forceinline__ float ex2(float x) {
  float y;
  asm("ex2.approx.ftz.f32 %0, %1;" : "=f"(y) : "f"(x));
  return y;
}
__device__ __forceinline__ float fadd(float a, float b) {
  float y;
  asm("add.f32 %0, %1, %2;" : "=f"(y) : "f"(a), "f"(b));
  return y;
}
__device__ __forceinline__ float rcp(float x) {
  float y;
  asm("rcp.approx.ftz.f32 %0, %1;" : "=f"(y) : "f"(x));
  return y;
}
__device__ __forceinline__ void stsm4(uint32_t addr, uint32_t a, uint32_t b, uint32_t c, uint32_t d) {
  asm volatile("stmatrix.sync.aligned.m8n8.x4.shared.b16 [%0], {%1, %2, %3, %4};" ::"r"(addr), "r"(a), "r"(b), "r"(c), "r"(d) : "memory");
}

__device__ __forceinline__ void tma4d_mc_hint(uint32_t dst, const CUtensorMap* m, uint32_t bar, int c3, uint64_t pol) {
  asm volatile("cp.async.bulk.tensor.4d.shared::cluster.global.mbarrier::complete_tx::bytes.multicast::cluster.L2::cache_hint"
               " [%0], [%1, {%3, %3, %3, %4}], [%2], %5, %6;"
               ::"r"(dst), "l"(m), "r"(bar), "r"(0), "r"(c3), "h"((uint16_t)3), "l"(pol) : "memory");
}
__device__ __forceinline__ void tma5d_mc(uint32_t dst, const CUtensorMap* m, uint32_t bar, int c2, int c4) {
  asm volatile("cp.async.bulk.tensor.5d.shared::cluster.global.mbarrier::complete_tx::bytes.multicast::cluster"
               " [%0], [%1, {%3, %3, %4, %3, %5}], [%2], %6;"
               ::"r"(dst), "l"(m), "r"(bar), "r"(0), "r"(c2), "r"(c4), "h"((uint16_t)3) : "memory");
}
__device__ __forceinline__ void bulk_load_hint(uint32_t dst, const void* src, uint32_t bytes, uint32_t bar, uint64_t pol) {
  asm volatile("cp.async.bulk.shared::cluster.global.mbarrier::complete_tx::bytes.L2::cache_hint [%0], [%1], %2, [%3], %4;"
               ::"r"(dst), "l"(src), "r"(bytes), "r"(bar), "l"(pol) : "memory");
}
__device__ __forceinline__ void stg2_if(bool on, void* p, uint32_t a, uint32_t b, uint32_t c, uint32_t d, uint32_t e, uint32_t f,
                                        uint32_t g, uint32_t h, uint64_t pol) {
  asm volatile("{\n.reg .pred p;\nsetp.ne.b32 p, %10, 0;\n"
               "@p st.global.L2::cache_hint.v4.b32 [%0], {%1, %2, %3, %4}, %9;\n"
               "@p st.global.L2::cache_hint.v4.b32 [%0 + 512], {%5, %6, %7, %8}, %9;\n}\n"
               ::"l"(p), "r"(a), "r"(b), "r"(c), "r"(d), "r"(e), "r"(f), "r"(g), "r"(h), "l"(pol), "r"((int)on) : "memory");
}
__device__ __forceinline__ uint64_t evict_first() {
  uint64_t p;
  asm("createpolicy.fractional.L2::evict_first.b64 %0, 1.0;" : "=l"(p));
  return p;
}
__device__ __forceinline__ bool elect() {
  uint32_t ok;
  asm volatile("{\n.reg .pred p;\nelect.sync _|p, 0xffffffff;\nselp.u32 %0, 1, 0, p;\n}\n" : "=r"(ok));
  return ok;
}
__device__ __forceinline__ void mbar_arrive(uint32_t bar) {
  asm volatile("mbarrier.arrive.shared::cta.b64 _, [%0];" ::"r"(bar) : "memory");
}
__device__ __forceinline__ void lds128(uint32_t p, uint32_t& a, uint32_t& b, uint32_t& c, uint32_t& d) {
  asm volatile("ld.shared.v4.b32 {%0, %1, %2, %3}, [%4];" : "=r"(a), "=r"(b), "=r"(c), "=r"(d) : "r"(p) : "memory");
}
__device__ __forceinline__ void wait_count(const unsigned int* p, uint32_t target) {
  asm volatile("{\n.reg .pred p;\n.reg .u32 n, v;\nmov.u32 n, 0;\n"
               "LOOP:\nld.acquire.gpu.global.u32 v, [%0];\nsetp.ge.u32 p, v, %1;\n@p bra DONE;\n"
               "nanosleep.u32 %2;\nadd.u32 n, n, 1;\nsetp.lt.u32 p, n, 0x400000;\n@p bra LOOP;\ntrap;\n"
               "DONE:\n}\n" ::"l"(p), "r"(target), "n"(300) : "memory");
}

__device__ __forceinline__ int o_wave(int a, int b, int i) {
  const int p = min(3, b - a - 1);
  return i < p ? b - 2 - i : i == p ? b - 1 : b - 1 - i;
}

struct Cursor {
  uint32_t n;
  __device__ __forceinline__ uint32_t off() const { return n & (8 * NBAR - 8); }
  __device__ __forceinline__ uint32_t ph() const { return (n / (8 * NBAR)) & 1; }
  __device__ __forceinline__ void next() { n += 8; }
};

constexpr float kScaleLog2 = 0.07216878364870322f * 1.4426950408889634f;
constexpr float kSumLimit = 1048576.0f;
constexpr float kMaxLag = 8.0f;

__global__ void __cluster_dims__(2, 1, 1) __launch_bounds__(384, 1)
fused_kernel(const __grid_constant__ Params P) {
  extern __shared__ uint8_t smem_raw[];
  const uint32_t sbase = (smem_u32(smem_raw) + 1023) & ~1023u;
  const uint32_t full0 = sbase + RING, empty0 = full0 + 8 * NBAR, odone = empty0 + 8 * NBAR, oready0 = odone + 8;
  const uint32_t fenced = oready0 + 64, hready0 = fenced + 8;
  const uint32_t rank = blockIdx.x & 1;
  const int role = blockIdx.x >> 1;
  const bool helper = role >= N_CL;
  const int team = helper ? 0 : role >> 2, nt = role & 3, blk = team >> 3;
  const uint32_t* prog = P.ops[helper ? N_TEAM + 2 * (role - N_CL) : team];
  auto q_role = [&](uint32_t op) { return helper ? (int)(((op >> 3) & 60) | ((op >> 12) & 3)) : role; };
  auto o_role = [&](uint32_t op) { return helper ? (int)(((op >> 26) & 56) | ((op >> 9) & 7)) : role; };
  const int wid = __shfl_sync(0xffffffffu, (int)(threadIdx.x >> 5), 0);
  const int wg = wid >> 2;

  const uint32_t op0 = P.first[helper ? N_TEAM + role - N_CL : team];
  if (__builtin_expect(wid == 8, 1)) {
    if (elect()) {
#pragma unroll
      for (int k = 0; k < EARLY; k++) mbar_init(full0 + 8 * k, 1);
      asm volatile("fence.mbarrier_init.release.cluster;" ::: "memory");
      if ((op0 & 3) == OP_Q) {
        const int qr = q_role(op0);
#pragma unroll
        for (int k = 0; k < EARLY; k++) {
          mbar_expect(full0 + 8 * k, SZ_WQ + SZ_A);
          tma2d(sbase + k * (SZ_WQ + SZ_A) + SZ_WQ, &P.x[qr >> 5], full0 + 8 * k, 64 * k, ((qr >> 2) & 7) * kSq + rank * 128);
          tma3d(sbase + k * (SZ_WQ + SZ_A), &P.wq[qr >> 5], full0 + 8 * k, 0, 64 * k, 3 * (4 * ((op0 >> 2) & 7) + (qr & 3)));
          tma3d(sbase + k * (SZ_WQ + SZ_A) + SZ_WQ / 2, &P.wq[qr >> 5], full0 + 8 * k, 0, 64 * k + 32, 3 * (4 * ((op0 >> 2) & 7) + (qr & 3)));
        }
      }
      asm volatile("prefetch.tensormap [%0];" ::"l"(&P.k[blk]) : "memory");
      asm volatile("prefetch.tensormap [%0];" ::"l"(&P.v[blk]) : "memory");
    }
  } else if (threadIdx.x == 0) {
#pragma unroll
    for (int i = EARLY; i < 2 * NBAR + 10 + MAX_PARK; i++) mbar_init(full0 + 8 * i, i >= NBAR && i <= 2 * NBAR ? 16 : 1);
    asm volatile("fence.mbarrier_init.release.cluster;" ::: "memory");
  }
  __syncwarp();
  asm volatile("barrier.cluster.arrive.relaxed.aligned;\nbarrier.cluster.wait.aligned;" ::: "memory");

  if (wg == 2) {
    asm volatile("setmaxnreg.dec.sync.aligned.u32 24;");
    if (wid == 8) {
      Cursor tail{0}, head{0};
      int sh = 0;
      uint32_t cur = 0, used = 0;
      uint64_t fifo = 0;
      uint32_t dst, bar, oready = oready0;
      const uint64_t pol = evict_first();
      auto acquire = [&](uint32_t bytes, int part = 0) {
        uint32_t fp = bytes >> 12;
        if (cur + fp > (RING >> 12)) { fp += (RING >> 12) - cur; cur = 0; }
        used += fp;
        bool more = false;
        uint32_t wbar, wph;
        while (used > (RING >> 12) || (part != 2 && sh == 5 * NFLIGHT)) {
          if (more) mbar_wait(wbar, wph);
          more = true;
          wbar = empty0 + tail.off(); wph = tail.ph();
          tail.next();
          used -= (uint32_t)fifo & 31;
          fifo >>= 5;
          sh -= 5;
        }
        fifo += (uint64_t)fp << sh;
        dst = sbase + (cur << 12);
        bar = full0 + head.off();
        cur += bytes >> 12;
        if (part != 1) {
          sh += 5;
          head.next();
        }
        if (more) mbar_wait(wbar, wph);
      };
      auto scratch = [&](const uint4* src, uint32_t bytes, int n) {
        asm volatile("fence.proxy.async.global;" ::: "memory");
#pragma unroll 1
        for (int i = 0; i < n; i++) {
          acquire(bytes);
          if (elect()) {
            bulk_load_hint(dst, src + i * (bytes / 16), bytes, bar, pol);
            mbar_expect(bar, bytes);
          }
        }
      };
      for (int pc = 0;; pc++) {
        const uint32_t op = prog[pc];
        const int type = op & 3, a = (op >> 2) & 7;
        if (type == OP_END) break;
        if (type == OP_Q) {
          const int qr = q_role(op);
#pragma unroll 1
          for (int k = 0; k < 10; k++) {
            acquire(SZ_WQ, 1);
            if ((pc > 0 || k >= EARLY) && elect()) tma3d_mc(dst + rank * (SZ_WQ / 2), &P.wq[qr >> 5], bar, 0, 64 * k + 32 * rank, 3 * (4 * a + (qr & 3)));
            acquire(SZ_A, 2);
            if ((pc > 0 || k >= EARLY) && elect()) {
              tma2d(dst, &P.x[qr >> 5], bar, 64 * k, ((qr >> 2) & 7) * kSq + rank * 128);
              mbar_expect(bar, SZ_WQ + SZ_A);
            }
          }
        } else if (type == OP_A) {
          const uint32_t nop = prog[pc + 1];
#pragma unroll 1
          for (int t = (op & F_PARK) ? 1 : 0; t < 33; t++) {
            int wave = a;
            if (t == 31 && (nop & 3) != OP_A) t++;
            if (t == 31) {
              wave = (nop >> 2) & 7;
              mbar_wait((nop & F_HELP) ? hready0 + 8 * ((nop >> 10) & 3) : fenced, 0);
              scratch(&g_o[((team * 2 + rank) * 96 + 3 * (4 * wave + nt)) * 1024], SZ_PARK, 2);
            }
            const int isv = t ? ~t & 1 : 0, j = (isv ? (t - 1) >> 1 : (t + 1) >> 1) & 15;
            const int row0 = ((team & 7) * kH + 4 * wave + nt) * kSk;
            if (t >= KV_TRANSIT) {
              const Cursor c{head.n - 8 * KV_TRANSIT};
              mbar_wait(full0 + c.off(), c.ph());
            }
            acquire(SZ_KV);
            if (elect()) {
              tma4d_mc_hint(dst + rank * (SZ_KV / 2), isv ? &P.v[blk] : &P.k[blk], bar, row0 / 8 + 8 * j + 4 * rank, pol);
              mbar_expect(bar, SZ_KV);
            }
          }
        } else {
          const int b = (op >> 5) & 15, ro = o_role(op);
#pragma unroll 1
          for (int i = 0; i < b - a; i++) {
            const int w = o_wave(a, b, i);
            mbar_wait(oready, 0);
            oready += 8;
            asm volatile("fence.proxy.async.global;" ::: "memory");
#pragma unroll 1
            for (int k = 12 * w; k < 12 * w + 12; k++) {
              acquire(SZ_A, 1);
              if (elect()) bulk_load_hint(dst, &g_o[(((ro >> 2) * 2 + rank) * 96 + k) * 1024], SZ_A, bar, pol);
              acquire(SZ_WO, 2);
              if (elect()) {
                tma5d_mc(dst + rank * 10240, &P.wo[ro >> 5], bar, 8 * k + 4 * rank, 5 * (ro & 3));
                mbar_expect(bar, SZ_WO + SZ_A);
              }
            }
          }
          if (op & F_LD) {
            if (op & F_PARK) mbar_wait(hready0 + 8 * (MAX_PARK - 1), 0);
            scratch(&g_part[(role * 2 + rank) * 5120], SZ_PART, 5);
          }
          if (!(op & F_ST)) {
            acquire(SZ_OUT);
            if (elect()) mbar_arrive(bar);
            __syncwarp();
            sh -= 5;
          }
        }
      }
      for (; sh > 0; sh -= 5) {
        mbar_wait(empty0 + tail.off(), tail.ph());
        tail.next();
      }
    } else if (threadIdx.x == 288) {
      uint32_t ph = 0;
      bool first = true;
      for (int pc = 0;; pc++) {
        const uint32_t op = prog[pc];
        if ((op & 3) == OP_END) break;
        if ((op & 3) != OP_A && !helper) continue;
        mbar_wait_long(odone, ph);
        ph ^= 1;
        unsigned int* flag = !helper ? &g_done[(team * 2 + rank) * 8 + ((op >> 2) & 7)]
                             : (op & 3) == OP_Q ? &g_help[(q_role(op) * 2 + rank) * MAX_PARK + ((op >> 10) & 3)]
                                                : &g_help[(o_role(op) * 2 + rank) * MAX_PARK + MAX_PARK - 1];
        asm volatile("red.release.gpu.global.add.u32 [%0], 1;" ::"l"(flag) : "memory");
        if (first) mbar_arrive(fenced);
        first = false;
      }
    } else if (threadIdx.x == 320) {
      uint32_t oready = oready0;
      for (int pc = 0;; pc++) {
        const uint32_t op = prog[pc];
        if ((op & 3) == OP_END) break;
        if ((op & 3) == OP_O) {
          const int a = (op >> 2) & 7, b = (op >> 5) & 15;
#pragma unroll 1
          for (int i = 0; i < b - a; i++) {
            const int ci = ((o_role(op) >> 2) * 2 + rank) * 8 + o_wave(a, b, i);
            wait_count(&g_done[ci], 4);
            mbar_arrive(oready);
            oready += 8;
            if (atomicAdd(&g_seen[ci], 1u) == 3u) { g_seen[ci] = 0; g_done[ci] = 0; }
          }
        }
        if ((op & 3) != OP_Q && (op & F_HELP) && (op & F_PARK)) {
          unsigned int* flag = &g_help[(role * 2 + rank) * MAX_PARK + ((op >> 10) & 3)];
          wait_count(flag, 1);
          mbar_arrive(hready0 + 8 * ((op >> 10) & 3));
          *flag = 0;
        }
      }
    }
  } else {
    asm volatile("setmaxnreg.inc.sync.aligned.u32 240;");
    const int lane = threadIdx.x & 31, warp = wid & 3;
    uint32_t empty_rem;
    asm volatile("mapa.shared::cluster.u32 %0, %1, %2;" : "=r"(empty_rem) : "r"(empty0), "r"(lane & 1));
    auto release = [&](int slot) { mbar_arrive_cluster_if(lane < 2, empty_rem + slot); };
    Cursor r{0};
    const uint32_t ring16 = (sbase & 0x3FFFF) >> 4;
    uint32_t cur = ring16;
    bool rdy0 = false, rdy1 = false;
    auto probe1 = [&]() { rdy0 = mbar_test(full0 + r.off(), r.ph()); };
    auto probe2 = [&]() {
      Cursor n = r;
      rdy0 = mbar_test(full0 + n.off(), n.ph());
      n.next();
      rdy1 = mbar_test(full0 + n.off(), n.ph());
    };
    auto take = [&](bool rdy, uint32_t bytes, uint32_t& addr) {
      const int bi = r.off();
      if (!__all_sync(0xffffffffu, rdy)) mbar_wait_math(full0 + r.off(), r.ph());
      r.next();
      if (cur > ring16 + ((RING - bytes) >> 4)) cur = ring16;
      addr = cur;
      cur += bytes >> 4;
      return bi;
    };
    auto second = [&](uint32_t bytes) {
      if (cur > ring16 + ((RING - bytes) >> 4)) cur = ring16;
      cur += bytes >> 4;
      return cur - (bytes >> 4);
    };
    const int row = wg * 64 + warp * 16 + (lane >> 2);
    int img0 = row * 4 + ((lane & 3) ^ ((row >> 1) & 3));
    uint4* pend = nullptr;
    const uint64_t spol = evict_first();
    int pc = 0;
    uint32_t op = prog[0];
    auto enter = [&]() {
      r.n = op >> 12; cur = ring16 + (((op >> 20) & 63) << 8);
    };
    auto drain = [&](uint32_t (&t)[48], uint32_t c) {
      if (!(op & (3u << 26)) || c >= 6) return;
#pragma unroll
      for (int i = 0; i < 6; i++)
        stg2_if(c == i, pend + i * 512, t[8 * i], t[8 * i + 1], t[8 * i + 2], t[8 * i + 3],
                t[8 * i + 4], t[8 * i + 5], t[8 * i + 6], t[8 * i + 7], spol);
      if ((op & (1u << 26)) && c == 5) {
        __syncwarp();
        mbar_arrive_if(lane < 2, odone);
      }
    };
    float s[32], o[96], c[80];
    uint32_t q[48], pa[16], pb[16];
    float mc0, mc1, l0, l1;
    bool gen;
    auto soft = [&](float (&s)[32], uint32_t (&pout)[16], bool first) {
      if (first) { gen = false; mc0 = 0.f; mc1 = 0.f; }
      float b0, b1;
      for (;;) {
        if (gen) {
          float m0 = fmaxf(s[0], s[1]), m1 = fmaxf(s[2], s[3]);
#pragma unroll
          for (int i = 1; i < 8; i++) { m0 = fmaxf(m0, fmaxf(s[4 * i], s[4 * i + 1])); m1 = fmaxf(m1, fmaxf(s[4 * i + 2], s[4 * i + 3])); }
          m0 = fmaxf(m0, __shfl_xor_sync(0xffffffffu, m0, 1)); m1 = fmaxf(m1, __shfl_xor_sync(0xffffffffu, m1, 1));
          m0 = fmaxf(m0, __shfl_xor_sync(0xffffffffu, m0, 2)); m1 = fmaxf(m1, __shfl_xor_sync(0xffffffffu, m1, 2));
          if (first) {
            mc0 = m0; mc1 = m1;
          } else if (__any_sync(0xffffffffu, !(m0 <= mc0 + kMaxLag && m1 <= mc1 + kMaxLag))) {
            m0 = fmaxf(mc0, m0); m1 = fmaxf(mc1, m1);
            const float a0 = ex2(mc0 - m0), a1 = ex2(mc1 - m1);
            mc0 = m0; mc1 = m1;
            l0 *= a0; l1 *= a1;
            wg_wait<0>();
            fence_regs(o);
#pragma unroll
            for (int i = 0; i < 96; i++) o[i] *= i & 2 ? a1 : a0;
          }
#pragma unroll
          for (int i = 0; i < 32; i++) s[i] -= i & 2 ? mc1 : mc0;
        }
#pragma unroll
        for (int i = 0; i < 8; i++) {
          const float e1 = ex2(s[4 * i + 1]), e0 = ex2(s[4 * i]), e3 = ex2(s[4 * i + 3]), e2 = ex2(s[4 * i + 2]);
          pout[2 * i] = pack_bf16(e0, e1);
          b0 = i ? b0 + fadd(e1, e0) : fadd(e1, e0);
          pout[2 * i + 1] = pack_bf16(e2, e3);
          b1 = i ? b1 + fadd(e3, e2) : fadd(e3, e2);
        }
        if (!__any_sync(0xffffffffu, !gen && !(fmaxf(b0, b1) <= kSumLimit && (!first || fminf(b0, b1) >= 1.0f / kSumLimit)))) break;
        gen = __any_sync(0xffffffffu, true);
      }
      l0 = first ? b0 : l0 + b0;
      l1 = first ? b1 : l1 + b1;
    };
    auto qk = [&](float (&s)[32], uint32_t ak, int k0, int k1) {
#pragma unroll
      for (int kk = k0; kk < k1; kk++)
        wgmma_rs_n64<0>(s, q[4 * kk], q[4 * kk + 1], q[4 * kk + 2], q[4 * kk + 3], mk_desc(ak, 16, KV_SBO, 1, (kk >> 2) * KV_CH + (kk & 3) * 2), kk != 0);
      wg_commit();
    };
    auto pv = [&](uint32_t (&pin)[16], uint32_t av, int acc) {
#pragma unroll
      for (int kk = 0; kk < 4; kk++)
        wgmma_rs_n192<1>(o, pin[4 * kk], pin[4 * kk + 1], pin[4 * kk + 2], pin[4 * kk + 3], mk_desc(av, KV_CH * 16, KV_SBO, 1, kk * (KV_SBO / 8)), acc || (kk != 0));
      wg_commit();
    };
    auto xw = [&](uint32_t ad, int acc) {
      const uint32_t da = second(SZ_A) + wg * 512;
      wg_fence();
#pragma unroll
      for (int kk = 0; kk < 4; kk++)
        wgmma_ss_n192<1>(o, mk_desc(da, 16, 1024, 1, kk * 2), mk_desc(ad, 4096, 1024, 1, (kk & 1) * 128 + (kk >> 1) * 768), acc || kk != 0);
      wg_commit();
    };
    auto ow = [&](int acc, int prev) {
      uint32_t da;
      const int bi = take(rdy0, SZ_A, da);
      const uint32_t db = second(SZ_WO);
      da += wg * 256;
      wg_fence();
      wgmma_ss_n160<1>(c, mk_desc(da, 16, 512, 2), mk_desc(db, 2048, 512, 2), acc);
      wgmma_ss_n160<1>(c, mk_desc(da, 16, 512, 2, 2), mk_desc(db, 2048, 512, 2, 64), 1);
      wg_commit();
      if (acc == 1) { wg_wait<1>(); release(prev); }
      wgmma_ss_n160<1>(c, mk_desc(da, 16, 512, 2, 512), mk_desc(db, 2048, 512, 2, 640), 1);
      wgmma_ss_n160<1>(c, mk_desc(da, 16, 512, 2, 514), mk_desc(db, 2048, 512, 2, 704), 1);
      wg_commit();
      return bi;
    };
    auto st_part = [&](int i) {
      stg2_if(true, pend + i * 512, __float_as_uint(c[8 * i]), __float_as_uint(c[8 * i + 1]), __float_as_uint(c[8 * i + 2]), __float_as_uint(c[8 * i + 3]),
              __float_as_uint(c[8 * i + 4]), __float_as_uint(c[8 * i + 5]), __float_as_uint(c[8 * i + 6]), __float_as_uint(c[8 * i + 7]), spol);
    };
#pragma unroll
    for (int i = 0; i < 48; i++) q[i] = 0;
    enter();

    if ((op & 3) == OP_Q) {
      uint32_t ad;
      int bi0 = take(false, SZ_WQ, ad), k = 0, lag = 0;
      xw(ad, 0);
      for (;;) {
#pragma unroll 1
        for (;;) {
          drain(q, k - lag);
          probe1();
          wg_wait<0>();
          release(bi0);
          bi0 = take(rdy0, SZ_WQ, ad);
          if (++k == 8) break;
          xw(ad, 1);
        }
        if (wg) bar_sync(2, 256);
        xw(ad, 1);
        const int bi9 = take(false, SZ_WQ, ad);
        xw(ad, 1);
        if (!wg) asm volatile("bar.arrive 2, 256;" ::: "memory");
        k = 0; lag = 0;
        uint32_t nop = prog[++pc];
        wg_wait<1>();
        release(bi0);
        probe2();
        wg_wait<0>();
        fence_regs(o);
        release(bi9);
#pragma unroll
        for (int i = 0; i < 48; i++) q[i] = pack_bf16(o[2 * i] * kScaleLog2, o[2 * i + 1] * kScaleLog2);
        fence_regs(q);
        if (op & F_PARK) {
          const int qt = helper ? (op >> 5) & 15 : team, qm = helper ? (op >> 12) & 3 : nt;
          pend = &g_o[((qt * 2 + rank) * 96 + 3 * (4 * ((op >> 2) & 7) + qm)) * 1024 + img0];
          op = nop;
          enter();
          if ((op & 3) != OP_Q) break;
          const int b = take(rdy0, SZ_WQ, ad);
          xw(ad, 0);
          bi0 = take(rdy1, SZ_WQ, ad);
          xw(ad, 1);
          wg_wait<1>();
          release(b);
          k = 1; lag = 1;
          continue;
        }
        int wave = (op >> 2) & 7, sk1;
        uint32_t ak1;
        {
          float s0[32];
          const int sk0 = take(rdy0, SZ_KV, ad);
          wg_fence();
          qk(s0, ad, 0, 12);
          sk1 = take(rdy1, SZ_KV, ak1);
          wg_fence();
          qk(s, ak1, 0, S1A);
          probe1();
          wg_wait<1>();
          fence_regs(s0);
          release(sk0);
          soft(s0, pa, true);
        }
        float i0, i1;
        auto sums = [&]() {
          l0 += __shfl_xor_sync(0xffffffffu, l0, 1); l1 += __shfl_xor_sync(0xffffffffu, l1, 1);
          l0 += __shfl_xor_sync(0xffffffffu, l0, 2); l1 += __shfl_xor_sync(0xffffffffu, l1, 2);
          i0 = rcp(l0); i1 = rcp(l1);
          asm volatile("" : "+f"(i0), "+f"(i1));
        };
        auto target = [&]() {
          pend = &g_o[((team * 2 + rank) * 96 + 3 * (4 * wave + nt)) * 1024 + img0];
          asm volatile("" : "+l"(pend));
        };
        bool late = false;
#pragma unroll
        for (int i = 0; i < 16; i++) pb[i] = 0;
        for (;;) {
          nop = prog[++pc];
          {
            uint32_t av;
            const int sv = take(rdy0, SZ_KV, av);
            wg_fence();
            qk(s, ak1, S1A, 12);
            pv(pa, av, 0);
            if (late) {
              stg2_if(true, pend + 4 * 512, pb[0], pb[1], pb[2], pb[3], pb[4], pb[5], pb[6], pb[7], spol);
              stg2_if(true, pend + 5 * 512, pb[8], pb[9], pb[10], pb[11], pb[12], pb[13], pb[14], pb[15], spol);
              __syncwarp();
              mbar_arrive_if(lane < 2, odone);
            }
            probe2();
            wg_wait<1>();
            fence_regs(s);
            release(sk1);
            soft(s, pb, false);
            wg_wait<0>();
            fence_regs(o);
            release(sv);
          }
          auto step = [&](uint32_t (&pin)[16], uint32_t (&pout)[16]) {
            uint32_t ak, av;
            const int sk = take(rdy0, SZ_KV, ak), sv = take(rdy1, SZ_KV, av);
            wg_fence();
            qk(s, ak, 0, 12);
            pv(pin, av, 1);
            probe2();
            wg_wait<1>();
            fence_regs(s);
            release(sk);
            soft(s, pout, false);
            wg_wait<0>();
            fence_regs(o);
            release(sv);
          };
#pragma unroll 1
          for (int jj = 0; jj < 7; jj++) {
            step(pb, pa);
            step(pa, pb);
          }
          if ((nop & 3) != OP_A) break;
          uint32_t ak, av;
          {
            const int b0 = take(rdy0, SZ_PARK, ak), b1 = take(rdy1, SZ_PARK, av);
            const uint32_t ad0 = ak, ad1 = av;
            probe2();
#pragma unroll
            for (int i = 0; i < 12; i++)
              lds128(sbase + ((i < 6 ? ad0 : ad1) - ring16 + img0) * 16 + ((i % 6) >> 1) * 8192 + (i & 1) * 512, q[4 * i], q[4 * i + 1], q[4 * i + 2], q[4 * i + 3]);
            release(b0); release(b1);
          }
          const int sk0 = take(rdy0, SZ_KV, ak), sv = take(rdy1, SZ_KV, av);
          wg_fence();
          qk(s, ak, 0, 8);
          sched_fence(img0, P.zero);
          sums();
          sched_fence(img0, P.zero);
          qk(s, ak, 8, 12);
          pv(pb, av, 1);
          probe2();
          wg_wait<1>();
          fence_regs(s);
          release(sk0);
          soft(s, pa, true);
          sk1 = take(rdy0, SZ_KV, ak1);
          rdy0 = rdy1;
          wg_wait<0>();
          target();
          fence_regs(o);
          release(sv);
          uint32_t t[48];
#pragma unroll
          for (int j = 0; j < 6; j++) {
#pragma unroll
            for (int i = 0; i < 4; i++) {
              t[8 * j + i] = pack_bf16(o[16 * j + 4 * i] * i0, o[16 * j + 4 * i + 1] * i0);
              t[8 * j + i + 4] = pack_bf16(o[16 * j + 4 * i + 2] * i1, o[16 * j + 4 * i + 3] * i1);
            }
            if (j < 4)
            stg2_if(true, pend + j * 512, t[8 * j], t[8 * j + 1], t[8 * j + 2], t[8 * j + 3], t[8 * j + 4], t[8 * j + 5], t[8 * j + 6], t[8 * j + 7], spol);
            if (j == 3) { wg_fence(); qk(s, ak1, 0, 4); }
            if (j == 5) { wg_fence(); qk(s, ak1, 4, S1A); }
            sched_fence(img0, P.zero);
          }
          if (P.zero) {
#pragma unroll
            for (int j = 0; j < 4; j++)
              stg2_if(true, pend, t[8 * j], t[8 * j + 1], t[8 * j + 2], t[8 * j + 3], t[8 * j + 4], t[8 * j + 5], t[8 * j + 6], t[8 * j + 7], spol);
          }
          late = true;
#pragma unroll
          for (int i = 0; i < 16; i++) pb[i] = t[32 + i];
          wave = (nop >> 2) & 7;
        }
        const int sv = take(rdy0, SZ_KV, ad);
        wg_fence();
        pv(pb, ad, 1);
        sums();
        target();
        op = nop;
        enter();
        rdy0 = rdy1;
        auto convert = [&](float (&u)[96], int j0, int j1) {
#pragma unroll
          for (int i = 4 * j0; i < 4 * j1; i++) {
            q[8 * (i >> 2) + (i & 3)] = pack_bf16(u[4 * i], u[4 * i + 1]);
            q[8 * (i >> 2) + (i & 3) + 4] = pack_bf16(u[4 * i + 2], u[4 * i + 3]);
          }
        };
        if ((op & 3) != OP_O) {
          if ((op & 3) == OP_Q) bi0 = take(rdy0, SZ_WQ, ad);
          wg_wait<0>();
          fence_regs(o);
          release(sv);
          float u[96];
#pragma unroll
          for (int i = 0; i < 96; i++) u[i] = o[i] * (i & 2 ? i1 : i0);
          if ((op & 3) != OP_Q) { convert(u, 0, 6); break; }
          fence_regs(u);
          xw(ad, 0);
          sched_fence(img0, P.zero);
          fence_regs(u);
          convert(u, 0, 1);
          stg2_if(true, pend, q[0], q[1], q[2], q[3], q[4], q[5], q[6], q[7], spol);
          probe1();
          wg_wait<0>();
          release(bi0);
          bi0 = take(rdy0, SZ_WQ, ad);
          xw(ad, 1);
          sched_fence(img0, P.zero);
          fence_regs(u);
          convert(u, 1, 6);
          k = 1;
          continue;
        }
        int bi = ow(0, 0);
        wg_wait<2>();
        fence_regs(o);
        release(sv);
#pragma unroll
        for (int j = 0; j < 6; j++) {
          uint32_t t[8];
#pragma unroll
          for (int i = 0; i < 4; i++) {
            t[i] = pack_bf16(o[16 * j + 4 * i] * i0, o[16 * j + 4 * i + 1] * i0);
            t[i + 4] = pack_bf16(o[16 * j + 4 * i + 2] * i1, o[16 * j + 4 * i + 3] * i1);
          }
          stg2_if(true, pend + j * 512, t[0], t[1], t[2], t[3], t[4], t[5], t[6], t[7], spol);
          if (j == 5) {
            __syncwarp();
            mbar_arrive_if(lane < 2, odone);
          }
          probe1();
          wg_wait<1>();
          bi = ow(1, bi);
          fence_regs(o);
        }
        {
          const int nk = 12 * (((op >> 5) & 15) - ((op >> 2) & 7)) - ((op & F_ST) ? 0 : 2);
#pragma unroll 1
          for (int k = 7; k < nk; k++) {
            probe1();
            wg_wait<1>();
            bi = ow(1, bi);
          }
        }
        if (!(op & F_ST)) {
          probe2();
          wg_wait<1>();
          if (wg) {
            wg_wait<0>();
            release(bi);
            bar_sync(2, 256);
          }
          bi0 = ow(2, 0);
          rdy0 = rdy1;
          const int b = ow(2, 0);
          if (!wg) asm volatile("bar.arrive 2, 256;" ::: "memory");
          wg_wait<4>();
          mbar_arrive_cluster_if(lane < 2 && !wg, empty_rem + bi);
          bi = b;
        }
        probe1();
        nop = prog[++pc];
        if (op & F_LD) {
          uint32_t t[80];
#pragma unroll
          for (int j = 0; j < 5; j++) {
            const int b = take(rdy0, SZ_PART, ad);
            probe1();
#pragma unroll
            for (int i = 4 * j; i < 4 * j + 4; i++)
              lds128(sbase + (ad - ring16 + img0) * 16 + ((i >> 1) & 1) * 8192 + (i & 1) * 512, t[4 * i], t[4 * i + 1], t[4 * i + 2], t[4 * i + 3]);
            release(b);
          }
          wg_wait<0>();
          fence_regs(c);
#pragma unroll
          for (int i = 0; i < 80; i++) c[i] += __uint_as_float(t[i]);
        }
        if (!(op & F_ST)) {
          wg_wait<0>();
          fence_regs(c);
          release(bi0);
          release(bi);
          goto finish;
        }
        op = nop;
        enter();
        bi0 = take(rdy0, SZ_WQ, ad);
        xw(ad, 0);
        pend = &g_part[((team * 4 + nt) * 2 + rank) * 5120 + img0];
        probe1();
        wg_wait<1>();
        fence_regs(c);
        release(bi);
        st_part(0); st_part(1);
        wg_wait<0>();
        release(bi0);
        bi0 = take(rdy0, SZ_WQ, ad);
        xw(ad, 1);
        st_part(2); st_part(3);
#pragma unroll
        for (int i = 0; i < 48; i++) q[i] = __float_as_uint(c[32 + i]);
        pend += 4 * 512;
        k = 1; lag = 2;
      }
    }
    rdy0 = false;
    {
      uint32_t t[48];
#pragma unroll
      for (int i = 0; i < 48; i++) t[i] = q[i] ^ P.zero;
      while ((op & 3) == OP_O) {
        int bi = ow(0, 0);
#pragma unroll 1
        for (int k = 1; k < 12 * (int)(((op >> 5) & 15) - ((op >> 2) & 7)); k++) {
          drain(t, k - 1);
          probe1();
          wg_wait<1>();
          bi = ow(1, bi);
        }
        rdy0 = false;
        wg_wait<0>();
        fence_regs(c);
        pc++;
        release(bi);
        if (!(op & F_ST)) goto finish;
        pend = &g_part[((((op >> 26) & 56) | ((op >> 9) & 7)) * 2 + rank) * 5120 + img0];
#pragma unroll
        for (int i = 6; i < 10; i++) st_part(i);
#pragma unroll
        for (int i = 0; i < 48; i++) t[i] = __float_as_uint(c[i]) ^ P.zero;
        op = prog[pc];
        enter();
      }
      for (int i = 0; i < 6; i++) drain(t, i);
    }
    if (false) {
    finish:
      uint32_t ad;
      take(rdy0, SZ_OUT, ad);
      const uint32_t wstage = sbase + (ad - ring16) * 16 + (wg * 4 + warp) * 5120;
      const uint32_t sa = wstage + (lane & 15) * 64;
#pragma unroll
      for (int i = 0; i < 10; i++) {
        const int u = (i & 1) * 2 + (lane >> 4);
        stsm4(sa + (i >> 1) * 1024 + ((u ^ ((lane >> 1) & 3)) << 4), pack_bf16(c[8 * i], c[8 * i + 1]), pack_bf16(c[8 * i + 2], c[8 * i + 3]),
              pack_bf16(c[8 * i + 4], c[8 * i + 5]), pack_bf16(c[8 * i + 6], c[8 * i + 7]));
      }
      asm volatile("fence.proxy.async.shared::cta;" ::: "memory");
      __syncwarp();
      if (lane == 0) {
        tma3d_store(&P.out, wstage, 0, (team & 7) * kSq + rank * 128 + wg * 64 + warp * 16, blk * 20 + nt * 5);
        asm volatile("cp.async.bulk.commit_group;\ncp.async.bulk.wait_group.read 0;" ::: "memory");
      }
    }
  }
}

typedef CUresult (*EncodeFn)(CUtensorMap*, CUtensorMapDataType, cuuint32_t, void*, const cuuint64_t*, const cuuint64_t*,
                             const cuuint32_t*, const cuuint32_t*, CUtensorMapInterleave, CUtensorMapSwizzle,
                             CUtensorMapL2promotion, CUtensorMapFloatOOBfill);

void encode(EncodeFn fn, CUtensorMap* m, const void* ptr, int rank, const cuuint64_t* dims, const cuuint64_t* strides,
            const cuuint32_t* box, CUtensorMapSwizzle swz) {
  const cuuint32_t es[5] = {1, 1, 1, 1, 1};
  CUresult r = fn(m, CU_TENSOR_MAP_DATA_TYPE_BFLOAT16, rank, const_cast<void*>(ptr), dims, strides, box, es,
                  CU_TENSOR_MAP_INTERLEAVE_NONE, swz, CU_TENSOR_MAP_L2_PROMOTION_L2_128B, CU_TENSOR_MAP_FLOAT_OOB_FILL_NONE);
  if (r != CUDA_SUCCESS) fprintf(stderr, "cuTensorMapEncodeTiled failed: %d\n", (int)r);
}

void annotate(uint32_t* ops, int n, bool helper) {
  uint32_t items = 0, cur = 0, pend = 0;
  auto item = [&](uint32_t bytes, int count, uint32_t bytes2 = 0) {
    for (int i = 0; i < count; i++) {
      if (cur + bytes > RING) cur = 0;
      cur += bytes;
      if (cur + bytes2 > RING) cur = 0;
      cur += bytes2;
      items++;
    }
  };
  for (int i = 0; i <= n; i++) {
    const uint32_t op = ops[i];
    ops[i] |= (items % (2 * NBAR)) << 15 | (cur >> 12) << 20 | pend << 26;
    if ((op & 3) == OP_Q) { item(SZ_WQ, 10, SZ_A); pend = (op & F_PARK) ? (helper ? 1 : 2) : 0; }
    if ((op & 3) == OP_A) {
      item(SZ_KV, (op & F_PARK) ? 30 : 31);
      if ((ops[i + 1] & 3) == OP_A) { item(SZ_PARK, 2); item(SZ_KV, 1); }
      item(SZ_KV, 1);
      pend = 1;
    }
    if ((op & 3) == OP_O) {
      item(SZ_A, 12 * (((op >> 5) & 15) - ((op >> 2) & 7)), SZ_WO);
      if (op & F_LD) item(SZ_PART, 5);
      pend = (op & F_ST) ? (helper ? 1 : 2) : 0;
    }
  }
}

void compile_programs(const char* const* text, bool helpers, Params& P) {
  struct Req { int when, team, wave, slot; } req[N_TEAM * MAX_PARK];
  int n_req = 0;
  for (int t = 0; t < N_TEAM; t++) {
    uint32_t* ops = P.ops[t];
    int n = 0, flags[8] = {0, 0, 0, 0, 0, 0, 0, 0}, n_park = 0, last_o = -1, when = 0, given = 0;
    for (const char* s = text[t]; *s; s++) {
      const int a = s[1] - '0';
      if (*s == 'Q' || (*s == 'H' && !helpers)) { ops[n++] = OP_Q | a << 2; when += 10; }
      else if (*s == 'P') { flags[a] = F_PARK; ops[n++] = OP_Q | a << 2 | flags[a]; when += 10; }
      else if (*s == 'H') { req[n_req++] = {when, t, a, n_park}; flags[a] = F_PARK | F_HELP | n_park++ << 10; }
      else if (*s == 'A') { ops[n++] = OP_A | a << 2 | flags[a]; when += 32; }
      else if (*s == 'G') { given = a; if (helpers) req[n_req++] = {1000, t, 0, -a}; }
      else if (*s == 'O') {
        ops[n] = OP_O | a << 2 | (s[2] - '0') << 5;
        if (given) ops[n] = helpers ? ops[n] | F_LD | F_PARK | (MAX_PARK - 1) << 10 : ops[n] & ~(7u << 2);
        if (last_o >= 0) { ops[last_o] |= F_ST; ops[n] |= F_LD; }
        last_o = n++;
        when += 10 * (s[2] - s[1]);
      }
    }
    for (int i = n; i < MAX_OPS; i++) ops[i] = OP_END;
    annotate(ops, n, false);
  }
  for (int i = 1; i < n_req; i++)
    for (int j = i; j > 0 && req[j].when < req[j - 1].when; j--) { Req r = req[j]; req[j] = req[j - 1]; req[j - 1] = r; }
  for (int h = 0; h < N_HELP; h++) {
    uint32_t* ops = P.ops[N_TEAM + 2 * h];
    int n = 0;
    for (int i = 0; i < n_req; i++)
      for (int m = h; m < 4; m += N_HELP) {
        const uint32_t ro = 4 * req[i].team + m;
        ops[n++] = req[i].slot >= 0 ? OP_Q | req[i].wave << 2 | req[i].team << 5 | F_PARK | req[i].slot << 10 | m << 12
                                    : OP_O | -req[i].slot << 5 | F_ST | (ro & 7) << 9 | (ro >> 3) << 29;
      }
    for (int i = n; i < 2 * MAX_OPS; i++) ops[i] = OP_END;
    annotate(ops, n, true);
  }
  for (int i = 0; i < 32; i++) P.first[i] = i < N_TEAM ? P.ops[i][0] : i < N_TEAM + N_HELP ? P.ops[2 * i - N_TEAM][0] : 0;
}

const char* const kPrograms[N_TEAM] = {
  "Q0A0Q1A1H2A2O03Q3A3Q4A4Q5A5Q6A6Q7A7O38",
  "Q0A0Q1A1Q2A2Q3A3O04Q4A4Q5A5Q6A6H7A7O48",
  "Q0A0H1A1Q2A2Q3A3Q4A4O05Q5A5Q6A6Q7A7O58",
  "Q0A0Q1A1Q2A2O03Q3A3Q4A4Q5A5Q6A6H7A7O38",
  "Q0A0Q1A1Q2A2O03Q3A3H4A4Q5A5Q6A6Q7A7O38",
  "Q0A0Q1A1H2A2Q3A3Q4A4O05Q5A5Q6A6Q7A7O58",
  "Q0A0Q1A1Q2A2Q3A3O03Q4A4H5A5Q6A6Q7A7O38",
  "Q0A0Q1A1Q2A2Q3A3Q4A4O05Q5A5Q6A6H7A7O58",
  "P3Q0A0Q1A1Q2A2A3H4A4Q5A5Q6A6Q7A7O08",
  "P5P7Q0A0Q1A1Q2A2H3A3Q4A4A5Q6A6A7G1O18",
  "Q0A0Q1A1Q2A2O02Q3A3H4A4Q5A5Q6A6Q7A7O28",
  "P3P5Q0A0Q1A1Q2A2A3Q4A4A5Q6A6H7A7O08",
  "Q0A0Q1A1Q2A2O02Q3A3Q4A4H5A5Q6A6Q7A7O28",
  "P7Q0A0Q1A1Q2A2Q3A3Q4A4Q5A5Q6A6A7G1O18",
  "P5Q0A0Q1A1Q2A2Q3A3Q4A4A5Q6A6H7A7O08",
  "Q0A0Q1A1Q2A2H3A3Q4A4Q5A5Q6A6Q7A7O08",
};

const char* const* bench_programs() {
  return kPrograms;
}

}

extern "C" void kernel_launch(void* const* d_in, const int* in_sizes, int n_in, void* d_out, int out_size) {
  (void)in_sizes; (void)n_in; (void)out_size;
  static EncodeFn fn = nullptr;
  static int n_clusters = 0;
  if (!fn) {
    cudaDriverEntryPointQueryResult qr;
    void* f = nullptr;
    cudaGetDriverEntryPoint("cuTensorMapEncodeTiled", &f, cudaEnableDefault, &qr);
    fn = (EncodeFn)f;
    cudaFuncSetAttribute(fused_kernel, cudaFuncAttributeMaxDynamicSharedMemorySize, SMEM_BYTES);
    cudaLaunchConfig_t cfg = {};
    cfg.gridDim = dim3(132); cfg.blockDim = dim3(384); cfg.dynamicSmemBytes = SMEM_BYTES;
    cudaLaunchAttribute at[1];
    at[0].id = cudaLaunchAttributeClusterDimension; at[0].val.clusterDim.x = 2; at[0].val.clusterDim.y = 1; at[0].val.clusterDim.z = 1;
    cfg.attrs = at; cfg.numAttrs = 1;
    if (cudaOccupancyMaxActiveClusters(&n_clusters, fused_kernel, &cfg) != cudaSuccess || n_clusters < 1) n_clusters = 1;
    (void)cudaGetLastError();
  }
  Params P;
  const CUtensorMapSwizzle S128 = CU_TENSOR_MAP_SWIZZLE_128B, S64 = CU_TENSOR_MAP_SWIZZLE_64B;
  for (int blk = 0; blk < 2; blk++) {
    void* const* in = d_in + 5 * blk;
    { const cuuint64_t d[] = {kD, kB * kSq}, s[] = {kD * 2}; const cuuint32_t b[] = {64, 128};
      encode(fn, &P.x[blk], in[0], 2, d, s, b, S128); }
    { const cuuint64_t d[] = {64, 8, 3, (cuuint64_t)kB * kH * kSk / 8}, s[] = {kDh * 2, 128, 8 * kDh * 2}; const cuuint32_t b[] = {64, 8, 3, 4};
      encode(fn, &P.k[blk], in[1], 4, d, s, b, S128);
      encode(fn, &P.v[blk], in[2], 4, d, s, b, S128); }
    { const cuuint64_t d[] = {64, kD, kHD / 64}, s[] = {kHD * 2, 128}; const cuuint32_t b[] = {64, 32, 3};
      encode(fn, &P.wq[blk], in[3], 3, d, s, b, S128); }
    { const cuuint64_t d[] = {32, 2, kHD / 8, 4, kD / 32}, s[] = {kD * 2, 8 * kD * 2, 2 * kD * 2, 64}; const cuuint32_t b[] = {32, 2, 4, 4, 5};
      encode(fn, &P.wo[blk], in[4], 5, d, s, b, S64); }
  }
  { const cuuint64_t d[] = {32, kB * kSq, 2 * kD / 32}, s[] = {2 * kD * 2, 64}; const cuuint32_t b[] = {32, 16, 5};
    encode(fn, &P.out, d_out, 3, d, s, b, S64); }

  P.zero = 0;
  if (n_clusters >= N_CL) {
    const bool helpers = n_clusters >= N_CL + N_HELP;
    compile_programs(bench_programs(), helpers, P);
    fused_kernel<<<2 * (N_CL + (helpers ? N_HELP : 0)), 384, SMEM_BYTES>>>(P);
  } else {
    for (int phase = 0; phase < 2; phase++) {
      const char* text[N_TEAM];
      for (int t = 0; t < N_TEAM; t++) text[t] = phase ? "O08" : "Q0A0Q1A1Q2A2Q3A3Q4A4Q5A5Q6A6Q7A7";
      compile_programs(text, false, P);
      fused_kernel<<<2 * N_CL, 384, SMEM_BYTES>>>(P);
    }
  }
}
```

```cpp
#include <cuda_runtime.h>
#include <cuda_bf16.h>
#include <cuda.h>
#include <stdint.h>
#include <stdio.h>

namespace {

constexpr int kB = 8, kSq = 256, kD = 640, kH = 32, kSk = 1024, kDh = 192;
constexpr int kHD = kH * kDh;
constexpr uint32_t RING = 224 * 1024;
constexpr uint32_t SZ_KV = 24576;
constexpr uint32_t SZ_WQ = 24576, SZ_WO = 20480, SZ_A = 16384;
constexpr uint32_t SZ_OUT = 40960;
constexpr uint32_t SZ_PARK = 24576;
constexpr uint32_t SZ_PART = 16384;
constexpr int NBAR = 16, NFLIGHT = 12;
constexpr int KV_TRANSIT = 4;
constexpr int EARLY = 3;
constexpr int S1A = 7;
constexpr uint32_t KV_CH = 64, KV_SBO = 3072;
constexpr int SMEM_BYTES = RING + 512 + 1024;
constexpr int N_TEAM = 16, N_CL = 64, N_HELP = 2, MAX_OPS = 24, MAX_PARK = 4;
enum { OP_END = 0, OP_Q = 1, OP_A = 2, OP_O = 3, F_PARK = 1 << 9, F_LD = 1 << 12, F_ST = 1 << 13, F_HELP = 1 << 12 };

struct alignas(64) Params {
  uint32_t first[32];
  CUtensorMap x[2], wq[2], kv[4], wo[2], out;
  uint32_t ops[N_TEAM + 2 * N_HELP][MAX_OPS];
  uint32_t zero;
};

__device__ uint4 g_o[N_TEAM * 2 * 96 * 1024];
__device__ uint4 g_part[N_CL * 2 * 5 * 1024];
__device__ unsigned int g_done[N_TEAM * 2 * 8];
__device__ unsigned int g_help[N_CL * 2 * MAX_PARK];
__device__ unsigned int g_seen[N_TEAM * 2 * 8];

template <int TB>
__device__ __forceinline__ void wgmma_rs_n64(float (&d)[32], uint32_t a0, uint32_t a1, uint32_t a2, uint32_t a3, uint64_t db, int scale_d) {
  asm volatile("{\n.reg .pred p;\nsetp.ne.b32 p, %37, 0;\n"
    "wgmma.mma_async.sync.aligned.m64n64k16.f32.bf16.bf16 {%0, %1, %2, %3, %4, %5, %6, %7, %8, %9, %10, %11, %12, %13, %14, %15, %16, %17, %18, %19, %20, %21, %22, %23, %24, %25, %26, %27, %28, %29, %30, %31}, {%32, %33, %34, %35}, %36, p, 1, 1, %38;\n}\n"
    : "+f"(d[0]), "+f"(d[1]), "+f"(d[2]), "+f"(d[3]), "+f"(d[4]), "+f"(d[5]), "+f"(d[6]), "+f"(d[7]), "+f"(d[8]), "+f"(d[9]), "+f"(d[10]), "+f"(d[11]), "+f"(d[12]), "+f"(d[13]), "+f"(d[14]), "+f"(d[15]), "+f"(d[16]), "+f"(d[17]), "+f"(d[18]), "+f"(d[19]), "+f"(d[20]), "+f"(d[21]), "+f"(d[22]), "+f"(d[23]), "+f"(d[24]), "+f"(d[25]), "+f"(d[26]), "+f"(d[27]), "+f"(d[28]), "+f"(d[29]), "+f"(d[30]), "+f"(d[31])
    : "r"(a0), "r"(a1), "r"(a2), "r"(a3), "l"(db), "r"(scale_d), "n"(TB));
}
template <int TB, int TA = 0>
__device__ __forceinline__ void wgmma_ss_n160(float (&d)[80], uint64_t da, uint64_t db, int scale_d) {
  asm volatile("{\n.reg .pred p;\nsetp.ne.b32 p, %82, 0;\n"
    "wgmma.mma_async.sync.aligned.m64n160k16.f32.bf16.bf16 {%0, %1, %2, %3, %4, %5, %6, %7, %8, %9, %10, %11, %12, %13, %14, %15, %16, %17, %18, %19, %20, %21, %22, %23, %24, %25, %26, %27, %28, %29, %30, %31, %32, %33, %34, %35, %36, %37, %38, %39, %40, %41, %42, %43, %44, %45, %46, %47, %48, %49, %50, %51, %52, %53, %54, %55, %56, %57, %58, %59, %60, %61, %62, %63, %64, %65, %66, %67, %68, %69, %70, %71, %72, %73, %74, %75, %76, %77, %78, %79}, %80, %81, p, 1, 1, %83, %84;\n}\n"
    : "+f"(d[0]), "+f"(d[1]), "+f"(d[2]), "+f"(d[3]), "+f"(d[4]), "+f"(d[5]), "+f"(d[6]), "+f"(d[7]), "+f"(d[8]), "+f"(d[9]), "+f"(d[10]), "+f"(d[11]), "+f"(d[12]), "+f"(d[13]), "+f"(d[14]), "+f"(d[15]), "+f"(d[16]), "+f"(d[17]), "+f"(d[18]), "+f"(d[19]), "+f"(d[20]), "+f"(d[21]), "+f"(d[22]), "+f"(d[23]), "+f"(d[24]), "+f"(d[25]), "+f"(d[26]), "+f"(d[27]), "+f"(d[28]), "+f"(d[29]), "+f"(d[30]), "+f"(d[31]), "+f"(d[32]), "+f"(d[33]), "+f"(d[34]), "+f"(d[35]), "+f"(d[36]), "+f"(d[37]), "+f"(d[38]), "+f"(d[39]), "+f"(d[40]), "+f"(d[41]), "+f"(d[42]), "+f"(d[43]), "+f"(d[44]), "+f"(d[45]), "+f"(d[46]), "+f"(d[47]), "+f"(d[48]), "+f"(d[49]), "+f"(d[50]), "+f"(d[51]), "+f"(d[52]), "+f"(d[53]), "+f"(d[54]), "+f"(d[55]), "+f"(d[56]), "+f"(d[57]), "+f"(d[58]), "+f"(d[59]), "+f"(d[60]), "+f"(d[61]), "+f"(d[62]), "+f"(d[63]), "+f"(d[64]), "+f"(d[65]), "+f"(d[66]), "+f"(d[67]), "+f"(d[68]), "+f"(d[69]), "+f"(d[70]), "+f"(d[71]), "+f"(d[72]), "+f"(d[73]), "+f"(d[74]), "+f"(d[75]), "+f"(d[76]), "+f"(d[77]), "+f"(d[78]), "+f"(d[79])
    : "l"(da), "l"(db), "r"(scale_d), "n"(TA), "n"(TB));
}
template <int TB, int TA = 0>
__device__ __forceinline__ void wgmma_ss_n192(float (&d)[96], uint64_t da, uint64_t db, int scale_d) {
  asm volatile("{\n.reg .pred p;\nsetp.ne.b32 p, %98, 0;\n"
    "wgmma.mma_async.sync.aligned.m64n192k16.f32.bf16.bf16 {%0, %1, %2, %3, %4, %5, %6, %7, %8, %9, %10, %11, %12, %13, %14, %15, %16, %17, %18, %19, %20, %21, %22, %23, %24, %25, %26, %27, %28, %29, %30, %31, %32, %33, %34, %35, %36, %37, %38, %39, %40, %41, %42, %43, %44, %45, %46, %47, %48, %49, %50, %51, %52, %53, %54, %55, %56, %57, %58, %59, %60, %61, %62, %63, %64, %65, %66, %67, %68, %69, %70, %71, %72, %73, %74, %75, %76, %77, %78, %79, %80, %81, %82, %83, %84, %85, %86, %87, %88, %89, %90, %91, %92, %93, %94, %95}, %96, %97, p, 1, 1, %99, %100;\n}\n"
    : "+f"(d[0]), "+f"(d[1]), "+f"(d[2]), "+f"(d[3]), "+f"(d[4]), "+f"(d[5]), "+f"(d[6]), "+f"(d[7]), "+f"(d[8]), "+f"(d[9]), "+f"(d[10]), "+f"(d[11]), "+f"(d[12]), "+f"(d[13]), "+f"(d[14]), "+f"(d[15]), "+f"(d[16]), "+f"(d[17]), "+f"(d[18]), "+f"(d[19]), "+f"(d[20]), "+f"(d[21]), "+f"(d[22]), "+f"(d[23]), "+f"(d[24]), "+f"(d[25]), "+f"(d[26]), "+f"(d[27]), "+f"(d[28]), "+f"(d[29]), "+f"(d[30]), "+f"(d[31]), "+f"(d[32]), "+f"(d[33]), "+f"(d[34]), "+f"(d[35]), "+f"(d[36]), "+f"(d[37]), "+f"(d[38]), "+f"(d[39]), "+f"(d[40]), "+f"(d[41]), "+f"(d[42]), "+f"(d[43]), "+f"(d[44]), "+f"(d[45]), "+f"(d[46]), "+f"(d[47]), "+f"(d[48]), "+f"(d[49]), "+f"(d[50]), "+f"(d[51]), "+f"(d[52]), "+f"(d[53]), "+f"(d[54]), "+f"(d[55]), "+f"(d[56]), "+f"(d[57]), "+f"(d[58]), "+f"(d[59]), "+f"(d[60]), "+f"(d[61]), "+f"(d[62]), "+f"(d[63]), "+f"(d[64]), "+f"(d[65]), "+f"(d[66]), "+f"(d[67]), "+f"(d[68]), "+f"(d[69]), "+f"(d[70]), "+f"(d[71]), "+f"(d[72]), "+f"(d[73]), "+f"(d[74]), "+f"(d[75]), "+f"(d[76]), "+f"(d[77]), "+f"(d[78]), "+f"(d[79]), "+f"(d[80]), "+f"(d[81]), "+f"(d[82]), "+f"(d[83]), "+f"(d[84]), "+f"(d[85]), "+f"(d[86]), "+f"(d[87]), "+f"(d[88]), "+f"(d[89]), "+f"(d[90]), "+f"(d[91]), "+f"(d[92]), "+f"(d[93]), "+f"(d[94]), "+f"(d[95])
    : "l"(da), "l"(db), "r"(scale_d), "n"(TA), "n"(TB));
}
template <int TB>
__device__ __forceinline__ void wgmma_rs_n192(float (&d)[96], uint32_t a0, uint32_t a1, uint32_t a2, uint32_t a3, uint64_t db, int scale_d) {
  asm volatile("{\n.reg .pred p;\nsetp.ne.b32 p, %101, 0;\n"
    "wgmma.mma_async.sync.aligned.m64n192k16.f32.bf16.bf16 {%0, %1, %2, %3, %4, %5, %6, %7, %8, %9, %10, %11, %12, %13, %14, %15, %16, %17, %18, %19, %20, %21, %22, %23, %24, %25, %26, %27, %28, %29, %30, %31, %32, %33, %34, %35, %36, %37, %38, %39, %40, %41, %42, %43, %44, %45, %46, %47, %48, %49, %50, %51, %52, %53, %54, %55, %56, %57, %58, %59, %60, %61, %62, %63, %64, %65, %66, %67, %68, %69, %70, %71, %72, %73, %74, %75, %76, %77, %78, %79, %80, %81, %82, %83, %84, %85, %86, %87, %88, %89, %90, %91, %92, %93, %94, %95}, {%96, %97, %98, %99}, %100, p, 1, 1, %102;\n}\n"
    : "+f"(d[0]), "+f"(d[1]), "+f"(d[2]), "+f"(d[3]), "+f"(d[4]), "+f"(d[5]), "+f"(d[6]), "+f"(d[7]), "+f"(d[8]), "+f"(d[9]), "+f"(d[10]), "+f"(d[11]), "+f"(d[12]), "+f"(d[13]), "+f"(d[14]), "+f"(d[15]), "+f"(d[16]), "+f"(d[17]), "+f"(d[18]), "+f"(d[19]), "+f"(d[20]), "+f"(d[21]), "+f"(d[22]), "+f"(d[23]), "+f"(d[24]), "+f"(d[25]), "+f"(d[26]), "+f"(d[27]), "+f"(d[28]), "+f"(d[29]), "+f"(d[30]), "+f"(d[31]), "+f"(d[32]), "+f"(d[33]), "+f"(d[34]), "+f"(d[35]), "+f"(d[36]), "+f"(d[37]), "+f"(d[38]), "+f"(d[39]), "+f"(d[40]), "+f"(d[41]), "+f"(d[42]), "+f"(d[43]), "+f"(d[44]), "+f"(d[45]), "+f"(d[46]), "+f"(d[47]), "+f"(d[48]), "+f"(d[49]), "+f"(d[50]), "+f"(d[51]), "+f"(d[52]), "+f"(d[53]), "+f"(d[54]), "+f"(d[55]), "+f"(d[56]), "+f"(d[57]), "+f"(d[58]), "+f"(d[59]), "+f"(d[60]), "+f"(d[61]), "+f"(d[62]), "+f"(d[63]), "+f"(d[64]), "+f"(d[65]), "+f"(d[66]), "+f"(d[67]), "+f"(d[68]), "+f"(d[69]), "+f"(d[70]), "+f"(d[71]), "+f"(d[72]), "+f"(d[73]), "+f"(d[74]), "+f"(d[75]), "+f"(d[76]), "+f"(d[77]), "+f"(d[78]), "+f"(d[79]), "+f"(d[80]), "+f"(d[81]), "+f"(d[82]), "+f"(d[83]), "+f"(d[84]), "+f"(d[85]), "+f"(d[86]), "+f"(d[87]), "+f"(d[88]), "+f"(d[89]), "+f"(d[90]), "+f"(d[91]), "+f"(d[92]), "+f"(d[93]), "+f"(d[94]), "+f"(d[95])
    : "r"(a0), "r"(a1), "r"(a2), "r"(a3), "l"(db), "r"(scale_d), "n"(TB));
}

__device__ __forceinline__ uint32_t smem_u32(const void* p) { return (uint32_t)__cvta_generic_to_shared(p); }
__device__ __forceinline__ void wg_fence() { asm volatile("wgmma.fence.sync.aligned;" ::: "memory"); }
__device__ __forceinline__ void wg_commit() { asm volatile("wgmma.commit_group.sync.aligned;" ::: "memory"); }
template <int N> __device__ __forceinline__ void wg_wait() { asm volatile("wgmma.wait_group.sync.aligned %0;" ::"n"(N) : "memory"); }
__device__ __forceinline__ void sched_fence(int& keep, uint32_t zero) {
  asm volatile("{\n.reg .u32 c;\nmov.u32 c, %%clock;\nand.b32 c, c, %1;\nxor.b32 %0, %0, c;\n}\n" : "+r"(keep) : "r"(zero) : "memory");
}
template <int N> __device__ __forceinline__ void fence_regs(float (&r)[N]) {
#pragma unroll
  for (int i = 0; i < N; i++) asm volatile("" : "+f"(r[i])::"memory");
}
template <int N> __device__ __forceinline__ void fence_regs(uint32_t (&r)[N]) {
#pragma unroll
  for (int i = 0; i < N; i++) asm volatile("" : "+r"(r[i])::"memory");
}
__device__ __forceinline__ uint64_t mk_desc(uint32_t a16, uint32_t lbo, uint32_t sbo, uint32_t swz, uint32_t off = 0) {
  uint64_t d;
  asm("mov.b64 %0, {%1, %2};" : "=l"(d) : "r"(a16), "r"((sbo >> 4) | (swz << 30)));
  return d + (off + ((lbo >> 4) << 16));
}
__device__ __forceinline__ void mbar_init(uint32_t bar, uint32_t cnt) {
  asm volatile("mbarrier.init.shared::cta.b64 [%0], %1;" ::"r"(bar), "r"(cnt) : "memory");
}
__device__ __forceinline__ void mbar_expect(uint32_t bar, uint32_t tx) {
  asm volatile("mbarrier.arrive.expect_tx.shared::cta.b64 _, [%0], %1;" ::"r"(bar), "r"(tx) : "memory");
}
__device__ __forceinline__ bool mbar_test(uint32_t bar, uint32_t ph) {
  uint32_t ok;
  asm volatile("{\n.reg .pred p;\nmbarrier.test_wait.parity.shared::cta.b64 p, [%1], %2;\nselp.u32 %0, 1, 0, p;\n}\n"
               : "=r"(ok) : "r"(bar), "r"(ph) : "memory");
  return ok;
}
__device__ __forceinline__ void mbar_wait(uint32_t bar, uint32_t ph) {
  asm volatile("{\n.reg .pred p;\n.reg .u32 n;\nmov.u32 n, 0;\n"
               "LOOP:\nadd.u32 n, n, 1;\nmbarrier.try_wait.parity.shared::cta.b64 p, [%0], %1;\n@p bra DONE;\n"
               "setp.lt.u32 p, n, 0x1000000;\n@p bra LOOP;\ntrap;\n"
               "DONE:\n}\n" ::"r"(bar), "r"(ph) : "memory");
}
__device__ __forceinline__ void mbar_wait_math(uint32_t bar, uint32_t ph) {
  asm volatile("{\n.reg .pred p;\nLOOP:\nmbarrier.try_wait.parity.shared::cta.b64 p, [%0], %1;\n@!p bra LOOP;\n}\n" ::"r"(bar), "r"(ph) : "memory");
}
__device__ __forceinline__ void mbar_wait_long(uint32_t bar, uint32_t ph) {
  asm volatile("{\n.reg .pred p;\n.reg .u32 n;\nmov.u32 n, 0;\n"
               "LOOP:\nmbarrier.try_wait.parity.shared::cta.b64 p, [%0], %1, %2;\n@p bra DONE;\n"
               "add.u32 n, n, 1;\nsetp.lt.u32 p, n, 0x40000;\n@p bra LOOP;\ntrap;\n"
               "DONE:\n}\n" ::"r"(bar), "r"(ph), "r"(20000) : "memory");
}
__device__ __forceinline__ void mbar_arrive_cluster_if(bool on, uint32_t addr) {
  asm volatile("{\n.reg .pred p;\nsetp.ne.b32 p, %1, 0;\n@p mbarrier.arrive.shared::cluster.b64 _, [%0];\n}\n" ::"r"(addr), "r"((int)on) : "memory");
}
__device__ __forceinline__ void mbar_arrive_if(bool on, uint32_t addr) {
  asm volatile("{\n.reg .pred p;\nsetp.ne.b32 p, %1, 0;\n@p mbarrier.arrive.shared::cta.b64 _, [%0];\n}\n" ::"r"(addr), "r"((int)on) : "memory");
}
__device__ __forceinline__ void tma2d(uint32_t dst, const CUtensorMap* m, uint32_t bar, int c0, int c1) {
  asm volatile("cp.async.bulk.tensor.2d.shared::cluster.global.mbarrier::complete_tx::bytes [%0], [%1, {%3, %4}], [%2];"
               ::"r"(dst), "l"(m), "r"(bar), "r"(c0), "r"(c1) : "memory");
}
__device__ __forceinline__ void tma3d(uint32_t dst, const CUtensorMap* m, uint32_t bar, int c0, int c1, int c2) {
  asm volatile("cp.async.bulk.tensor.3d.shared::cluster.global.mbarrier::complete_tx::bytes [%0], [%1, {%3, %4, %5}], [%2];"
               ::"r"(dst), "l"(m), "r"(bar), "r"(c0), "r"(c1), "r"(c2) : "memory");
}
__device__ __forceinline__ void tma3d_mc(uint32_t dst, const CUtensorMap* m, uint32_t bar, int c0, int c1, int c2) {
  asm volatile("cp.async.bulk.tensor.3d.shared::cluster.global.mbarrier::complete_tx::bytes.multicast::cluster"
               " [%0], [%1, {%3, %4, %5}], [%2], %6;"
               ::"r"(dst), "l"(m), "r"(bar), "r"(c0), "r"(c1), "r"(c2), "h"((uint16_t)3) : "memory");
}
__device__ __forceinline__ void tma3d_store(const CUtensorMap* m, uint32_t src, int c0, int c1, int c2) {
  asm volatile("cp.async.bulk.tensor.3d.global.shared::cta.bulk_group [%0, {%2, %3, %4}], [%1];"
               ::"l"(m), "r"(src), "r"(c0), "r"(c1), "r"(c2) : "memory");
}
__device__ __forceinline__ void bar_sync(int id, int n) { asm volatile("bar.sync %0, %1;" ::"r"(id), "r"(n) : "memory"); }
__device__ __forceinline__ uint32_t pack_bf16(float lo, float hi) {
  uint32_t r;
  asm("cvt.rn.bf16x2.f32 %0, %1, %2;" : "=r"(r) : "f"(hi), "f"(lo));
  return r;
}
__device__ __forceinline__ float ex2(float x) {
  float y;
  asm("ex2.approx.ftz.f32 %0, %1;" : "=f"(y) : "f"(x));
  return y;
}
__device__ __forceinline__ float fadd(float a, float b) {
  float y;
  asm("add.f32 %0, %1, %2;" : "=f"(y) : "f"(a), "f"(b));
  return y;
}
__device__ __forceinline__ float rcp(float x) {
  float y;
  asm("rcp.approx.ftz.f32 %0, %1;" : "=f"(y) : "f"(x));
  return y;
}
__device__ __forceinline__ void stsm4(uint32_t addr, uint32_t a, uint32_t b, uint32_t c, uint32_t d) {
  asm volatile("stmatrix.sync.aligned.m8n8.x4.shared.b16 [%0], {%1, %2, %3, %4};" ::"r"(addr), "r"(a), "r"(b), "r"(c), "r"(d) : "memory");
}

__device__ __forceinline__ void tma4d_mc_hint(uint32_t dst, const CUtensorMap* m, uint32_t bar, int c3, uint64_t pol) {
  asm volatile("cp.async.bulk.tensor.4d.shared::cluster.global.mbarrier::complete_tx::bytes.multicast::cluster.L2::cache_hint"
               " [%0], [%1, {%3, %3, %3, %4}], [%2], %5, %6;"
               ::"r"(dst), "l"(m), "r"(bar), "r"(0), "r"(c3), "h"((uint16_t)3), "l"(pol) : "memory");
}
__device__ __forceinline__ void tma5d_mc(uint32_t dst, const CUtensorMap* m, uint32_t bar, int c2, int c4) {
  asm volatile("cp.async.bulk.tensor.5d.shared::cluster.global.mbarrier::complete_tx::bytes.multicast::cluster"
               " [%0], [%1, {%3, %3, %4, %3, %5}], [%2], %6;"
               ::"r"(dst), "l"(m), "r"(bar), "r"(0), "r"(c2), "r"(c4), "h"((uint16_t)3) : "memory");
}
__device__ __forceinline__ void bulk_load_hint(uint32_t dst, const void* src, uint32_t bytes, uint32_t bar, uint64_t pol) {
  asm volatile("cp.async.bulk.shared::cluster.global.mbarrier::complete_tx::bytes.L2::cache_hint [%0], [%1], %2, [%3], %4;"
               ::"r"(dst), "l"(src), "r"(bytes), "r"(bar), "l"(pol) : "memory");
}
__device__ __forceinline__ void stg2_if(bool on, void* p, uint32_t a, uint32_t b, uint32_t c, uint32_t d, uint32_t e, uint32_t f,
                                        uint32_t g, uint32_t h, uint64_t pol) {
  asm volatile("{\n.reg .pred p;\nsetp.ne.b32 p, %10, 0;\n"
               "@p st.global.L2::cache_hint.v4.b32 [%0], {%1, %2, %3, %4}, %9;\n"
               "@p st.global.L2::cache_hint.v4.b32 [%0 + 512], {%5, %6, %7, %8}, %9;\n}\n"
               ::"l"(p), "r"(a), "r"(b), "r"(c), "r"(d), "r"(e), "r"(f), "r"(g), "r"(h), "l"(pol), "r"((int)on) : "memory");
}
__device__ __forceinline__ uint64_t evict_first() {
  uint64_t p;
  asm("createpolicy.fractional.L2::evict_first.b64 %0, 1.0;" : "=l"(p));
  return p;
}
__device__ __forceinline__ bool elect() {
  uint32_t ok;
  asm volatile("{\n.reg .pred p;\nelect.sync _|p, 0xffffffff;\nselp.u32 %0, 1, 0, p;\n}\n" : "=r"(ok));
  return ok;
}
__device__ __forceinline__ void mbar_arrive(uint32_t bar) {
  asm volatile("mbarrier.arrive.shared::cta.b64 _, [%0];" ::"r"(bar) : "memory");
}
__device__ __forceinline__ void lds128(uint32_t p, uint32_t& a, uint32_t& b, uint32_t& c, uint32_t& d) {
  asm volatile("ld.shared.v4.b32 {%0, %1, %2, %3}, [%4];" : "=r"(a), "=r"(b), "=r"(c), "=r"(d) : "r"(p) : "memory");
}
__device__ __forceinline__ void wait_count(const unsigned int* p, uint32_t target) {
  asm volatile("{\n.reg .pred p;\n.reg .u32 n, v;\nmov.u32 n, 0;\n"
               "LOOP:\nld.acquire.gpu.global.u32 v, [%0];\nsetp.ge.u32 p, v, %1;\n@p bra DONE;\n"
               "nanosleep.u32 %2;\nadd.u32 n, n, 1;\nsetp.lt.u32 p, n, 0x400000;\n@p bra LOOP;\ntrap;\n"
               "DONE:\n}\n" ::"l"(p), "r"(target), "n"(300) : "memory");
}

__device__ __forceinline__ int o_wave(int a, int b, int i) {
  const int p = min(3, b - a - 1);
  return i < p ? b - 2 - i : i == p ? b - 1 : b - 1 - i;
}

struct Cursor {
  uint32_t n;
  __device__ __forceinline__ uint32_t off() const { return n & (8 * NBAR - 8); }
  __device__ __forceinline__ uint32_t ph() const { return (n / (8 * NBAR)) & 1; }
  __device__ __forceinline__ void next() { n += 8; }
};

constexpr float kScaleLog2 = 0.07216878364870322f * 1.4426950408889634f;
constexpr float kSumLimit = 1048576.0f;
constexpr float kMaxLag = 8.0f;

__global__ void __cluster_dims__(2, 1, 1) __launch_bounds__(384, 1)
fused_kernel(const __grid_constant__ Params P) {
  extern __shared__ uint8_t smem_raw[];
  const uint32_t sbase = (smem_u32(smem_raw) + 1023) & ~1023u;
  const uint32_t full0 = sbase + RING, empty0 = full0 + 8 * NBAR, odone = empty0 + 8 * NBAR, oready0 = odone + 8;
  const uint32_t fenced = oready0 + 64, hready0 = fenced + 8;
  const uint32_t rank = blockIdx.x & 1;
  const int role = blockIdx.x >> 1;
  const bool helper = role >= N_CL;
  const int team = helper ? 0 : role >> 2, nt = role & 3, blk = team >> 3;
  const uint32_t* prog = P.ops[helper ? N_TEAM + 2 * (role - N_CL) : team];
  auto q_role = [&](uint32_t op) { return helper ? (int)(((op >> 3) & 60) | ((op >> 12) & 3)) : role; };
  auto o_role = [&](uint32_t op) { return helper ? (int)(((op >> 26) & 56) | ((op >> 9) & 7)) : role; };
  const int wid = __shfl_sync(0xffffffffu, (int)(threadIdx.x >> 5), 0);
  const int wg = wid >> 2;

  const uint32_t op0 = P.first[helper ? N_TEAM + role - N_CL : team];
  if (__builtin_expect(wid == 8, 1)) {
    if (elect()) {
#pragma unroll
      for (int k = 0; k < EARLY; k++) mbar_init(full0 + 8 * k, 1);
      asm volatile("fence.mbarrier_init.release.cluster;" ::: "memory");
      if ((op0 & 3) == OP_Q) {
        const int qr = q_role(op0);
#pragma unroll
        for (int k = 0; k < EARLY; k++) {
          mbar_expect(full0 + 8 * k, SZ_WQ + SZ_A);
          tma2d(sbase + k * (SZ_WQ + SZ_A) + SZ_WQ, &P.x[qr >> 5], full0 + 8 * k, 64 * k, ((qr >> 2) & 7) * kSq + rank * 128);
          tma3d(sbase + k * (SZ_WQ + SZ_A), &P.wq[qr >> 5], full0 + 8 * k, 0, 64 * k, 3 * (4 * ((op0 >> 2) & 7) + (qr & 3)));
          tma3d(sbase + k * (SZ_WQ + SZ_A) + SZ_WQ / 2, &P.wq[qr >> 5], full0 + 8 * k, 0, 64 * k + 32, 3 * (4 * ((op0 >> 2) & 7) + (qr & 3)));
        }
      }
      asm volatile("prefetch.tensormap [%0];" ::"l"(&P.kv[blk]) : "memory");
      asm volatile("prefetch.tensormap [%0];" ::"l"(&P.kv[blk + 2]) : "memory");
    }
  } else if (threadIdx.x == 0) {
#pragma unroll
    for (int i = EARLY; i < 2 * NBAR + 10 + MAX_PARK; i++) mbar_init(full0 + 8 * i, i >= NBAR && i <= 2 * NBAR ? 16 : 1);
    asm volatile("fence.mbarrier_init.release.cluster;" ::: "memory");
  }
  __syncwarp();
  asm volatile("barrier.cluster.arrive.relaxed.aligned;\nbarrier.cluster.wait.aligned;" ::: "memory");

  if (wg == 2) {
    asm volatile("setmaxnreg.dec.sync.aligned.u32 24;");
    if (wid == 8) {
      Cursor tail{0}, head{0};
      int sh = 0;
      uint32_t cur = 0, used = 0;
      uint64_t fifo = 0;
      uint32_t dst, bar, oready = oready0;
      int c0;
      const void* ptr;
      const uint64_t pol = evict_first();
      auto acquire = [&](uint32_t bytes, bool first, bool last, auto prepare) {
        uint32_t fp = bytes >> 12;
        if (cur + fp > (RING >> 12)) { fp += (RING >> 12) - cur; cur = 0; }
        used += fp;
        bool more = false;
        uint32_t wbar, wph;
        while (used > (RING >> 12) || (first && sh == 5 * NFLIGHT)) {
          if (more) mbar_wait(wbar, wph);
          more = true;
          wbar = empty0 + tail.off(); wph = tail.ph();
          tail.next();
          used -= (uint32_t)fifo & 31;
          fifo >>= 5;
          sh -= 5;
        }
        fifo += (uint64_t)fp << sh;
        dst = sbase + (cur << 12);
        bar = full0 + head.off();
        cur += bytes >> 12;
        sh += last ? 5 : 0;
        head.n += last ? 8 : 0;
        prepare();
        asm volatile("" : "+r"(dst), "+r"(bar), "+r"(c0), "+l"(ptr));
        if (more) mbar_wait(wbar, wph);
      };
      auto written = [&](uint32_t flag) {
        mbar_wait(flag, 0);
        asm volatile("fence.proxy.async.global;" ::: "memory");
      };
      for (int pc = 0;; pc++) {
        const uint32_t op = prog[pc];
        const int type = op & 3, a = (op >> 2) & 7;
        if (type == OP_END) break;
        if (type == OP_Q) {
          const int qr = q_role(op);
#pragma unroll 1
          for (int k = 0; k < 10; k++) {
            acquire(SZ_WQ, true, false, [&]() { dst += rank * (SZ_WQ / 2); c0 = 64 * k + 32 * rank; ptr = &P.wq[qr >> 5]; });
            if ((pc > 0 || k >= EARLY) && elect()) tma3d_mc(dst, (const CUtensorMap*)ptr, bar, 0, c0, 3 * (4 * a + (qr & 3)));
            acquire(SZ_A, false, true, [&]() { c0 = 64 * k; ptr = &P.x[qr >> 5]; });
            if ((pc > 0 || k >= EARLY) && elect()) {
              tma2d(dst, (const CUtensorMap*)ptr, bar, c0, ((qr >> 2) & 7) * kSq + rank * 128);
              mbar_expect(bar, SZ_WQ + SZ_A);
            }
          }
        } else if (type == OP_A) {
          const uint32_t nop = prog[pc + 1];
          const int row8 = ((team & 7) * kH + nt) * (kSk / 8) + 4 * rank, wave8 = 4 * (kSk / 8);
#pragma unroll 1
          for (int t = (op & F_PARK) ? 1 : 0; t < 33; t++) {
            int wave = a;
            if (t == 31 && (nop & 3) != OP_A) t++;
            if (t == 31) {
              wave = (nop >> 2) & 7;
              written((nop & F_HELP) ? hready0 + 8 * ((nop >> 10) & 3) : fenced);
#pragma unroll 1
              for (int i = 0; i < 2; i++) {
                acquire(SZ_PARK, true, true, [&]() { c0 = 0; ptr = &g_o[((team * 2 + rank) * 96 + 3 * (4 * wave + nt)) * 1024 + i * (SZ_PARK / 16)]; });
                if (elect()) {
                  bulk_load_hint(dst, ptr, SZ_PARK, bar, pol);
                  mbar_expect(bar, SZ_PARK);
                }
              }
            }
            if (t >= KV_TRANSIT) {
              const Cursor c{head.n - 8 * KV_TRANSIT};
              mbar_wait(full0 + c.off(), c.ph());
            }
            acquire(SZ_KV, true, true, [&]() {
              const int isv = t ? ~t & 1 : 0;
              c0 = row8 + wave * wave8 + 8 * (((t + 1 - 2 * isv) >> 1) & 15);
              ptr = &P.kv[blk + 2 * isv];
              dst += rank * (SZ_KV / 2);
            });
            if (elect()) {
              tma4d_mc_hint(dst, (const CUtensorMap*)ptr, bar, c0, pol);
              mbar_expect(bar, SZ_KV);
            }
          }
        } else {
          const int b = (op >> 5) & 15, ro = o_role(op);
#pragma unroll 1
          for (int j = 0; j < b - a; j++) {
            const int w = o_wave(a, b, j);
            written(oready);
            oready += 8;
#pragma unroll 1
            for (int k = 12 * w; k < 12 * w + 12; k++) {
              acquire(SZ_A, true, false, [&]() { c0 = 0; ptr = &g_o[(((ro >> 2) * 2 + rank) * 96 + k) * 1024]; });
              if (elect()) bulk_load_hint(dst, ptr, SZ_A, bar, pol);
              acquire(SZ_WO, false, true, [&]() { c0 = 8 * k + 4 * rank; ptr = &P.wo[ro >> 5]; dst += rank * (SZ_WO / 2); });
              if (elect()) {
                tma5d_mc(dst, (const CUtensorMap*)ptr, bar, c0, 5 * (ro & 3));
                mbar_expect(bar, SZ_WO + SZ_A);
              }
            }
          }
          if ((op & F_LD) && (op & F_PARK)) written(hready0 + 8 * (MAX_PARK - 1));
#pragma unroll 1
          for (int i = (op & F_LD) ? 0 : 5; i < ((op & F_ST) ? 5 : 6); i++) {
            acquire(i < 5 ? SZ_PART : SZ_OUT, true, i < 5, [&]() { c0 = 0; ptr = &g_part[(role * 2 + rank) * 5120 + i * (SZ_PART / 16)]; });
            if (i < 5 && elect()) bulk_load_hint(dst, ptr, SZ_PART, bar, pol);
            if (elect()) mbar_expect(bar, i < 5 ? SZ_PART : 0);
          }
        }
      }
#pragma unroll 1
      for (; sh > 0; sh -= 5) {
        mbar_wait(empty0 + tail.off(), tail.ph());
        tail.next();
      }
    } else if (threadIdx.x == 288) {
      uint32_t ph = 0;
      bool first = true;
      for (int pc = 0;; pc++) {
        const uint32_t op = prog[pc];
        if ((op & 3) == OP_END) break;
        if ((op & 3) != OP_A && !helper) continue;
        mbar_wait_long(odone, ph);
        ph ^= 1;
        unsigned int* flag = !helper ? &g_done[(team * 2 + rank) * 8 + ((op >> 2) & 7)]
                             : (op & 3) == OP_Q ? &g_help[(q_role(op) * 2 + rank) * MAX_PARK + ((op >> 10) & 3)]
                                                : &g_help[(o_role(op) * 2 + rank) * MAX_PARK + MAX_PARK - 1];
        asm volatile("red.release.gpu.global.add.u32 [%0], 1;" ::"l"(flag) : "memory");
        if (first) mbar_arrive(fenced);
        first = false;
      }
    } else if (threadIdx.x == 320) {
      uint32_t oready = oready0;
      for (int pc = 0;; pc++) {
        const uint32_t op = prog[pc];
        if ((op & 3) == OP_END) break;
        if ((op & 3) == OP_O) {
          const int a = (op >> 2) & 7, b = (op >> 5) & 15;
#pragma unroll 1
          for (int i = 0; i < b - a; i++) {
            const int ci = ((o_role(op) >> 2) * 2 + rank) * 8 + o_wave(a, b, i);
            wait_count(&g_done[ci], 4);
            mbar_arrive(oready);
            oready += 8;
            if (atomicAdd(&g_seen[ci], 1u) == 3u) { g_seen[ci] = 0; g_done[ci] = 0; }
          }
        }
        if ((op & 3) != OP_Q && (op & F_HELP) && (op & F_PARK)) {
          unsigned int* flag = &g_help[(role * 2 + rank) * MAX_PARK + ((op >> 10) & 3)];
          wait_count(flag, 1);
          mbar_arrive(hready0 + 8 * ((op >> 10) & 3));
          *flag = 0;
        }
      }
    }
  } else {
    asm volatile("setmaxnreg.inc.sync.aligned.u32 240;");
    const int lane = threadIdx.x & 31, warp = wid & 3;
    uint32_t empty_rem;
    asm volatile("mapa.shared::cluster.u32 %0, %1, %2;" : "=r"(empty_rem) : "r"(empty0), "r"(lane & 1));
    auto release = [&](int slot) { mbar_arrive_cluster_if(lane < 2, empty_rem + slot); };
    Cursor r{0};
    const uint32_t ring16 = (sbase & 0x3FFFF) >> 4;
    uint32_t cur = ring16;
    bool rdy0 = false, rdy1 = false;
    auto probe1 = [&]() { rdy0 = mbar_test(full0 + r.off(), r.ph()); };
    auto probe2 = [&]() {
      Cursor n = r;
      rdy0 = mbar_test(full0 + n.off(), n.ph());
      n.next();
      rdy1 = mbar_test(full0 + n.off(), n.ph());
    };
    auto take = [&](bool rdy, uint32_t bytes, uint32_t& addr) {
      const int bi = r.off();
      if (!__all_sync(0xffffffffu, rdy)) mbar_wait_math(full0 + r.off(), r.ph());
      r.next();
      if (cur > ring16 + ((RING - bytes) >> 4)) cur = ring16;
      addr = cur;
      cur += bytes >> 4;
      return bi;
    };
    auto second = [&](uint32_t bytes) {
      if (cur > ring16 + ((RING - bytes) >> 4)) cur = ring16;
      cur += bytes >> 4;
      return cur - (bytes >> 4);
    };
    const int row = wg * 64 + warp * 16 + (lane >> 2);
    int img0 = row * 4 + ((lane & 3) ^ ((row >> 1) & 3));
    uint4* pend = nullptr;
    const uint64_t spol = evict_first();
    int pc = 0;
    uint32_t op = prog[0];
    auto enter = [&]() {
      r.n = op >> 12; cur = ring16 + (((op >> 20) & 63) << 8);
    };
    auto drain = [&](uint32_t (&t)[48], uint32_t c) {
      if (!(op & (3u << 26)) || c >= 6) return;
#pragma unroll
      for (int i = 0; i < 6; i++)
        stg2_if(c == i, pend + i * 512, t[8 * i], t[8 * i + 1], t[8 * i + 2], t[8 * i + 3],
                t[8 * i + 4], t[8 * i + 5], t[8 * i + 6], t[8 * i + 7], spol);
      if ((op & (1u << 26)) && c == 5) {
        __syncwarp();
        mbar_arrive_if(lane < 2, odone);
      }
    };
    float s[32], o[96], c[80];
    uint32_t q[48], pa[16], pb[16];
    float mc0, mc1, l0, l1;
    bool gen;
    auto soft = [&](float (&s)[32], uint32_t (&pout)[16], bool first) {
      if (first) { gen = false; mc0 = 0.f; mc1 = 0.f; }
      float b0, b1;
      for (;;) {
        if (gen) {
          float m0 = fmaxf(s[0], s[1]), m1 = fmaxf(s[2], s[3]);
#pragma unroll
          for (int i = 1; i < 8; i++) { m0 = fmaxf(m0, fmaxf(s[4 * i], s[4 * i + 1])); m1 = fmaxf(m1, fmaxf(s[4 * i + 2], s[4 * i + 3])); }
          m0 = fmaxf(m0, __shfl_xor_sync(0xffffffffu, m0, 1)); m1 = fmaxf(m1, __shfl_xor_sync(0xffffffffu, m1, 1));
          m0 = fmaxf(m0, __shfl_xor_sync(0xffffffffu, m0, 2)); m1 = fmaxf(m1, __shfl_xor_sync(0xffffffffu, m1, 2));
          if (first) {
            mc0 = m0; mc1 = m1;
          } else if (__any_sync(0xffffffffu, !(m0 <= mc0 + kMaxLag && m1 <= mc1 + kMaxLag))) {
            m0 = fmaxf(mc0, m0); m1 = fmaxf(mc1, m1);
            const float a0 = ex2(mc0 - m0), a1 = ex2(mc1 - m1);
            mc0 = m0; mc1 = m1;
            l0 *= a0; l1 *= a1;
            wg_wait<0>();
            fence_regs(o);
#pragma unroll
            for (int i = 0; i < 96; i++) o[i] *= i & 2 ? a1 : a0;
          }
#pragma unroll
          for (int i = 0; i < 32; i++) s[i] -= i & 2 ? mc1 : mc0;
        }
#pragma unroll
        for (int i = 0; i < 8; i++) {
          const float e1 = ex2(s[4 * i + 1]), e0 = ex2(s[4 * i]), e3 = ex2(s[4 * i + 3]), e2 = ex2(s[4 * i + 2]);
          pout[2 * i] = pack_bf16(e0, e1);
          b0 = i ? b0 + fadd(e1, e0) : fadd(e1, e0);
          pout[2 * i + 1] = pack_bf16(e2, e3);
          b1 = i ? b1 + fadd(e3, e2) : fadd(e3, e2);
        }
        if (!__any_sync(0xffffffffu, !gen && !(fmaxf(b0, b1) <= kSumLimit && (!first || fminf(b0, b1) >= 1.0f / kSumLimit)))) break;
        gen = __any_sync(0xffffffffu, true);
      }
      l0 = first ? b0 : l0 + b0;
      l1 = first ? b1 : l1 + b1;
    };
    auto qk = [&](float (&s)[32], uint32_t ak, int k0, int k1) {
#pragma unroll
      for (int kk = k0; kk < k1; kk++)
        wgmma_rs_n64<0>(s, q[4 * kk], q[4 * kk + 1], q[4 * kk + 2], q[4 * kk + 3], mk_desc(ak, 16, KV_SBO, 1, (kk >> 2) * KV_CH + (kk & 3) * 2), kk != 0);
      wg_commit();
    };
    auto pv = [&](uint32_t (&pin)[16], uint32_t av, int acc) {
#pragma unroll
      for (int kk = 0; kk < 4; kk++)
        wgmma_rs_n192<1>(o, pin[4 * kk], pin[4 * kk + 1], pin[4 * kk + 2], pin[4 * kk + 3], mk_desc(av, KV_CH * 16, KV_SBO, 1, kk * (KV_SBO / 8)), acc || (kk != 0));
      wg_commit();
    };
    auto xw = [&](uint32_t ad, int acc) {
      const uint32_t da = second(SZ_A) + wg * 512;
      wg_fence();
#pragma unroll
      for (int kk = 0; kk < 4; kk++)
        wgmma_ss_n192<1>(o, mk_desc(da, 16, 1024, 1, kk * 2), mk_desc(ad, 4096, 1024, 1, (kk & 1) * 128 + (kk >> 1) * 768), acc || kk != 0);
      wg_commit();
    };
    auto ow = [&](int acc, int prev) {
      uint32_t da;
      const int bi = take(rdy0, SZ_A, da);
      const uint32_t db = second(SZ_WO);
      da += wg * 256;
      wg_fence();
      wgmma_ss_n160<1>(c, mk_desc(da, 16, 512, 2), mk_desc(db, 2048, 512, 2), acc);
      wgmma_ss_n160<1>(c, mk_desc(da, 16, 512, 2, 2), mk_desc(db, 2048, 512, 2, 64), 1);
      wg_commit();
      if (acc == 1) { wg_wait<1>(); release(prev); }
      wgmma_ss_n160<1>(c, mk_desc(da, 16, 512, 2, 512), mk_desc(db, 2048, 512, 2, 640), 1);
      wgmma_ss_n160<1>(c, mk_desc(da, 16, 512, 2, 514), mk_desc(db, 2048, 512, 2, 704), 1);
      wg_commit();
      return bi;
    };
    auto st_part = [&](int i) {
      stg2_if(true, pend + i * 512, __float_as_uint(c[8 * i]), __float_as_uint(c[8 * i + 1]), __float_as_uint(c[8 * i + 2]), __float_as_uint(c[8 * i + 3]),
              __float_as_uint(c[8 * i + 4]), __float_as_uint(c[8 * i + 5]), __float_as_uint(c[8 * i + 6]), __float_as_uint(c[8 * i + 7]), spol);
    };
#pragma unroll
    for (int i = 0; i < 48; i++) q[i] = 0;
    enter();

    if ((op & 3) == OP_Q) {
      uint32_t ad;
      int bi0 = take(false, SZ_WQ, ad), k = 0, lag = 0;
      xw(ad, 0);
      for (;;) {
#pragma unroll 1
        for (;;) {
          drain(q, k - lag);
          probe1();
          wg_wait<0>();
          release(bi0);
          bi0 = take(rdy0, SZ_WQ, ad);
          if (++k == 8) break;
          xw(ad, 1);
        }
        if (wg) bar_sync(2, 256);
        xw(ad, 1);
        const int bi9 = take(false, SZ_WQ, ad);
        xw(ad, 1);
        if (!wg) asm volatile("bar.arrive 2, 256;" ::: "memory");
        k = 0; lag = 0;
        uint32_t nop = prog[++pc];
        wg_wait<1>();
        release(bi0);
        probe2();
        wg_wait<0>();
        fence_regs(o);
        release(bi9);
#pragma unroll
        for (int i = 0; i < 48; i++) q[i] = pack_bf16(o[2 * i] * kScaleLog2, o[2 * i + 1] * kScaleLog2);
        fence_regs(q);
        if (op & F_PARK) {
          const int qt = helper ? (op >> 5) & 15 : team, qm = helper ? (op >> 12) & 3 : nt;
          pend = &g_o[((qt * 2 + rank) * 96 + 3 * (4 * ((op >> 2) & 7) + qm)) * 1024 + img0];
          op = nop;
          enter();
          if ((op & 3) != OP_Q) break;
          const int b = take(rdy0, SZ_WQ, ad);
          xw(ad, 0);
          bi0 = take(rdy1, SZ_WQ, ad);
          xw(ad, 1);
          wg_wait<1>();
          release(b);
          k = 1; lag = 1;
          continue;
        }
        int wave = (op >> 2) & 7, sk1;
        uint32_t ak1;
        {
          float s0[32];
          const int sk0 = take(rdy0, SZ_KV, ad);
          wg_fence();
          qk(s0, ad, 0, 12);
          sk1 = take(rdy1, SZ_KV, ak1);
          wg_fence();
          qk(s, ak1, 0, S1A);
          probe1();
          wg_wait<1>();
          fence_regs(s0);
          release(sk0);
          soft(s0, pa, true);
        }
        float i0, i1;
        auto sums = [&]() {
          l0 += __shfl_xor_sync(0xffffffffu, l0, 1); l1 += __shfl_xor_sync(0xffffffffu, l1, 1);
          l0 += __shfl_xor_sync(0xffffffffu, l0, 2); l1 += __shfl_xor_sync(0xffffffffu, l1, 2);
          i0 = rcp(l0); i1 = rcp(l1);
          asm volatile("" : "+f"(i0), "+f"(i1));
        };
        auto target = [&]() {
          pend = &g_o[((team * 2 + rank) * 96 + 3 * (4 * wave + nt)) * 1024 + img0];
          asm volatile("" : "+l"(pend));
        };
        bool late = false;
#pragma unroll
        for (int i = 0; i < 16; i++) pb[i] = 0;
        for (;;) {
          nop = prog[++pc];
          {
            uint32_t av;
            const int sv = take(rdy0, SZ_KV, av);
            wg_fence();
            qk(s, ak1, S1A, 12);
            pv(pa, av, 0);
            if (late) {
              stg2_if(true, pend + 4 * 512, pb[0], pb[1], pb[2], pb[3], pb[4], pb[5], pb[6], pb[7], spol);
              stg2_if(true, pend + 5 * 512, pb[8], pb[9], pb[10], pb[11], pb[12], pb[13], pb[14], pb[15], spol);
              __syncwarp();
              mbar_arrive_if(lane < 2, odone);
            }
            probe2();
            wg_wait<1>();
            fence_regs(s);
            release(sk1);
            soft(s, pb, false);
            wg_wait<0>();
            fence_regs(o);
            release(sv);
          }
          auto step = [&](uint32_t (&pin)[16], uint32_t (&pout)[16]) {
            uint32_t ak, av;
            const int sk = take(rdy0, SZ_KV, ak), sv = take(rdy1, SZ_KV, av);
            wg_fence();
            qk(s, ak, 0, 12);
            pv(pin, av, 1);
            probe2();
            wg_wait<1>();
            fence_regs(s);
            release(sk);
            soft(s, pout, false);
            wg_wait<0>();
            fence_regs(o);
            release(sv);
          };
#pragma unroll 1
          for (int jj = 0; jj < 7; jj++) {
            step(pb, pa);
            step(pa, pb);
          }
          if ((nop & 3) != OP_A) break;
          uint32_t ak, av;
          {
            const int b0 = take(rdy0, SZ_PARK, ak), b1 = take(rdy1, SZ_PARK, av);
            const uint32_t ad0 = ak, ad1 = av;
            probe2();
#pragma unroll
            for (int i = 0; i < 12; i++)
              lds128(sbase + ((i < 6 ? ad0 : ad1) - ring16 + img0) * 16 + ((i % 6) >> 1) * 8192 + (i & 1) * 512, q[4 * i], q[4 * i + 1], q[4 * i + 2], q[4 * i + 3]);
            release(b0); release(b1);
          }
          const int sk0 = take(rdy0, SZ_KV, ak), sv = take(rdy1, SZ_KV, av);
          wg_fence();
          qk(s, ak, 0, 8);
          sched_fence(img0, P.zero);
          sums();
          sched_fence(img0, P.zero);
          qk(s, ak, 8, 12);
          pv(pb, av, 1);
          probe2();
          wg_wait<1>();
          fence_regs(s);
          release(sk0);
          soft(s, pa, true);
          sk1 = take(rdy0, SZ_KV, ak1);
          rdy0 = rdy1;
          wg_wait<0>();
          target();
          fence_regs(o);
          release(sv);
          uint32_t t[48];
#pragma unroll
          for (int j = 0; j < 6; j++) {
#pragma unroll
            for (int i = 0; i < 4; i++) {
              t[8 * j + i] = pack_bf16(o[16 * j + 4 * i] * i0, o[16 * j + 4 * i + 1] * i0);
              t[8 * j + i + 4] = pack_bf16(o[16 * j + 4 * i + 2] * i1, o[16 * j + 4 * i + 3] * i1);
            }
            if (j < 4)
            stg2_if(true, pend + j * 512, t[8 * j], t[8 * j + 1], t[8 * j + 2], t[8 * j + 3], t[8 * j + 4], t[8 * j + 5], t[8 * j + 6], t[8 * j + 7], spol);
            if (j == 3) { wg_fence(); qk(s, ak1, 0, 4); }
            if (j == 5) { wg_fence(); qk(s, ak1, 4, S1A); }
            sched_fence(img0, P.zero);
          }
          if (P.zero) {
#pragma unroll
            for (int j = 0; j < 4; j++)
              stg2_if(true, pend, t[8 * j], t[8 * j + 1], t[8 * j + 2], t[8 * j + 3], t[8 * j + 4], t[8 * j + 5], t[8 * j + 6], t[8 * j + 7], spol);
          }
          late = true;
#pragma unroll
          for (int i = 0; i < 16; i++) pb[i] = t[32 + i];
          wave = (nop >> 2) & 7;
        }
        const int sv = take(rdy0, SZ_KV, ad);
        wg_fence();
        pv(pb, ad, 1);
        sums();
        target();
        op = nop;
        enter();
        rdy0 = rdy1;
        auto convert = [&](float (&u)[96], int j0, int j1) {
#pragma unroll
          for (int i = 4 * j0; i < 4 * j1; i++) {
            q[8 * (i >> 2) + (i & 3)] = pack_bf16(u[4 * i], u[4 * i + 1]);
            q[8 * (i >> 2) + (i & 3) + 4] = pack_bf16(u[4 * i + 2], u[4 * i + 3]);
          }
        };
        if ((op & 3) != OP_O) {
          if ((op & 3) == OP_Q) bi0 = take(rdy0, SZ_WQ, ad);
          wg_wait<0>();
          fence_regs(o);
          release(sv);
          float u[96];
#pragma unroll
          for (int i = 0; i < 96; i++) u[i] = o[i] * (i & 2 ? i1 : i0);
          if ((op & 3) != OP_Q) { convert(u, 0, 6); break; }
          fence_regs(u);
          xw(ad, 0);
          sched_fence(img0, P.zero);
          fence_regs(u);
          convert(u, 0, 1);
          stg2_if(true, pend, q[0], q[1], q[2], q[3], q[4], q[5], q[6], q[7], spol);
          probe1();
          wg_wait<0>();
          release(bi0);
          bi0 = take(rdy0, SZ_WQ, ad);
          xw(ad, 1);
          sched_fence(img0, P.zero);
          fence_regs(u);
          convert(u, 1, 6);
          k = 1;
          continue;
        }
        int bi = ow(0, 0);
        wg_wait<2>();
        fence_regs(o);
        release(sv);
#pragma unroll
        for (int j = 0; j < 6; j++) {
          uint32_t t[8];
#pragma unroll
          for (int i = 0; i < 4; i++) {
            t[i] = pack_bf16(o[16 * j + 4 * i] * i0, o[16 * j + 4 * i + 1] * i0);
            t[i + 4] = pack_bf16(o[16 * j + 4 * i + 2] * i1, o[16 * j + 4 * i + 3] * i1);
          }
          stg2_if(true, pend + j * 512, t[0], t[1], t[2], t[3], t[4], t[5], t[6], t[7], spol);
          if (j == 5) {
            __syncwarp();
            mbar_arrive_if(lane < 2, odone);
          }
          probe1();
          wg_wait<1>();
          bi = ow(1, bi);
          fence_regs(o);
        }
        {
          const int nk = 12 * (((op >> 5) & 15) - ((op >> 2) & 7)) - ((op & F_ST) ? 0 : 2);
#pragma unroll 1
          for (int k = 7; k < nk; k++) {
            probe1();
            wg_wait<1>();
            bi = ow(1, bi);
          }
        }
        if (!(op & F_ST)) {
          probe2();
          wg_wait<1>();
          if (wg) {
            wg_wait<0>();
            release(bi);
            bar_sync(2, 256);
          }
          bi0 = ow(2, 0);
          rdy0 = rdy1;
          const int b = ow(2, 0);
          if (!wg) asm volatile("bar.arrive 2, 256;" ::: "memory");
          wg_wait<4>();
          mbar_arrive_cluster_if(lane < 2 && !wg, empty_rem + bi);
          bi = b;
        }
        probe1();
        nop = prog[++pc];
        if (op & F_LD) {
          uint32_t t[80];
#pragma unroll
          for (int j = 0; j < 5; j++) {
            const int b = take(rdy0, SZ_PART, ad);
            probe1();
#pragma unroll
            for (int i = 4 * j; i < 4 * j + 4; i++)
              lds128(sbase + (ad - ring16 + img0) * 16 + ((i >> 1) & 1) * 8192 + (i & 1) * 512, t[4 * i], t[4 * i + 1], t[4 * i + 2], t[4 * i + 3]);
            release(b);
          }
          wg_wait<0>();
          fence_regs(c);
#pragma unroll
          for (int i = 0; i < 80; i++) c[i] += __uint_as_float(t[i]);
        }
        if (!(op & F_ST)) {
          wg_wait<0>();
          fence_regs(c);
          release(bi0);
          release(bi);
          goto finish;
        }
        op = nop;
        enter();
        bi0 = take(rdy0, SZ_WQ, ad);
        xw(ad, 0);
        pend = &g_part[((team * 4 + nt) * 2 + rank) * 5120 + img0];
        probe1();
        wg_wait<1>();
        fence_regs(c);
        release(bi);
        st_part(0); st_part(1);
        wg_wait<0>();
        release(bi0);
        bi0 = take(rdy0, SZ_WQ, ad);
        xw(ad, 1);
        st_part(2); st_part(3);
#pragma unroll
        for (int i = 0; i < 48; i++) q[i] = __float_as_uint(c[32 + i]);
        pend += 4 * 512;
        k = 1; lag = 2;
      }
    }
    rdy0 = false;
    {
      uint32_t t[48];
#pragma unroll
      for (int i = 0; i < 48; i++) t[i] = q[i] ^ P.zero;
      while ((op & 3) == OP_O) {
        int bi = ow(0, 0);
#pragma unroll 1
        for (int k = 1; k < 12 * (int)(((op >> 5) & 15) - ((op >> 2) & 7)); k++) {
          drain(t, k - 1);
          probe1();
          wg_wait<1>();
          bi = ow(1, bi);
        }
        rdy0 = false;
        wg_wait<0>();
        fence_regs(c);
        pc++;
        release(bi);
        if (!(op & F_ST)) goto finish;
        pend = &g_part[((((op >> 26) & 56) | ((op >> 9) & 7)) * 2 + rank) * 5120 + img0];
#pragma unroll
        for (int i = 6; i < 10; i++) st_part(i);
#pragma unroll
        for (int i = 0; i < 48; i++) t[i] = __float_as_uint(c[i]) ^ P.zero;
        op = prog[pc];
        enter();
      }
      for (int i = 0; i < 6; i++) drain(t, i);
    }
    if (false) {
    finish:
      uint32_t ad;
      take(rdy0, SZ_OUT, ad);
      const uint32_t wstage = sbase + (ad - ring16) * 16 + (wg * 4 + warp) * 5120;
      const uint32_t sa = wstage + (lane & 15) * 64;
#pragma unroll
      for (int i = 0; i < 10; i++) {
        const int u = (i & 1) * 2 + (lane >> 4);
        stsm4(sa + (i >> 1) * 1024 + ((u ^ ((lane >> 1) & 3)) << 4), pack_bf16(c[8 * i], c[8 * i + 1]), pack_bf16(c[8 * i + 2], c[8 * i + 3]),
              pack_bf16(c[8 * i + 4], c[8 * i + 5]), pack_bf16(c[8 * i + 6], c[8 * i + 7]));
      }
      asm volatile("fence.proxy.async.shared::cta;" ::: "memory");
      __syncwarp();
      if (lane == 0) {
        tma3d_store(&P.out, wstage, 0, (team & 7) * kSq + rank * 128 + wg * 64 + warp * 16, blk * 20 + nt * 5);
        asm volatile("cp.async.bulk.commit_group;\ncp.async.bulk.wait_group.read 0;" ::: "memory");
      }
    }
  }
}

typedef CUresult (*EncodeFn)(CUtensorMap*, CUtensorMapDataType, cuuint32_t, void*, const cuuint64_t*, const cuuint64_t*,
                             const cuuint32_t*, const cuuint32_t*, CUtensorMapInterleave, CUtensorMapSwizzle,
                             CUtensorMapL2promotion, CUtensorMapFloatOOBfill);

void encode(EncodeFn fn, CUtensorMap* m, const void* ptr, int rank, const cuuint64_t* dims, const cuuint64_t* strides,
            const cuuint32_t* box, CUtensorMapSwizzle swz) {
  const cuuint32_t es[5] = {1, 1, 1, 1, 1};
  CUresult r = fn(m, CU_TENSOR_MAP_DATA_TYPE_BFLOAT16, rank, const_cast<void*>(ptr), dims, strides, box, es,
                  CU_TENSOR_MAP_INTERLEAVE_NONE, swz, CU_TENSOR_MAP_L2_PROMOTION_L2_128B, CU_TENSOR_MAP_FLOAT_OOB_FILL_NONE);
  if (r != CUDA_SUCCESS) fprintf(stderr, "cuTensorMapEncodeTiled failed: %d\n", (int)r);
}

void annotate(uint32_t* ops, int n, bool helper) {
  uint32_t items = 0, cur = 0, pend = 0;
  auto item = [&](uint32_t bytes, int count, uint32_t bytes2 = 0) {
    for (int i = 0; i < count; i++) {
      if (cur + bytes > RING) cur = 0;
      cur += bytes;
      if (cur + bytes2 > RING) cur = 0;
      cur += bytes2;
      items++;
    }
  };
  for (int i = 0; i <= n; i++) {
    const uint32_t op = ops[i];
    ops[i] |= (items % (2 * NBAR)) << 15 | (cur >> 12) << 20 | pend << 26;
    if ((op & 3) == OP_Q) { item(SZ_WQ, 10, SZ_A); pend = (op & F_PARK) ? (helper ? 1 : 2) : 0; }
    if ((op & 3) == OP_A) {
      item(SZ_KV, (op & F_PARK) ? 30 : 31);
      if ((ops[i + 1] & 3) == OP_A) { item(SZ_PARK, 2); item(SZ_KV, 1); }
      item(SZ_KV, 1);
      pend = 1;
    }
    if ((op & 3) == OP_O) {
      item(SZ_A, 12 * (((op >> 5) & 15) - ((op >> 2) & 7)), SZ_WO);
      if (op & F_LD) item(SZ_PART, 5);
      pend = (op & F_ST) ? (helper ? 1 : 2) : 0;
    }
  }
}

void compile_programs(const char* const* text, bool helpers, Params& P) {
  struct Req { int when, team, wave, slot; } req[N_TEAM * MAX_PARK];
  int n_req = 0;
  for (int t = 0; t < N_TEAM; t++) {
    uint32_t* ops = P.ops[t];
    int n = 0, flags[8] = {0, 0, 0, 0, 0, 0, 0, 0}, n_park = 0, last_o = -1, when = 0, given = 0;
    for (const char* s = text[t]; *s; s++) {
      const int a = s[1] - '0';
      if (*s == 'Q' || (*s == 'H' && !helpers)) { ops[n++] = OP_Q | a << 2; when += 10; }
      else if (*s == 'P') { flags[a] = F_PARK; ops[n++] = OP_Q | a << 2 | flags[a]; when += 10; }
      else if (*s == 'H') { req[n_req++] = {when, t, a, n_park}; flags[a] = F_PARK | F_HELP | n_park++ << 10; }
      else if (*s == 'A') { ops[n++] = OP_A | a << 2 | flags[a]; when += 32; }
      else if (*s == 'G') { given = a; if (helpers) req[n_req++] = {1000, t, 0, -a}; }
      else if (*s == 'O') {
        ops[n] = OP_O | a << 2 | (s[2] - '0') << 5;
        if (given) ops[n] = helpers ? ops[n] | F_LD | F_PARK | (MAX_PARK - 1) << 10 : ops[n] & ~(7u << 2);
        if (last_o >= 0) { ops[last_o] |= F_ST; ops[n] |= F_LD; }
        last_o = n++;
        when += 10 * (s[2] - s[1]);
      }
    }
    for (int i = n; i < MAX_OPS; i++) ops[i] = OP_END;
    annotate(ops, n, false);
  }
  for (int i = 1; i < n_req; i++)
    for (int j = i; j > 0 && req[j].when < req[j - 1].when; j--) { Req r = req[j]; req[j] = req[j - 1]; req[j - 1] = r; }
  for (int h = 0; h < N_HELP; h++) {
    uint32_t* ops = P.ops[N_TEAM + 2 * h];
    int n = 0;
    for (int i = 0; i < n_req; i++)
      for (int m = h; m < 4; m += N_HELP) {
        const uint32_t ro = 4 * req[i].team + m;
        ops[n++] = req[i].slot >= 0 ? OP_Q | req[i].wave << 2 | req[i].team << 5 | F_PARK | req[i].slot << 10 | m << 12
                                    : OP_O | -req[i].slot << 5 | F_ST | (ro & 7) << 9 | (ro >> 3) << 29;
      }
    for (int i = n; i < 2 * MAX_OPS; i++) ops[i] = OP_END;
    annotate(ops, n, true);
  }
  for (int i = 0; i < 32; i++) P.first[i] = i < N_TEAM ? P.ops[i][0] : i < N_TEAM + N_HELP ? P.ops[2 * i - N_TEAM][0] : 0;
}

const char* const kPrograms[N_TEAM] = {
  "Q0A0Q1A1H2A2O03Q3A3Q4A4Q5A5Q6A6Q7A7O38",
  "Q0A0Q1A1Q2A2Q3A3O04Q4A4Q5A5Q6A6H7A7O48",
  "Q0A0H1A1Q2A2Q3A3Q4A4O05Q5A5Q6A6Q7A7O58",
  "Q0A0Q1A1Q2A2O03Q3A3Q4A4Q5A5Q6A6H7A7O38",
  "Q0A0Q1A1Q2A2O03Q3A3H4A4Q5A5Q6A6Q7A7O38",
  "Q0A0Q1A1H2A2Q3A3Q4A4O05Q5A5Q6A6Q7A7O58",
  "Q0A0Q1A1Q2A2Q3A3O03Q4A4H5A5Q6A6Q7A7O38",
  "Q0A0Q1A1Q2A2Q3A3Q4A4O05Q5A5Q6A6H7A7O58",
  "P3Q0A0Q1A1Q2A2A3H4A4Q5A5Q6A6Q7A7O08",
  "P5P7Q0A0Q1A1Q2A2H3A3Q4A4A5Q6A6A7G1O18",
  "Q0A0Q1A1Q2A2O02Q3A3H4A4Q5A5Q6A6Q7A7O28",
  "P3P5Q0A0Q1A1Q2A2A3Q4A4A5Q6A6H7A7O08",
  "Q0A0Q1A1Q2A2O02Q3A3Q4A4H5A5Q6A6Q7A7O28",
  "P7Q0A0Q1A1Q2A2Q3A3Q4A4Q5A5Q6A6A7G1O18",
  "P5Q0A0Q1A1Q2A2Q3A3Q4A4A5Q6A6H7A7O08",
  "Q0A0Q1A1Q2A2H3A3Q4A4Q5A5Q6A6Q7A7O08",
};

const char* const* bench_programs() {
  return kPrograms;
}

}

extern "C" void kernel_launch(void* const* d_in, const int* in_sizes, int n_in, void* d_out, int out_size) {
  (void)in_sizes; (void)n_in; (void)out_size;
  static EncodeFn fn = nullptr;
  static int n_clusters = 0;
  if (!fn) {
    cudaDriverEntryPointQueryResult qr;
    void* f = nullptr;
    cudaGetDriverEntryPoint("cuTensorMapEncodeTiled", &f, cudaEnableDefault, &qr);
    fn = (EncodeFn)f;
    cudaFuncSetAttribute(fused_kernel, cudaFuncAttributeMaxDynamicSharedMemorySize, SMEM_BYTES);
    cudaLaunchConfig_t cfg = {};
    cfg.gridDim = dim3(132); cfg.blockDim = dim3(384); cfg.dynamicSmemBytes = SMEM_BYTES;
    cudaLaunchAttribute at[1];
    at[0].id = cudaLaunchAttributeClusterDimension; at[0].val.clusterDim.x = 2; at[0].val.clusterDim.y = 1; at[0].val.clusterDim.z = 1;
    cfg.attrs = at; cfg.numAttrs = 1;
    if (cudaOccupancyMaxActiveClusters(&n_clusters, fused_kernel, &cfg) != cudaSuccess || n_clusters < 1) n_clusters = 1;
    (void)cudaGetLastError();
  }
  Params P;
  const CUtensorMapSwizzle S128 = CU_TENSOR_MAP_SWIZZLE_128B, S64 = CU_TENSOR_MAP_SWIZZLE_64B;
  for (int blk = 0; blk < 2; blk++) {
    void* const* in = d_in + 5 * blk;
    { const cuuint64_t d[] = {kD, kB * kSq}, s[] = {kD * 2}; const cuuint32_t b[] = {64, 128};
      encode(fn, &P.x[blk], in[0], 2, d, s, b, S128); }
    { const cuuint64_t d[] = {64, 8, 3, (cuuint64_t)kB * kH * kSk / 8}, s[] = {kDh * 2, 128, 8 * kDh * 2}; const cuuint32_t b[] = {64, 8, 3, 4};
      encode(fn, &P.kv[blk], in[1], 4, d, s, b, S128);
      encode(fn, &P.kv[blk + 2], in[2], 4, d, s, b, S128); }
    { const cuuint64_t d[] = {64, kD, kHD / 64}, s[] = {kHD * 2, 128}; const cuuint32_t b[] = {64, 32, 3};
      encode(fn, &P.wq[blk], in[3], 3, d, s, b, S128); }
    { const cuuint64_t d[] = {32, 2, kHD / 8, 4, kD / 32}, s[] = {kD * 2, 8 * kD * 2, 2 * kD * 2, 64}; const cuuint32_t b[] = {32, 2, 4, 4, 5};
      encode(fn, &P.wo[blk], in[4], 5, d, s, b, S64); }
  }
  { const cuuint64_t d[] = {32, kB * kSq, 2 * kD / 32}, s[] = {2 * kD * 2, 64}; const cuuint32_t b[] = {32, 16, 5};
    encode(fn, &P.out, d_out, 3, d, s, b, S64); }

  P.zero = 0;
  if (n_clusters >= N_CL) {
    const bool helpers = n_clusters >= N_CL + N_HELP;
    compile_programs(bench_programs(), helpers, P);
    fused_kernel<<<2 * (N_CL + (helpers ? N_HELP : 0)), 384, SMEM_BYTES>>>(P);
  } else {
    for (int phase = 0; phase < 2; phase++) {
      const char* text[N_TEAM];
      for (int t = 0; t < N_TEAM; t++) text[t] = phase ? "O08" : "Q0A0Q1A1Q2A2Q3A3Q4A4Q5A5Q6A6Q7A7";
      compile_programs(text, false, P);
      fused_kernel<<<2 * N_CL, 384, SMEM_BYTES>>>(P);
    }
  }
}
```

```cpp
#include <cuda_runtime.h>
#include <cuda_bf16.h>
#include <cuda.h>
#include <stdint.h>
#include <stdio.h>

namespace {

constexpr int kB = 8, kSq = 256, kD = 640, kH = 32, kSk = 1024, kDh = 192;
constexpr int kHD = kH * kDh;
constexpr uint32_t RING = 224 * 1024;
constexpr uint32_t SZ_KV = 24576;
constexpr uint32_t SZ_WQ = 24576, SZ_WO = 20480, SZ_A = 16384;
constexpr uint32_t SZ_OUT = 40960;
constexpr uint32_t SZ_PARK = 24576;
constexpr uint32_t SZ_PART = 16384;
constexpr int NBAR = 16, NFLIGHT = 12;
constexpr int KV_TRANSIT = 4;
constexpr int EARLY = 3;
constexpr int S1A = 7;
constexpr uint32_t KV_CH = 64, KV_SBO = 3072;
constexpr int SMEM_BYTES = RING + 512 + 1024;
constexpr int N_TEAM = 16, N_CL = 64, N_HELP = 2, MAX_OPS = 24, MAX_PARK = 4;
enum { OP_END = 0, OP_Q = 1, OP_A = 2, OP_O = 3, F_PARK = 1 << 9, F_LD = 1 << 12, F_ST = 1 << 13, F_HELP = 1 << 12 };

struct alignas(64) Params {
  uint32_t first[32];
  CUtensorMap x[2], wq[2], kv[4], wo[2], out;
  uint32_t ops[N_TEAM + 2 * N_HELP][MAX_OPS];
  uint32_t zero;
};

__device__ uint4 g_o[N_TEAM * 2 * 96 * 1024];
__device__ uint4 g_part[N_CL * 2 * 5 * 1024];
__device__ unsigned int g_done[N_TEAM * 2 * 8];
__device__ unsigned int g_help[N_CL * 2 * MAX_PARK];
__device__ unsigned int g_seen[N_TEAM * 2 * 8];

template <int TB>
__device__ __forceinline__ void wgmma_rs_n64(float (&d)[32], uint32_t a0, uint32_t a1, uint32_t a2, uint32_t a3, uint64_t db, int scale_d) {
  asm volatile("{\n.reg .pred p;\nsetp.ne.b32 p, %37, 0;\n"
    "wgmma.mma_async.sync.aligned.m64n64k16.f32.bf16.bf16 {%0, %1, %2, %3, %4, %5, %6, %7, %8, %9, %10, %11, %12, %13, %14, %15, %16, %17, %18, %19, %20, %21, %22, %23, %24, %25, %26, %27, %28, %29, %30, %31}, {%32, %33, %34, %35}, %36, p, 1, 1, %38;\n}\n"
    : "+f"(d[0]), "+f"(d[1]), "+f"(d[2]), "+f"(d[3]), "+f"(d[4]), "+f"(d[5]), "+f"(d[6]), "+f"(d[7]), "+f"(d[8]), "+f"(d[9]), "+f"(d[10]), "+f"(d[11]), "+f"(d[12]), "+f"(d[13]), "+f"(d[14]), "+f"(d[15]), "+f"(d[16]), "+f"(d[17]), "+f"(d[18]), "+f"(d[19]), "+f"(d[20]), "+f"(d[21]), "+f"(d[22]), "+f"(d[23]), "+f"(d[24]), "+f"(d[25]), "+f"(d[26]), "+f"(d[27]), "+f"(d[28]), "+f"(d[29]), "+f"(d[30]), "+f"(d[31])
    : "r"(a0), "r"(a1), "r"(a2), "r"(a3), "l"(db), "r"(scale_d), "n"(TB));
}
template <int TB, int TA = 0>
__device__ __forceinline__ void wgmma_ss_n160(float (&d)[80], uint64_t da, uint64_t db, int scale_d) {
  asm volatile("{\n.reg .pred p;\nsetp.ne.b32 p, %82, 0;\n"
    "wgmma.mma_async.sync.aligned.m64n160k16.f32.bf16.bf16 {%0, %1, %2, %3, %4, %5, %6, %7, %8, %9, %10, %11, %12, %13, %14, %15, %16, %17, %18, %19, %20, %21, %22, %23, %24, %25, %26, %27, %28, %29, %30, %31, %32, %33, %34, %35, %36, %37, %38, %39, %40, %41, %42, %43, %44, %45, %46, %47, %48, %49, %50, %51, %52, %53, %54, %55, %56, %57, %58, %59, %60, %61, %62, %63, %64, %65, %66, %67, %68, %69, %70, %71, %72, %73, %74, %75, %76, %77, %78, %79}, %80, %81, p, 1, 1, %83, %84;\n}\n"
    : "+f"(d[0]), "+f"(d[1]), "+f"(d[2]), "+f"(d[3]), "+f"(d[4]), "+f"(d[5]), "+f"(d[6]), "+f"(d[7]), "+f"(d[8]), "+f"(d[9]), "+f"(d[10]), "+f"(d[11]), "+f"(d[12]), "+f"(d[13]), "+f"(d[14]), "+f"(d[15]), "+f"(d[16]), "+f"(d[17]), "+f"(d[18]), "+f"(d[19]), "+f"(d[20]), "+f"(d[21]), "+f"(d[22]), "+f"(d[23]), "+f"(d[24]), "+f"(d[25]), "+f"(d[26]), "+f"(d[27]), "+f"(d[28]), "+f"(d[29]), "+f"(d[30]), "+f"(d[31]), "+f"(d[32]), "+f"(d[33]), "+f"(d[34]), "+f"(d[35]), "+f"(d[36]), "+f"(d[37]), "+f"(d[38]), "+f"(d[39]), "+f"(d[40]), "+f"(d[41]), "+f"(d[42]), "+f"(d[43]), "+f"(d[44]), "+f"(d[45]), "+f"(d[46]), "+f"(d[47]), "+f"(d[48]), "+f"(d[49]), "+f"(d[50]), "+f"(d[51]), "+f"(d[52]), "+f"(d[53]), "+f"(d[54]), "+f"(d[55]), "+f"(d[56]), "+f"(d[57]), "+f"(d[58]), "+f"(d[59]), "+f"(d[60]), "+f"(d[61]), "+f"(d[62]), "+f"(d[63]), "+f"(d[64]), "+f"(d[65]), "+f"(d[66]), "+f"(d[67]), "+f"(d[68]), "+f"(d[69]), "+f"(d[70]), "+f"(d[71]), "+f"(d[72]), "+f"(d[73]), "+f"(d[74]), "+f"(d[75]), "+f"(d[76]), "+f"(d[77]), "+f"(d[78]), "+f"(d[79])
    : "l"(da), "l"(db), "r"(scale_d), "n"(TA), "n"(TB));
}
template <int TB, int TA = 0>
__device__ __forceinline__ void wgmma_ss_n192(float (&d)[96], uint64_t da, uint64_t db, int scale_d) {
  asm volatile("{\n.reg .pred p;\nsetp.ne.b32 p, %98, 0;\n"
    "wgmma.mma_async.sync.aligned.m64n192k16.f32.bf16.bf16 {%0, %1, %2, %3, %4, %5, %6, %7, %8, %9, %10, %11, %12, %13, %14, %15, %16, %17, %18, %19, %20, %21, %22, %23, %24, %25, %26, %27, %28, %29, %30, %31, %32, %33, %34, %35, %36, %37, %38, %39, %40, %41, %42, %43, %44, %45, %46, %47, %48, %49, %50, %51, %52, %53, %54, %55, %56, %57, %58, %59, %60, %61, %62, %63, %64, %65, %66, %67, %68, %69, %70, %71, %72, %73, %74, %75, %76, %77, %78, %79, %80, %81, %82, %83, %84, %85, %86, %87, %88, %89, %90, %91, %92, %93, %94, %95}, %96, %97, p, 1, 1, %99, %100;\n}\n"
    : "+f"(d[0]), "+f"(d[1]), "+f"(d[2]), "+f"(d[3]), "+f"(d[4]), "+f"(d[5]), "+f"(d[6]), "+f"(d[7]), "+f"(d[8]), "+f"(d[9]), "+f"(d[10]), "+f"(d[11]), "+f"(d[12]), "+f"(d[13]), "+f"(d[14]), "+f"(d[15]), "+f"(d[16]), "+f"(d[17]), "+f"(d[18]), "+f"(d[19]), "+f"(d[20]), "+f"(d[21]), "+f"(d[22]), "+f"(d[23]), "+f"(d[24]), "+f"(d[25]), "+f"(d[26]), "+f"(d[27]), "+f"(d[28]), "+f"(d[29]), "+f"(d[30]), "+f"(d[31]), "+f"(d[32]), "+f"(d[33]), "+f"(d[34]), "+f"(d[35]), "+f"(d[36]), "+f"(d[37]), "+f"(d[38]), "+f"(d[39]), "+f"(d[40]), "+f"(d[41]), "+f"(d[42]), "+f"(d[43]), "+f"(d[44]), "+f"(d[45]), "+f"(d[46]), "+f"(d[47]), "+f"(d[48]), "+f"(d[49]), "+f"(d[50]), "+f"(d[51]), "+f"(d[52]), "+f"(d[53]), "+f"(d[54]), "+f"(d[55]), "+f"(d[56]), "+f"(d[57]), "+f"(d[58]), "+f"(d[59]), "+f"(d[60]), "+f"(d[61]), "+f"(d[62]), "+f"(d[63]), "+f"(d[64]), "+f"(d[65]), "+f"(d[66]), "+f"(d[67]), "+f"(d[68]), "+f"(d[69]), "+f"(d[70]), "+f"(d[71]), "+f"(d[72]), "+f"(d[73]), "+f"(d[74]), "+f"(d[75]), "+f"(d[76]), "+f"(d[77]), "+f"(d[78]), "+f"(d[79]), "+f"(d[80]), "+f"(d[81]), "+f"(d[82]), "+f"(d[83]), "+f"(d[84]), "+f"(d[85]), "+f"(d[86]), "+f"(d[87]), "+f"(d[88]), "+f"(d[89]), "+f"(d[90]), "+f"(d[91]), "+f"(d[92]), "+f"(d[93]), "+f"(d[94]), "+f"(d[95])
    : "l"(da), "l"(db), "r"(scale_d), "n"(TA), "n"(TB));
}
template <int TB>
__device__ __forceinline__ void wgmma_rs_n192(float (&d)[96], uint32_t a0, uint32_t a1, uint32_t a2, uint32_t a3, uint64_t db, int scale_d) {
  asm volatile("{\n.reg .pred p;\nsetp.ne.b32 p, %101, 0;\n"
    "wgmma.mma_async.sync.aligned.m64n192k16.f32.bf16.bf16 {%0, %1, %2, %3, %4, %5, %6, %7, %8, %9, %10, %11, %12, %13, %14, %15, %16, %17, %18, %19, %20, %21, %22, %23, %24, %25, %26, %27, %28, %29, %30, %31, %32, %33, %34, %35, %36, %37, %38, %39, %40, %41, %42, %43, %44, %45, %46, %47, %48, %49, %50, %51, %52, %53, %54, %55, %56, %57, %58, %59, %60, %61, %62, %63, %64, %65, %66, %67, %68, %69, %70, %71, %72, %73, %74, %75, %76, %77, %78, %79, %80, %81, %82, %83, %84, %85, %86, %87, %88, %89, %90, %91, %92, %93, %94, %95}, {%96, %97, %98, %99}, %100, p, 1, 1, %102;\n}\n"
    : "+f"(d[0]), "+f"(d[1]), "+f"(d[2]), "+f"(d[3]), "+f"(d[4]), "+f"(d[5]), "+f"(d[6]), "+f"(d[7]), "+f"(d[8]), "+f"(d[9]), "+f"(d[10]), "+f"(d[11]), "+f"(d[12]), "+f"(d[13]), "+f"(d[14]), "+f"(d[15]), "+f"(d[16]), "+f"(d[17]), "+f"(d[18]), "+f"(d[19]), "+f"(d[20]), "+f"(d[21]), "+f"(d[22]), "+f"(d[23]), "+f"(d[24]), "+f"(d[25]), "+f"(d[26]), "+f"(d[27]), "+f"(d[28]), "+f"(d[29]), "+f"(d[30]), "+f"(d[31]), "+f"(d[32]), "+f"(d[33]), "+f"(d[34]), "+f"(d[35]), "+f"(d[36]), "+f"(d[37]), "+f"(d[38]), "+f"(d[39]), "+f"(d[40]), "+f"(d[41]), "+f"(d[42]), "+f"(d[43]), "+f"(d[44]), "+f"(d[45]), "+f"(d[46]), "+f"(d[47]), "+f"(d[48]), "+f"(d[49]), "+f"(d[50]), "+f"(d[51]), "+f"(d[52]), "+f"(d[53]), "+f"(d[54]), "+f"(d[55]), "+f"(d[56]), "+f"(d[57]), "+f"(d[58]), "+f"(d[59]), "+f"(d[60]), "+f"(d[61]), "+f"(d[62]), "+f"(d[63]), "+f"(d[64]), "+f"(d[65]), "+f"(d[66]), "+f"(d[67]), "+f"(d[68]), "+f"(d[69]), "+f"(d[70]), "+f"(d[71]), "+f"(d[72]), "+f"(d[73]), "+f"(d[74]), "+f"(d[75]), "+f"(d[76]), "+f"(d[77]), "+f"(d[78]), "+f"(d[79]), "+f"(d[80]), "+f"(d[81]), "+f"(d[82]), "+f"(d[83]), "+f"(d[84]), "+f"(d[85]), "+f"(d[86]), "+f"(d[87]), "+f"(d[88]), "+f"(d[89]), "+f"(d[90]), "+f"(d[91]), "+f"(d[92]), "+f"(d[93]), "+f"(d[94]), "+f"(d[95])
    : "r"(a0), "r"(a1), "r"(a2), "r"(a3), "l"(db), "r"(scale_d), "n"(TB));
}

__device__ __forceinline__ uint32_t smem_u32(const void* p) { return (uint32_t)__cvta_generic_to_shared(p); }
__device__ __forceinline__ void wg_fence() { asm volatile("wgmma.fence.sync.aligned;" ::: "memory"); }
__device__ __forceinline__ void wg_commit() { asm volatile("wgmma.commit_group.sync.aligned;" ::: "memory"); }
template <int N> __device__ __forceinline__ void wg_wait() { asm volatile("wgmma.wait_group.sync.aligned %0;" ::"n"(N) : "memory"); }
__device__ __forceinline__ void sched_fence(int& keep, uint32_t zero) {
  asm volatile("{\n.reg .u32 c;\nmov.u32 c, %%clock;\nand.b32 c, c, %1;\nxor.b32 %0, %0, c;\n}\n" : "+r"(keep) : "r"(zero) : "memory");
}
template <int N> __device__ __forceinline__ void fence_regs(float (&r)[N]) {
#pragma unroll
  for (int i = 0; i < N; i++) asm volatile("" : "+f"(r[i])::"memory");
}
template <int N> __device__ __forceinline__ void fence_regs(uint32_t (&r)[N]) {
#pragma unroll
  for (int i = 0; i < N; i++) asm volatile("" : "+r"(r[i])::"memory");
}
__device__ __forceinline__ uint64_t mk_desc(uint32_t a16, uint32_t lbo, uint32_t sbo, uint32_t swz, uint32_t off = 0) {
  uint64_t d;
  asm("mov.b64 %0, {%1, %2};" : "=l"(d) : "r"(a16), "r"((sbo >> 4) | (swz << 30)));
  return d + (off + ((lbo >> 4) << 16));
}
__device__ __forceinline__ void mbar_init(uint32_t bar, uint32_t cnt) {
  asm volatile("mbarrier.init.shared::cta.b64 [%0], %1;" ::"r"(bar), "r"(cnt) : "memory");
}
__device__ __forceinline__ void mbar_expect(uint32_t bar, uint32_t tx) {
  asm volatile("mbarrier.arrive.expect_tx.shared::cta.b64 _, [%0], %1;" ::"r"(bar), "r"(tx) : "memory");
}
__device__ __forceinline__ bool mbar_test(uint32_t bar, uint32_t ph) {
  uint32_t ok;
  asm volatile("{\n.reg .pred p;\nmbarrier.test_wait.parity.shared::cta.b64 p, [%1], %2;\nselp.u32 %0, 1, 0, p;\n}\n"
               : "=r"(ok) : "r"(bar), "r"(ph) : "memory");
  return ok;
}
__device__ __forceinline__ void mbar_wait(uint32_t bar, uint32_t ph) {
  asm volatile("{\n.reg .pred p;\n.reg .u32 n;\nmov.u32 n, 0;\n"
               "LOOP:\nadd.u32 n, n, 1;\nmbarrier.try_wait.parity.shared::cta.b64 p, [%0], %1;\n@p bra DONE;\n"
               "setp.lt.u32 p, n, 0x1000000;\n@p bra LOOP;\ntrap;\n"
               "DONE:\n}\n" ::"r"(bar), "r"(ph) : "memory");
}
__device__ __forceinline__ void mbar_wait_math(uint32_t bar, uint32_t ph) {
  asm volatile("{\n.reg .pred p;\nLOOP:\nmbarrier.try_wait.parity.shared::cta.b64 p, [%0], %1;\n@!p bra LOOP;\n}\n" ::"r"(bar), "r"(ph) : "memory");
}
__device__ __forceinline__ void mbar_wait_long(uint32_t bar, uint32_t ph) {
  asm volatile("{\n.reg .pred p;\n.reg .u32 n;\nmov.u32 n, 0;\n"
               "LOOP:\nmbarrier.try_wait.parity.shared::cta.b64 p, [%0], %1, %2;\n@p bra DONE;\n"
               "add.u32 n, n, 1;\nsetp.lt.u32 p, n, 0x40000;\n@p bra LOOP;\ntrap;\n"
               "DONE:\n}\n" ::"r"(bar), "r"(ph), "r"(20000) : "memory");
}
__device__ __forceinline__ void mbar_arrive_cluster_if(bool on, uint32_t addr) {
  asm volatile("{\n.reg .pred p;\nsetp.ne.b32 p, %1, 0;\n@p mbarrier.arrive.shared::cluster.b64 _, [%0];\n}\n" ::"r"(addr), "r"((int)on) : "memory");
}
__device__ __forceinline__ void mbar_arrive_if(bool on, uint32_t addr) {
  asm volatile("{\n.reg .pred p;\nsetp.ne.b32 p, %1, 0;\n@p mbarrier.arrive.shared::cta.b64 _, [%0];\n}\n" ::"r"(addr), "r"((int)on) : "memory");
}
__device__ __forceinline__ void tma2d(uint32_t dst, const CUtensorMap* m, uint32_t bar, int c0, int c1) {
  asm volatile("cp.async.bulk.tensor.2d.shared::cluster.global.mbarrier::complete_tx::bytes [%0], [%1, {%3, %4}], [%2];"
               ::"r"(dst), "l"(m), "r"(bar), "r"(c0), "r"(c1) : "memory");
}
__device__ __forceinline__ void tma3d(uint32_t dst, const CUtensorMap* m, uint32_t bar, int c0, int c1, int c2) {
  asm volatile("cp.async.bulk.tensor.3d.shared::cluster.global.mbarrier::complete_tx::bytes [%0], [%1, {%3, %4, %5}], [%2];"
               ::"r"(dst), "l"(m), "r"(bar), "r"(c0), "r"(c1), "r"(c2) : "memory");
}
__device__ __forceinline__ void tma3d_mc(uint32_t dst, const CUtensorMap* m, uint32_t bar, int c0, int c1, int c2) {
  asm volatile("cp.async.bulk.tensor.3d.shared::cluster.global.mbarrier::complete_tx::bytes.multicast::cluster"
               " [%0], [%1, {%3, %4, %5}], [%2], %6;"
               ::"r"(dst), "l"(m), "r"(bar), "r"(c0), "r"(c1), "r"(c2), "h"((uint16_t)3) : "memory");
}
__device__ __forceinline__ void tma3d_store(const CUtensorMap* m, uint32_t src, int c0, int c1, int c2) {
  asm volatile("cp.async.bulk.tensor.3d.global.shared::cta.bulk_group [%0, {%2, %3, %4}], [%1];"
               ::"l"(m), "r"(src), "r"(c0), "r"(c1), "r"(c2) : "memory");
}
__device__ __forceinline__ void bar_sync(int id, int n) { asm volatile("bar.sync %0, %1;" ::"r"(id), "r"(n) : "memory"); }
__device__ __forceinline__ uint32_t pack_bf16(float lo, float hi) {
  uint32_t r;
  asm("cvt.rn.bf16x2.f32 %0, %1, %2;" : "=r"(r) : "f"(hi), "f"(lo));
  return r;
}
__device__ __forceinline__ float ex2(float x) {
  float y;
  asm("ex2.approx.ftz.f32 %0, %1;" : "=f"(y) : "f"(x));
  return y;
}
__device__ __forceinline__ float fadd(float a, float b) {
  float y;
  asm("add.f32 %0, %1, %2;" : "=f"(y) : "f"(a), "f"(b));
  return y;
}
__device__ __forceinline__ float rcp(float x) {
  float y;
  asm("rcp.approx.ftz.f32 %0, %1;" : "=f"(y) : "f"(x));
  return y;
}
__device__ __forceinline__ void stsm4(uint32_t addr, uint32_t a, uint32_t b, uint32_t c, uint32_t d) {
  asm volatile("stmatrix.sync.aligned.m8n8.x4.shared.b16 [%0], {%1, %2, %3, %4};" ::"r"(addr), "r"(a), "r"(b), "r"(c), "r"(d) : "memory");
}

__device__ __forceinline__ void tma4d_mc_hint(uint32_t dst, const CUtensorMap* m, uint32_t bar, int c3, uint64_t pol) {
  asm volatile("cp.async.bulk.tensor.4d.shared::cluster.global.mbarrier::complete_tx::bytes.multicast::cluster.L2::cache_hint"
               " [%0], [%1, {%3, %3, %3, %4}], [%2], %5, %6;"
               ::"r"(dst), "l"(m), "r"(bar), "r"(0), "r"(c3), "h"((uint16_t)3), "l"(pol) : "memory");
}
__device__ __forceinline__ void tma5d_mc(uint32_t dst, const CUtensorMap* m, uint32_t bar, int c2, int c4) {
  asm volatile("cp.async.bulk.tensor.5d.shared::cluster.global.mbarrier::complete_tx::bytes.multicast::cluster"
               " [%0], [%1, {%3, %3, %4, %3, %5}], [%2], %6;"
               ::"r"(dst), "l"(m), "r"(bar), "r"(0), "r"(c2), "r"(c4), "h"((uint16_t)3) : "memory");
}
__device__ __forceinline__ void bulk_load_hint(uint32_t dst, const void* src, uint32_t bytes, uint32_t bar, uint64_t pol) {
  asm volatile("cp.async.bulk.shared::cluster.global.mbarrier::complete_tx::bytes.L2::cache_hint [%0], [%1], %2, [%3], %4;"
               ::"r"(dst), "l"(src), "r"(bytes), "r"(bar), "l"(pol) : "memory");
}
__device__ __forceinline__ void stg2_if(bool on, void* p, uint32_t a, uint32_t b, uint32_t c, uint32_t d, uint32_t e, uint32_t f,
                                        uint32_t g, uint32_t h, uint64_t pol) {
  asm volatile("{\n.reg .pred p;\nsetp.ne.b32 p, %10, 0;\n"
               "@p st.global.L2::cache_hint.v4.b32 [%0], {%1, %2, %3, %4}, %9;\n"
               "@p st.global.L2::cache_hint.v4.b32 [%0 + 512], {%5, %6, %7, %8}, %9;\n}\n"
               ::"l"(p), "r"(a), "r"(b), "r"(c), "r"(d), "r"(e), "r"(f), "r"(g), "r"(h), "l"(pol), "r"((int)on) : "memory");
}
__device__ __forceinline__ uint64_t evict_first() {
  uint64_t p;
  asm("createpolicy.fractional.L2::evict_first.b64 %0, 1.0;" : "=l"(p));
  return p;
}
__device__ __forceinline__ bool elect() {
  uint32_t ok;
  asm volatile("{\n.reg .pred p;\nelect.sync _|p, 0xffffffff;\nselp.u32 %0, 1, 0, p;\n}\n" : "=r"(ok));
  return ok;
}
__device__ __forceinline__ void mbar_arrive(uint32_t bar) {
  asm volatile("mbarrier.arrive.shared::cta.b64 _, [%0];" ::"r"(bar) : "memory");
}
__device__ __forceinline__ void lds128(uint32_t p, uint32_t& a, uint32_t& b, uint32_t& c, uint32_t& d) {
  asm volatile("ld.shared.v4.b32 {%0, %1, %2, %3}, [%4];" : "=r"(a), "=r"(b), "=r"(c), "=r"(d) : "r"(p) : "memory");
}
__device__ __forceinline__ void wait_count(const unsigned int* p, uint32_t target) {
  asm volatile("{\n.reg .pred p;\n.reg .u32 n, v;\nmov.u32 n, 0;\n"
               "LOOP:\nld.acquire.gpu.global.u32 v, [%0];\nsetp.ge.u32 p, v, %1;\n@p bra DONE;\n"
               "nanosleep.u32 %2;\nadd.u32 n, n, 1;\nsetp.lt.u32 p, n, 0x400000;\n@p bra LOOP;\ntrap;\n"
               "DONE:\n}\n" ::"l"(p), "r"(target), "n"(300) : "memory");
}

__device__ __forceinline__ int o_wave(int a, int b, int i) {
  const int p = min(3, b - a - 1);
  return i < p ? b - 2 - i : i == p ? b - 1 : b - 1 - i;
}

struct Cursor {
  uint32_t n;
  __device__ __forceinline__ uint32_t off() const { return n & (8 * NBAR - 8); }
  __device__ __forceinline__ uint32_t ph() const { return (n / (8 * NBAR)) & 1; }
  __device__ __forceinline__ void next() { n += 8; }
};

constexpr float kScaleLog2 = 0.07216878364870322f * 1.4426950408889634f;
constexpr float kSumLimit = 1048576.0f;
constexpr float kMaxLag = 8.0f;

__global__ void __cluster_dims__(2, 1, 1) __launch_bounds__(384, 1)
fused_kernel(const __grid_constant__ Params P) {
  extern __shared__ uint8_t smem_raw[];
  const uint32_t sbase = (smem_u32(smem_raw) + 1023) & ~1023u;
  const uint32_t full0 = sbase + RING, empty0 = full0 + 8 * NBAR, odone = empty0 + 8 * NBAR, oready0 = odone + 8;
  const uint32_t fenced = oready0 + 64, hready0 = fenced + 8;
  const uint32_t rank = blockIdx.x & 1;
  const int role = blockIdx.x >> 1;
  const bool helper = role >= N_CL;
  const int team = helper ? 0 : role >> 2, nt = role & 3, blk = team >> 3;
  const uint32_t* prog = P.ops[helper ? N_TEAM + 2 * (role - N_CL) : team];
  auto q_role = [&](uint32_t op) { return helper ? (int)(((op >> 3) & 60) | ((op >> 12) & 3)) : role; };
  auto o_role = [&](uint32_t op) { return helper ? (int)(((op >> 26) & 56) | ((op >> 9) & 7)) : role; };
  const int wid = __shfl_sync(0xffffffffu, (int)(threadIdx.x >> 5), 0);
  const int wg = wid >> 2;

  const uint32_t op0 = P.first[helper ? N_TEAM + role - N_CL : team];
  if (__builtin_expect(wid == 8, 1)) {
    if (elect()) {
#pragma unroll
      for (int k = 0; k < EARLY; k++) mbar_init(full0 + 8 * k, 1);
      asm volatile("fence.mbarrier_init.release.cluster;" ::: "memory");
      if ((op0 & 3) == OP_Q) {
        const int qr = q_role(op0);
#pragma unroll
        for (int k = 0; k < EARLY; k++) {
          mbar_expect(full0 + 8 * k, SZ_WQ + SZ_A);
          tma2d(sbase + k * (SZ_WQ + SZ_A) + SZ_WQ, &P.x[qr >> 5], full0 + 8 * k, 64 * k, ((qr >> 2) & 7) * kSq + rank * 128);
          tma3d(sbase + k * (SZ_WQ + SZ_A), &P.wq[qr >> 5], full0 + 8 * k, 0, 64 * k, 3 * (4 * ((op0 >> 2) & 7) + (qr & 3)));
          tma3d(sbase + k * (SZ_WQ + SZ_A) + SZ_WQ / 2, &P.wq[qr >> 5], full0 + 8 * k, 0, 64 * k + 32, 3 * (4 * ((op0 >> 2) & 7) + (qr & 3)));
        }
      }
      asm volatile("prefetch.tensormap [%0];" ::"l"(&P.kv[blk]) : "memory");
      asm volatile("prefetch.tensormap [%0];" ::"l"(&P.kv[blk + 2]) : "memory");
    }
  } else if (threadIdx.x == 0) {
#pragma unroll
    for (int i = EARLY; i < 2 * NBAR + 10 + MAX_PARK; i++) mbar_init(full0 + 8 * i, i >= NBAR && i <= 2 * NBAR ? 16 : 1);
    asm volatile("fence.mbarrier_init.release.cluster;" ::: "memory");
  }
  __syncwarp();
  asm volatile("barrier.cluster.arrive.relaxed.aligned;\nbarrier.cluster.wait.aligned;" ::: "memory");

  if (wg == 2) {
    asm volatile("setmaxnreg.dec.sync.aligned.u32 24;");
    if (wid == 8) {
      Cursor tail{0u - 8}, head{0};
      int sh = 0;
      uint32_t cur = 0, used = 0;
      uint64_t fifo = 0;
      uint32_t dst, bar, oready = oready0;
      int c0;
      const void* ptr;
      const uint64_t pol = evict_first();
      auto acquire = [&](uint32_t bytes, bool first, bool last, auto prepare) {
        uint32_t fp = bytes >> 12;
        if (cur + fp > (RING >> 12)) { fp += (RING >> 12) - cur; cur = 0; }
        used += fp;
        bool wait = false;
        while (used > (RING >> 12) || (first && sh == 5 * NFLIGHT)) {
          wait = true;
          tail.next();
          used -= (uint32_t)fifo & 31;
          fifo >>= 5;
          sh -= 5;
        }
        fifo += (uint64_t)fp << sh;
        dst = sbase + (cur << 12);
        bar = full0 + head.off();
        cur += bytes >> 12;
        sh += last ? 5 : 0;
        head.n += last ? 8 : 0;
        prepare();
        asm volatile("" : "+r"(dst), "+r"(bar), "+r"(c0), "+l"(ptr));
        if (wait) mbar_wait(empty0 + tail.off(), tail.ph());
      };
      auto written = [&](uint32_t flag) {
        mbar_wait(flag, 0);
        asm volatile("fence.proxy.async.global;" ::: "memory");
      };
      for (int pc = 0;; pc++) {
        const uint32_t op = prog[pc];
        const int type = op & 3, a = (op >> 2) & 7;
        if (type == OP_END) break;
        if (type == OP_Q) {
          const int qr = q_role(op);
#pragma unroll 1
          for (int k = 0; k < 10; k++) {
            acquire(SZ_WQ, true, false, [&]() { dst += rank * (SZ_WQ / 2); c0 = 64 * k + 32 * rank; ptr = &P.wq[qr >> 5]; });
            if ((pc > 0 || k >= EARLY) && elect()) tma3d_mc(dst, (const CUtensorMap*)ptr, bar, 0, c0, 3 * (4 * a + (qr & 3)));
            acquire(SZ_A, false, true, [&]() { c0 = 64 * k; ptr = &P.x[qr >> 5]; });
            if ((pc > 0 || k >= EARLY) && elect()) {
              tma2d(dst, (const CUtensorMap*)ptr, bar, c0, ((qr >> 2) & 7) * kSq + rank * 128);
              mbar_expect(bar, SZ_WQ + SZ_A);
            }
          }
        } else if (type == OP_A) {
          const uint32_t nop = prog[pc + 1];
          const int row8 = ((team & 7) * kH + nt) * (kSk / 8) + 4 * rank, wave8 = 4 * (kSk / 8);
#pragma unroll 1
          for (int t = (op & F_PARK) ? 1 : 0; t < 33; t++) {
            int wave = a;
            if (t == 31 && (nop & 3) != OP_A) t++;
            if (t == 31) {
              wave = (nop >> 2) & 7;
              written((nop & F_HELP) ? hready0 + 8 * ((nop >> 10) & 3) : fenced);
#pragma unroll 1
              for (int i = 0; i < 2; i++) {
                acquire(SZ_PARK, true, true, [&]() { c0 = 0; ptr = &g_o[((team * 2 + rank) * 96 + 3 * (4 * wave + nt)) * 1024 + i * (SZ_PARK / 16)]; });
                if (elect()) {
                  bulk_load_hint(dst, ptr, SZ_PARK, bar, pol);
                  mbar_expect(bar, SZ_PARK);
                }
              }
            }
            acquire(SZ_KV, true, true, [&]() {
              const int isv = t ? ~t & 1 : 0;
              c0 = row8 + wave * wave8 + 8 * (((t + 1 - 2 * isv) >> 1) & 15);
              ptr = &P.kv[blk + 2 * isv];
              dst += rank * (SZ_KV / 2);
            });
            if (t >= KV_TRANSIT) {
              const Cursor c{head.n - 8 * (KV_TRANSIT + 1)};
              mbar_wait(full0 + c.off(), c.ph());
            }
            if (elect()) {
              tma4d_mc_hint(dst, (const CUtensorMap*)ptr, bar, c0, pol);
              mbar_expect(bar, SZ_KV);
            }
          }
        } else {
          const int b = (op >> 5) & 15, ro = o_role(op);
#pragma unroll 1
          for (int j = 0; j < b - a; j++) {
            const int w = o_wave(a, b, j);
            written(oready);
            oready += 8;
#pragma unroll 1
            for (int k = 12 * w; k < 12 * w + 12; k++) {
              acquire(SZ_A, true, false, [&]() { c0 = 0; ptr = &g_o[(((ro >> 2) * 2 + rank) * 96 + k) * 1024]; });
              if (elect()) bulk_load_hint(dst, ptr, SZ_A, bar, pol);
              acquire(SZ_WO, false, true, [&]() { c0 = 8 * k + 4 * rank; ptr = &P.wo[ro >> 5]; dst += rank * (SZ_WO / 2); });
              if (elect()) {
                tma5d_mc(dst, (const CUtensorMap*)ptr, bar, c0, 5 * (ro & 3));
                mbar_expect(bar, SZ_WO + SZ_A);
              }
            }
          }
          if ((op & F_LD) && (op & F_PARK)) written(hready0 + 8 * (MAX_PARK - 1));
#pragma unroll 1
          for (int i = (op & F_LD) ? 0 : 5; i < ((op & F_ST) ? 5 : 6); i++) {
            acquire(i < 5 ? SZ_PART : SZ_OUT, true, i < 5, [&]() { c0 = 0; ptr = &g_part[(role * 2 + rank) * 5120 + i * (SZ_PART / 16)]; });
            if (i < 5 && elect()) bulk_load_hint(dst, ptr, SZ_PART, bar, pol);
            if (elect()) mbar_expect(bar, i < 5 ? SZ_PART : 0);
          }
        }
      }
#pragma unroll 1
      for (Cursor c{head.n - 8 * NBAR}; c.n != head.n; c.next()) mbar_wait(empty0 + c.off(), c.ph());
    } else if (threadIdx.x == 288) {
      uint32_t ph = 0;
      bool first = true;
      for (int pc = 0;; pc++) {
        const uint32_t op = prog[pc];
        if ((op & 3) == OP_END) break;
        if ((op & 3) != OP_A && !helper) continue;
        mbar_wait_long(odone, ph);
        ph ^= 1;
        unsigned int* flag = !helper ? &g_done[(team * 2 + rank) * 8 + ((op >> 2) & 7)]
                             : (op & 3) == OP_Q ? &g_help[(q_role(op) * 2 + rank) * MAX_PARK + ((op >> 10) & 3)]
                                                : &g_help[(o_role(op) * 2 + rank) * MAX_PARK + MAX_PARK - 1];
        asm volatile("red.release.gpu.global.add.u32 [%0], 1;" ::"l"(flag) : "memory");
        if (first) mbar_arrive(fenced);
        first = false;
      }
    } else if (threadIdx.x == 320) {
      uint32_t oready = oready0;
      for (int pc = 0;; pc++) {
        const uint32_t op = prog[pc];
        if ((op & 3) == OP_END) break;
        if ((op & 3) == OP_O) {
          const int a = (op >> 2) & 7, b = (op >> 5) & 15;
#pragma unroll 1
          for (int i = 0; i < b - a; i++) {
            const int ci = ((o_role(op) >> 2) * 2 + rank) * 8 + o_wave(a, b, i);
            wait_count(&g_done[ci], 4);
            mbar_arrive(oready);
            oready += 8;
            if (atomicAdd(&g_seen[ci], 1u) == 3u) { g_seen[ci] = 0; g_done[ci] = 0; }
          }
        }
        if ((op & 3) != OP_Q && (op & F_HELP) && (op & F_PARK)) {
          unsigned int* flag = &g_help[(role * 2 + rank) * MAX_PARK + ((op >> 10) & 3)];
          wait_count(flag, 1);
          mbar_arrive(hready0 + 8 * ((op >> 10) & 3));
          *flag = 0;
        }
      }
    }
  } else {
    asm volatile("setmaxnreg.inc.sync.aligned.u32 240;");
    const int lane = threadIdx.x & 31, warp = wid & 3;
    uint32_t empty_rem;
    asm volatile("mapa.shared::cluster.u32 %0, %1, %2;" : "=r"(empty_rem) : "r"(empty0), "r"(lane & 1));
    auto release = [&](int slot) { mbar_arrive_cluster_if(lane < 2, empty_rem + slot); };
    Cursor r{0};
    const uint32_t ring16 = (sbase & 0x3FFFF) >> 4;
    uint32_t cur = ring16;
    bool rdy0 = false, rdy1 = false;
    auto probe1 = [&]() { rdy0 = mbar_test(full0 + r.off(), r.ph()); };
    auto probe2 = [&]() {
      Cursor n = r;
      rdy0 = mbar_test(full0 + n.off(), n.ph());
      n.next();
      rdy1 = mbar_test(full0 + n.off(), n.ph());
    };
    auto take = [&](bool rdy, uint32_t bytes, uint32_t& addr) {
      const int bi = r.off();
      if (!__all_sync(0xffffffffu, rdy)) mbar_wait_math(full0 + r.off(), r.ph());
      r.next();
      if (cur > ring16 + ((RING - bytes) >> 4)) cur = ring16;
      addr = cur;
      cur += bytes >> 4;
      return bi;
    };
    auto second = [&](uint32_t bytes) {
      if (cur > ring16 + ((RING - bytes) >> 4)) cur = ring16;
      cur += bytes >> 4;
      return cur - (bytes >> 4);
    };
    const int row = wg * 64 + warp * 16 + (lane >> 2);
    int img0 = row * 4 + ((lane & 3) ^ ((row >> 1) & 3));
    uint4* pend = nullptr;
    const uint64_t spol = evict_first();
    int pc = 0;
    uint32_t op = prog[0];
    auto enter = [&]() {
      r.n = op >> 12; cur = ring16 + (((op >> 20) & 63) << 8);
    };
    auto drain = [&](uint32_t (&t)[48], uint32_t c) {
      if (!(op & (3u << 26)) || c >= 6) return;
#pragma unroll
      for (int i = 0; i < 6; i++)
        stg2_if(c == i, pend + i * 512, t[8 * i], t[8 * i + 1], t[8 * i + 2], t[8 * i + 3],
                t[8 * i + 4], t[8 * i + 5], t[8 * i + 6], t[8 * i + 7], spol);
      if ((op & (1u << 26)) && c == 5) {
        __syncwarp();
        mbar_arrive_if(lane < 2, odone);
      }
    };
    float s[32], o[96], c[80];
    uint32_t q[48], pa[16], pb[16];
    float mc0, mc1, l0, l1;
    bool gen;
    auto soft = [&](float (&s)[32], uint32_t (&pout)[16], bool first) {
      if (first) { gen = false; mc0 = 0.f; mc1 = 0.f; }
      float b0, b1;
      for (;;) {
        if (gen) {
          float m0 = fmaxf(s[0], s[1]), m1 = fmaxf(s[2], s[3]);
#pragma unroll
          for (int i = 1; i < 8; i++) { m0 = fmaxf(m0, fmaxf(s[4 * i], s[4 * i + 1])); m1 = fmaxf(m1, fmaxf(s[4 * i + 2], s[4 * i + 3])); }
          m0 = fmaxf(m0, __shfl_xor_sync(0xffffffffu, m0, 1)); m1 = fmaxf(m1, __shfl_xor_sync(0xffffffffu, m1, 1));
          m0 = fmaxf(m0, __shfl_xor_sync(0xffffffffu, m0, 2)); m1 = fmaxf(m1, __shfl_xor_sync(0xffffffffu, m1, 2));
          if (first) {
            mc0 = m0; mc1 = m1;
          } else if (__any_sync(0xffffffffu, !(m0 <= mc0 + kMaxLag && m1 <= mc1 + kMaxLag))) {
            m0 = fmaxf(mc0, m0); m1 = fmaxf(mc1, m1);
            const float a0 = ex2(mc0 - m0), a1 = ex2(mc1 - m1);
            mc0 = m0; mc1 = m1;
            l0 *= a0; l1 *= a1;
            wg_wait<0>();
            fence_regs(o);
#pragma unroll
            for (int i = 0; i < 96; i++) o[i] *= i & 2 ? a1 : a0;
          }
#pragma unroll
          for (int i = 0; i < 32; i++) s[i] -= i & 2 ? mc1 : mc0;
        }
#pragma unroll
        for (int i = 0; i < 8; i++) {
          const float e1 = ex2(s[4 * i + 1]), e0 = ex2(s[4 * i]), e3 = ex2(s[4 * i + 3]), e2 = ex2(s[4 * i + 2]);
          pout[2 * i] = pack_bf16(e0, e1);
          b0 = i ? b0 + fadd(e1, e0) : fadd(e1, e0);
          pout[2 * i + 1] = pack_bf16(e2, e3);
          b1 = i ? b1 + fadd(e3, e2) : fadd(e3, e2);
        }
        if (!__any_sync(0xffffffffu, !gen && !(fmaxf(b0, b1) <= kSumLimit && (!first || fminf(b0, b1) >= 1.0f / kSumLimit)))) break;
        gen = __any_sync(0xffffffffu, true);
      }
      l0 = first ? b0 : l0 + b0;
      l1 = first ? b1 : l1 + b1;
    };
    auto qk = [&](float (&s)[32], uint32_t ak, int k0, int k1) {
#pragma unroll
      for (int kk = k0; kk < k1; kk++)
        wgmma_rs_n64<0>(s, q[4 * kk], q[4 * kk + 1], q[4 * kk + 2], q[4 * kk + 3], mk_desc(ak, 16, KV_SBO, 1, (kk >> 2) * KV_CH + (kk & 3) * 2), kk != 0);
      wg_commit();
    };
    auto pv = [&](uint32_t (&pin)[16], uint32_t av, int acc) {
#pragma unroll
      for (int kk = 0; kk < 4; kk++)
        wgmma_rs_n192<1>(o, pin[4 * kk], pin[4 * kk + 1], pin[4 * kk + 2], pin[4 * kk + 3], mk_desc(av, KV_CH * 16, KV_SBO, 1, kk * (KV_SBO / 8)), acc || (kk != 0));
      wg_commit();
    };
    auto xw = [&](uint32_t ad, int acc) {
      const uint32_t da = second(SZ_A) + wg * 512;
      wg_fence();
#pragma unroll
      for (int kk = 0; kk < 4; kk++)
        wgmma_ss_n192<1>(o, mk_desc(da, 16, 1024, 1, kk * 2), mk_desc(ad, 4096, 1024, 1, (kk & 1) * 128 + (kk >> 1) * 768), acc || kk != 0);
      wg_commit();
    };
    auto ow = [&](int acc, int prev) {
      uint32_t da;
      const int bi = take(rdy0, SZ_A, da);
      const uint32_t db = second(SZ_WO);
      da += wg * 256;
      wg_fence();
      wgmma_ss_n160<1>(c, mk_desc(da, 16, 512, 2), mk_desc(db, 2048, 512, 2), acc);
      wgmma_ss_n160<1>(c, mk_desc(da, 16, 512, 2, 2), mk_desc(db, 2048, 512, 2, 64), 1);
      wg_commit();
      if (acc == 1) { wg_wait<1>(); release(prev); }
      wgmma_ss_n160<1>(c, mk_desc(da, 16, 512, 2, 512), mk_desc(db, 2048, 512, 2, 640), 1);
      wgmma_ss_n160<1>(c, mk_desc(da, 16, 512, 2, 514), mk_desc(db, 2048, 512, 2, 704), 1);
      wg_commit();
      return bi;
    };
    auto st_part = [&](int i) {
      stg2_if(true, pend + i * 512, __float_as_uint(c[8 * i]), __float_as_uint(c[8 * i + 1]), __float_as_uint(c[8 * i + 2]), __float_as_uint(c[8 * i + 3]),
              __float_as_uint(c[8 * i + 4]), __float_as_uint(c[8 * i + 5]), __float_as_uint(c[8 * i + 6]), __float_as_uint(c[8 * i + 7]), spol);
    };
#pragma unroll
    for (int i = 0; i < 48; i++) q[i] = 0;
    enter();

    if ((op & 3) == OP_Q) {
      uint32_t ad;
      int bi0 = take(false, SZ_WQ, ad), k = 0, lag = 0;
      xw(ad, 0);
      for (;;) {
#pragma unroll 1
        for (;;) {
          drain(q, k - lag);
          probe1();
          wg_wait<0>();
          release(bi0);
          bi0 = take(rdy0, SZ_WQ, ad);
          if (++k == 8) break;
          xw(ad, 1);
        }
        if (wg) bar_sync(2, 256);
        xw(ad, 1);
        const int bi9 = take(false, SZ_WQ, ad);
        xw(ad, 1);
        if (!wg) asm volatile("bar.arrive 2, 256;" ::: "memory");
        k = 0; lag = 0;
        uint32_t nop = prog[++pc];
        wg_wait<1>();
        release(bi0);
        probe2();
        wg_wait<0>();
        fence_regs(o);
        release(bi9);
#pragma unroll
        for (int i = 0; i < 48; i++) q[i] = pack_bf16(o[2 * i] * kScaleLog2, o[2 * i + 1] * kScaleLog2);
        fence_regs(q);
        if (op & F_PARK) {
          const int qt = helper ? (op >> 5) & 15 : team, qm = helper ? (op >> 12) & 3 : nt;
          pend = &g_o[((qt * 2 + rank) * 96 + 3 * (4 * ((op >> 2) & 7) + qm)) * 1024 + img0];
          op = nop;
          enter();
          if ((op & 3) != OP_Q) break;
          const int b = take(rdy0, SZ_WQ, ad);
          xw(ad, 0);
          bi0 = take(rdy1, SZ_WQ, ad);
          xw(ad, 1);
          wg_wait<1>();
          release(b);
          k = 1; lag = 1;
          continue;
        }
        int wave = (op >> 2) & 7, sk1;
        uint32_t ak1;
        {
          float s0[32];
          const int sk0 = take(rdy0, SZ_KV, ad);
          wg_fence();
          qk(s0, ad, 0, 12);
          sk1 = take(rdy1, SZ_KV, ak1);
          wg_fence();
          qk(s, ak1, 0, S1A);
          probe1();
          wg_wait<1>();
          fence_regs(s0);
          release(sk0);
          soft(s0, pa, true);
        }
        float i0, i1;
        auto sums = [&]() {
          l0 += __shfl_xor_sync(0xffffffffu, l0, 1); l1 += __shfl_xor_sync(0xffffffffu, l1, 1);
          l0 += __shfl_xor_sync(0xffffffffu, l0, 2); l1 += __shfl_xor_sync(0xffffffffu, l1, 2);
          i0 = rcp(l0); i1 = rcp(l1);
          asm volatile("" : "+f"(i0), "+f"(i1));
        };
        auto target = [&]() {
          pend = &g_o[((team * 2 + rank) * 96 + 3 * (4 * wave + nt)) * 1024 + img0];
          asm volatile("" : "+l"(pend));
        };
        bool late = false;
#pragma unroll
        for (int i = 0; i < 16; i++) pb[i] = 0;
        for (;;) {
          nop = prog[++pc];
          {
            uint32_t av;
            const int sv = take(rdy0, SZ_KV, av);
            wg_fence();
            qk(s, ak1, S1A, 12);
            pv(pa, av, 0);
            if (late) {
              stg2_if(true, pend + 4 * 512, pb[0], pb[1], pb[2], pb[3], pb[4], pb[5], pb[6], pb[7], spol);
              stg2_if(true, pend + 5 * 512, pb[8], pb[9], pb[10], pb[11], pb[12], pb[13], pb[14], pb[15], spol);
              __syncwarp();
              mbar_arrive_if(lane < 2, odone);
            }
            probe2();
            wg_wait<1>();
            fence_regs(s);
            release(sk1);
            soft(s, pb, false);
            wg_wait<0>();
            fence_regs(o);
            release(sv);
          }
          auto step = [&](uint32_t (&pin)[16], uint32_t (&pout)[16]) {
            uint32_t ak, av;
            const int sk = take(rdy0, SZ_KV, ak), sv = take(rdy1, SZ_KV, av);
            wg_fence();
            qk(s, ak, 0, 12);
            pv(pin, av, 1);
            probe2();
            wg_wait<1>();
            fence_regs(s);
            release(sk);
            soft(s, pout, false);
            wg_wait<0>();
            fence_regs(o);
            release(sv);
          };
#pragma unroll 1
          for (int jj = 0; jj < 7; jj++) {
            step(pb, pa);
            step(pa, pb);
          }
          if ((nop & 3) != OP_A) break;
          uint32_t ak, av;
          {
            const int b0 = take(rdy0, SZ_PARK, ak), b1 = take(rdy1, SZ_PARK, av);
            const uint32_t ad0 = ak, ad1 = av;
            probe2();
#pragma unroll
            for (int i = 0; i < 12; i++)
              lds128(sbase + ((i < 6 ? ad0 : ad1) - ring16 + img0) * 16 + ((i % 6) >> 1) * 8192 + (i & 1) * 512, q[4 * i], q[4 * i + 1], q[4 * i + 2], q[4 * i + 3]);
            release(b0); release(b1);
          }
          const int sk0 = take(rdy0, SZ_KV, ak), sv = take(rdy1, SZ_KV, av);
          wg_fence();
          qk(s, ak, 0, 8);
          sched_fence(img0, P.zero);
          sums();
          sched_fence(img0, P.zero);
          qk(s, ak, 8, 12);
          pv(pb, av, 1);
          probe2();
          wg_wait<1>();
          fence_regs(s);
          release(sk0);
          soft(s, pa, true);
          sk1 = take(rdy0, SZ_KV, ak1);
          rdy0 = rdy1;
          wg_wait<0>();
          target();
          fence_regs(o);
          release(sv);
          uint32_t t[48];
#pragma unroll
          for (int j = 0; j < 6; j++) {
#pragma unroll
            for (int i = 0; i < 4; i++) {
              t[8 * j + i] = pack_bf16(o[16 * j + 4 * i] * i0, o[16 * j + 4 * i + 1] * i0);
              t[8 * j + i + 4] = pack_bf16(o[16 * j + 4 * i + 2] * i1, o[16 * j + 4 * i + 3] * i1);
            }
            if (j < 4)
            stg2_if(true, pend + j * 512, t[8 * j], t[8 * j + 1], t[8 * j + 2], t[8 * j + 3], t[8 * j + 4], t[8 * j + 5], t[8 * j + 6], t[8 * j + 7], spol);
            if (j == 3) { wg_fence(); qk(s, ak1, 0, 4); }
            if (j == 5) { wg_fence(); qk(s, ak1, 4, S1A); }
            sched_fence(img0, P.zero);
          }
          if (P.zero) {
#pragma unroll
            for (int j = 0; j < 4; j++)
              stg2_if(true, pend, t[8 * j], t[8 * j + 1], t[8 * j + 2], t[8 * j + 3], t[8 * j + 4], t[8 * j + 5], t[8 * j + 6], t[8 * j + 7], spol);
          }
          late = true;
#pragma unroll
          for (int i = 0; i < 16; i++) pb[i] = t[32 + i];
          wave = (nop >> 2) & 7;
        }
        const int sv = take(rdy0, SZ_KV, ad);
        wg_fence();
        pv(pb, ad, 1);
        sums();
        target();
        op = nop;
        enter();
        rdy0 = rdy1;
        auto convert = [&](float (&u)[96], int j0, int j1) {
#pragma unroll
          for (int i = 4 * j0; i < 4 * j1; i++) {
            q[8 * (i >> 2) + (i & 3)] = pack_bf16(u[4 * i], u[4 * i + 1]);
            q[8 * (i >> 2) + (i & 3) + 4] = pack_bf16(u[4 * i + 2], u[4 * i + 3]);
          }
        };
        if ((op & 3) != OP_O) {
          if ((op & 3) == OP_Q) bi0 = take(rdy0, SZ_WQ, ad);
          wg_wait<0>();
          fence_regs(o);
          release(sv);
          float u[96];
#pragma unroll
          for (int i = 0; i < 96; i++) u[i] = o[i] * (i & 2 ? i1 : i0);
          if ((op & 3) != OP_Q) { convert(u, 0, 6); break; }
          fence_regs(u);
          xw(ad, 0);
          sched_fence(img0, P.zero);
          fence_regs(u);
          convert(u, 0, 1);
          stg2_if(true, pend, q[0], q[1], q[2], q[3], q[4], q[5], q[6], q[7], spol);
          probe1();
          wg_wait<0>();
          release(bi0);
          bi0 = take(rdy0, SZ_WQ, ad);
          xw(ad, 1);
          sched_fence(img0, P.zero);
          fence_regs(u);
          convert(u, 1, 6);
          k = 1;
          continue;
        }
        int bi = ow(0, 0);
        wg_wait<2>();
        fence_regs(o);
        release(sv);
#pragma unroll
        for (int j = 0; j < 6; j++) {
          uint32_t t[8];
#pragma unroll
          for (int i = 0; i < 4; i++) {
            t[i] = pack_bf16(o[16 * j + 4 * i] * i0, o[16 * j + 4 * i + 1] * i0);
            t[i + 4] = pack_bf16(o[16 * j + 4 * i + 2] * i1, o[16 * j + 4 * i + 3] * i1);
          }
          stg2_if(true, pend + j * 512, t[0], t[1], t[2], t[3], t[4], t[5], t[6], t[7], spol);
          if (j == 5) {
            __syncwarp();
            mbar_arrive_if(lane < 2, odone);
          }
          probe1();
          wg_wait<1>();
          bi = ow(1, bi);
          fence_regs(o);
        }
        {
          const int nk = 12 * (((op >> 5) & 15) - ((op >> 2) & 7)) - ((op & F_ST) ? 0 : 2);
#pragma unroll 1
          for (int k = 7; k < nk; k++) {
            probe1();
            wg_wait<1>();
            bi = ow(1, bi);
          }
        }
        if (!(op & F_ST)) {
          probe2();
          wg_wait<1>();
          if (wg) {
            wg_wait<0>();
            release(bi);
            bar_sync(2, 256);
          }
          bi0 = ow(2, 0);
          rdy0 = rdy1;
          const int b = ow(2, 0);
          if (!wg) asm volatile("bar.arrive 2, 256;" ::: "memory");
          wg_wait<4>();
          mbar_arrive_cluster_if(lane < 2 && !wg, empty_rem + bi);
          bi = b;
        }
        probe1();
        nop = prog[++pc];
        if (op & F_LD) {
          uint32_t t[80];
#pragma unroll
          for (int j = 0; j < 5; j++) {
            const int b = take(rdy0, SZ_PART, ad);
            probe1();
#pragma unroll
            for (int i = 4 * j; i < 4 * j + 4; i++)
              lds128(sbase + (ad - ring16 + img0) * 16 + ((i >> 1) & 1) * 8192 + (i & 1) * 512, t[4 * i], t[4 * i + 1], t[4 * i + 2], t[4 * i + 3]);
            release(b);
          }
          wg_wait<0>();
          fence_regs(c);
#pragma unroll
          for (int i = 0; i < 80; i++) c[i] += __uint_as_float(t[i]);
        }
        if (!(op & F_ST)) {
          wg_wait<0>();
          fence_regs(c);
          release(bi0);
          release(bi);
          goto finish;
        }
        op = nop;
        enter();
        bi0 = take(rdy0, SZ_WQ, ad);
        xw(ad, 0);
        pend = &g_part[((team * 4 + nt) * 2 + rank) * 5120 + img0];
        probe1();
        wg_wait<1>();
        fence_regs(c);
        release(bi);
        st_part(0); st_part(1);
        wg_wait<0>();
        release(bi0);
        bi0 = take(rdy0, SZ_WQ, ad);
        xw(ad, 1);
        st_part(2); st_part(3);
#pragma unroll
        for (int i = 0; i < 48; i++) q[i] = __float_as_uint(c[32 + i]);
        pend += 4 * 512;
        k = 1; lag = 2;
      }
    }
    rdy0 = false;
    {
      uint32_t t[48];
#pragma unroll
      for (int i = 0; i < 48; i++) t[i] = q[i] ^ P.zero;
      while ((op & 3) == OP_O) {
        int bi = ow(0, 0);
#pragma unroll 1
        for (int k = 1; k < 12 * (int)(((op >> 5) & 15) - ((op >> 2) & 7)); k++) {
          drain(t, k - 1);
          probe1();
          wg_wait<1>();
          bi = ow(1, bi);
        }
        rdy0 = false;
        wg_wait<0>();
        fence_regs(c);
        pc++;
        release(bi);
        if (!(op & F_ST)) goto finish;
        pend = &g_part[((((op >> 26) & 56) | ((op >> 9) & 7)) * 2 + rank) * 5120 + img0];
#pragma unroll
        for (int i = 6; i < 10; i++) st_part(i);
#pragma unroll
        for (int i = 0; i < 48; i++) t[i] = __float_as_uint(c[i]) ^ P.zero;
        op = prog[pc];
        enter();
      }
      for (int i = 0; i < 6; i++) drain(t, i);
    }
    if (false) {
    finish:
      uint32_t ad;
      take(rdy0, SZ_OUT, ad);
      const uint32_t wstage = sbase + (ad - ring16) * 16 + (wg * 4 + warp) * 5120;
      const uint32_t sa = wstage + (lane & 15) * 64;
#pragma unroll
      for (int i = 0; i < 10; i++) {
        const int u = (i & 1) * 2 + (lane >> 4);
        stsm4(sa + (i >> 1) * 1024 + ((u ^ ((lane >> 1) & 3)) << 4), pack_bf16(c[8 * i], c[8 * i + 1]), pack_bf16(c[8 * i + 2], c[8 * i + 3]),
              pack_bf16(c[8 * i + 4], c[8 * i + 5]), pack_bf16(c[8 * i + 6], c[8 * i + 7]));
      }
      asm volatile("fence.proxy.async.shared::cta;" ::: "memory");
      __syncwarp();
      if (lane == 0) {
        tma3d_store(&P.out, wstage, 0, (team & 7) * kSq + rank * 128 + wg * 64 + warp * 16, blk * 20 + nt * 5);
        asm volatile("cp.async.bulk.commit_group;\ncp.async.bulk.wait_group.read 0;" ::: "memory");
      }
    }
  }
}

typedef CUresult (*EncodeFn)(CUtensorMap*, CUtensorMapDataType, cuuint32_t, void*, const cuuint64_t*, const cuuint64_t*,
                             const cuuint32_t*, const cuuint32_t*, CUtensorMapInterleave, CUtensorMapSwizzle,
                             CUtensorMapL2promotion, CUtensorMapFloatOOBfill);

void encode(EncodeFn fn, CUtensorMap* m, const void* ptr, int rank, const cuuint64_t* dims, const cuuint64_t* strides,
            const cuuint32_t* box, CUtensorMapSwizzle swz) {
  const cuuint32_t es[5] = {1, 1, 1, 1, 1};
  CUresult r = fn(m, CU_TENSOR_MAP_DATA_TYPE_BFLOAT16, rank, const_cast<void*>(ptr), dims, strides, box, es,
                  CU_TENSOR_MAP_INTERLEAVE_NONE, swz, CU_TENSOR_MAP_L2_PROMOTION_L2_128B, CU_TENSOR_MAP_FLOAT_OOB_FILL_NONE);
  if (r != CUDA_SUCCESS) fprintf(stderr, "cuTensorMapEncodeTiled failed: %d\n", (int)r);
}

void annotate(uint32_t* ops, int n, bool helper) {
  uint32_t items = 0, cur = 0, pend = 0;
  auto item = [&](uint32_t bytes, int count, uint32_t bytes2 = 0) {
    for (int i = 0; i < count; i++) {
      if (cur + bytes > RING) cur = 0;
      cur += bytes;
      if (cur + bytes2 > RING) cur = 0;
      cur += bytes2;
      items++;
    }
  };
  for (int i = 0; i <= n; i++) {
    const uint32_t op = ops[i];
    ops[i] |= (items % (2 * NBAR)) << 15 | (cur >> 12) << 20 | pend << 26;
    if ((op & 3) == OP_Q) { item(SZ_WQ, 10, SZ_A); pend = (op & F_PARK) ? (helper ? 1 : 2) : 0; }
    if ((op & 3) == OP_A) {
      item(SZ_KV, (op & F_PARK) ? 30 : 31);
      if ((ops[i + 1] & 3) == OP_A) { item(SZ_PARK, 2); item(SZ_KV, 1); }
      item(SZ_KV, 1);
      pend = 1;
    }
    if ((op & 3) == OP_O) {
      item(SZ_A, 12 * (((op >> 5) & 15) - ((op >> 2) & 7)), SZ_WO);
      if (op & F_LD) item(SZ_PART, 5);
      pend = (op & F_ST) ? (helper ? 1 : 2) : 0;
    }
  }
}

void compile_programs(const char* const* text, bool helpers, Params& P) {
  struct Req { int when, team, wave, slot; } req[N_TEAM * MAX_PARK];
  int n_req = 0;
  for (int t = 0; t < N_TEAM; t++) {
    uint32_t* ops = P.ops[t];
    int n = 0, flags[8] = {0, 0, 0, 0, 0, 0, 0, 0}, n_park = 0, last_o = -1, when = 0, given = 0;
    for (const char* s = text[t]; *s; s++) {
      const int a = s[1] - '0';
      if (*s == 'Q' || (*s == 'H' && !helpers)) { ops[n++] = OP_Q | a << 2; when += 10; }
      else if (*s == 'P') { flags[a] = F_PARK; ops[n++] = OP_Q | a << 2 | flags[a]; when += 10; }
      else if (*s == 'H') { req[n_req++] = {when, t, a, n_park}; flags[a] = F_PARK | F_HELP | n_park++ << 10; }
      else if (*s == 'A') { ops[n++] = OP_A | a << 2 | flags[a]; when += 32; }
      else if (*s == 'G') { given = a; if (helpers) req[n_req++] = {1000, t, 0, -a}; }
      else if (*s == 'O') {
        ops[n] = OP_O | a << 2 | (s[2] - '0') << 5;
        if (given) ops[n] = helpers ? ops[n] | F_LD | F_PARK | (MAX_PARK - 1) << 10 : ops[n] & ~(7u << 2);
        if (last_o >= 0) { ops[last_o] |= F_ST; ops[n] |= F_LD; }
        last_o = n++;
        when += 10 * (s[2] - s[1]);
      }
    }
    for (int i = n; i < MAX_OPS; i++) ops[i] = OP_END;
    annotate(ops, n, false);
  }
  for (int i = 1; i < n_req; i++)
    for (int j = i; j > 0 && req[j].when < req[j - 1].when; j--) { Req r = req[j]; req[j] = req[j - 1]; req[j - 1] = r; }
  for (int h = 0; h < N_HELP; h++) {
    uint32_t* ops = P.ops[N_TEAM + 2 * h];
    int n = 0;
    for (int i = 0; i < n_req; i++)
      for (int m = h; m < 4; m += N_HELP) {
        const uint32_t ro = 4 * req[i].team + m;
        ops[n++] = req[i].slot >= 0 ? OP_Q | req[i].wave << 2 | req[i].team << 5 | F_PARK | req[i].slot << 10 | m << 12
                                    : OP_O | -req[i].slot << 5 | F_ST | (ro & 7) << 9 | (ro >> 3) << 29;
      }
    for (int i = n; i < 2 * MAX_OPS; i++) ops[i] = OP_END;
    annotate(ops, n, true);
  }
  for (int i = 0; i < 32; i++) P.first[i] = i < N_TEAM ? P.ops[i][0] : i < N_TEAM + N_HELP ? P.ops[2 * i - N_TEAM][0] : 0;
}

const char* const kPrograms[N_TEAM] = {
  "Q0A0Q1A1H2A2O03Q3A3Q4A4Q5A5Q6A6Q7A7O38",
  "Q0A0Q1A1Q2A2Q3A3O04Q4A4Q5A5Q6A6H7A7O48",
  "Q0A0H1A1Q2A2Q3A3Q4A4O05Q5A5Q6A6Q7A7O58",
  "Q0A0Q1A1Q2A2O03Q3A3Q4A4Q5A5Q6A6H7A7O38",
  "Q0A0Q1A1Q2A2O03Q3A3H4A4Q5A5Q6A6Q7A7O38",
  "Q0A0Q1A1H2A2Q3A3Q4A4O05Q5A5Q6A6Q7A7O58",
  "Q0A0Q1A1Q2A2Q3A3O03Q4A4H5A5Q6A6Q7A7O38",
  "Q0A0Q1A1Q2A2Q3A3Q4A4O05Q5A5Q6A6H7A7O58",
  "P3Q0A0Q1A1Q2A2A3H4A4Q5A5Q6A6Q7A7O08",
  "P5P7Q0A0Q1A1Q2A2H3A3Q4A4A5Q6A6A7G1O18",
  "Q0A0Q1A1Q2A2O02Q3A3H4A4Q5A5Q6A6Q7A7O28",
  "P3P5Q0A0Q1A1Q2A2A3Q4A4A5Q6A6H7A7O08",
  "Q0A0Q1A1Q2A2O02Q3A3Q4A4H5A5Q6A6Q7A7O28",
  "P7Q0A0Q1A1Q2A2Q3A3Q4A4Q5A5Q6A6A7G1O18",
  "P5Q0A0Q1A1Q2A2Q3A3Q4A4A5Q6A6H7A7O08",
  "Q0A0Q1A1Q2A2H3A3Q4A4Q5A5Q6A6Q7A7O08",
};

const char* const* bench_programs() {
  return kPrograms;
}

}

extern "C" void kernel_launch(void* const* d_in, const int* in_sizes, int n_in, void* d_out, int out_size) {
  (void)in_sizes; (void)n_in; (void)out_size;
  static EncodeFn fn = nullptr;
  static int n_clusters = 0;
  if (!fn) {
    cudaDriverEntryPointQueryResult qr;
    void* f = nullptr;
    cudaGetDriverEntryPoint("cuTensorMapEncodeTiled", &f, cudaEnableDefault, &qr);
    fn = (EncodeFn)f;
    cudaFuncSetAttribute(fused_kernel, cudaFuncAttributeMaxDynamicSharedMemorySize, SMEM_BYTES);
    cudaLaunchConfig_t cfg = {};
    cfg.gridDim = dim3(132); cfg.blockDim = dim3(384); cfg.dynamicSmemBytes = SMEM_BYTES;
    cudaLaunchAttribute at[1];
    at[0].id = cudaLaunchAttributeClusterDimension; at[0].val.clusterDim.x = 2; at[0].val.clusterDim.y = 1; at[0].val.clusterDim.z = 1;
    cfg.attrs = at; cfg.numAttrs = 1;
    if (cudaOccupancyMaxActiveClusters(&n_clusters, fused_kernel, &cfg) != cudaSuccess || n_clusters < 1) n_clusters = 1;
    (void)cudaGetLastError();
  }
  Params P;
  const CUtensorMapSwizzle S128 = CU_TENSOR_MAP_SWIZZLE_128B, S64 = CU_TENSOR_MAP_SWIZZLE_64B;
  for (int blk = 0; blk < 2; blk++) {
    void* const* in = d_in + 5 * blk;
    { const cuuint64_t d[] = {kD, kB * kSq}, s[] = {kD * 2}; const cuuint32_t b[] = {64, 128};
      encode(fn, &P.x[blk], in[0], 2, d, s, b, S128); }
    { const cuuint64_t d[] = {64, 8, 3, (cuuint64_t)kB * kH * kSk / 8}, s[] = {kDh * 2, 128, 8 * kDh * 2}; const cuuint32_t b[] = {64, 8, 3, 4};
      encode(fn, &P.kv[blk], in[1], 4, d, s, b, S128);
      encode(fn, &P.kv[blk + 2], in[2], 4, d, s, b, S128); }
    { const cuuint64_t d[] = {64, kD, kHD / 64}, s[] = {kHD * 2, 128}; const cuuint32_t b[] = {64, 32, 3};
      encode(fn, &P.wq[blk], in[3], 3, d, s, b, S128); }
    { const cuuint64_t d[] = {32, 2, kHD / 8, 4, kD / 32}, s[] = {kD * 2, 8 * kD * 2, 2 * kD * 2, 64}; const cuuint32_t b[] = {32, 2, 4, 4, 5};
      encode(fn, &P.wo[blk], in[4], 5, d, s, b, S64); }
  }
  { const cuuint64_t d[] = {32, kB * kSq, 2 * kD / 32}, s[] = {2 * kD * 2, 64}; const cuuint32_t b[] = {32, 16, 5};
    encode(fn, &P.out, d_out, 3, d, s, b, S64); }

  P.zero = 0;
  if (n_clusters >= N_CL) {
    const bool helpers = n_clusters >= N_CL + N_HELP;
    compile_programs(bench_programs(), helpers, P);
    fused_kernel<<<2 * (N_CL + (helpers ? N_HELP : 0)), 384, SMEM_BYTES>>>(P);
  } else {
    for (int phase = 0; phase < 2; phase++) {
      const char* text[N_TEAM];
      for (int t = 0; t < N_TEAM; t++) text[t] = phase ? "O08" : "Q0A0Q1A1Q2A2Q3A3Q4A4Q5A5Q6A6Q7A7";
      compile_programs(text, false, P);
      fused_kernel<<<2 * N_CL, 384, SMEM_BYTES>>>(P);
    }
  }
}
```

```cpp
#include <cuda_runtime.h>
#include <cuda_bf16.h>
#include <cuda.h>
#include <stdint.h>
#include <stdio.h>

namespace {

constexpr int kB = 8, kSq = 256, kD = 640, kH = 32, kSk = 1024, kDh = 192;
constexpr int kHD = kH * kDh;
constexpr uint32_t RING = 224 * 1024;
constexpr uint32_t SZ_KV = 24576;
constexpr uint32_t SZ_WQ = 24576, SZ_WO = 20480, SZ_A = 16384;
constexpr uint32_t SZ_OUT = 40960;
constexpr uint32_t SZ_PARK = 24576;
constexpr uint32_t SZ_PART = 16384;
constexpr int NBAR = 16;
constexpr int KV_TRANSIT = 4;
constexpr int EARLY = 3;
constexpr int S1A = 7;
constexpr uint32_t KV_CH = 64, KV_SBO = 3072;
constexpr int SMEM_BYTES = RING + 512 + 1024;
constexpr int N_TEAM = 16, N_CL = 64, N_HELP = 2, MAX_OPS = 24, MAX_PARK = 4;
enum { OP_END = 0, OP_Q = 1, OP_A = 2, OP_O = 3, F_PARK = 1 << 9, F_LD = 1 << 12, F_ST = 1 << 13, F_HELP = 1 << 12 };

struct alignas(64) Params {
  uint32_t first[32];
  CUtensorMap x[2], wq[2], kv[4], wo[2], out;
  uint32_t ops[N_TEAM + 2 * N_HELP][MAX_OPS];
  uint32_t zero;
};

__device__ uint4 g_o[N_TEAM * 2 * 96 * 1024];
__device__ uint4 g_part[N_CL * 2 * 5 * 1024];
__device__ unsigned int g_done[N_TEAM * 2 * 8];
__device__ unsigned int g_help[N_CL * 2 * MAX_PARK];
__device__ unsigned int g_seen[N_TEAM * 2 * 8];

template <int TB>
__device__ __forceinline__ void wgmma_rs_n64(float (&d)[32], uint32_t a0, uint32_t a1, uint32_t a2, uint32_t a3, uint64_t db, int scale_d) {
  asm volatile("{\n.reg .pred p;\nsetp.ne.b32 p, %37, 0;\n"
    "wgmma.mma_async.sync.aligned.m64n64k16.f32.bf16.bf16 {%0, %1, %2, %3, %4, %5, %6, %7, %8, %9, %10, %11, %12, %13, %14, %15, %16, %17, %18, %19, %20, %21, %22, %23, %24, %25, %26, %27, %28, %29, %30, %31}, {%32, %33, %34, %35}, %36, p, 1, 1, %38;\n}\n"
    : "+f"(d[0]), "+f"(d[1]), "+f"(d[2]), "+f"(d[3]), "+f"(d[4]), "+f"(d[5]), "+f"(d[6]), "+f"(d[7]), "+f"(d[8]), "+f"(d[9]), "+f"(d[10]), "+f"(d[11]), "+f"(d[12]), "+f"(d[13]), "+f"(d[14]), "+f"(d[15]), "+f"(d[16]), "+f"(d[17]), "+f"(d[18]), "+f"(d[19]), "+f"(d[20]), "+f"(d[21]), "+f"(d[22]), "+f"(d[23]), "+f"(d[24]), "+f"(d[25]), "+f"(d[26]), "+f"(d[27]), "+f"(d[28]), "+f"(d[29]), "+f"(d[30]), "+f"(d[31])
    : "r"(a0), "r"(a1), "r"(a2), "r"(a3), "l"(db), "r"(scale_d), "n"(TB));
}
template <int TB, int TA = 0>
__device__ __forceinline__ void wgmma_ss_n160(float (&d)[80], uint64_t da, uint64_t db, int scale_d) {
  asm volatile("{\n.reg .pred p;\nsetp.ne.b32 p, %82, 0;\n"
    "wgmma.mma_async.sync.aligned.m64n160k16.f32.bf16.bf16 {%0, %1, %2, %3, %4, %5, %6, %7, %8, %9, %10, %11, %12, %13, %14, %15, %16, %17, %18, %19, %20, %21, %22, %23, %24, %25, %26, %27, %28, %29, %30, %31, %32, %33, %34, %35, %36, %37, %38, %39, %40, %41, %42, %43, %44, %45, %46, %47, %48, %49, %50, %51, %52, %53, %54, %55, %56, %57, %58, %59, %60, %61, %62, %63, %64, %65, %66, %67, %68, %69, %70, %71, %72, %73, %74, %75, %76, %77, %78, %79}, %80, %81, p, 1, 1, %83, %84;\n}\n"
    : "+f"(d[0]), "+f"(d[1]), "+f"(d[2]), "+f"(d[3]), "+f"(d[4]), "+f"(d[5]), "+f"(d[6]), "+f"(d[7]), "+f"(d[8]), "+f"(d[9]), "+f"(d[10]), "+f"(d[11]), "+f"(d[12]), "+f"(d[13]), "+f"(d[14]), "+f"(d[15]), "+f"(d[16]), "+f"(d[17]), "+f"(d[18]), "+f"(d[19]), "+f"(d[20]), "+f"(d[21]), "+f"(d[22]), "+f"(d[23]), "+f"(d[24]), "+f"(d[25]), "+f"(d[26]), "+f"(d[27]), "+f"(d[28]), "+f"(d[29]), "+f"(d[30]), "+f"(d[31]), "+f"(d[32]), "+f"(d[33]), "+f"(d[34]), "+f"(d[35]), "+f"(d[36]), "+f"(d[37]), "+f"(d[38]), "+f"(d[39]), "+f"(d[40]), "+f"(d[41]), "+f"(d[42]), "+f"(d[43]), "+f"(d[44]), "+f"(d[45]), "+f"(d[46]), "+f"(d[47]), "+f"(d[48]), "+f"(d[49]), "+f"(d[50]), "+f"(d[51]), "+f"(d[52]), "+f"(d[53]), "+f"(d[54]), "+f"(d[55]), "+f"(d[56]), "+f"(d[57]), "+f"(d[58]), "+f"(d[59]), "+f"(d[60]), "+f"(d[61]), "+f"(d[62]), "+f"(d[63]), "+f"(d[64]), "+f"(d[65]), "+f"(d[66]), "+f"(d[67]), "+f"(d[68]), "+f"(d[69]), "+f"(d[70]), "+f"(d[71]), "+f"(d[72]), "+f"(d[73]), "+f"(d[74]), "+f"(d[75]), "+f"(d[76]), "+f"(d[77]), "+f"(d[78]), "+f"(d[79])
    : "l"(da), "l"(db), "r"(scale_d), "n"(TA), "n"(TB));
}
template <int TB, int TA = 0>
__device__ __forceinline__ void wgmma_ss_n192(float (&d)[96], uint64_t da, uint64_t db, int scale_d) {
  asm volatile("{\n.reg .pred p;\nsetp.ne.b32 p, %98, 0;\n"
    "wgmma.mma_async.sync.aligned.m64n192k16.f32.bf16.bf16 {%0, %1, %2, %3, %4, %5, %6, %7, %8, %9, %10, %11, %12, %13, %14, %15, %16, %17, %18, %19, %20, %21, %22, %23, %24, %25, %26, %27, %28, %29, %30, %31, %32, %33, %34, %35, %36, %37, %38, %39, %40, %41, %42, %43, %44, %45, %46, %47, %48, %49, %50, %51, %52, %53, %54, %55, %56, %57, %58, %59, %60, %61, %62, %63, %64, %65, %66, %67, %68, %69, %70, %71, %72, %73, %74, %75, %76, %77, %78, %79, %80, %81, %82, %83, %84, %85, %86, %87, %88, %89, %90, %91, %92, %93, %94, %95}, %96, %97, p, 1, 1, %99, %100;\n}\n"
    : "+f"(d[0]), "+f"(d[1]), "+f"(d[2]), "+f"(d[3]), "+f"(d[4]), "+f"(d[5]), "+f"(d[6]), "+f"(d[7]), "+f"(d[8]), "+f"(d[9]), "+f"(d[10]), "+f"(d[11]), "+f"(d[12]), "+f"(d[13]), "+f"(d[14]), "+f"(d[15]), "+f"(d[16]), "+f"(d[17]), "+f"(d[18]), "+f"(d[19]), "+f"(d[20]), "+f"(d[21]), "+f"(d[22]), "+f"(d[23]), "+f"(d[24]), "+f"(d[25]), "+f"(d[26]), "+f"(d[27]), "+f"(d[28]), "+f"(d[29]), "+f"(d[30]), "+f"(d[31]), "+f"(d[32]), "+f"(d[33]), "+f"(d[34]), "+f"(d[35]), "+f"(d[36]), "+f"(d[37]), "+f"(d[38]), "+f"(d[39]), "+f"(d[40]), "+f"(d[41]), "+f"(d[42]), "+f"(d[43]), "+f"(d[44]), "+f"(d[45]), "+f"(d[46]), "+f"(d[47]), "+f"(d[48]), "+f"(d[49]), "+f"(d[50]), "+f"(d[51]), "+f"(d[52]), "+f"(d[53]), "+f"(d[54]), "+f"(d[55]), "+f"(d[56]), "+f"(d[57]), "+f"(d[58]), "+f"(d[59]), "+f"(d[60]), "+f"(d[61]), "+f"(d[62]), "+f"(d[63]), "+f"(d[64]), "+f"(d[65]), "+f"(d[66]), "+f"(d[67]), "+f"(d[68]), "+f"(d[69]), "+f"(d[70]), "+f"(d[71]), "+f"(d[72]), "+f"(d[73]), "+f"(d[74]), "+f"(d[75]), "+f"(d[76]), "+f"(d[77]), "+f"(d[78]), "+f"(d[79]), "+f"(d[80]), "+f"(d[81]), "+f"(d[82]), "+f"(d[83]), "+f"(d[84]), "+f"(d[85]), "+f"(d[86]), "+f"(d[87]), "+f"(d[88]), "+f"(d[89]), "+f"(d[90]), "+f"(d[91]), "+f"(d[92]), "+f"(d[93]), "+f"(d[94]), "+f"(d[95])
    : "l"(da), "l"(db), "r"(scale_d), "n"(TA), "n"(TB));
}
template <int TB>
__device__ __forceinline__ void wgmma_rs_n192(float (&d)[96], uint32_t a0, uint32_t a1, uint32_t a2, uint32_t a3, uint64_t db, int scale_d) {
  asm volatile("{\n.reg .pred p;\nsetp.ne.b32 p, %101, 0;\n"
    "wgmma.mma_async.sync.aligned.m64n192k16.f32.bf16.bf16 {%0, %1, %2, %3, %4, %5, %6, %7, %8, %9, %10, %11, %12, %13, %14, %15, %16, %17, %18, %19, %20, %21, %22, %23, %24, %25, %26, %27, %28, %29, %30, %31, %32, %33, %34, %35, %36, %37, %38, %39, %40, %41, %42, %43, %44, %45, %46, %47, %48, %49, %50, %51, %52, %53, %54, %55, %56, %57, %58, %59, %60, %61, %62, %63, %64, %65, %66, %67, %68, %69, %70, %71, %72, %73, %74, %75, %76, %77, %78, %79, %80, %81, %82, %83, %84, %85, %86, %87, %88, %89, %90, %91, %92, %93, %94, %95}, {%96, %97, %98, %99}, %100, p, 1, 1, %102;\n}\n"
    : "+f"(d[0]), "+f"(d[1]), "+f"(d[2]), "+f"(d[3]), "+f"(d[4]), "+f"(d[5]), "+f"(d[6]), "+f"(d[7]), "+f"(d[8]), "+f"(d[9]), "+f"(d[10]), "+f"(d[11]), "+f"(d[12]), "+f"(d[13]), "+f"(d[14]), "+f"(d[15]), "+f"(d[16]), "+f"(d[17]), "+f"(d[18]), "+f"(d[19]), "+f"(d[20]), "+f"(d[21]), "+f"(d[22]), "+f"(d[23]), "+f"(d[24]), "+f"(d[25]), "+f"(d[26]), "+f"(d[27]), "+f"(d[28]), "+f"(d[29]), "+f"(d[30]), "+f"(d[31]), "+f"(d[32]), "+f"(d[33]), "+f"(d[34]), "+f"(d[35]), "+f"(d[36]), "+f"(d[37]), "+f"(d[38]), "+f"(d[39]), "+f"(d[40]), "+f"(d[41]), "+f"(d[42]), "+f"(d[43]), "+f"(d[44]), "+f"(d[45]), "+f"(d[46]), "+f"(d[47]), "+f"(d[48]), "+f"(d[49]), "+f"(d[50]), "+f"(d[51]), "+f"(d[52]), "+f"(d[53]), "+f"(d[54]), "+f"(d[55]), "+f"(d[56]), "+f"(d[57]), "+f"(d[58]), "+f"(d[59]), "+f"(d[60]), "+f"(d[61]), "+f"(d[62]), "+f"(d[63]), "+f"(d[64]), "+f"(d[65]), "+f"(d[66]), "+f"(d[67]), "+f"(d[68]), "+f"(d[69]), "+f"(d[70]), "+f"(d[71]), "+f"(d[72]), "+f"(d[73]), "+f"(d[74]), "+f"(d[75]), "+f"(d[76]), "+f"(d[77]), "+f"(d[78]), "+f"(d[79]), "+f"(d[80]), "+f"(d[81]), "+f"(d[82]), "+f"(d[83]), "+f"(d[84]), "+f"(d[85]), "+f"(d[86]), "+f"(d[87]), "+f"(d[88]), "+f"(d[89]), "+f"(d[90]), "+f"(d[91]), "+f"(d[92]), "+f"(d[93]), "+f"(d[94]), "+f"(d[95])
    : "r"(a0), "r"(a1), "r"(a2), "r"(a3), "l"(db), "r"(scale_d), "n"(TB));
}

__device__ __forceinline__ uint32_t smem_u32(const void* p) { return (uint32_t)__cvta_generic_to_shared(p); }
__device__ __forceinline__ void wg_fence() { asm volatile("wgmma.fence.sync.aligned;" ::: "memory"); }
__device__ __forceinline__ void wg_commit() { asm volatile("wgmma.commit_group.sync.aligned;" ::: "memory"); }
template <int N> __device__ __forceinline__ void wg_wait() { asm volatile("wgmma.wait_group.sync.aligned %0;" ::"n"(N) : "memory"); }
__device__ __forceinline__ void sched_fence(int& keep, uint32_t zero) {
  asm volatile("{\n.reg .u32 c;\nmov.u32 c, %%clock;\nand.b32 c, c, %1;\nxor.b32 %0, %0, c;\n}\n" : "+r"(keep) : "r"(zero) : "memory");
}
template <int N> __device__ __forceinline__ void fence_regs(float (&r)[N]) {
#pragma unroll
  for (int i = 0; i < N; i++) asm volatile("" : "+f"(r[i])::"memory");
}
template <int N> __device__ __forceinline__ void fence_regs(uint32_t (&r)[N]) {
#pragma unroll
  for (int i = 0; i < N; i++) asm volatile("" : "+r"(r[i])::"memory");
}
__device__ __forceinline__ uint64_t mk_desc(uint32_t a16, uint32_t lbo, uint32_t sbo, uint32_t swz, uint32_t off = 0) {
  uint64_t d;
  asm("mov.b64 %0, {%1, %2};" : "=l"(d) : "r"(a16), "r"((sbo >> 4) | (swz << 30)));
  return d + (off + ((lbo >> 4) << 16));
}
__device__ __forceinline__ void mbar_init(uint32_t bar, uint32_t cnt) {
  asm volatile("mbarrier.init.shared::cta.b64 [%0], %1;" ::"r"(bar), "r"(cnt) : "memory");
}
__device__ __forceinline__ void mbar_expect(uint32_t bar, uint32_t tx) {
  asm volatile("mbarrier.arrive.expect_tx.shared::cta.b64 _, [%0], %1;" ::"r"(bar), "r"(tx) : "memory");
}
__device__ __forceinline__ bool mbar_test(uint32_t bar, uint32_t ph) {
  uint32_t ok;
  asm volatile("{\n.reg .pred p;\nmbarrier.test_wait.parity.shared::cta.b64 p, [%1], %2;\nselp.u32 %0, 1, 0, p;\n}\n"
               : "=r"(ok) : "r"(bar), "r"(ph) : "memory");
  return ok;
}
__device__ __forceinline__ void mbar_wait(uint32_t bar, uint32_t ph) {
  asm volatile("{\n.reg .pred p;\n.reg .u32 n;\nmov.u32 n, 0;\n"
               "LOOP:\nadd.u32 n, n, 1;\nmbarrier.try_wait.parity.shared::cta.b64 p, [%0], %1;\n@p bra DONE;\n"
               "setp.lt.u32 p, n, 0x1000000;\n@p bra LOOP;\ntrap;\n"
               "DONE:\n}\n" ::"r"(bar), "r"(ph) : "memory");
}
__device__ __forceinline__ void mbar_wait_math(uint32_t bar, uint32_t ph) {
  asm volatile("{\n.reg .pred p;\nLOOP:\nmbarrier.try_wait.parity.shared::cta.b64 p, [%0], %1;\n@!p bra LOOP;\n}\n" ::"r"(bar), "r"(ph) : "memory");
}
__device__ __forceinline__ void mbar_wait_long(uint32_t bar, uint32_t ph) {
  asm volatile("{\n.reg .pred p;\n.reg .u32 n;\nmov.u32 n, 0;\n"
               "LOOP:\nmbarrier.try_wait.parity.shared::cta.b64 p, [%0], %1, %2;\n@p bra DONE;\n"
               "add.u32 n, n, 1;\nsetp.lt.u32 p, n, 0x40000;\n@p bra LOOP;\ntrap;\n"
               "DONE:\n}\n" ::"r"(bar), "r"(ph), "r"(20000) : "memory");
}
__device__ __forceinline__ void mbar_arrive_cluster_if(bool on, uint32_t addr) {
  asm volatile("{\n.reg .pred p;\nsetp.ne.b32 p, %1, 0;\n@p mbarrier.arrive.shared::cluster.b64 _, [%0];\n}\n" ::"r"(addr), "r"((int)on) : "memory");
}
__device__ __forceinline__ void mbar_arrive_if(bool on, uint32_t addr) {
  asm volatile("{\n.reg .pred p;\nsetp.ne.b32 p, %1, 0;\n@p mbarrier.arrive.shared::cta.b64 _, [%0];\n}\n" ::"r"(addr), "r"((int)on) : "memory");
}
__device__ __forceinline__ void tma2d(uint32_t dst, const CUtensorMap* m, uint32_t bar, int c0, int c1) {
  asm volatile("cp.async.bulk.tensor.2d.shared::cluster.global.mbarrier::complete_tx::bytes [%0], [%1, {%3, %4}], [%2];"
               ::"r"(dst), "l"(m), "r"(bar), "r"(c0), "r"(c1) : "memory");
}
__device__ __forceinline__ void tma3d(uint32_t dst, const CUtensorMap* m, uint32_t bar, int c0, int c1, int c2) {
  asm volatile("cp.async.bulk.tensor.3d.shared::cluster.global.mbarrier::complete_tx::bytes [%0], [%1, {%3, %4, %5}], [%2];"
               ::"r"(dst), "l"(m), "r"(bar), "r"(c0), "r"(c1), "r"(c2) : "memory");
}
__device__ __forceinline__ void tma3d_mc(uint32_t dst, const CUtensorMap* m, uint32_t bar, int c0, int c1, int c2) {
  asm volatile("cp.async.bulk.tensor.3d.shared::cluster.global.mbarrier::complete_tx::bytes.multicast::cluster"
               " [%0], [%1, {%3, %4, %5}], [%2], %6;"
               ::"r"(dst), "l"(m), "r"(bar), "r"(c0), "r"(c1), "r"(c2), "h"((uint16_t)3) : "memory");
}
__device__ __forceinline__ void tma3d_store(const CUtensorMap* m, uint32_t src, int c0, int c1, int c2) {
  asm volatile("cp.async.bulk.tensor.3d.global.shared::cta.bulk_group [%0, {%2, %3, %4}], [%1];"
               ::"l"(m), "r"(src), "r"(c0), "r"(c1), "r"(c2) : "memory");
}
__device__ __forceinline__ void bar_sync(int id, int n) { asm volatile("bar.sync %0, %1;" ::"r"(id), "r"(n) : "memory"); }
__device__ __forceinline__ uint32_t pack_bf16(float lo, float hi) {
  uint32_t r;
  asm("cvt.rn.bf16x2.f32 %0, %1, %2;" : "=r"(r) : "f"(hi), "f"(lo));
  return r;
}
__device__ __forceinline__ float ex2(float x) {
  float y;
  asm("ex2.approx.ftz.f32 %0, %1;" : "=f"(y) : "f"(x));
  return y;
}
__device__ __forceinline__ float fadd(float a, float b) {
  float y;
  asm("add.f32 %0, %1, %2;" : "=f"(y) : "f"(a), "f"(b));
  return y;
}
__device__ __forceinline__ float rcp(float x) {
  float y;
  asm("rcp.approx.ftz.f32 %0, %1;" : "=f"(y) : "f"(x));
  return y;
}
__device__ __forceinline__ void stsm4(uint32_t addr, uint32_t a, uint32_t b, uint32_t c, uint32_t d) {
  asm volatile("stmatrix.sync.aligned.m8n8.x4.shared.b16 [%0], {%1, %2, %3, %4};" ::"r"(addr), "r"(a), "r"(b), "r"(c), "r"(d) : "memory");
}

__device__ __forceinline__ void tma4d_mc_hint(uint32_t dst, const CUtensorMap* m, uint32_t bar, int c3, uint64_t pol) {
  asm volatile("cp.async.bulk.tensor.4d.shared::cluster.global.mbarrier::complete_tx::bytes.multicast::cluster.L2::cache_hint"
               " [%0], [%1, {%3, %3, %3, %4}], [%2], %5, %6;"
               ::"r"(dst), "l"(m), "r"(bar), "r"(0), "r"(c3), "h"((uint16_t)3), "l"(pol) : "memory");
}
__device__ __forceinline__ void tma5d_mc(uint32_t dst, const CUtensorMap* m, uint32_t bar, int c2, int c4) {
  asm volatile("cp.async.bulk.tensor.5d.shared::cluster.global.mbarrier::complete_tx::bytes.multicast::cluster"
               " [%0], [%1, {%3, %3, %4, %3, %5}], [%2], %6;"
               ::"r"(dst), "l"(m), "r"(bar), "r"(0), "r"(c2), "r"(c4), "h"((uint16_t)3) : "memory");
}
__device__ __forceinline__ void bulk_load_hint(uint32_t dst, const void* src, uint32_t bytes, uint32_t bar, uint64_t pol) {
  asm volatile("cp.async.bulk.shared::cluster.global.mbarrier::complete_tx::bytes.L2::cache_hint [%0], [%1], %2, [%3], %4;"
               ::"r"(dst), "l"(src), "r"(bytes), "r"(bar), "l"(pol) : "memory");
}
__device__ __forceinline__ void stg2_if(bool on, void* p, uint32_t a, uint32_t b, uint32_t c, uint32_t d, uint32_t e, uint32_t f,
                                        uint32_t g, uint32_t h, uint64_t pol) {
  asm volatile("{\n.reg .pred p;\nsetp.ne.b32 p, %10, 0;\n"
               "@p st.global.L2::cache_hint.v4.b32 [%0], {%1, %2, %3, %4}, %9;\n"
               "@p st.global.L2::cache_hint.v4.b32 [%0 + 512], {%5, %6, %7, %8}, %9;\n}\n"
               ::"l"(p), "r"(a), "r"(b), "r"(c), "r"(d), "r"(e), "r"(f), "r"(g), "r"(h), "l"(pol), "r"((int)on) : "memory");
}
__device__ __forceinline__ uint64_t evict_first() {
  uint64_t p;
  asm("createpolicy.fractional.L2::evict_first.b64 %0, 1.0;" : "=l"(p));
  return p;
}
__device__ __forceinline__ bool elect() {
  uint32_t ok;
  asm volatile("{\n.reg .pred p;\nelect.sync _|p, 0xffffffff;\nselp.u32 %0, 1, 0, p;\n}\n" : "=r"(ok));
  return ok;
}
__device__ __forceinline__ void mbar_arrive(uint32_t bar) {
  asm volatile("mbarrier.arrive.shared::cta.b64 _, [%0];" ::"r"(bar) : "memory");
}
__device__ __forceinline__ void lds128(uint32_t p, uint32_t& a, uint32_t& b, uint32_t& c, uint32_t& d) {
  asm volatile("ld.shared.v4.b32 {%0, %1, %2, %3}, [%4];" : "=r"(a), "=r"(b), "=r"(c), "=r"(d) : "r"(p) : "memory");
}
__device__ __forceinline__ void wait_count(const unsigned int* p, uint32_t target) {
  asm volatile("{\n.reg .pred p;\n.reg .u32 n, v;\nmov.u32 n, 0;\n"
               "LOOP:\nld.acquire.gpu.global.u32 v, [%0];\nsetp.ge.u32 p, v, %1;\n@p bra DONE;\n"
               "nanosleep.u32 %2;\nadd.u32 n, n, 1;\nsetp.lt.u32 p, n, 0x400000;\n@p bra LOOP;\ntrap;\n"
               "DONE:\n}\n" ::"l"(p), "r"(target), "n"(300) : "memory");
}

__device__ __forceinline__ int o_wave(int a, int b, int i) {
  const int p = min(3, b - a - 1);
  return i < p ? b - 2 - i : i == p ? b - 1 : b - 1 - i;
}

struct Cursor {
  uint32_t n;
  __device__ __forceinline__ uint32_t off() const { return n & (8 * NBAR - 8); }
  __device__ __forceinline__ uint32_t ph() const { return (n / (8 * NBAR)) & 1; }
  __device__ __forceinline__ void next() { n += 8; }
};

constexpr float kScaleLog2 = 0.07216878364870322f * 1.4426950408889634f;
constexpr float kSumLimit = 1048576.0f;
constexpr float kMaxLag = 8.0f;

__global__ void __cluster_dims__(2, 1, 1) __launch_bounds__(384, 1)
fused_kernel(const __grid_constant__ Params P) {
  extern __shared__ uint8_t smem_raw[];
  const uint32_t sbase = (smem_u32(smem_raw) + 1023) & ~1023u;
  const uint32_t full0 = sbase + RING, empty0 = full0 + 8 * NBAR, odone = empty0 + 8 * NBAR, oready0 = odone + 8;
  const uint32_t fenced = oready0 + 64, hready0 = fenced + 8;
  const uint32_t rank = blockIdx.x & 1;
  const int role = blockIdx.x >> 1;
  const bool helper = role >= N_CL;
  const int team = helper ? 0 : role >> 2, nt = role & 3, blk = team >> 3;
  const uint32_t* prog = P.ops[helper ? N_TEAM + 2 * (role - N_CL) : team];
  auto q_role = [&](uint32_t op) { return helper ? (int)(((op >> 3) & 60) | ((op >> 12) & 3)) : role; };
  auto o_role = [&](uint32_t op) { return helper ? (int)(((op >> 26) & 56) | ((op >> 9) & 7)) : role; };
  const int wid = __shfl_sync(0xffffffffu, (int)(threadIdx.x >> 5), 0);
  const int wg = wid >> 2;

  const uint32_t op0 = P.first[helper ? N_TEAM + role - N_CL : team];
  if (__builtin_expect(wid == 8, 1)) {
    if (elect()) {
#pragma unroll
      for (int k = 0; k < EARLY; k++) mbar_init(full0 + 8 * k, 1);
      asm volatile("fence.mbarrier_init.release.cluster;" ::: "memory");
      if ((op0 & 3) == OP_Q) {
        const int qr = q_role(op0);
#pragma unroll
        for (int k = 0; k < EARLY; k++) {
          mbar_expect(full0 + 8 * k, SZ_WQ + SZ_A);
          tma2d(sbase + k * (SZ_WQ + SZ_A) + SZ_WQ, &P.x[qr >> 5], full0 + 8 * k, 64 * k, ((qr >> 2) & 7) * kSq + rank * 128);
          tma3d(sbase + k * (SZ_WQ + SZ_A), &P.wq[qr >> 5], full0 + 8 * k, 0, 64 * k, 3 * (4 * ((op0 >> 2) & 7) + (qr & 3)));
          tma3d(sbase + k * (SZ_WQ + SZ_A) + SZ_WQ / 2, &P.wq[qr >> 5], full0 + 8 * k, 0, 64 * k + 32, 3 * (4 * ((op0 >> 2) & 7) + (qr & 3)));
        }
      }
      asm volatile("prefetch.tensormap [%0];" ::"l"(&P.kv[blk]) : "memory");
      asm volatile("prefetch.tensormap [%0];" ::"l"(&P.kv[blk + 2]) : "memory");
    }
  } else if (threadIdx.x == 0) {
#pragma unroll
    for (int i = EARLY; i < 2 * NBAR + 10 + MAX_PARK; i++) mbar_init(full0 + 8 * i, i >= NBAR && i <= 2 * NBAR ? 16 : 1);
    asm volatile("fence.mbarrier_init.release.cluster;" ::: "memory");
  }
  __syncwarp();
  asm volatile("barrier.cluster.arrive.relaxed.aligned;\nbarrier.cluster.wait.aligned;" ::: "memory");

  if (wg == 2) {
    asm volatile("setmaxnreg.dec.sync.aligned.u32 24;");
    if (wid == 8) {
      Cursor tail{0u - 8}, head{0};
      int sh = 0;
      uint32_t cur = 0, used = 0;
      uint64_t fifo = 0;
      uint32_t oready = oready0;
      const uint64_t pol = evict_first();
      struct Load { uint32_t dst, bar, wbar, wph; int c0; const void* ptr; bool wait; };
      auto reserve = [&](uint32_t bytes, bool last, uint32_t half, int c0, const void* ptr) {
        uint32_t fp = bytes >> 12;
        if (cur + fp > (RING >> 12)) { fp += (RING >> 12) - cur; cur = 0; }
        used += fp;
        bool wait = false;
        while (used > (RING >> 12)) {
          wait = true;
          tail.next();
          used -= (uint32_t)fifo & 31;
          fifo >>= 5;
          sh -= 5;
        }
        fifo += (uint64_t)fp << sh;
        Load l{sbase + (cur << 12) + rank * half, full0 + head.off(), empty0 + tail.off(), tail.ph(), c0, ptr, wait};
        cur += bytes >> 12;
        sh += last ? 5 : 0;
        head.n += last ? 8 : 0;
        asm volatile("" : "+r"(l.dst), "+r"(l.bar), "+r"(l.c0), "+l"(l.ptr), "+r"(l.wbar), "+r"(l.wph));
        return l;
      };
      auto vacated = [&](const Load& l) { if (l.wait) mbar_wait(l.wbar, l.wph); };
      auto written = [&](uint32_t flag) {
        mbar_wait(flag, 0);
        asm volatile("fence.proxy.async.global;" ::: "memory");
      };
      for (int pc = 0;; pc++) {
        const uint32_t op = prog[pc];
        const int type = op & 3, a = (op >> 2) & 7;
        if (type == OP_END) break;
        if (type == OP_Q) {
          const int qr = q_role(op);
          const CUtensorMap *mw = &P.wq[qr >> 5], *mx = &P.x[qr >> 5];
          asm volatile("" : "+l"(mw), "+l"(mx));
          auto res_w = [&](int k) { return reserve(SZ_WQ, false, SZ_WQ / 2, 64 * k + 32 * rank, mw); };
          auto load_w = [&](const Load& w, int k) {
            vacated(w);
            if ((pc > 0 || k >= EARLY) && elect()) tma3d_mc(w.dst, (const CUtensorMap*)w.ptr, w.bar, 0, w.c0, 3 * (4 * a + (qr & 3)));
          };
          auto load_x = [&](const Load& x, int k) {
            vacated(x);
            if ((pc > 0 || k >= EARLY) && elect()) {
              tma2d(x.dst, (const CUtensorMap*)x.ptr, x.bar, x.c0, ((qr >> 2) & 7) * kSq + rank * 128);
              mbar_expect(x.bar, SZ_WQ + SZ_A);
            }
          };
#pragma unroll 1
          for (int k = 0; k < 10; k++) {
            load_w(res_w(k), k);
            load_x(reserve(SZ_A, true, 0, 64 * k, mx), k);
          }
        } else if (type == OP_A) {
          const uint32_t nop = prog[pc + 1];
          const int row8 = ((team & 7) * kH + nt) * (kSk / 8) + 4 * rank, wave8 = 4 * (kSk / 8);
          auto transit = [&]() {
            const Cursor c{head.n - 8 * (KV_TRANSIT + 1)};
            mbar_wait(full0 + c.off(), c.ph());
          };
          const char* map = (const char*)&P.kv[blk];
          asm volatile("" : "+l"(map));
          int t = (op & F_PARK) ? 1 : 0, c0 = row8 + a * wave8 + 8 * t, isv = 0;
#pragma unroll 1
          for (; t < 31; t++) {
            const Load l = reserve(SZ_KV, true, SZ_KV / 2, c0, map + isv);
            vacated(l);
            if (t >= KV_TRANSIT) transit();
            if (elect()) {
              tma4d_mc_hint(l.dst, (const CUtensorMap*)l.ptr, l.bar, l.c0, pol);
              mbar_expect(l.bar, SZ_KV);
            }
            isv = (t & 1) << 8;
            c0 += isv ? -8 : t ? 16 : 8;
          }
          const int next = (nop >> 2) & 7;
          if ((nop & 3) == OP_A) written((nop & F_HELP) ? hready0 + 8 * ((nop >> 10) & 3) : fenced);
#pragma unroll 1
          for (int i = (nop & 3) == OP_A ? 0 : 3; i < 4; i++) {
            const Load l = reserve(SZ_KV, true, i < 2 ? 0 : SZ_KV / 2, i == 3 ? c0 - 8 : row8 + next * wave8,
                                   i < 2 ? (const char*)&g_o[((team * 2 + rank) * 96 + 3 * (4 * next + nt)) * 1024 + i * (SZ_PARK / 16)] : map + ((i & 1) << 8));
            vacated(l);
            if (i < 2) {
              if (elect()) bulk_load_hint(l.dst, l.ptr, SZ_PARK, l.bar, pol);
              __syncwarp();
            } else {
              transit();
              if (elect()) tma4d_mc_hint(l.dst, (const CUtensorMap*)l.ptr, l.bar, l.c0, pol);
              __syncwarp();
            }
            if (elect()) mbar_expect(l.bar, SZ_KV);
          }
        } else {
          const int b = (op >> 5) & 15, ro = o_role(op);
          const CUtensorMap* mw = &P.wo[ro >> 5];
          const uint4* so = &g_o[((ro >> 2) * 2 + rank) * 96 * 1024];
          asm volatile("" : "+l"(mw), "+l"(so));
#pragma unroll 1
          for (int j = 0; j < b - a; j++) {
            const int w = o_wave(a, b, j);
            written(oready);
            oready += 8;
#pragma unroll 1
            for (int k = 12 * w; k < 12 * w + 12; k++) {
              const Load o = reserve(SZ_A, false, 0, 0, so + k * 1024);
              vacated(o);
              if (elect()) bulk_load_hint(o.dst, o.ptr, SZ_A, o.bar, pol);
              const Load w = reserve(SZ_WO, true, SZ_WO / 2, 8 * k + 4 * rank, mw);
              vacated(w);
              if (elect()) {
                tma5d_mc(w.dst, (const CUtensorMap*)w.ptr, w.bar, w.c0, 5 * (ro & 3));
                mbar_expect(w.bar, SZ_WO + SZ_A);
              }
            }
          }
          if ((op & F_LD) && (op & F_PARK)) written(hready0 + 8 * (MAX_PARK - 1));
#pragma unroll 1
          for (int i = (op & F_LD) ? 0 : 5; i < ((op & F_ST) ? 5 : 6); i++) {
            const Load l = reserve(i < 5 ? SZ_PART : SZ_OUT, i < 5, 0, 0, &g_part[(role * 2 + rank) * 5120 + i * (SZ_PART / 16)]);
            vacated(l);
            if (i < 5 && elect()) bulk_load_hint(l.dst, l.ptr, SZ_PART, l.bar, pol);
            if (elect()) mbar_expect(l.bar, i < 5 ? SZ_PART : 0);
          }
        }
      }
#pragma unroll 1
      for (Cursor c{head.n - 8 * NBAR}; c.n != head.n; c.next()) mbar_wait(empty0 + c.off(), c.ph());
    } else if (threadIdx.x == 288) {
      uint32_t ph = 0;
      bool first = true;
      for (int pc = 0;; pc++) {
        const uint32_t op = prog[pc];
        if ((op & 3) == OP_END) break;
        if ((op & 3) != OP_A && !helper) continue;
        mbar_wait_long(odone, ph);
        ph ^= 1;
        unsigned int* flag = !helper ? &g_done[(team * 2 + rank) * 8 + ((op >> 2) & 7)]
                             : (op & 3) == OP_Q ? &g_help[(q_role(op) * 2 + rank) * MAX_PARK + ((op >> 10) & 3)]
                                                : &g_help[(o_role(op) * 2 + rank) * MAX_PARK + MAX_PARK - 1];
        asm volatile("red.release.gpu.global.add.u32 [%0], 1;" ::"l"(flag) : "memory");
        if (first) mbar_arrive(fenced);
        first = false;
      }
    } else if (threadIdx.x == 320) {
      uint32_t oready = oready0;
      for (int pc = 0;; pc++) {
        const uint32_t op = prog[pc];
        if ((op & 3) == OP_END) break;
        if ((op & 3) == OP_O) {
          const int a = (op >> 2) & 7, b = (op >> 5) & 15;
#pragma unroll 1
          for (int i = 0; i < b - a; i++) {
            const int ci = ((o_role(op) >> 2) * 2 + rank) * 8 + o_wave(a, b, i);
            wait_count(&g_done[ci], 4);
            mbar_arrive(oready);
            oready += 8;
            if (atomicAdd(&g_seen[ci], 1u) == 3u) { g_seen[ci] = 0; g_done[ci] = 0; }
          }
        }
        if ((op & 3) != OP_Q && (op & F_HELP) && (op & F_PARK)) {
          unsigned int* flag = &g_help[(role * 2 + rank) * MAX_PARK + ((op >> 10) & 3)];
          wait_count(flag, 1);
          mbar_arrive(hready0 + 8 * ((op >> 10) & 3));
          *flag = 0;
        }
      }
    }
  } else {
    asm volatile("setmaxnreg.inc.sync.aligned.u32 240;");
    const int lane = threadIdx.x & 31, warp = wid & 3;
    uint32_t empty_rem;
    asm volatile("mapa.shared::cluster.u32 %0, %1, %2;" : "=r"(empty_rem) : "r"(empty0), "r"(lane & 1));
    auto release = [&](int slot) { mbar_arrive_cluster_if(lane < 2, empty_rem + slot); };
    Cursor r{0};
    const uint32_t ring16 = (sbase & 0x3FFFF) >> 4;
    uint32_t cur = ring16;
    bool rdy0 = false, rdy1 = false;
    auto probe1 = [&]() { rdy0 = mbar_test(full0 + r.off(), r.ph()); };
    auto probe2 = [&]() {
      Cursor n = r;
      rdy0 = mbar_test(full0 + n.off(), n.ph());
      n.next();
      rdy1 = mbar_test(full0 + n.off(), n.ph());
    };
    auto take = [&](bool rdy, uint32_t bytes, uint32_t& addr) {
      const int bi = r.off();
      if (!__all_sync(0xffffffffu, rdy)) mbar_wait_math(full0 + r.off(), r.ph());
      r.next();
      if (cur > ring16 + ((RING - bytes) >> 4)) cur = ring16;
      addr = cur;
      cur += bytes >> 4;
      return bi;
    };
    auto second = [&](uint32_t bytes) {
      if (cur > ring16 + ((RING - bytes) >> 4)) cur = ring16;
      cur += bytes >> 4;
      return cur - (bytes >> 4);
    };
    const int row = wg * 64 + warp * 16 + (lane >> 2);
    int img0 = row * 4 + ((lane & 3) ^ ((row >> 1) & 3));
    uint4* pend = nullptr;
    const uint64_t spol = evict_first();
    int pc = 0;
    uint32_t op = prog[0];
    auto enter = [&]() {
      r.n = op >> 12; cur = ring16 + (((op >> 20) & 63) << 8);
    };
    auto drain = [&](uint32_t (&t)[48], uint32_t c) {
      if (!(op & (3u << 26)) || c >= 6) return;
#pragma unroll
      for (int i = 0; i < 6; i++)
        stg2_if(c == i, pend + i * 512, t[8 * i], t[8 * i + 1], t[8 * i + 2], t[8 * i + 3],
                t[8 * i + 4], t[8 * i + 5], t[8 * i + 6], t[8 * i + 7], spol);
      if ((op & (1u << 26)) && c == 5) {
        __syncwarp();
        mbar_arrive_if(lane < 2, odone);
      }
    };
    float s[32], o[96], c[80];
    uint32_t q[48], pa[16], pb[16];
    float mc0, mc1, l0, l1;
    bool gen;
    auto soft = [&](float (&s)[32], uint32_t (&pout)[16], bool first) {
      if (first) { gen = false; mc0 = 0.f; mc1 = 0.f; }
      float b0, b1;
      for (;;) {
        if (gen) {
          float m0 = fmaxf(s[0], s[1]), m1 = fmaxf(s[2], s[3]);
#pragma unroll
          for (int i = 1; i < 8; i++) { m0 = fmaxf(m0, fmaxf(s[4 * i], s[4 * i + 1])); m1 = fmaxf(m1, fmaxf(s[4 * i + 2], s[4 * i + 3])); }
          m0 = fmaxf(m0, __shfl_xor_sync(0xffffffffu, m0, 1)); m1 = fmaxf(m1, __shfl_xor_sync(0xffffffffu, m1, 1));
          m0 = fmaxf(m0, __shfl_xor_sync(0xffffffffu, m0, 2)); m1 = fmaxf(m1, __shfl_xor_sync(0xffffffffu, m1, 2));
          if (first) {
            mc0 = m0; mc1 = m1;
          } else if (__any_sync(0xffffffffu, !(m0 <= mc0 + kMaxLag && m1 <= mc1 + kMaxLag))) {
            m0 = fmaxf(mc0, m0); m1 = fmaxf(mc1, m1);
            const float a0 = ex2(mc0 - m0), a1 = ex2(mc1 - m1);
            mc0 = m0; mc1 = m1;
            l0 *= a0; l1 *= a1;
            wg_wait<0>();
            fence_regs(o);
#pragma unroll
            for (int i = 0; i < 96; i++) o[i] *= i & 2 ? a1 : a0;
          }
#pragma unroll
          for (int i = 0; i < 32; i++) s[i] -= i & 2 ? mc1 : mc0;
        }
#pragma unroll
        for (int i = 0; i < 8; i++) {
          const float e1 = ex2(s[4 * i + 1]), e0 = ex2(s[4 * i]), e3 = ex2(s[4 * i + 3]), e2 = ex2(s[4 * i + 2]);
          pout[2 * i] = pack_bf16(e0, e1);
          b0 = i ? b0 + fadd(e1, e0) : fadd(e1, e0);
          pout[2 * i + 1] = pack_bf16(e2, e3);
          b1 = i ? b1 + fadd(e3, e2) : fadd(e3, e2);
        }
        if (!__any_sync(0xffffffffu, !gen && !(fmaxf(b0, b1) <= kSumLimit && (!first || fminf(b0, b1) >= 1.0f / kSumLimit)))) break;
        gen = __any_sync(0xffffffffu, true);
      }
      l0 = first ? b0 : l0 + b0;
      l1 = first ? b1 : l1 + b1;
    };
    auto qk = [&](float (&s)[32], uint32_t ak, int k0, int k1) {
#pragma unroll
      for (int kk = k0; kk < k1; kk++)
        wgmma_rs_n64<0>(s, q[4 * kk], q[4 * kk + 1], q[4 * kk + 2], q[4 * kk + 3], mk_desc(ak, 16, KV_SBO, 1, (kk >> 2) * KV_CH + (kk & 3) * 2), kk != 0);
      wg_commit();
    };
    auto pv = [&](uint32_t (&pin)[16], uint32_t av, int acc) {
#pragma unroll
      for (int kk = 0; kk < 4; kk++)
        wgmma_rs_n192<1>(o, pin[4 * kk], pin[4 * kk + 1], pin[4 * kk + 2], pin[4 * kk + 3], mk_desc(av, KV_CH * 16, KV_SBO, 1, kk * (KV_SBO / 8)), acc || (kk != 0));
      wg_commit();
    };
    auto xw = [&](uint32_t ad, int acc) {
      const uint32_t da = second(SZ_A) + wg * 512;
      wg_fence();
#pragma unroll
      for (int kk = 0; kk < 4; kk++)
        wgmma_ss_n192<1>(o, mk_desc(da, 16, 1024, 1, kk * 2), mk_desc(ad, 4096, 1024, 1, (kk & 1) * 128 + (kk >> 1) * 768), acc || kk != 0);
      wg_commit();
    };
    auto ow = [&](int acc, int prev) {
      uint32_t da;
      const int bi = take(rdy0, SZ_A, da);
      const uint32_t db = second(SZ_WO);
      da += wg * 256;
      wg_fence();
      wgmma_ss_n160<1>(c, mk_desc(da, 16, 512, 2), mk_desc(db, 2048, 512, 2), acc);
      wgmma_ss_n160<1>(c, mk_desc(da, 16, 512, 2, 2), mk_desc(db, 2048, 512, 2, 64), 1);
      wg_commit();
      if (acc == 1) { wg_wait<1>(); release(prev); }
      wgmma_ss_n160<1>(c, mk_desc(da, 16, 512, 2, 512), mk_desc(db, 2048, 512, 2, 640), 1);
      wgmma_ss_n160<1>(c, mk_desc(da, 16, 512, 2, 514), mk_desc(db, 2048, 512, 2, 704), 1);
      wg_commit();
      return bi;
    };
    auto st_part = [&](int i) {
      stg2_if(true, pend + i * 512, __float_as_uint(c[8 * i]), __float_as_uint(c[8 * i + 1]), __float_as_uint(c[8 * i + 2]), __float_as_uint(c[8 * i + 3]),
              __float_as_uint(c[8 * i + 4]), __float_as_uint(c[8 * i + 5]), __float_as_uint(c[8 * i + 6]), __float_as_uint(c[8 * i + 7]), spol);
    };
#pragma unroll
    for (int i = 0; i < 48; i++) q[i] = 0;
    enter();

    if ((op & 3) == OP_Q) {
      uint32_t ad;
      int bi0 = take(false, SZ_WQ, ad), k = 0, lag = 0;
      xw(ad, 0);
      for (;;) {
#pragma unroll 1
        for (;;) {
          drain(q, k - lag);
          probe1();
          wg_wait<0>();
          release(bi0);
          bi0 = take(rdy0, SZ_WQ, ad);
          if (++k == 8) break;
          xw(ad, 1);
        }
        if (wg) bar_sync(2, 256);
        xw(ad, 1);
        const int bi9 = take(false, SZ_WQ, ad);
        xw(ad, 1);
        if (!wg) asm volatile("bar.arrive 2, 256;" ::: "memory");
        k = 0; lag = 0;
        uint32_t nop = prog[++pc];
        wg_wait<1>();
        release(bi0);
        probe2();
        wg_wait<0>();
        fence_regs(o);
        release(bi9);
#pragma unroll
        for (int i = 0; i < 48; i++) q[i] = pack_bf16(o[2 * i] * kScaleLog2, o[2 * i + 1] * kScaleLog2);
        fence_regs(q);
        if (op & F_PARK) {
          const int qt = helper ? (op >> 5) & 15 : team, qm = helper ? (op >> 12) & 3 : nt;
          pend = &g_o[((qt * 2 + rank) * 96 + 3 * (4 * ((op >> 2) & 7) + qm)) * 1024 + img0];
          op = nop;
          enter();
          if ((op & 3) != OP_Q) break;
          const int b = take(rdy0, SZ_WQ, ad);
          xw(ad, 0);
          bi0 = take(rdy1, SZ_WQ, ad);
          xw(ad, 1);
          wg_wait<1>();
          release(b);
          k = 1; lag = 1;
          continue;
        }
        int wave = (op >> 2) & 7, sk1;
        uint32_t ak1;
        {
          float s0[32];
          const int sk0 = take(rdy0, SZ_KV, ad);
          wg_fence();
          qk(s0, ad, 0, 12);
          sk1 = take(rdy1, SZ_KV, ak1);
          wg_fence();
          qk(s, ak1, 0, S1A);
          probe1();
          wg_wait<1>();
          fence_regs(s0);
          release(sk0);
          soft(s0, pa, true);
        }
        float i0, i1;
        auto sums = [&]() {
          l0 += __shfl_xor_sync(0xffffffffu, l0, 1); l1 += __shfl_xor_sync(0xffffffffu, l1, 1);
          l0 += __shfl_xor_sync(0xffffffffu, l0, 2); l1 += __shfl_xor_sync(0xffffffffu, l1, 2);
          i0 = rcp(l0); i1 = rcp(l1);
          asm volatile("" : "+f"(i0), "+f"(i1));
        };
        auto target = [&]() {
          pend = &g_o[((team * 2 + rank) * 96 + 3 * (4 * wave + nt)) * 1024 + img0];
          asm volatile("" : "+l"(pend));
        };
        bool late = false;
#pragma unroll
        for (int i = 0; i < 16; i++) pb[i] = 0;
        for (;;) {
          nop = prog[++pc];
          {
            uint32_t av;
            const int sv = take(rdy0, SZ_KV, av);
            wg_fence();
            qk(s, ak1, S1A, 12);
            pv(pa, av, 0);
            if (late) {
              stg2_if(true, pend + 4 * 512, pb[0], pb[1], pb[2], pb[3], pb[4], pb[5], pb[6], pb[7], spol);
              stg2_if(true, pend + 5 * 512, pb[8], pb[9], pb[10], pb[11], pb[12], pb[13], pb[14], pb[15], spol);
              __syncwarp();
              mbar_arrive_if(lane < 2, odone);
            }
            probe2();
            wg_wait<1>();
            fence_regs(s);
            release(sk1);
            soft(s, pb, false);
            wg_wait<0>();
            fence_regs(o);
            release(sv);
          }
          auto step = [&](uint32_t (&pin)[16], uint32_t (&pout)[16]) {
            uint32_t ak, av;
            const int sk = take(rdy0, SZ_KV, ak), sv = take(rdy1, SZ_KV, av);
            wg_fence();
            qk(s, ak, 0, 12);
            pv(pin, av, 1);
            probe2();
            wg_wait<1>();
            fence_regs(s);
            release(sk);
            soft(s, pout, false);
            wg_wait<0>();
            fence_regs(o);
            release(sv);
          };
#pragma unroll 1
          for (int jj = 0; jj < 7; jj++) {
            step(pb, pa);
            step(pa, pb);
          }
          if ((nop & 3) != OP_A) break;
          uint32_t ak, av;
          {
            const int b0 = take(rdy0, SZ_PARK, ak), b1 = take(rdy1, SZ_PARK, av);
            const uint32_t ad0 = ak, ad1 = av;
            probe2();
#pragma unroll
            for (int i = 0; i < 12; i++)
              lds128(sbase + ((i < 6 ? ad0 : ad1) - ring16 + img0) * 16 + ((i % 6) >> 1) * 8192 + (i & 1) * 512, q[4 * i], q[4 * i + 1], q[4 * i + 2], q[4 * i + 3]);
            release(b0); release(b1);
          }
          const int sk0 = take(rdy0, SZ_KV, ak), sv = take(rdy1, SZ_KV, av);
          wg_fence();
          qk(s, ak, 0, 8);
          sched_fence(img0, P.zero);
          sums();
          sched_fence(img0, P.zero);
          qk(s, ak, 8, 12);
          pv(pb, av, 1);
          probe2();
          wg_wait<1>();
          fence_regs(s);
          release(sk0);
          soft(s, pa, true);
          sk1 = take(rdy0, SZ_KV, ak1);
          rdy0 = rdy1;
          wg_wait<0>();
          target();
          fence_regs(o);
          release(sv);
          uint32_t t[48];
#pragma unroll
          for (int j = 0; j < 6; j++) {
#pragma unroll
            for (int i = 0; i < 4; i++) {
              t[8 * j + i] = pack_bf16(o[16 * j + 4 * i] * i0, o[16 * j + 4 * i + 1] * i0);
              t[8 * j + i + 4] = pack_bf16(o[16 * j + 4 * i + 2] * i1, o[16 * j + 4 * i + 3] * i1);
            }
            if (j < 4)
            stg2_if(true, pend + j * 512, t[8 * j], t[8 * j + 1], t[8 * j + 2], t[8 * j + 3], t[8 * j + 4], t[8 * j + 5], t[8 * j + 6], t[8 * j + 7], spol);
            if (j == 3) { wg_fence(); qk(s, ak1, 0, 4); }
            if (j == 5) { wg_fence(); qk(s, ak1, 4, S1A); }
            sched_fence(img0, P.zero);
          }
          if (P.zero) {
#pragma unroll
            for (int j = 0; j < 4; j++)
              stg2_if(true, pend, t[8 * j], t[8 * j + 1], t[8 * j + 2], t[8 * j + 3], t[8 * j + 4], t[8 * j + 5], t[8 * j + 6], t[8 * j + 7], spol);
          }
          late = true;
#pragma unroll
          for (int i = 0; i < 16; i++) pb[i] = t[32 + i];
          wave = (nop >> 2) & 7;
        }
        const int sv = take(rdy0, SZ_KV, ad);
        wg_fence();
        pv(pb, ad, 1);
        sums();
        target();
        op = nop;
        enter();
        rdy0 = rdy1;
        auto convert = [&](float (&u)[96], int j0, int j1) {
#pragma unroll
          for (int i = 4 * j0; i < 4 * j1; i++) {
            q[8 * (i >> 2) + (i & 3)] = pack_bf16(u[4 * i], u[4 * i + 1]);
            q[8 * (i >> 2) + (i & 3) + 4] = pack_bf16(u[4 * i + 2], u[4 * i + 3]);
          }
        };
        if ((op & 3) != OP_O) {
          if ((op & 3) == OP_Q) bi0 = take(rdy0, SZ_WQ, ad);
          wg_wait<0>();
          fence_regs(o);
          release(sv);
          float u[96];
#pragma unroll
          for (int i = 0; i < 96; i++) u[i] = o[i] * (i & 2 ? i1 : i0);
          if ((op & 3) != OP_Q) { convert(u, 0, 6); break; }
          fence_regs(u);
          xw(ad, 0);
          sched_fence(img0, P.zero);
          fence_regs(u);
          convert(u, 0, 1);
          stg2_if(true, pend, q[0], q[1], q[2], q[3], q[4], q[5], q[6], q[7], spol);
          probe1();
          wg_wait<0>();
          release(bi0);
          bi0 = take(rdy0, SZ_WQ, ad);
          xw(ad, 1);
          sched_fence(img0, P.zero);
          fence_regs(u);
          convert(u, 1, 6);
          k = 1;
          continue;
        }
        int bi = ow(0, 0);
        wg_wait<2>();
        fence_regs(o);
        release(sv);
#pragma unroll
        for (int j = 0; j < 6; j++) {
          uint32_t t[8];
#pragma unroll
          for (int i = 0; i < 4; i++) {
            t[i] = pack_bf16(o[16 * j + 4 * i] * i0, o[16 * j + 4 * i + 1] * i0);
            t[i + 4] = pack_bf16(o[16 * j + 4 * i + 2] * i1, o[16 * j + 4 * i + 3] * i1);
          }
          stg2_if(true, pend + j * 512, t[0], t[1], t[2], t[3], t[4], t[5], t[6], t[7], spol);
          if (j == 5) {
            __syncwarp();
            mbar_arrive_if(lane < 2, odone);
          }
          probe1();
          wg_wait<1>();
          bi = ow(1, bi);
          fence_regs(o);
        }
        {
          const int nk = 12 * (((op >> 5) & 15) - ((op >> 2) & 7)) - ((op & F_ST) ? 0 : 2);
#pragma unroll 1
          for (int k = 7; k < nk; k++) {
            probe1();
            wg_wait<1>();
            bi = ow(1, bi);
          }
        }
        if (!(op & F_ST)) {
          probe2();
          wg_wait<1>();
          if (wg) {
            wg_wait<0>();
            release(bi);
            bar_sync(2, 256);
          }
          bi0 = ow(2, 0);
          rdy0 = rdy1;
          const int b = ow(2, 0);
          if (!wg) asm volatile("bar.arrive 2, 256;" ::: "memory");
          wg_wait<4>();
          mbar_arrive_cluster_if(lane < 2 && !wg, empty_rem + bi);
          bi = b;
        }
        probe1();
        nop = prog[++pc];
        if (op & F_LD) {
          uint32_t t[80];
#pragma unroll
          for (int j = 0; j < 5; j++) {
            const int b = take(rdy0, SZ_PART, ad);
            probe1();
#pragma unroll
            for (int i = 4 * j; i < 4 * j + 4; i++)
              lds128(sbase + (ad - ring16 + img0) * 16 + ((i >> 1) & 1) * 8192 + (i & 1) * 512, t[4 * i], t[4 * i + 1], t[4 * i + 2], t[4 * i + 3]);
            release(b);
          }
          wg_wait<0>();
          fence_regs(c);
#pragma unroll
          for (int i = 0; i < 80; i++) c[i] += __uint_as_float(t[i]);
        }
        if (!(op & F_ST)) {
          wg_wait<0>();
          fence_regs(c);
          release(bi0);
          release(bi);
          goto finish;
        }
        op = nop;
        enter();
        bi0 = take(rdy0, SZ_WQ, ad);
        xw(ad, 0);
        pend = &g_part[((team * 4 + nt) * 2 + rank) * 5120 + img0];
        probe1();
        wg_wait<1>();
        fence_regs(c);
        release(bi);
        st_part(0); st_part(1);
        wg_wait<0>();
        release(bi0);
        bi0 = take(rdy0, SZ_WQ, ad);
        xw(ad, 1);
        st_part(2); st_part(3);
#pragma unroll
        for (int i = 0; i < 48; i++) q[i] = __float_as_uint(c[32 + i]);
        pend += 4 * 512;
        k = 1; lag = 2;
      }
    }
    rdy0 = false;
    {
      uint32_t t[48];
#pragma unroll
      for (int i = 0; i < 48; i++) t[i] = q[i] ^ P.zero;
      while ((op & 3) == OP_O) {
        int bi = ow(0, 0);
#pragma unroll 1
        for (int k = 1; k < 12 * (int)(((op >> 5) & 15) - ((op >> 2) & 7)); k++) {
          drain(t, k - 1);
          probe1();
          wg_wait<1>();
          bi = ow(1, bi);
        }
        rdy0 = false;
        wg_wait<0>();
        fence_regs(c);
        pc++;
        release(bi);
        if (!(op & F_ST)) goto finish;
        pend = &g_part[((((op >> 26) & 56) | ((op >> 9) & 7)) * 2 + rank) * 5120 + img0];
#pragma unroll
        for (int i = 6; i < 10; i++) st_part(i);
#pragma unroll
        for (int i = 0; i < 48; i++) t[i] = __float_as_uint(c[i]) ^ P.zero;
        op = prog[pc];
        enter();
      }
      for (int i = 0; i < 6; i++) drain(t, i);
    }
    if (false) {
    finish:
      uint32_t ad;
      take(rdy0, SZ_OUT, ad);
      const uint32_t wstage = sbase + (ad - ring16) * 16 + (wg * 4 + warp) * 5120;
      const uint32_t sa = wstage + (lane & 15) * 64;
#pragma unroll
      for (int i = 0; i < 10; i++) {
        const int u = (i & 1) * 2 + (lane >> 4);
        stsm4(sa + (i >> 1) * 1024 + ((u ^ ((lane >> 1) & 3)) << 4), pack_bf16(c[8 * i], c[8 * i + 1]), pack_bf16(c[8 * i + 2], c[8 * i + 3]),
              pack_bf16(c[8 * i + 4], c[8 * i + 5]), pack_bf16(c[8 * i + 6], c[8 * i + 7]));
      }
      asm volatile("fence.proxy.async.shared::cta;" ::: "memory");
      __syncwarp();
      if (lane == 0) {
        tma3d_store(&P.out, wstage, 0, (team & 7) * kSq + rank * 128 + wg * 64 + warp * 16, blk * 20 + nt * 5);
        asm volatile("cp.async.bulk.commit_group;\ncp.async.bulk.wait_group.read 0;" ::: "memory");
      }
    }
  }
}

typedef CUresult (*EncodeFn)(CUtensorMap*, CUtensorMapDataType, cuuint32_t, void*, const cuuint64_t*, const cuuint64_t*,
                             const cuuint32_t*, const cuuint32_t*, CUtensorMapInterleave, CUtensorMapSwizzle,
                             CUtensorMapL2promotion, CUtensorMapFloatOOBfill);

void encode(EncodeFn fn, CUtensorMap* m, const void* ptr, int rank, const cuuint64_t* dims, const cuuint64_t* strides,
            const cuuint32_t* box, CUtensorMapSwizzle swz) {
  const cuuint32_t es[5] = {1, 1, 1, 1, 1};
  CUresult r = fn(m, CU_TENSOR_MAP_DATA_TYPE_BFLOAT16, rank, const_cast<void*>(ptr), dims, strides, box, es,
                  CU_TENSOR_MAP_INTERLEAVE_NONE, swz, CU_TENSOR_MAP_L2_PROMOTION_L2_128B, CU_TENSOR_MAP_FLOAT_OOB_FILL_NONE);
  if (r != CUDA_SUCCESS) fprintf(stderr, "cuTensorMapEncodeTiled failed: %d\n", (int)r);
}

void annotate(uint32_t* ops, int n, bool helper) {
  uint32_t items = 0, cur = 0, pend = 0;
  auto item = [&](uint32_t bytes, int count, uint32_t bytes2 = 0) {
    for (int i = 0; i < count; i++) {
      if (cur + bytes > RING) cur = 0;
      cur += bytes;
      if (cur + bytes2 > RING) cur = 0;
      cur += bytes2;
      items++;
    }
  };
  for (int i = 0; i <= n; i++) {
    const uint32_t op = ops[i];
    ops[i] |= (items % (2 * NBAR)) << 15 | (cur >> 12) << 20 | pend << 26;
    if ((op & 3) == OP_Q) { item(SZ_WQ, 10, SZ_A); pend = (op & F_PARK) ? (helper ? 1 : 2) : 0; }
    if ((op & 3) == OP_A) {
      item(SZ_KV, (op & F_PARK) ? 30 : 31);
      if ((ops[i + 1] & 3) == OP_A) { item(SZ_PARK, 2); item(SZ_KV, 1); }
      item(SZ_KV, 1);
      pend = 1;
    }
    if ((op & 3) == OP_O) {
      item(SZ_A, 12 * (((op >> 5) & 15) - ((op >> 2) & 7)), SZ_WO);
      if (op & F_LD) item(SZ_PART, 5);
      pend = (op & F_ST) ? (helper ? 1 : 2) : 0;
    }
  }
}

void compile_programs(const char* const* text, bool helpers, Params& P) {
  struct Req { int when, team, wave, slot; } req[N_TEAM * MAX_PARK];
  int n_req = 0;
  for (int t = 0; t < N_TEAM; t++) {
    uint32_t* ops = P.ops[t];
    int n = 0, flags[8] = {0, 0, 0, 0, 0, 0, 0, 0}, n_park = 0, last_o = -1, when = 0, given = 0;
    for (const char* s = text[t]; *s; s++) {
      const int a = s[1] - '0';
      if (*s == 'Q' || (*s == 'H' && !helpers)) { ops[n++] = OP_Q | a << 2; when += 10; }
      else if (*s == 'P') { flags[a] = F_PARK; ops[n++] = OP_Q | a << 2 | flags[a]; when += 10; }
      else if (*s == 'H') { req[n_req++] = {when, t, a, n_park}; flags[a] = F_PARK | F_HELP | n_park++ << 10; }
      else if (*s == 'A') { ops[n++] = OP_A | a << 2 | flags[a]; when += 32; }
      else if (*s == 'G') { given = a; if (helpers) req[n_req++] = {1000, t, 0, -a}; }
      else if (*s == 'O') {
        ops[n] = OP_O | a << 2 | (s[2] - '0') << 5;
        if (given) ops[n] = helpers ? ops[n] | F_LD | F_PARK | (MAX_PARK - 1) << 10 : ops[n] & ~(7u << 2);
        if (last_o >= 0) { ops[last_o] |= F_ST; ops[n] |= F_LD; }
        last_o = n++;
        when += 10 * (s[2] - s[1]);
      }
    }
    for (int i = n; i < MAX_OPS; i++) ops[i] = OP_END;
    annotate(ops, n, false);
  }
  for (int i = 1; i < n_req; i++)
    for (int j = i; j > 0 && req[j].when < req[j - 1].when; j--) { Req r = req[j]; req[j] = req[j - 1]; req[j - 1] = r; }
  for (int h = 0; h < N_HELP; h++) {
    uint32_t* ops = P.ops[N_TEAM + 2 * h];
    int n = 0;
    for (int i = 0; i < n_req; i++)
      for (int m = h; m < 4; m += N_HELP) {
        const uint32_t ro = 4 * req[i].team + m;
        ops[n++] = req[i].slot >= 0 ? OP_Q | req[i].wave << 2 | req[i].team << 5 | F_PARK | req[i].slot << 10 | m << 12
                                    : OP_O | -req[i].slot << 5 | F_ST | (ro & 7) << 9 | (ro >> 3) << 29;
      }
    for (int i = n; i < 2 * MAX_OPS; i++) ops[i] = OP_END;
    annotate(ops, n, true);
  }
  for (int i = 0; i < 32; i++) P.first[i] = i < N_TEAM ? P.ops[i][0] : i < N_TEAM + N_HELP ? P.ops[2 * i - N_TEAM][0] : 0;
}

const char* const kPrograms[N_TEAM] = {
  "Q0A0Q1A1H2A2O03Q3A3Q4A4Q5A5Q6A6Q7A7O38",
  "Q0A0Q1A1Q2A2Q3A3O04Q4A4Q5A5Q6A6H7A7O48",
  "Q0A0H1A1Q2A2Q3A3Q4A4O05Q5A5Q6A6Q7A7O58",
  "Q0A0Q1A1Q2A2O03Q3A3Q4A4Q5A5Q6A6H7A7O38",
  "Q0A0Q1A1Q2A2O03Q3A3H4A4Q5A5Q6A6Q7A7O38",
  "Q0A0Q1A1H2A2Q3A3Q4A4O05Q5A5Q6A6Q7A7O58",
  "Q0A0Q1A1Q2A2Q3A3O03Q4A4H5A5Q6A6Q7A7O38",
  "Q0A0Q1A1Q2A2Q3A3Q4A4O05Q5A5Q6A6H7A7O58",
  "P3Q0A0Q1A1Q2A2A3H4A4Q5A5Q6A6Q7A7O08",
  "P5P7Q0A0Q1A1Q2A2H3A3Q4A4A5Q6A6A7G1O18",
  "Q0A0Q1A1Q2A2O02Q3A3H4A4Q5A5Q6A6Q7A7O28",
  "P3P5Q0A0Q1A1Q2A2A3Q4A4A5Q6A6H7A7O08",
  "Q0A0Q1A1Q2A2O02Q3A3Q4A4H5A5Q6A6Q7A7O28",
  "P7Q0A0Q1A1Q2A2Q3A3Q4A4Q5A5Q6A6A7G1O18",
  "P5Q0A0Q1A1Q2A2Q3A3Q4A4A5Q6A6H7A7O08",
  "Q0A0Q1A1Q2A2H3A3Q4A4Q5A5Q6A6Q7A7O08",
};

const char* const* bench_programs() {
  return kPrograms;
}

}

extern "C" void kernel_launch(void* const* d_in, const int* in_sizes, int n_in, void* d_out, int out_size) {
  (void)in_sizes; (void)n_in; (void)out_size;
  static EncodeFn fn = nullptr;
  static int n_clusters = 0;
  if (!fn) {
    cudaDriverEntryPointQueryResult qr;
    void* f = nullptr;
    cudaGetDriverEntryPoint("cuTensorMapEncodeTiled", &f, cudaEnableDefault, &qr);
    fn = (EncodeFn)f;
    cudaFuncSetAttribute(fused_kernel, cudaFuncAttributeMaxDynamicSharedMemorySize, SMEM_BYTES);
    cudaLaunchConfig_t cfg = {};
    cfg.gridDim = dim3(132); cfg.blockDim = dim3(384); cfg.dynamicSmemBytes = SMEM_BYTES;
    cudaLaunchAttribute at[1];
    at[0].id = cudaLaunchAttributeClusterDimension; at[0].val.clusterDim.x = 2; at[0].val.clusterDim.y = 1; at[0].val.clusterDim.z = 1;
    cfg.attrs = at; cfg.numAttrs = 1;
    if (cudaOccupancyMaxActiveClusters(&n_clusters, fused_kernel, &cfg) != cudaSuccess || n_clusters < 1) n_clusters = 1;
    (void)cudaGetLastError();
  }
  Params P;
  const CUtensorMapSwizzle S128 = CU_TENSOR_MAP_SWIZZLE_128B, S64 = CU_TENSOR_MAP_SWIZZLE_64B;
  for (int blk = 0; blk < 2; blk++) {
    void* const* in = d_in + 5 * blk;
    { const cuuint64_t d[] = {kD, kB * kSq}, s[] = {kD * 2}; const cuuint32_t b[] = {64, 128};
      encode(fn, &P.x[blk], in[0], 2, d, s, b, S128); }
    { const cuuint64_t d[] = {64, 8, 3, (cuuint64_t)kB * kH * kSk / 8}, s[] = {kDh * 2, 128, 8 * kDh * 2}; const cuuint32_t b[] = {64, 8, 3, 4};
      encode(fn, &P.kv[blk], in[1], 4, d, s, b, S128);
      encode(fn, &P.kv[blk + 2], in[2], 4, d, s, b, S128); }
    { const cuuint64_t d[] = {64, kD, kHD / 64}, s[] = {kHD * 2, 128}; const cuuint32_t b[] = {64, 32, 3};
      encode(fn, &P.wq[blk], in[3], 3, d, s, b, S128); }
    { const cuuint64_t d[] = {32, 2, kHD / 8, 4, kD / 32}, s[] = {kD * 2, 8 * kD * 2, 2 * kD * 2, 64}; const cuuint32_t b[] = {32, 2, 4, 4, 5};
      encode(fn, &P.wo[blk], in[4], 5, d, s, b, S64); }
  }
  { const cuuint64_t d[] = {32, kB * kSq, 2 * kD / 32}, s[] = {2 * kD * 2, 64}; const cuuint32_t b[] = {32, 16, 5};
    encode(fn, &P.out, d_out, 3, d, s, b, S64); }

  P.zero = 0;
  if (n_clusters >= N_CL) {
    const bool helpers = n_clusters >= N_CL + N_HELP;
    compile_programs(bench_programs(), helpers, P);
    fused_kernel<<<2 * (N_CL + (helpers ? N_HELP : 0)), 384, SMEM_BYTES>>>(P);
  } else {
    for (int phase = 0; phase < 2; phase++) {
      const char* text[N_TEAM];
      for (int t = 0; t < N_TEAM; t++) text[t] = phase ? "O08" : "Q0A0Q1A1Q2A2Q3A3Q4A4Q5A5Q6A6Q7A7";
      compile_programs(text, false, P);
      fused_kernel<<<2 * N_CL, 384, SMEM_BYTES>>>(P);
    }
  }
}
```

```cpp
#include <cuda_runtime.h>
#include <cuda_bf16.h>
#include <cuda.h>
#include <stdint.h>
#include <stdio.h>

namespace {

constexpr int kB = 8, kSq = 256, kD = 640, kH = 32, kSk = 1024, kDh = 192;
constexpr int kHD = kH * kDh;
constexpr uint32_t RING = 224 * 1024;
constexpr uint32_t SZ_KV = 24576;
constexpr uint32_t SZ_WQ = 24576, SZ_WO = 20480, SZ_A = 16384;
constexpr uint32_t SZ_OUT = 40960;
constexpr uint32_t SZ_PARK = 24576;
constexpr uint32_t SZ_PART = 16384;
constexpr int NBAR = 16;
constexpr int KV_TRANSIT = 4;
constexpr int EARLY = 3;
constexpr int S1A = 7;
constexpr uint32_t KV_CH = 64, KV_SBO = 3072;
constexpr int SMEM_BYTES = RING + 512 + 1024;
constexpr int N_TEAM = 16, N_CL = 64, N_HELP = 2, MAX_OPS = 24, MAX_PARK = 4;
enum { OP_END = 0, OP_Q = 1, OP_A = 2, OP_O = 3, F_PARK = 1 << 9, F_LD = 1 << 12, F_ST = 1 << 13, F_HELP = 1 << 12 };

struct alignas(64) Params {
  uint32_t first[32];
  CUtensorMap x[2], wq[2], kv[4], wo[2], out;
  uint32_t ops[N_TEAM + 2 * N_HELP][MAX_OPS];
  uint32_t zero;
};

__device__ uint4 g_o[N_TEAM * 2 * 96 * 1024];
__device__ uint4 g_part[N_CL * 2 * 5 * 1024];
__device__ unsigned int g_done[N_TEAM * 2 * 8];
__device__ unsigned int g_help[N_CL * 2 * MAX_PARK];
__device__ unsigned int g_seen[N_TEAM * 2 * 8];

template <int TB>
__device__ __forceinline__ void wgmma_rs_n64(float (&d)[32], uint32_t a0, uint32_t a1, uint32_t a2, uint32_t a3, uint64_t db, int scale_d) {
  asm volatile("{\n.reg .pred p;\nsetp.ne.b32 p, %37, 0;\n"
    "wgmma.mma_async.sync.aligned.m64n64k16.f32.bf16.bf16 {%0, %1, %2, %3, %4, %5, %6, %7, %8, %9, %10, %11, %12, %13, %14, %15, %16, %17, %18, %19, %20, %21, %22, %23, %24, %25, %26, %27, %28, %29, %30, %31}, {%32, %33, %34, %35}, %36, p, 1, 1, %38;\n}\n"
    : "+f"(d[0]), "+f"(d[1]), "+f"(d[2]), "+f"(d[3]), "+f"(d[4]), "+f"(d[5]), "+f"(d[6]), "+f"(d[7]), "+f"(d[8]), "+f"(d[9]), "+f"(d[10]), "+f"(d[11]), "+f"(d[12]), "+f"(d[13]), "+f"(d[14]), "+f"(d[15]), "+f"(d[16]), "+f"(d[17]), "+f"(d[18]), "+f"(d[19]), "+f"(d[20]), "+f"(d[21]), "+f"(d[22]), "+f"(d[23]), "+f"(d[24]), "+f"(d[25]), "+f"(d[26]), "+f"(d[27]), "+f"(d[28]), "+f"(d[29]), "+f"(d[30]), "+f"(d[31])
    : "r"(a0), "r"(a1), "r"(a2), "r"(a3), "l"(db), "r"(scale_d), "n"(TB));
}
template <int TB, int TA = 0>
__device__ __forceinline__ void wgmma_ss_n160(float (&d)[80], uint64_t da, uint64_t db, int scale_d) {
  asm volatile("{\n.reg .pred p;\nsetp.ne.b32 p, %82, 0;\n"
    "wgmma.mma_async.sync.aligned.m64n160k16.f32.bf16.bf16 {%0, %1, %2, %3, %4, %5, %6, %7, %8, %9, %10, %11, %12, %13, %14, %15, %16, %17, %18, %19, %20, %21, %22, %23, %24, %25, %26, %27, %28, %29, %30, %31, %32, %33, %34, %35, %36, %37, %38, %39, %40, %41, %42, %43, %44, %45, %46, %47, %48, %49, %50, %51, %52, %53, %54, %55, %56, %57, %58, %59, %60, %61, %62, %63, %64, %65, %66, %67, %68, %69, %70, %71, %72, %73, %74, %75, %76, %77, %78, %79}, %80, %81, p, 1, 1, %83, %84;\n}\n"
    : "+f"(d[0]), "+f"(d[1]), "+f"(d[2]), "+f"(d[3]), "+f"(d[4]), "+f"(d[5]), "+f"(d[6]), "+f"(d[7]), "+f"(d[8]), "+f"(d[9]), "+f"(d[10]), "+f"(d[11]), "+f"(d[12]), "+f"(d[13]), "+f"(d[14]), "+f"(d[15]), "+f"(d[16]), "+f"(d[17]), "+f"(d[18]), "+f"(d[19]), "+f"(d[20]), "+f"(d[21]), "+f"(d[22]), "+f"(d[23]), "+f"(d[24]), "+f"(d[25]), "+f"(d[26]), "+f"(d[27]), "+f"(d[28]), "+f"(d[29]), "+f"(d[30]), "+f"(d[31]), "+f"(d[32]), "+f"(d[33]), "+f"(d[34]), "+f"(d[35]), "+f"(d[36]), "+f"(d[37]), "+f"(d[38]), "+f"(d[39]), "+f"(d[40]), "+f"(d[41]), "+f"(d[42]), "+f"(d[43]), "+f"(d[44]), "+f"(d[45]), "+f"(d[46]), "+f"(d[47]), "+f"(d[48]), "+f"(d[49]), "+f"(d[50]), "+f"(d[51]), "+f"(d[52]), "+f"(d[53]), "+f"(d[54]), "+f"(d[55]), "+f"(d[56]), "+f"(d[57]), "+f"(d[58]), "+f"(d[59]), "+f"(d[60]), "+f"(d[61]), "+f"(d[62]), "+f"(d[63]), "+f"(d[64]), "+f"(d[65]), "+f"(d[66]), "+f"(d[67]), "+f"(d[68]), "+f"(d[69]), "+f"(d[70]), "+f"(d[71]), "+f"(d[72]), "+f"(d[73]), "+f"(d[74]), "+f"(d[75]), "+f"(d[76]), "+f"(d[77]), "+f"(d[78]), "+f"(d[79])
    : "l"(da), "l"(db), "r"(scale_d), "n"(TA), "n"(TB));
}
template <int TB, int TA = 0>
__device__ __forceinline__ void wgmma_ss_n192(float (&d)[96], uint64_t da, uint64_t db, int scale_d) {
  asm volatile("{\n.reg .pred p;\nsetp.ne.b32 p, %98, 0;\n"
    "wgmma.mma_async.sync.aligned.m64n192k16.f32.bf16.bf16 {%0, %1, %2, %3, %4, %5, %6, %7, %8, %9, %10, %11, %12, %13, %14, %15, %16, %17, %18, %19, %20, %21, %22, %23, %24, %25, %26, %27, %28, %29, %30, %31, %32, %33, %34, %35, %36, %37, %38, %39, %40, %41, %42, %43, %44, %45, %46, %47, %48, %49, %50, %51, %52, %53, %54, %55, %56, %57, %58, %59, %60, %61, %62, %63, %64, %65, %66, %67, %68, %69, %70, %71, %72, %73, %74, %75, %76, %77, %78, %79, %80, %81, %82, %83, %84, %85, %86, %87, %88, %89, %90, %91, %92, %93, %94, %95}, %96, %97, p, 1, 1, %99, %100;\n}\n"
    : "+f"(d[0]), "+f"(d[1]), "+f"(d[2]), "+f"(d[3]), "+f"(d[4]), "+f"(d[5]), "+f"(d[6]), "+f"(d[7]), "+f"(d[8]), "+f"(d[9]), "+f"(d[10]), "+f"(d[11]), "+f"(d[12]), "+f"(d[13]), "+f"(d[14]), "+f"(d[15]), "+f"(d[16]), "+f"(d[17]), "+f"(d[18]), "+f"(d[19]), "+f"(d[20]), "+f"(d[21]), "+f"(d[22]), "+f"(d[23]), "+f"(d[24]), "+f"(d[25]), "+f"(d[26]), "+f"(d[27]), "+f"(d[28]), "+f"(d[29]), "+f"(d[30]), "+f"(d[31]), "+f"(d[32]), "+f"(d[33]), "+f"(d[34]), "+f"(d[35]), "+f"(d[36]), "+f"(d[37]), "+f"(d[38]), "+f"(d[39]), "+f"(d[40]), "+f"(d[41]), "+f"(d[42]), "+f"(d[43]), "+f"(d[44]), "+f"(d[45]), "+f"(d[46]), "+f"(d[47]), "+f"(d[48]), "+f"(d[49]), "+f"(d[50]), "+f"(d[51]), "+f"(d[52]), "+f"(d[53]), "+f"(d[54]), "+f"(d[55]), "+f"(d[56]), "+f"(d[57]), "+f"(d[58]), "+f"(d[59]), "+f"(d[60]), "+f"(d[61]), "+f"(d[62]), "+f"(d[63]), "+f"(d[64]), "+f"(d[65]), "+f"(d[66]), "+f"(d[67]), "+f"(d[68]), "+f"(d[69]), "+f"(d[70]), "+f"(d[71]), "+f"(d[72]), "+f"(d[73]), "+f"(d[74]), "+f"(d[75]), "+f"(d[76]), "+f"(d[77]), "+f"(d[78]), "+f"(d[79]), "+f"(d[80]), "+f"(d[81]), "+f"(d[82]), "+f"(d[83]), "+f"(d[84]), "+f"(d[85]), "+f"(d[86]), "+f"(d[87]), "+f"(d[88]), "+f"(d[89]), "+f"(d[90]), "+f"(d[91]), "+f"(d[92]), "+f"(d[93]), "+f"(d[94]), "+f"(d[95])
    : "l"(da), "l"(db), "r"(scale_d), "n"(TA), "n"(TB));
}
template <int TB>
__device__ __forceinline__ void wgmma_rs_n192(float (&d)[96], uint32_t a0, uint32_t a1, uint32_t a2, uint32_t a3, uint64_t db, int scale_d) {
  asm volatile("{\n.reg .pred p;\nsetp.ne.b32 p, %101, 0;\n"
    "wgmma.mma_async.sync.aligned.m64n192k16.f32.bf16.bf16 {%0, %1, %2, %3, %4, %5, %6, %7, %8, %9, %10, %11, %12, %13, %14, %15, %16, %17, %18, %19, %20, %21, %22, %23, %24, %25, %26, %27, %28, %29, %30, %31, %32, %33, %34, %35, %36, %37, %38, %39, %40, %41, %42, %43, %44, %45, %46, %47, %48, %49, %50, %51, %52, %53, %54, %55, %56, %57, %58, %59, %60, %61, %62, %63, %64, %65, %66, %67, %68, %69, %70, %71, %72, %73, %74, %75, %76, %77, %78, %79, %80, %81, %82, %83, %84, %85, %86, %87, %88, %89, %90, %91, %92, %93, %94, %95}, {%96, %97, %98, %99}, %100, p, 1, 1, %102;\n}\n"
    : "+f"(d[0]), "+f"(d[1]), "+f"(d[2]), "+f"(d[3]), "+f"(d[4]), "+f"(d[5]), "+f"(d[6]), "+f"(d[7]), "+f"(d[8]), "+f"(d[9]), "+f"(d[10]), "+f"(d[11]), "+f"(d[12]), "+f"(d[13]), "+f"(d[14]), "+f"(d[15]), "+f"(d[16]), "+f"(d[17]), "+f"(d[18]), "+f"(d[19]), "+f"(d[20]), "+f"(d[21]), "+f"(d[22]), "+f"(d[23]), "+f"(d[24]), "+f"(d[25]), "+f"(d[26]), "+f"(d[27]), "+f"(d[28]), "+f"(d[29]), "+f"(d[30]), "+f"(d[31]), "+f"(d[32]), "+f"(d[33]), "+f"(d[34]), "+f"(d[35]), "+f"(d[36]), "+f"(d[37]), "+f"(d[38]), "+f"(d[39]), "+f"(d[40]), "+f"(d[41]), "+f"(d[42]), "+f"(d[43]), "+f"(d[44]), "+f"(d[45]), "+f"(d[46]), "+f"(d[47]), "+f"(d[48]), "+f"(d[49]), "+f"(d[50]), "+f"(d[51]), "+f"(d[52]), "+f"(d[53]), "+f"(d[54]), "+f"(d[55]), "+f"(d[56]), "+f"(d[57]), "+f"(d[58]), "+f"(d[59]), "+f"(d[60]), "+f"(d[61]), "+f"(d[62]), "+f"(d[63]), "+f"(d[64]), "+f"(d[65]), "+f"(d[66]), "+f"(d[67]), "+f"(d[68]), "+f"(d[69]), "+f"(d[70]), "+f"(d[71]), "+f"(d[72]), "+f"(d[73]), "+f"(d[74]), "+f"(d[75]), "+f"(d[76]), "+f"(d[77]), "+f"(d[78]), "+f"(d[79]), "+f"(d[80]), "+f"(d[81]), "+f"(d[82]), "+f"(d[83]), "+f"(d[84]), "+f"(d[85]), "+f"(d[86]), "+f"(d[87]), "+f"(d[88]), "+f"(d[89]), "+f"(d[90]), "+f"(d[91]), "+f"(d[92]), "+f"(d[93]), "+f"(d[94]), "+f"(d[95])
    : "r"(a0), "r"(a1), "r"(a2), "r"(a3), "l"(db), "r"(scale_d), "n"(TB));
}

__device__ __forceinline__ uint32_t smem_u32(const void* p) { return (uint32_t)__cvta_generic_to_shared(p); }
__device__ __forceinline__ void wg_fence() { asm volatile("wgmma.fence.sync.aligned;" ::: "memory"); }
__device__ __forceinline__ void wg_commit() { asm volatile("wgmma.commit_group.sync.aligned;" ::: "memory"); }
template <int N> __device__ __forceinline__ void wg_wait() { asm volatile("wgmma.wait_group.sync.aligned %0;" ::"n"(N) : "memory"); }
__device__ __forceinline__ void sched_fence(int& keep, uint32_t zero) {
  asm volatile("{\n.reg .u32 c;\nmov.u32 c, %%clock;\nand.b32 c, c, %1;\nxor.b32 %0, %0, c;\n}\n" : "+r"(keep) : "r"(zero) : "memory");
}
template <int N> __device__ __forceinline__ void fence_regs(float (&r)[N]) {
#pragma unroll
  for (int i = 0; i < N; i++) asm volatile("" : "+f"(r[i])::"memory");
}
template <int N> __device__ __forceinline__ void fence_regs(uint32_t (&r)[N]) {
#pragma unroll
  for (int i = 0; i < N; i++) asm volatile("" : "+r"(r[i])::"memory");
}
__device__ __forceinline__ uint64_t mk_desc(uint32_t a16, uint32_t lbo, uint32_t sbo, uint32_t swz, uint32_t off = 0) {
  uint64_t d;
  asm("mov.b64 %0, {%1, %2};" : "=l"(d) : "r"(a16), "r"((sbo >> 4) | (swz << 30)));
  return d + (off + ((lbo >> 4) << 16));
}
__device__ __forceinline__ void mbar_init(uint32_t bar, uint32_t cnt) {
  asm volatile("mbarrier.init.shared::cta.b64 [%0], %1;" ::"r"(bar), "r"(cnt) : "memory");
}
__device__ __forceinline__ void mbar_expect(uint32_t bar, uint32_t tx) {
  asm volatile("mbarrier.arrive.expect_tx.shared::cta.b64 _, [%0], %1;" ::"r"(bar), "r"(tx) : "memory");
}
__device__ __forceinline__ bool mbar_test(uint32_t bar, uint32_t ph) {
  uint32_t ok;
  asm volatile("{\n.reg .pred p;\nmbarrier.test_wait.parity.shared::cta.b64 p, [%1], %2;\nselp.u32 %0, 1, 0, p;\n}\n"
               : "=r"(ok) : "r"(bar), "r"(ph) : "memory");
  return ok;
}
__device__ __forceinline__ void mbar_wait(uint32_t bar, uint32_t ph) {
  asm volatile("{\n.reg .pred p;\n.reg .u32 n;\nmov.u32 n, 0;\n"
               "LOOP:\nadd.u32 n, n, 1;\nmbarrier.try_wait.parity.shared::cta.b64 p, [%0], %1;\n@p bra DONE;\n"
               "setp.lt.u32 p, n, 0x1000000;\n@p bra LOOP;\ntrap;\n"
               "DONE:\n}\n" ::"r"(bar), "r"(ph) : "memory");
}
__device__ __forceinline__ void mbar_wait_math(uint32_t bar, uint32_t ph) {
  asm volatile("{\n.reg .pred p;\nLOOP:\nmbarrier.try_wait.parity.shared::cta.b64 p, [%0], %1;\n@!p bra LOOP;\n}\n" ::"r"(bar), "r"(ph) : "memory");
}
__device__ __forceinline__ void mbar_wait_long(uint32_t bar, uint32_t ph) {
  asm volatile("{\n.reg .pred p;\n.reg .u32 n;\nmov.u32 n, 0;\n"
               "LOOP:\nmbarrier.try_wait.parity.shared::cta.b64 p, [%0], %1, %2;\n@p bra DONE;\n"
               "add.u32 n, n, 1;\nsetp.lt.u32 p, n, 0x40000;\n@p bra LOOP;\ntrap;\n"
               "DONE:\n}\n" ::"r"(bar), "r"(ph), "r"(20000) : "memory");
}
__device__ __forceinline__ void mbar_arrive_cluster_if(bool on, uint32_t addr) {
  asm volatile("{\n.reg .pred p;\nsetp.ne.b32 p, %1, 0;\n@p mbarrier.arrive.shared::cluster.b64 _, [%0];\n}\n" ::"r"(addr), "r"((int)on) : "memory");
}
__device__ __forceinline__ void mbar_arrive_if(bool on, uint32_t addr) {
  asm volatile("{\n.reg .pred p;\nsetp.ne.b32 p, %1, 0;\n@p mbarrier.arrive.shared::cta.b64 _, [%0];\n}\n" ::"r"(addr), "r"((int)on) : "memory");
}
__device__ __forceinline__ void tma2d(uint32_t dst, const CUtensorMap* m, uint32_t bar, int c0, int c1) {
  asm volatile("cp.async.bulk.tensor.2d.shared::cluster.global.mbarrier::complete_tx::bytes [%0], [%1, {%3, %4}], [%2];"
               ::"r"(dst), "l"(m), "r"(bar), "r"(c0), "r"(c1) : "memory");
}
__device__ __forceinline__ void tma3d(uint32_t dst, const CUtensorMap* m, uint32_t bar, int c0, int c1, int c2) {
  asm volatile("cp.async.bulk.tensor.3d.shared::cluster.global.mbarrier::complete_tx::bytes [%0], [%1, {%3, %4, %5}], [%2];"
               ::"r"(dst), "l"(m), "r"(bar), "r"(c0), "r"(c1), "r"(c2) : "memory");
}
__device__ __forceinline__ void tma3d_mc(uint32_t dst, const CUtensorMap* m, uint32_t bar, int c0, int c1, int c2) {
  asm volatile("cp.async.bulk.tensor.3d.shared::cluster.global.mbarrier::complete_tx::bytes.multicast::cluster"
               " [%0], [%1, {%3, %4, %5}], [%2], %6;"
               ::"r"(dst), "l"(m), "r"(bar), "r"(c0), "r"(c1), "r"(c2), "h"((uint16_t)3) : "memory");
}
__device__ __forceinline__ void tma3d_store(const CUtensorMap* m, uint32_t src, int c0, int c1, int c2) {
  asm volatile("cp.async.bulk.tensor.3d.global.shared::cta.bulk_group [%0, {%2, %3, %4}], [%1];"
               ::"l"(m), "r"(src), "r"(c0), "r"(c1), "r"(c2) : "memory");
}
__device__ __forceinline__ void bar_sync(int id, int n) { asm volatile("bar.sync %0, %1;" ::"r"(id), "r"(n) : "memory"); }
__device__ __forceinline__ uint32_t pack_bf16(float lo, float hi) {
  uint32_t r;
  asm("cvt.rn.bf16x2.f32 %0, %1, %2;" : "=r"(r) : "f"(hi), "f"(lo));
  return r;
}
__device__ __forceinline__ float ex2(float x) {
  float y;
  asm("ex2.approx.ftz.f32 %0, %1;" : "=f"(y) : "f"(x));
  return y;
}
__device__ __forceinline__ float fadd(float a, float b) {
  float y;
  asm("add.f32 %0, %1, %2;" : "=f"(y) : "f"(a), "f"(b));
  return y;
}
__device__ __forceinline__ float rcp(float x) {
  float y;
  asm("rcp.approx.ftz.f32 %0, %1;" : "=f"(y) : "f"(x));
  return y;
}
__device__ __forceinline__ void stsm4(uint32_t addr, uint32_t a, uint32_t b, uint32_t c, uint32_t d) {
  asm volatile("stmatrix.sync.aligned.m8n8.x4.shared.b16 [%0], {%1, %2, %3, %4};" ::"r"(addr), "r"(a), "r"(b), "r"(c), "r"(d) : "memory");
}

__device__ __forceinline__ void tma4d_mc_hint(uint32_t dst, const CUtensorMap* m, uint32_t bar, int c3, uint64_t pol) {
  asm volatile("cp.async.bulk.tensor.4d.shared::cluster.global.mbarrier::complete_tx::bytes.multicast::cluster.L2::cache_hint"
               " [%0], [%1, {%3, %3, %3, %4}], [%2], %5, %6;"
               ::"r"(dst), "l"(m), "r"(bar), "r"(0), "r"(c3), "h"((uint16_t)3), "l"(pol) : "memory");
}
__device__ __forceinline__ void tma5d_mc(uint32_t dst, const CUtensorMap* m, uint32_t bar, int c2, int c4) {
  asm volatile("cp.async.bulk.tensor.5d.shared::cluster.global.mbarrier::complete_tx::bytes.multicast::cluster"
               " [%0], [%1, {%3, %3, %4, %3, %5}], [%2], %6;"
               ::"r"(dst), "l"(m), "r"(bar), "r"(0), "r"(c2), "r"(c4), "h"((uint16_t)3) : "memory");
}
__device__ __forceinline__ void bulk_load_hint(uint32_t dst, const void* src, uint32_t bytes, uint32_t bar, uint64_t pol) {
  asm volatile("cp.async.bulk.shared::cluster.global.mbarrier::complete_tx::bytes.L2::cache_hint [%0], [%1], %2, [%3], %4;"
               ::"r"(dst), "l"(src), "r"(bytes), "r"(bar), "l"(pol) : "memory");
}
__device__ __forceinline__ void stg2_if(bool on, void* p, uint32_t a, uint32_t b, uint32_t c, uint32_t d, uint32_t e, uint32_t f,
                                        uint32_t g, uint32_t h, uint64_t pol) {
  asm volatile("{\n.reg .pred p;\nsetp.ne.b32 p, %10, 0;\n"
               "@p st.global.L2::cache_hint.v4.b32 [%0], {%1, %2, %3, %4}, %9;\n"
               "@p st.global.L2::cache_hint.v4.b32 [%0 + 512], {%5, %6, %7, %8}, %9;\n}\n"
               ::"l"(p), "r"(a), "r"(b), "r"(c), "r"(d), "r"(e), "r"(f), "r"(g), "r"(h), "l"(pol), "r"((int)on) : "memory");
}
__device__ __forceinline__ uint64_t evict_first() {
  uint64_t p;
  asm("createpolicy.fractional.L2::evict_first.b64 %0, 1.0;" : "=l"(p));
  return p;
}
__device__ __forceinline__ bool elect() {
  uint32_t ok;
  asm volatile("{\n.reg .pred p;\nelect.sync _|p, 0xffffffff;\nselp.u32 %0, 1, 0, p;\n}\n" : "=r"(ok));
  return ok;
}
__device__ __forceinline__ void mbar_arrive(uint32_t bar) {
  asm volatile("mbarrier.arrive.shared::cta.b64 _, [%0];" ::"r"(bar) : "memory");
}
template <int OFF> __device__ __forceinline__ void lds2_if(bool on, uint32_t p, uint32_t* r) {
  asm volatile("{\n.reg .pred p;\nsetp.ne.b32 p, %9, 0;\n@p ld.shared.v4.b32 {%0, %1, %2, %3}, [%8 + %10];\n"
               "@p ld.shared.v4.b32 {%4, %5, %6, %7}, [%8 + %11];\n}\n"
               : "+r"(r[0]), "+r"(r[1]), "+r"(r[2]), "+r"(r[3]), "+r"(r[4]), "+r"(r[5]), "+r"(r[6]), "+r"(r[7])
               : "r"(p), "r"((int)on), "n"(OFF), "n"(OFF + 512) : "memory");
}
__device__ __forceinline__ void lds128(uint32_t p, uint32_t& a, uint32_t& b, uint32_t& c, uint32_t& d) {
  asm volatile("ld.shared.v4.b32 {%0, %1, %2, %3}, [%4];" : "=r"(a), "=r"(b), "=r"(c), "=r"(d) : "r"(p) : "memory");
}
__device__ __forceinline__ void wait_count(const unsigned int* p, uint32_t target) {
  asm volatile("{\n.reg .pred p;\n.reg .u32 n, v;\nmov.u32 n, 0;\n"
               "LOOP:\nld.acquire.gpu.global.u32 v, [%0];\nsetp.ge.u32 p, v, %1;\n@p bra DONE;\n"
               "nanosleep.u32 %2;\nadd.u32 n, n, 1;\nsetp.lt.u32 p, n, 0x400000;\n@p bra LOOP;\ntrap;\n"
               "DONE:\n}\n" ::"l"(p), "r"(target), "n"(300) : "memory");
}

__device__ __forceinline__ int o_wave(int a, int b, int i) {
  const int p = min(3, b - a - 1);
  return i < p ? b - 2 - i : i == p ? b - 1 : b - 1 - i;
}

struct Cursor {
  uint32_t n;
  __device__ __forceinline__ uint32_t off() const { return n & (8 * NBAR - 8); }
  __device__ __forceinline__ uint32_t ph() const { return (n / (8 * NBAR)) & 1; }
  __device__ __forceinline__ void next() { n += 8; }
};

constexpr float kScaleLog2 = 0.07216878364870322f * 1.4426950408889634f;
constexpr float kSumLimit = 1048576.0f;
constexpr float kMaxLag = 8.0f;

__global__ void __cluster_dims__(2, 1, 1) __launch_bounds__(384, 1)
fused_kernel(const __grid_constant__ Params P) {
  extern __shared__ uint8_t smem_raw[];
  const uint32_t sbase = (smem_u32(smem_raw) + 1023) & ~1023u;
  const uint32_t full0 = sbase + RING, empty0 = full0 + 8 * NBAR, odone = empty0 + 8 * NBAR, oready0 = odone + 8;
  const uint32_t fenced = oready0 + 64, hready0 = fenced + 8;
  const uint32_t rank = blockIdx.x & 1;
  const int role = blockIdx.x >> 1;
  const bool helper = role >= N_CL;
  const int team = helper ? 0 : role >> 2, nt = role & 3, blk = team >> 3;
  const uint32_t* prog = P.ops[helper ? N_TEAM + 2 * (role - N_CL) : team];
  auto q_role = [&](uint32_t op) { return helper ? (int)(((op >> 3) & 60) | ((op >> 12) & 3)) : role; };
  auto o_role = [&](uint32_t op) { return helper ? (int)(((op >> 26) & 56) | ((op >> 9) & 7)) : role; };
  const int wid = __shfl_sync(0xffffffffu, (int)(threadIdx.x >> 5), 0);
  const int wg = wid >> 2;

  const uint32_t op0 = P.first[helper ? N_TEAM + role - N_CL : team];
  if (__builtin_expect(wid == 8, 1)) {
    if (elect()) {
#pragma unroll
      for (int k = 0; k < EARLY; k++) mbar_init(full0 + 8 * k, 1);
      asm volatile("fence.mbarrier_init.release.cluster;" ::: "memory");
      if ((op0 & 3) == OP_Q) {
        const int qr = q_role(op0);
#pragma unroll
        for (int k = 0; k < EARLY; k++) {
          mbar_expect(full0 + 8 * k, SZ_WQ + SZ_A);
          tma2d(sbase + k * (SZ_WQ + SZ_A) + SZ_WQ, &P.x[qr >> 5], full0 + 8 * k, 64 * k, ((qr >> 2) & 7) * kSq + rank * 128);
          tma3d(sbase + k * (SZ_WQ + SZ_A), &P.wq[qr >> 5], full0 + 8 * k, 0, 64 * k, 3 * (4 * ((op0 >> 2) & 7) + (qr & 3)));
          tma3d(sbase + k * (SZ_WQ + SZ_A) + SZ_WQ / 2, &P.wq[qr >> 5], full0 + 8 * k, 0, 64 * k + 32, 3 * (4 * ((op0 >> 2) & 7) + (qr & 3)));
        }
      }
      asm volatile("prefetch.tensormap [%0];" ::"l"(&P.kv[blk]) : "memory");
      asm volatile("prefetch.tensormap [%0];" ::"l"(&P.kv[blk + 2]) : "memory");
    }
  } else if (threadIdx.x == 0) {
#pragma unroll
    for (int i = EARLY; i < 2 * NBAR + 10 + MAX_PARK; i++) mbar_init(full0 + 8 * i, i >= NBAR && i <= 2 * NBAR ? 16 : 1);
    asm volatile("fence.mbarrier_init.release.cluster;" ::: "memory");
  }
  __syncwarp();
  asm volatile("barrier.cluster.arrive.relaxed.aligned;\nbarrier.cluster.wait.aligned;" ::: "memory");

  if (wg == 2) {
    asm volatile("setmaxnreg.dec.sync.aligned.u32 24;");
    if (wid == 8) {
      Cursor tail{0u - 8}, head{0};
      int sh = 0;
      uint32_t cur = 0, used = 0;
      uint64_t fifo = 0;
      uint32_t oready = oready0;
      const uint64_t pol = evict_first();
      struct Load { uint32_t dst, bar, wbar, wph; int c0; const void* ptr; bool wait; };
      auto reserve = [&](uint32_t bytes, bool last, uint32_t half, int c0, const void* ptr) {
        uint32_t fp = bytes >> 12;
        if (cur + fp > (RING >> 12)) { fp += (RING >> 12) - cur; cur = 0; }
        used += fp;
        bool wait = false;
        while (used > (RING >> 12)) {
          wait = true;
          tail.next();
          used -= (uint32_t)fifo & 31;
          fifo >>= 5;
          sh -= 5;
        }
        fifo += (uint64_t)fp << sh;
        Load l{sbase + (cur << 12) + rank * half, full0 + head.off(), empty0 + tail.off(), tail.ph(), c0, ptr, wait};
        cur += bytes >> 12;
        sh += last ? 5 : 0;
        head.n += last ? 8 : 0;
        asm volatile("" : "+r"(l.dst), "+r"(l.bar), "+r"(l.c0), "+l"(l.ptr), "+r"(l.wbar), "+r"(l.wph));
        return l;
      };
      auto vacated = [&](const Load& l) { if (l.wait) mbar_wait(l.wbar, l.wph); };
      auto written = [&](uint32_t flag) {
        mbar_wait(flag, 0);
        asm volatile("fence.proxy.async.global;" ::: "memory");
      };
      for (int pc = 0;; pc++) {
        const uint32_t op = prog[pc];
        const int type = op & 3, a = (op >> 2) & 7;
        if (type == OP_END) break;
        if (type == OP_Q) {
          const int qr = q_role(op);
          const CUtensorMap *mw = &P.wq[qr >> 5], *mx = &P.x[qr >> 5];
          asm volatile("" : "+l"(mw), "+l"(mx));
          auto res_w = [&](int k) { return reserve(SZ_WQ, false, SZ_WQ / 2, 64 * k + 32 * rank, mw); };
          auto load_w = [&](const Load& w, int k) {
            vacated(w);
            if ((pc > 0 || k >= EARLY) && elect()) tma3d_mc(w.dst, (const CUtensorMap*)w.ptr, w.bar, 0, w.c0, 3 * (4 * a + (qr & 3)));
          };
          auto load_x = [&](const Load& x, int k) {
            vacated(x);
            if ((pc > 0 || k >= EARLY) && elect()) {
              tma2d(x.dst, (const CUtensorMap*)x.ptr, x.bar, x.c0, ((qr >> 2) & 7) * kSq + rank * 128);
              mbar_expect(x.bar, SZ_WQ + SZ_A);
            }
          };
#pragma unroll 1
          for (int k = 0; k < 10; k++) {
            load_w(res_w(k), k);
            load_x(reserve(SZ_A, true, 0, 64 * k, mx), k);
          }
        } else if (type == OP_A) {
          const uint32_t nop = prog[pc + 1];
          const int row8 = ((team & 7) * kH + nt) * (kSk / 8) + 4 * rank, wave8 = 4 * (kSk / 8);
          auto transit = [&]() {
            const Cursor c{head.n - 8 * (KV_TRANSIT + 1)};
            mbar_wait(full0 + c.off(), c.ph());
          };
          const char* map = (const char*)&P.kv[blk];
          asm volatile("" : "+l"(map));
          int t = (op & F_PARK) ? 1 : 0, c0 = row8 + a * wave8 + 8 * t, isv = 0;
#pragma unroll 1
          for (; t < 31; t++) {
            const Load l = reserve(SZ_KV, true, SZ_KV / 2, c0, map + isv);
            vacated(l);
            if (t >= KV_TRANSIT) transit();
            if (elect()) {
              tma4d_mc_hint(l.dst, (const CUtensorMap*)l.ptr, l.bar, l.c0, pol);
              mbar_expect(l.bar, SZ_KV);
            }
            isv = (t & 1) << 8;
            c0 += isv ? -8 : t ? 16 : 8;
          }
          const int next = (nop >> 2) & 7;
          if ((nop & 3) == OP_A) written((nop & F_HELP) ? hready0 + 8 * ((nop >> 10) & 3) : fenced);
#pragma unroll 1
          for (int i = (nop & 3) == OP_A ? 0 : 3; i < 4; i++) {
            const Load l = reserve(SZ_KV, true, i < 2 ? 0 : SZ_KV / 2, i == 3 ? c0 - 8 : row8 + next * wave8,
                                   i < 2 ? (const char*)&g_o[((team * 2 + rank) * 96 + 3 * (4 * next + nt)) * 1024 + i * (SZ_PARK / 16)] : map + ((i & 1) << 8));
            vacated(l);
            if (i < 2) {
              if (elect()) bulk_load_hint(l.dst, l.ptr, SZ_PARK, l.bar, pol);
              __syncwarp();
            } else {
              transit();
              if (elect()) tma4d_mc_hint(l.dst, (const CUtensorMap*)l.ptr, l.bar, l.c0, pol);
              __syncwarp();
            }
            if (elect()) mbar_expect(l.bar, SZ_KV);
          }
        } else {
          const int b = (op >> 5) & 15, ro = o_role(op);
          const CUtensorMap* mw = &P.wo[ro >> 5];
          const uint4* so = &g_o[((ro >> 2) * 2 + rank) * 96 * 1024];
          asm volatile("" : "+l"(mw), "+l"(so));
#pragma unroll 1
          for (int j = 0; j < b - a; j++) {
            const int w = o_wave(a, b, j);
            written(oready);
            oready += 8;
#pragma unroll 1
            for (int k = 12 * w; k < 12 * w + 12; k++) {
              const Load o = reserve(SZ_A, false, 0, 0, so + k * 1024);
              vacated(o);
              if (elect()) bulk_load_hint(o.dst, o.ptr, SZ_A, o.bar, pol);
              const Load w = reserve(SZ_WO, true, SZ_WO / 2, 8 * k + 4 * rank, mw);
              vacated(w);
              if (elect()) {
                tma5d_mc(w.dst, (const CUtensorMap*)w.ptr, w.bar, w.c0, 5 * (ro & 3));
                mbar_expect(w.bar, SZ_WO + SZ_A);
              }
            }
          }
          if ((op & F_LD) && (op & F_PARK)) written(hready0 + 8 * (MAX_PARK - 1));
#pragma unroll 1
          for (int i = (op & F_LD) ? 0 : 5; i < ((op & F_ST) ? 5 : 6); i++) {
            const Load l = reserve(i < 5 ? SZ_PART : SZ_OUT, i < 5, 0, 0, &g_part[(role * 2 + rank) * 5120 + i * (SZ_PART / 16)]);
            vacated(l);
            if (i < 5 && elect()) bulk_load_hint(l.dst, l.ptr, SZ_PART, l.bar, pol);
            if (elect()) mbar_expect(l.bar, i < 5 ? SZ_PART : 0);
          }
        }
      }
#pragma unroll 1
      for (Cursor c{head.n - 8 * NBAR}; c.n != head.n; c.next()) mbar_wait(empty0 + c.off(), c.ph());
    } else if (threadIdx.x == 288) {
      uint32_t ph = 0;
      bool first = true;
      for (int pc = 0;; pc++) {
        const uint32_t op = prog[pc];
        if ((op & 3) == OP_END) break;
        if ((op & 3) != OP_A && !helper) continue;
        mbar_wait_long(odone, ph);
        ph ^= 1;
        unsigned int* flag = !helper ? &g_done[(team * 2 + rank) * 8 + ((op >> 2) & 7)]
                             : (op & 3) == OP_Q ? &g_help[(q_role(op) * 2 + rank) * MAX_PARK + ((op >> 10) & 3)]
                                                : &g_help[(o_role(op) * 2 + rank) * MAX_PARK + MAX_PARK - 1];
        asm volatile("red.release.gpu.global.add.u32 [%0], 1;" ::"l"(flag) : "memory");
        if (first) mbar_arrive(fenced);
        first = false;
      }
    } else if (threadIdx.x == 320) {
      uint32_t oready = oready0;
      for (int pc = 0;; pc++) {
        const uint32_t op = prog[pc];
        if ((op & 3) == OP_END) break;
        if ((op & 3) == OP_O) {
          const int a = (op >> 2) & 7, b = (op >> 5) & 15;
#pragma unroll 1
          for (int i = 0; i < b - a; i++) {
            const int ci = ((o_role(op) >> 2) * 2 + rank) * 8 + o_wave(a, b, i);
            wait_count(&g_done[ci], 4);
            mbar_arrive(oready);
            oready += 8;
            if (atomicAdd(&g_seen[ci], 1u) == 3u) { g_seen[ci] = 0; g_done[ci] = 0; }
          }
        }
        if ((op & 3) != OP_Q && (op & F_HELP) && (op & F_PARK)) {
          unsigned int* flag = &g_help[(role * 2 + rank) * MAX_PARK + ((op >> 10) & 3)];
          wait_count(flag, 1);
          mbar_arrive(hready0 + 8 * ((op >> 10) & 3));
          *flag = 0;
        }
      }
    }
  } else {
    asm volatile("setmaxnreg.inc.sync.aligned.u32 240;");
    const int lane = threadIdx.x & 31, warp = wid & 3;
    uint32_t empty_rem;
    asm volatile("mapa.shared::cluster.u32 %0, %1, %2;" : "=r"(empty_rem) : "r"(empty0), "r"(lane & 1));
    auto release = [&](int slot) { mbar_arrive_cluster_if(lane < 2, empty_rem + slot); };
    Cursor r{0};
    const uint32_t ring16 = (sbase & 0x3FFFF) >> 4;
    uint32_t cur = ring16;
    bool rdy0 = false, rdy1 = false;
    auto probe1 = [&]() { rdy0 = mbar_test(full0 + r.off(), r.ph()); };
    auto probe2 = [&]() {
      Cursor n = r;
      rdy0 = mbar_test(full0 + n.off(), n.ph());
      n.next();
      rdy1 = mbar_test(full0 + n.off(), n.ph());
    };
    auto take = [&](bool rdy, uint32_t bytes, uint32_t& addr) {
      const int bi = r.off();
      if (!__all_sync(0xffffffffu, rdy)) mbar_wait_math(full0 + r.off(), r.ph());
      r.next();
      if (cur > ring16 + ((RING - bytes) >> 4)) cur = ring16;
      addr = cur;
      cur += bytes >> 4;
      return bi;
    };
    auto at = [&](uint32_t a16) {
      uint32_t a = sbase + (a16 - ring16) * 16;
      asm("" : "+r"(a));
      return a;
    };
    auto second = [&](uint32_t bytes) {
      if (cur > ring16 + ((RING - bytes) >> 4)) cur = ring16;
      cur += bytes >> 4;
      return cur - (bytes >> 4);
    };
    const int row = wg * 64 + warp * 16 + (lane >> 2);
    int img0 = (row * 4 + ((lane & 3) ^ ((row >> 1) & 3))) * 16;
    uint4* pend = nullptr;
    const uint64_t spol = evict_first();
    int pc = 0;
    uint32_t op = prog[0];
    auto enter = [&]() {
      r.n = op >> 12; cur = ring16 + (((op >> 20) & 63) << 8);
    };
    auto drain = [&](uint32_t (&t)[48], uint32_t c) {
      if (!(op & (3u << 26)) || c >= 6) return;
#pragma unroll
      for (int i = 0; i < 6; i++)
        stg2_if(c == i, pend + i * 512, t[8 * i], t[8 * i + 1], t[8 * i + 2], t[8 * i + 3],
                t[8 * i + 4], t[8 * i + 5], t[8 * i + 6], t[8 * i + 7], spol);
      if ((op & (1u << 26)) && c == 5) {
        __syncwarp();
        mbar_arrive_if(lane < 2, odone);
      }
    };
    float s[32], o[96], c[80];
    uint32_t q[48], pa[16], pb[16];
    float mc0, mc1, l0, l1;
    bool gen;
    auto soft = [&](float (&s)[32], uint32_t (&pout)[16], bool first) {
      if (first) { gen = false; mc0 = 0.f; mc1 = 0.f; }
      float b0, b1;
      for (;;) {
        if (gen) {
          float m0 = fmaxf(s[0], s[1]), m1 = fmaxf(s[2], s[3]);
#pragma unroll
          for (int i = 1; i < 8; i++) { m0 = fmaxf(m0, fmaxf(s[4 * i], s[4 * i + 1])); m1 = fmaxf(m1, fmaxf(s[4 * i + 2], s[4 * i + 3])); }
          m0 = fmaxf(m0, __shfl_xor_sync(0xffffffffu, m0, 1)); m1 = fmaxf(m1, __shfl_xor_sync(0xffffffffu, m1, 1));
          m0 = fmaxf(m0, __shfl_xor_sync(0xffffffffu, m0, 2)); m1 = fmaxf(m1, __shfl_xor_sync(0xffffffffu, m1, 2));
          if (first) {
            mc0 = m0; mc1 = m1;
          } else if (__any_sync(0xffffffffu, !(m0 <= mc0 + kMaxLag && m1 <= mc1 + kMaxLag))) {
            m0 = fmaxf(mc0, m0); m1 = fmaxf(mc1, m1);
            const float a0 = ex2(mc0 - m0), a1 = ex2(mc1 - m1);
            mc0 = m0; mc1 = m1;
            l0 *= a0; l1 *= a1;
            wg_wait<0>();
            fence_regs(o);
#pragma unroll
            for (int i = 0; i < 96; i++) o[i] *= i & 2 ? a1 : a0;
          }
#pragma unroll
          for (int i = 0; i < 32; i++) s[i] -= i & 2 ? mc1 : mc0;
        }
#pragma unroll
        for (int i = 0; i < 8; i++) {
          const float e1 = ex2(s[4 * i + 1]), e0 = ex2(s[4 * i]), e3 = ex2(s[4 * i + 3]), e2 = ex2(s[4 * i + 2]);
          pout[2 * i] = pack_bf16(e0, e1);
          b0 = i ? b0 + fadd(e1, e0) : fadd(e1, e0);
          pout[2 * i + 1] = pack_bf16(e2, e3);
          b1 = i ? b1 + fadd(e3, e2) : fadd(e3, e2);
        }
        if (!__any_sync(0xffffffffu, !gen && !(fmaxf(b0, b1) <= kSumLimit && (!first || fminf(b0, b1) >= 1.0f / kSumLimit)))) break;
        gen = __any_sync(0xffffffffu, true);
      }
      l0 = first ? b0 : l0 + b0;
      l1 = first ? b1 : l1 + b1;
    };
    auto qk = [&](float (&s)[32], uint32_t ak, int k0, int k1) {
#pragma unroll
      for (int kk = k0; kk < k1; kk++)
        wgmma_rs_n64<0>(s, q[4 * kk], q[4 * kk + 1], q[4 * kk + 2], q[4 * kk + 3], mk_desc(ak, 16, KV_SBO, 1, (kk >> 2) * KV_CH + (kk & 3) * 2), kk != 0);
      wg_commit();
    };
    auto pv = [&](uint32_t (&pin)[16], uint32_t av, int acc) {
#pragma unroll
      for (int kk = 0; kk < 4; kk++)
        wgmma_rs_n192<1>(o, pin[4 * kk], pin[4 * kk + 1], pin[4 * kk + 2], pin[4 * kk + 3], mk_desc(av, KV_CH * 16, KV_SBO, 1, kk * (KV_SBO / 8)), acc || (kk != 0));
      wg_commit();
    };
    auto xw = [&](uint32_t ad, int acc) {
      const uint32_t da = second(SZ_A) + wg * 512;
      wg_fence();
#pragma unroll
      for (int kk = 0; kk < 4; kk++)
        wgmma_ss_n192<1>(o, mk_desc(da, 16, 1024, 1, kk * 2), mk_desc(ad, 4096, 1024, 1, (kk & 1) * 128 + (kk >> 1) * 768), acc || kk != 0);
      wg_commit();
    };
    auto ow = [&](int acc, int prev) {
      uint32_t da;
      const int bi = take(rdy0, SZ_A, da);
      const uint32_t db = second(SZ_WO);
      da += wg * 256;
      wg_fence();
      wgmma_ss_n160<1>(c, mk_desc(da, 16, 512, 2), mk_desc(db, 2048, 512, 2), acc);
      wgmma_ss_n160<1>(c, mk_desc(da, 16, 512, 2, 2), mk_desc(db, 2048, 512, 2, 64), 1);
      wg_commit();
      if (acc == 1) { wg_wait<1>(); release(prev); }
      wgmma_ss_n160<1>(c, mk_desc(da, 16, 512, 2, 512), mk_desc(db, 2048, 512, 2, 640), 1);
      wgmma_ss_n160<1>(c, mk_desc(da, 16, 512, 2, 514), mk_desc(db, 2048, 512, 2, 704), 1);
      wg_commit();
      return bi;
    };
    auto st_part = [&](int i) {
      stg2_if(true, pend + i * 512, __float_as_uint(c[8 * i]), __float_as_uint(c[8 * i + 1]), __float_as_uint(c[8 * i + 2]), __float_as_uint(c[8 * i + 3]),
              __float_as_uint(c[8 * i + 4]), __float_as_uint(c[8 * i + 5]), __float_as_uint(c[8 * i + 6]), __float_as_uint(c[8 * i + 7]), spol);
    };
#pragma unroll
    for (int i = 0; i < 48; i++) q[i] = 0;
    enter();

    if ((op & 3) == OP_Q) {
      uint32_t ad;
      int bi0 = take(false, SZ_WQ, ad), k = 0, lag = 0;
      xw(ad, 0);
      for (;;) {
#pragma unroll 1
        for (;;) {
          drain(q, k - lag);
          probe1();
          wg_wait<0>();
          release(bi0);
          bi0 = take(rdy0, SZ_WQ, ad);
          if (++k == 8) break;
          xw(ad, 1);
        }
        if (wg) bar_sync(2, 256);
        xw(ad, 1);
        const int bi9 = take(false, SZ_WQ, ad);
        xw(ad, 1);
        if (!wg) asm volatile("bar.arrive 2, 256;" ::: "memory");
        k = 0; lag = 0;
        uint32_t nop = prog[++pc];
        wg_wait<1>();
        release(bi0);
        probe2();
        wg_wait<0>();
        fence_regs(o);
        release(bi9);
#pragma unroll
        for (int i = 0; i < 48; i++) q[i] = pack_bf16(o[2 * i] * kScaleLog2, o[2 * i + 1] * kScaleLog2);
        fence_regs(q);
        if (op & F_PARK) {
          const int qt = helper ? (op >> 5) & 15 : team, qm = helper ? (op >> 12) & 3 : nt;
          pend = (uint4*)((char*)&g_o[((qt * 2 + rank) * 96 + 3 * (4 * ((op >> 2) & 7) + qm)) * 1024] + img0);
          op = nop;
          enter();
          if ((op & 3) != OP_Q) break;
          const int b = take(rdy0, SZ_WQ, ad);
          xw(ad, 0);
          bi0 = take(rdy1, SZ_WQ, ad);
          xw(ad, 1);
          wg_wait<1>();
          release(b);
          k = 1; lag = 1;
          continue;
        }
        int wave = (op >> 2) & 7, sk1;
        uint32_t ak1;
        {
          float s0[32];
          const int sk0 = take(rdy0, SZ_KV, ad);
          wg_fence();
          qk(s0, ad, 0, 12);
          sk1 = take(rdy1, SZ_KV, ak1);
          wg_fence();
          qk(s, ak1, 0, S1A);
          probe1();
          wg_wait<1>();
          fence_regs(s0);
          release(sk0);
          soft(s0, pa, true);
        }
        float i0, i1;
        auto sums = [&]() {
          l0 += __shfl_xor_sync(0xffffffffu, l0, 1); l1 += __shfl_xor_sync(0xffffffffu, l1, 1);
          l0 += __shfl_xor_sync(0xffffffffu, l0, 2); l1 += __shfl_xor_sync(0xffffffffu, l1, 2);
          i0 = rcp(l0); i1 = rcp(l1);
          asm volatile("" : "+f"(i0), "+f"(i1));
        };
        auto target = [&]() {
          pend = (uint4*)((char*)&g_o[((team * 2 + rank) * 96 + 3 * (4 * wave + nt)) * 1024] + img0);
          asm volatile("" : "+l"(pend));
        };
        bool late = false;
#pragma unroll
        for (int i = 0; i < 16; i++) pb[i] = 0;
        for (;;) {
          nop = prog[++pc];
          {
            uint32_t av;
            const int sv = take(rdy0, SZ_KV, av);
            wg_fence();
            qk(s, ak1, S1A, 12);
            pv(pa, av, 0);
            if (late) {
              stg2_if(true, pend + 4 * 512, pb[0], pb[1], pb[2], pb[3], pb[4], pb[5], pb[6], pb[7], spol);
              stg2_if(true, pend + 5 * 512, pb[8], pb[9], pb[10], pb[11], pb[12], pb[13], pb[14], pb[15], spol);
              __syncwarp();
              mbar_arrive_if(lane < 2, odone);
            }
            probe2();
            wg_wait<1>();
            fence_regs(s);
            release(sk1);
            soft(s, pb, false);
            wg_wait<0>();
            fence_regs(o);
            release(sv);
          }
          auto step = [&](uint32_t (&pin)[16], uint32_t (&pout)[16], bool hook, bool unpark) {
            uint32_t ak, av;
            const int sk = take(rdy0, SZ_KV, ak), sv = take(rdy1, SZ_KV, av);
            wg_fence();
            qk(s, ak, 0, 12);
            pv(pin, av, 1);
            if (hook && unpark) { take(false, SZ_PARK, ak); take(false, SZ_PARK, av); }
            probe2();
            wg_wait<1>();
            fence_regs(s);
            release(sk);
            if (hook) {
              lds2_if<0>(unpark, img0 + at(ak), q);
              lds2_if<8192>(unpark, img0 + at(ak), q + 8);
              lds2_if<16384>(unpark, img0 + at(ak), q + 16);
              lds2_if<0>(unpark, img0 + at(av), q + 24);
              lds2_if<8192>(unpark, img0 + at(av), q + 32);
              lds2_if<16384>(unpark, img0 + at(av), q + 40);
            }
            soft(s, pout, false);
            wg_wait<0>();
            fence_regs(o);
            release(sv);
          };
          const int jpark = (nop & 3) == OP_A ? 6 : 7;
#pragma unroll 1
          for (int jj = 0; jj < 7; jj++) {
            step(pb, pa, false, false);
            step(pa, pb, true, jj == jpark);
          }
          if ((nop & 3) != OP_A) break;
          uint32_t ak, av;
          release(Cursor{r.n - 16}.off());
          release(Cursor{r.n - 8}.off());
          const int sk0 = take(rdy0, SZ_KV, ak), sv = take(rdy1, SZ_KV, av);
          wg_fence();
          qk(s, ak, 0, 8);
          sched_fence(img0, P.zero);
          sums();
          sched_fence(img0, P.zero);
          qk(s, ak, 8, 12);
          pv(pb, av, 1);
          probe2();
          wg_wait<1>();
          fence_regs(s);
          release(sk0);
          soft(s, pa, true);
          sk1 = take(rdy0, SZ_KV, ak1);
          rdy0 = rdy1;
          wg_wait<0>();
          target();
          fence_regs(o);
          release(sv);
          uint32_t t[48];
#pragma unroll
          for (int j = 0; j < 6; j++) {
#pragma unroll
            for (int i = 0; i < 4; i++) {
              t[8 * j + i] = pack_bf16(o[16 * j + 4 * i] * i0, o[16 * j + 4 * i + 1] * i0);
              t[8 * j + i + 4] = pack_bf16(o[16 * j + 4 * i + 2] * i1, o[16 * j + 4 * i + 3] * i1);
            }
            if (j < 4)
            stg2_if(true, pend + j * 512, t[8 * j], t[8 * j + 1], t[8 * j + 2], t[8 * j + 3], t[8 * j + 4], t[8 * j + 5], t[8 * j + 6], t[8 * j + 7], spol);
            if (j == 3) { wg_fence(); qk(s, ak1, 0, 4); }
            if (j == 5) { wg_fence(); qk(s, ak1, 4, S1A); }
            sched_fence(img0, P.zero);
          }
          if (P.zero) {
#pragma unroll
            for (int j = 0; j < 4; j++)
              stg2_if(true, pend, t[8 * j], t[8 * j + 1], t[8 * j + 2], t[8 * j + 3], t[8 * j + 4], t[8 * j + 5], t[8 * j + 6], t[8 * j + 7], spol);
          }
          late = true;
#pragma unroll
          for (int i = 0; i < 16; i++) pb[i] = t[32 + i];
          wave = (nop >> 2) & 7;
        }
        const int sv = take(rdy0, SZ_KV, ad);
        wg_fence();
        pv(pb, ad, 1);
        sums();
        target();
        op = nop;
        enter();
        rdy0 = rdy1;
        auto convert = [&](float (&u)[96], int j0, int j1) {
#pragma unroll
          for (int i = 4 * j0; i < 4 * j1; i++) {
            q[8 * (i >> 2) + (i & 3)] = pack_bf16(u[4 * i], u[4 * i + 1]);
            q[8 * (i >> 2) + (i & 3) + 4] = pack_bf16(u[4 * i + 2], u[4 * i + 3]);
          }
        };
        if ((op & 3) != OP_O) {
          if ((op & 3) == OP_Q) bi0 = take(rdy0, SZ_WQ, ad);
          wg_wait<0>();
          fence_regs(o);
          release(sv);
          float u[96];
#pragma unroll
          for (int i = 0; i < 96; i++) u[i] = o[i] * (i & 2 ? i1 : i0);
          if ((op & 3) != OP_Q) { convert(u, 0, 6); break; }
          fence_regs(u);
          xw(ad, 0);
          sched_fence(img0, P.zero);
          fence_regs(u);
          convert(u, 0, 1);
          stg2_if(true, pend, q[0], q[1], q[2], q[3], q[4], q[5], q[6], q[7], spol);
          probe1();
          wg_wait<0>();
          release(bi0);
          bi0 = take(rdy0, SZ_WQ, ad);
          xw(ad, 1);
          sched_fence(img0, P.zero);
          fence_regs(u);
          convert(u, 1, 6);
          k = 1;
          continue;
        }
        int bi = ow(0, 0);
        wg_wait<2>();
        fence_regs(o);
        release(sv);
#pragma unroll
        for (int j = 0; j < 6; j++) {
          uint32_t t[8];
#pragma unroll
          for (int i = 0; i < 4; i++) {
            t[i] = pack_bf16(o[16 * j + 4 * i] * i0, o[16 * j + 4 * i + 1] * i0);
            t[i + 4] = pack_bf16(o[16 * j + 4 * i + 2] * i1, o[16 * j + 4 * i + 3] * i1);
          }
          stg2_if(true, pend + j * 512, t[0], t[1], t[2], t[3], t[4], t[5], t[6], t[7], spol);
          if (j == 5) {
            __syncwarp();
            mbar_arrive_if(lane < 2, odone);
          }
          probe1();
          wg_wait<1>();
          bi = ow(1, bi);
          fence_regs(o);
        }
        {
          const int nk = 12 * (((op >> 5) & 15) - ((op >> 2) & 7)) - ((op & F_ST) ? 0 : 2);
#pragma unroll 1
          for (int k = 7; k < nk; k++) {
            probe1();
            wg_wait<1>();
            bi = ow(1, bi);
          }
        }
        if (!(op & F_ST)) {
          probe2();
          wg_wait<1>();
          if (wg) {
            wg_wait<0>();
            release(bi);
            bar_sync(2, 256);
          }
          bi0 = ow(2, 0);
          rdy0 = rdy1;
          const int b = ow(2, 0);
          if (!wg) asm volatile("bar.arrive 2, 256;" ::: "memory");
          wg_wait<4>();
          mbar_arrive_cluster_if(lane < 2 && !wg, empty_rem + bi);
          bi = b;
        }
        probe1();
        nop = prog[++pc];
        if (op & F_LD) {
          uint32_t t[80];
#pragma unroll
          for (int j = 0; j < 5; j++) {
            const int b = take(rdy0, SZ_PART, ad);
            probe1();
#pragma unroll
            for (int i = 4 * j; i < 4 * j + 4; i++)
              lds128(img0 + at(ad) + ((i >> 1) & 1) * 8192 + (i & 1) * 512, t[4 * i], t[4 * i + 1], t[4 * i + 2], t[4 * i + 3]);
            release(b);
          }
          wg_wait<0>();
          fence_regs(c);
#pragma unroll
          for (int i = 0; i < 80; i++) c[i] += __uint_as_float(t[i]);
        }
        if (!(op & F_ST)) {
          wg_wait<0>();
          fence_regs(c);
          release(bi0);
          release(bi);
          goto finish;
        }
        op = nop;
        enter();
        bi0 = take(rdy0, SZ_WQ, ad);
        xw(ad, 0);
        pend = (uint4*)((char*)&g_part[((team * 4 + nt) * 2 + rank) * 5120] + img0);
        probe1();
        wg_wait<1>();
        fence_regs(c);
        release(bi);
        st_part(0); st_part(1);
        wg_wait<0>();
        release(bi0);
        bi0 = take(rdy0, SZ_WQ, ad);
        xw(ad, 1);
        st_part(2); st_part(3);
#pragma unroll
        for (int i = 0; i < 48; i++) q[i] = __float_as_uint(c[32 + i]);
        pend += 4 * 512;
        k = 1; lag = 2;
      }
    }
    rdy0 = false;
    {
      uint32_t t[48];
#pragma unroll
      for (int i = 0; i < 48; i++) t[i] = q[i] ^ P.zero;
      while ((op & 3) == OP_O) {
        int bi = ow(0, 0);
#pragma unroll 1
        for (int k = 1; k < 12 * (int)(((op >> 5) & 15) - ((op >> 2) & 7)); k++) {
          drain(t, k - 1);
          probe1();
          wg_wait<1>();
          bi = ow(1, bi);
        }
        rdy0 = false;
        wg_wait<0>();
        fence_regs(c);
        pc++;
        release(bi);
        if (!(op & F_ST)) goto finish;
        pend = (uint4*)((char*)&g_part[((((op >> 26) & 56) | ((op >> 9) & 7)) * 2 + rank) * 5120] + img0);
#pragma unroll
        for (int i = 6; i < 10; i++) st_part(i);
#pragma unroll
        for (int i = 0; i < 48; i++) t[i] = __float_as_uint(c[i]) ^ P.zero;
        op = prog[pc];
        enter();
      }
      for (int i = 0; i < 6; i++) drain(t, i);
    }
    if (false) {
    finish:
      uint32_t ad;
      take(rdy0, SZ_OUT, ad);
      const uint32_t wstage = sbase + (ad - ring16) * 16 + (wg * 4 + warp) * 5120;
      const uint32_t sa = wstage + (lane & 15) * 64;
#pragma unroll
      for (int i = 0; i < 10; i++) {
        const int u = (i & 1) * 2 + (lane >> 4);
        stsm4(sa + (i >> 1) * 1024 + ((u ^ ((lane >> 1) & 3)) << 4), pack_bf16(c[8 * i], c[8 * i + 1]), pack_bf16(c[8 * i + 2], c[8 * i + 3]),
              pack_bf16(c[8 * i + 4], c[8 * i + 5]), pack_bf16(c[8 * i + 6], c[8 * i + 7]));
      }
      asm volatile("fence.proxy.async.shared::cta;" ::: "memory");
      __syncwarp();
      if (lane == 0) {
        tma3d_store(&P.out, wstage, 0, (team & 7) * kSq + rank * 128 + wg * 64 + warp * 16, blk * 20 + nt * 5);
        asm volatile("cp.async.bulk.commit_group;\ncp.async.bulk.wait_group.read 0;" ::: "memory");
      }
    }
  }
}

typedef CUresult (*EncodeFn)(CUtensorMap*, CUtensorMapDataType, cuuint32_t, void*, const cuuint64_t*, const cuuint64_t*,
                             const cuuint32_t*, const cuuint32_t*, CUtensorMapInterleave, CUtensorMapSwizzle,
                             CUtensorMapL2promotion, CUtensorMapFloatOOBfill);

void encode(EncodeFn fn, CUtensorMap* m, const void* ptr, int rank, const cuuint64_t* dims, const cuuint64_t* strides,
            const cuuint32_t* box, CUtensorMapSwizzle swz) {
  const cuuint32_t es[5] = {1, 1, 1, 1, 1};
  CUresult r = fn(m, CU_TENSOR_MAP_DATA_TYPE_BFLOAT16, rank, const_cast<void*>(ptr), dims, strides, box, es,
                  CU_TENSOR_MAP_INTERLEAVE_NONE, swz, CU_TENSOR_MAP_L2_PROMOTION_L2_128B, CU_TENSOR_MAP_FLOAT_OOB_FILL_NONE);
  if (r != CUDA_SUCCESS) fprintf(stderr, "cuTensorMapEncodeTiled failed: %d\n", (int)r);
}

void annotate(uint32_t* ops, int n, bool helper) {
  uint32_t items = 0, cur = 0, pend = 0;
  auto item = [&](uint32_t bytes, int count, uint32_t bytes2 = 0) {
    for (int i = 0; i < count; i++) {
      if (cur + bytes > RING) cur = 0;
      cur += bytes;
      if (cur + bytes2 > RING) cur = 0;
      cur += bytes2;
      items++;
    }
  };
  for (int i = 0; i <= n; i++) {
    const uint32_t op = ops[i];
    ops[i] |= (items % (2 * NBAR)) << 15 | (cur >> 12) << 20 | pend << 26;
    if ((op & 3) == OP_Q) { item(SZ_WQ, 10, SZ_A); pend = (op & F_PARK) ? (helper ? 1 : 2) : 0; }
    if ((op & 3) == OP_A) {
      item(SZ_KV, (op & F_PARK) ? 30 : 31);
      if ((ops[i + 1] & 3) == OP_A) { item(SZ_PARK, 2); item(SZ_KV, 1); }
      item(SZ_KV, 1);
      pend = 1;
    }
    if ((op & 3) == OP_O) {
      item(SZ_A, 12 * (((op >> 5) & 15) - ((op >> 2) & 7)), SZ_WO);
      if (op & F_LD) item(SZ_PART, 5);
      pend = (op & F_ST) ? (helper ? 1 : 2) : 0;
    }
  }
}

void compile_programs(const char* const* text, bool helpers, Params& P) {
  struct Req { int when, team, wave, slot; } req[N_TEAM * MAX_PARK];
  int n_req = 0;
  for (int t = 0; t < N_TEAM; t++) {
    uint32_t* ops = P.ops[t];
    int n = 0, flags[8] = {0, 0, 0, 0, 0, 0, 0, 0}, n_park = 0, last_o = -1, when = 0, given = 0;
    for (const char* s = text[t]; *s; s++) {
      const int a = s[1] - '0';
      if (*s == 'Q' || (*s == 'H' && !helpers)) { ops[n++] = OP_Q | a << 2; when += 10; }
      else if (*s == 'P') { flags[a] = F_PARK; ops[n++] = OP_Q | a << 2 | flags[a]; when += 10; }
      else if (*s == 'H') { req[n_req++] = {when, t, a, n_park}; flags[a] = F_PARK | F_HELP | n_park++ << 10; }
      else if (*s == 'A') { ops[n++] = OP_A | a << 2 | flags[a]; when += 32; }
      else if (*s == 'G') { given = a; if (helpers) req[n_req++] = {1000, t, 0, -a}; }
      else if (*s == 'O') {
        ops[n] = OP_O | a << 2 | (s[2] - '0') << 5;
        if (given) ops[n] = helpers ? ops[n] | F_LD | F_PARK | (MAX_PARK - 1) << 10 : ops[n] & ~(7u << 2);
        if (last_o >= 0) { ops[last_o] |= F_ST; ops[n] |= F_LD; }
        last_o = n++;
        when += 10 * (s[2] - s[1]);
      }
    }
    for (int i = n; i < MAX_OPS; i++) ops[i] = OP_END;
    annotate(ops, n, false);
  }
  for (int i = 1; i < n_req; i++)
    for (int j = i; j > 0 && req[j].when < req[j - 1].when; j--) { Req r = req[j]; req[j] = req[j - 1]; req[j - 1] = r; }
  for (int h = 0; h < N_HELP; h++) {
    uint32_t* ops = P.ops[N_TEAM + 2 * h];
    int n = 0;
    for (int i = 0; i < n_req; i++)
      for (int m = h; m < 4; m += N_HELP) {
        const uint32_t ro = 4 * req[i].team + m;
        ops[n++] = req[i].slot >= 0 ? OP_Q | req[i].wave << 2 | req[i].team << 5 | F_PARK | req[i].slot << 10 | m << 12
                                    : OP_O | -req[i].slot << 5 | F_ST | (ro & 7) << 9 | (ro >> 3) << 29;
      }
    for (int i = n; i < 2 * MAX_OPS; i++) ops[i] = OP_END;
    annotate(ops, n, true);
  }
  for (int i = 0; i < 32; i++) P.first[i] = i < N_TEAM ? P.ops[i][0] : i < N_TEAM + N_HELP ? P.ops[2 * i - N_TEAM][0] : 0;
}

const char* const kPrograms[N_TEAM] = {
  "Q0A0Q1A1H2A2O03Q3A3Q4A4Q5A5Q6A6Q7A7O38",
  "Q0A0Q1A1Q2A2Q3A3O04Q4A4Q5A5Q6A6H7A7O48",
  "Q0A0H1A1Q2A2Q3A3Q4A4O05Q5A5Q6A6Q7A7O58",
  "Q0A0Q1A1Q2A2O03Q3A3Q4A4Q5A5Q6A6H7A7O38",
  "Q0A0Q1A1Q2A2O03Q3A3H4A4Q5A5Q6A6Q7A7O38",
  "Q0A0Q1A1H2A2Q3A3Q4A4O05Q5A5Q6A6Q7A7O58",
  "Q0A0Q1A1Q2A2Q3A3O03Q4A4H5A5Q6A6Q7A7O38",
  "Q0A0Q1A1Q2A2Q3A3Q4A4O05Q5A5Q6A6H7A7O58",
  "P3Q0A0Q1A1Q2A2A3H4A4Q5A5Q6A6Q7A7O08",
  "P5P7Q0A0Q1A1Q2A2H3A3Q4A4A5Q6A6A7G1O18",
  "Q0A0Q1A1Q2A2O02Q3A3H4A4Q5A5Q6A6Q7A7O28",
  "P3P5Q0A0Q1A1Q2A2A3Q4A4A5Q6A6H7A7O08",
  "Q0A0Q1A1Q2A2O02Q3A3Q4A4H5A5Q6A6Q7A7O28",
  "P7Q0A0Q1A1Q2A2Q3A3Q4A4Q5A5Q6A6A7G1O18",
  "P5Q0A0Q1A1Q2A2Q3A3Q4A4A5Q6A6H7A7O08",
  "Q0A0Q1A1Q2A2H3A3Q4A4Q5A5Q6A6Q7A7O08",
};

const char* const* bench_programs() {
  return kPrograms;
}

}

extern "C" void kernel_launch(void* const* d_in, const int* in_sizes, int n_in, void* d_out, int out_size) {
  (void)in_sizes; (void)n_in; (void)out_size;
  static EncodeFn fn = nullptr;
  static int n_clusters = 0;
  if (!fn) {
    cudaDriverEntryPointQueryResult qr;
    void* f = nullptr;
    cudaGetDriverEntryPoint("cuTensorMapEncodeTiled", &f, cudaEnableDefault, &qr);
    fn = (EncodeFn)f;
    cudaFuncSetAttribute(fused_kernel, cudaFuncAttributeMaxDynamicSharedMemorySize, SMEM_BYTES);
    cudaLaunchConfig_t cfg = {};
    cfg.gridDim = dim3(132); cfg.blockDim = dim3(384); cfg.dynamicSmemBytes = SMEM_BYTES;
    cudaLaunchAttribute at[1];
    at[0].id = cudaLaunchAttributeClusterDimension; at[0].val.clusterDim.x = 2; at[0].val.clusterDim.y = 1; at[0].val.clusterDim.z = 1;
    cfg.attrs = at; cfg.numAttrs = 1;
    if (cudaOccupancyMaxActiveClusters(&n_clusters, fused_kernel, &cfg) != cudaSuccess || n_clusters < 1) n_clusters = 1;
    (void)cudaGetLastError();
  }
  Params P;
  const CUtensorMapSwizzle S128 = CU_TENSOR_MAP_SWIZZLE_128B, S64 = CU_TENSOR_MAP_SWIZZLE_64B;
  for (int blk = 0; blk < 2; blk++) {
    void* const* in = d_in + 5 * blk;
    { const cuuint64_t d[] = {kD, kB * kSq}, s[] = {kD * 2}; const cuuint32_t b[] = {64, 128};
      encode(fn, &P.x[blk], in[0], 2, d, s, b, S128); }
    { const cuuint64_t d[] = {64, 8, 3, (cuuint64_t)kB * kH * kSk / 8}, s[] = {kDh * 2, 128, 8 * kDh * 2}; const cuuint32_t b[] = {64, 8, 3, 4};
      encode(fn, &P.kv[blk], in[1], 4, d, s, b, S128);
      encode(fn, &P.kv[blk + 2], in[2], 4, d, s, b, S128); }
    { const cuuint64_t d[] = {64, kD, kHD / 64}, s[] = {kHD * 2, 128}; const cuuint32_t b[] = {64, 32, 3};
      encode(fn, &P.wq[blk], in[3], 3, d, s, b, S128); }
    { const cuuint64_t d[] = {32, 2, kHD / 8, 4, kD / 32}, s[] = {kD * 2, 8 * kD * 2, 2 * kD * 2, 64}; const cuuint32_t b[] = {32, 2, 4, 4, 5};
      encode(fn, &P.wo[blk], in[4], 5, d, s, b, S64); }
  }
  { const cuuint64_t d[] = {32, kB * kSq, 2 * kD / 32}, s[] = {2 * kD * 2, 64}; const cuuint32_t b[] = {32, 16, 5};
    encode(fn, &P.out, d_out, 3, d, s, b, S64); }

  P.zero = 0;
  if (n_clusters >= N_CL) {
    const bool helpers = n_clusters >= N_CL + N_HELP;
    compile_programs(bench_programs(), helpers, P);
    fused_kernel<<<2 * (N_CL + (helpers ? N_HELP : 0)), 384, SMEM_BYTES>>>(P);
  } else {
    for (int phase = 0; phase < 2; phase++) {
      const char* text[N_TEAM];
      for (int t = 0; t < N_TEAM; t++) text[t] = phase ? "O08" : "Q0A0Q1A1Q2A2Q3A3Q4A4Q5A5Q6A6Q7A7";
      compile_programs(text, false, P);
      fused_kernel<<<2 * N_CL, 384, SMEM_BYTES>>>(P);
    }
  }
}
```

```cpp
#include <cuda_runtime.h>
#include <cuda_bf16.h>
#include <cuda.h>
#include <stdint.h>
#include <stdio.h>

namespace {

constexpr int kB = 8, kSq = 256, kD = 640, kH = 32, kSk = 1024, kDh = 192;
constexpr int kHD = kH * kDh;
constexpr uint32_t RING = 224 * 1024;
constexpr uint32_t SZ_KV = 24576;
constexpr uint32_t SZ_WQ = 24576, SZ_WO = 20480, SZ_A = 16384;
constexpr uint32_t SZ_OUT = 40960;
constexpr uint32_t SZ_PARK = 24576;
constexpr uint32_t SZ_PART = 16384;
constexpr int NBAR = 16;
constexpr int KV_TRANSIT = 4;
constexpr int EARLY = 3;
constexpr int S1A = 7;
constexpr uint32_t KV_CH = 64, KV_SBO = 3072;
constexpr int SMEM_BYTES = RING + 512 + 1024;
constexpr int N_TEAM = 16, N_CL = 64, N_HELP = 2, MAX_OPS = 24, MAX_PARK = 4;
enum { OP_END = 0, OP_Q = 1, OP_A = 2, OP_O = 3, F_PARK = 1 << 9, F_LD = 1 << 12, F_ST = 1 << 13, F_HELP = 1 << 12 };

struct alignas(64) Params {
  uint32_t first[32];
  CUtensorMap x[2], wq[2], kv[4], wo[2], out;
  uint32_t ops[N_TEAM + 2 * N_HELP][MAX_OPS];
  uint32_t zero;
};

__device__ uint4 g_o[N_TEAM * 2 * 96 * 1024];
__device__ uint4 g_part[N_CL * 2 * 5 * 1024];
__device__ unsigned int g_done[N_TEAM * 2 * 8];
__device__ unsigned int g_help[N_CL * 2 * MAX_PARK];
__device__ unsigned int g_seen[N_TEAM * 2 * 8];

template <int TB>
__device__ __forceinline__ void wgmma_rs_n64(float (&d)[32], uint32_t a0, uint32_t a1, uint32_t a2, uint32_t a3, uint64_t db, int scale_d) {
  asm volatile("{\n.reg .pred p;\nsetp.ne.b32 p, %37, 0;\n"
    "wgmma.mma_async.sync.aligned.m64n64k16.f32.bf16.bf16 {%0, %1, %2, %3, %4, %5, %6, %7, %8, %9, %10, %11, %12, %13, %14, %15, %16, %17, %18, %19, %20, %21, %22, %23, %24, %25, %26, %27, %28, %29, %30, %31}, {%32, %33, %34, %35}, %36, p, 1, 1, %38;\n}\n"
    : "+f"(d[0]), "+f"(d[1]), "+f"(d[2]), "+f"(d[3]), "+f"(d[4]), "+f"(d[5]), "+f"(d[6]), "+f"(d[7]), "+f"(d[8]), "+f"(d[9]), "+f"(d[10]), "+f"(d[11]), "+f"(d[12]), "+f"(d[13]), "+f"(d[14]), "+f"(d[15]), "+f"(d[16]), "+f"(d[17]), "+f"(d[18]), "+f"(d[19]), "+f"(d[20]), "+f"(d[21]), "+f"(d[22]), "+f"(d[23]), "+f"(d[24]), "+f"(d[25]), "+f"(d[26]), "+f"(d[27]), "+f"(d[28]), "+f"(d[29]), "+f"(d[30]), "+f"(d[31])
    : "r"(a0), "r"(a1), "r"(a2), "r"(a3), "l"(db), "r"(scale_d), "n"(TB));
}
template <int TB, int TA = 0>
__device__ __forceinline__ void wgmma_ss_n160(float (&d)[80], uint64_t da, uint64_t db, int scale_d) {
  asm volatile("{\n.reg .pred p;\nsetp.ne.b32 p, %82, 0;\n"
    "wgmma.mma_async.sync.aligned.m64n160k16.f32.bf16.bf16 {%0, %1, %2, %3, %4, %5, %6, %7, %8, %9, %10, %11, %12, %13, %14, %15, %16, %17, %18, %19, %20, %21, %22, %23, %24, %25, %26, %27, %28, %29, %30, %31, %32, %33, %34, %35, %36, %37, %38, %39, %40, %41, %42, %43, %44, %45, %46, %47, %48, %49, %50, %51, %52, %53, %54, %55, %56, %57, %58, %59, %60, %61, %62, %63, %64, %65, %66, %67, %68, %69, %70, %71, %72, %73, %74, %75, %76, %77, %78, %79}, %80, %81, p, 1, 1, %83, %84;\n}\n"
    : "+f"(d[0]), "+f"(d[1]), "+f"(d[2]), "+f"(d[3]), "+f"(d[4]), "+f"(d[5]), "+f"(d[6]), "+f"(d[7]), "+f"(d[8]), "+f"(d[9]), "+f"(d[10]), "+f"(d[11]), "+f"(d[12]), "+f"(d[13]), "+f"(d[14]), "+f"(d[15]), "+f"(d[16]), "+f"(d[17]), "+f"(d[18]), "+f"(d[19]), "+f"(d[20]), "+f"(d[21]), "+f"(d[22]), "+f"(d[23]), "+f"(d[24]), "+f"(d[25]), "+f"(d[26]), "+f"(d[27]), "+f"(d[28]), "+f"(d[29]), "+f"(d[30]), "+f"(d[31]), "+f"(d[32]), "+f"(d[33]), "+f"(d[34]), "+f"(d[35]), "+f"(d[36]), "+f"(d[37]), "+f"(d[38]), "+f"(d[39]), "+f"(d[40]), "+f"(d[41]), "+f"(d[42]), "+f"(d[43]), "+f"(d[44]), "+f"(d[45]), "+f"(d[46]), "+f"(d[47]), "+f"(d[48]), "+f"(d[49]), "+f"(d[50]), "+f"(d[51]), "+f"(d[52]), "+f"(d[53]), "+f"(d[54]), "+f"(d[55]), "+f"(d[56]), "+f"(d[57]), "+f"(d[58]), "+f"(d[59]), "+f"(d[60]), "+f"(d[61]), "+f"(d[62]), "+f"(d[63]), "+f"(d[64]), "+f"(d[65]), "+f"(d[66]), "+f"(d[67]), "+f"(d[68]), "+f"(d[69]), "+f"(d[70]), "+f"(d[71]), "+f"(d[72]), "+f"(d[73]), "+f"(d[74]), "+f"(d[75]), "+f"(d[76]), "+f"(d[77]), "+f"(d[78]), "+f"(d[79])
    : "l"(da), "l"(db), "r"(scale_d), "n"(TA), "n"(TB));
}
template <int TB, int TA = 0>
__device__ __forceinline__ void wgmma_ss_n192(float (&d)[96], uint64_t da, uint64_t db, int scale_d) {
  asm volatile("{\n.reg .pred p;\nsetp.ne.b32 p, %98, 0;\n"
    "wgmma.mma_async.sync.aligned.m64n192k16.f32.bf16.bf16 {%0, %1, %2, %3, %4, %5, %6, %7, %8, %9, %10, %11, %12, %13, %14, %15, %16, %17, %18, %19, %20, %21, %22, %23, %24, %25, %26, %27, %28, %29, %30, %31, %32, %33, %34, %35, %36, %37, %38, %39, %40, %41, %42, %43, %44, %45, %46, %47, %48, %49, %50, %51, %52, %53, %54, %55, %56, %57, %58, %59, %60, %61, %62, %63, %64, %65, %66, %67, %68, %69, %70, %71, %72, %73, %74, %75, %76, %77, %78, %79, %80, %81, %82, %83, %84, %85, %86, %87, %88, %89, %90, %91, %92, %93, %94, %95}, %96, %97, p, 1, 1, %99, %100;\n}\n"
    : "+f"(d[0]), "+f"(d[1]), "+f"(d[2]), "+f"(d[3]), "+f"(d[4]), "+f"(d[5]), "+f"(d[6]), "+f"(d[7]), "+f"(d[8]), "+f"(d[9]), "+f"(d[10]), "+f"(d[11]), "+f"(d[12]), "+f"(d[13]), "+f"(d[14]), "+f"(d[15]), "+f"(d[16]), "+f"(d[17]), "+f"(d[18]), "+f"(d[19]), "+f"(d[20]), "+f"(d[21]), "+f"(d[22]), "+f"(d[23]), "+f"(d[24]), "+f"(d[25]), "+f"(d[26]), "+f"(d[27]), "+f"(d[28]), "+f"(d[29]), "+f"(d[30]), "+f"(d[31]), "+f"(d[32]), "+f"(d[33]), "+f"(d[34]), "+f"(d[35]), "+f"(d[36]), "+f"(d[37]), "+f"(d[38]), "+f"(d[39]), "+f"(d[40]), "+f"(d[41]), "+f"(d[42]), "+f"(d[43]), "+f"(d[44]), "+f"(d[45]), "+f"(d[46]), "+f"(d[47]), "+f"(d[48]), "+f"(d[49]), "+f"(d[50]), "+f"(d[51]), "+f"(d[52]), "+f"(d[53]), "+f"(d[54]), "+f"(d[55]), "+f"(d[56]), "+f"(d[57]), "+f"(d[58]), "+f"(d[59]), "+f"(d[60]), "+f"(d[61]), "+f"(d[62]), "+f"(d[63]), "+f"(d[64]), "+f"(d[65]), "+f"(d[66]), "+f"(d[67]), "+f"(d[68]), "+f"(d[69]), "+f"(d[70]), "+f"(d[71]), "+f"(d[72]), "+f"(d[73]), "+f"(d[74]), "+f"(d[75]), "+f"(d[76]), "+f"(d[77]), "+f"(d[78]), "+f"(d[79]), "+f"(d[80]), "+f"(d[81]), "+f"(d[82]), "+f"(d[83]), "+f"(d[84]), "+f"(d[85]), "+f"(d[86]), "+f"(d[87]), "+f"(d[88]), "+f"(d[89]), "+f"(d[90]), "+f"(d[91]), "+f"(d[92]), "+f"(d[93]), "+f"(d[94]), "+f"(d[95])
    : "l"(da), "l"(db), "r"(scale_d), "n"(TA), "n"(TB));
}
template <int TB>
__device__ __forceinline__ void wgmma_rs_n192(float (&d)[96], uint32_t a0, uint32_t a1, uint32_t a2, uint32_t a3, uint64_t db, int scale_d) {
  asm volatile("{\n.reg .pred p;\nsetp.ne.b32 p, %101, 0;\n"
    "wgmma.mma_async.sync.aligned.m64n192k16.f32.bf16.bf16 {%0, %1, %2, %3, %4, %5, %6, %7, %8, %9, %10, %11, %12, %13, %14, %15, %16, %17, %18, %19, %20, %21, %22, %23, %24, %25, %26, %27, %28, %29, %30, %31, %32, %33, %34, %35, %36, %37, %38, %39, %40, %41, %42, %43, %44, %45, %46, %47, %48, %49, %50, %51, %52, %53, %54, %55, %56, %57, %58, %59, %60, %61, %62, %63, %64, %65, %66, %67, %68, %69, %70, %71, %72, %73, %74, %75, %76, %77, %78, %79, %80, %81, %82, %83, %84, %85, %86, %87, %88, %89, %90, %91, %92, %93, %94, %95}, {%96, %97, %98, %99}, %100, p, 1, 1, %102;\n}\n"
    : "+f"(d[0]), "+f"(d[1]), "+f"(d[2]), "+f"(d[3]), "+f"(d[4]), "+f"(d[5]), "+f"(d[6]), "+f"(d[7]), "+f"(d[8]), "+f"(d[9]), "+f"(d[10]), "+f"(d[11]), "+f"(d[12]), "+f"(d[13]), "+f"(d[14]), "+f"(d[15]), "+f"(d[16]), "+f"(d[17]), "+f"(d[18]), "+f"(d[19]), "+f"(d[20]), "+f"(d[21]), "+f"(d[22]), "+f"(d[23]), "+f"(d[24]), "+f"(d[25]), "+f"(d[26]), "+f"(d[27]), "+f"(d[28]), "+f"(d[29]), "+f"(d[30]), "+f"(d[31]), "+f"(d[32]), "+f"(d[33]), "+f"(d[34]), "+f"(d[35]), "+f"(d[36]), "+f"(d[37]), "+f"(d[38]), "+f"(d[39]), "+f"(d[40]), "+f"(d[41]), "+f"(d[42]), "+f"(d[43]), "+f"(d[44]), "+f"(d[45]), "+f"(d[46]), "+f"(d[47]), "+f"(d[48]), "+f"(d[49]), "+f"(d[50]), "+f"(d[51]), "+f"(d[52]), "+f"(d[53]), "+f"(d[54]), "+f"(d[55]), "+f"(d[56]), "+f"(d[57]), "+f"(d[58]), "+f"(d[59]), "+f"(d[60]), "+f"(d[61]), "+f"(d[62]), "+f"(d[63]), "+f"(d[64]), "+f"(d[65]), "+f"(d[66]), "+f"(d[67]), "+f"(d[68]), "+f"(d[69]), "+f"(d[70]), "+f"(d[71]), "+f"(d[72]), "+f"(d[73]), "+f"(d[74]), "+f"(d[75]), "+f"(d[76]), "+f"(d[77]), "+f"(d[78]), "+f"(d[79]), "+f"(d[80]), "+f"(d[81]), "+f"(d[82]), "+f"(d[83]), "+f"(d[84]), "+f"(d[85]), "+f"(d[86]), "+f"(d[87]), "+f"(d[88]), "+f"(d[89]), "+f"(d[90]), "+f"(d[91]), "+f"(d[92]), "+f"(d[93]), "+f"(d[94]), "+f"(d[95])
    : "r"(a0), "r"(a1), "r"(a2), "r"(a3), "l"(db), "r"(scale_d), "n"(TB));
}

__device__ __forceinline__ uint32_t smem_u32(const void* p) { return (uint32_t)__cvta_generic_to_shared(p); }
__device__ __forceinline__ void wg_fence() { asm volatile("wgmma.fence.sync.aligned;" ::: "memory"); }
__device__ __forceinline__ void wg_commit() { asm volatile("wgmma.commit_group.sync.aligned;" ::: "memory"); }
template <int N> __device__ __forceinline__ void wg_wait() { asm volatile("wgmma.wait_group.sync.aligned %0;" ::"n"(N) : "memory"); }
__device__ __forceinline__ void sched_fence(int& keep, uint32_t zero) {
  asm volatile("{\n.reg .u32 c;\nmov.u32 c, %%clock;\nand.b32 c, c, %1;\nxor.b32 %0, %0, c;\n}\n" : "+r"(keep) : "r"(zero) : "memory");
}
template <int N> __device__ __forceinline__ void fence_regs(float (&r)[N]) {
#pragma unroll
  for (int i = 0; i < N; i++) asm volatile("" : "+f"(r[i])::"memory");
}
template <int N> __device__ __forceinline__ void fence_regs(uint32_t (&r)[N]) {
#pragma unroll
  for (int i = 0; i < N; i++) asm volatile("" : "+r"(r[i])::"memory");
}
__device__ __forceinline__ uint64_t mk_desc(uint32_t a16, uint32_t lbo, uint32_t sbo, uint32_t swz, uint32_t off = 0) {
  uint64_t d;
  asm("mov.b64 %0, {%1, %2};" : "=l"(d) : "r"(a16), "r"((sbo >> 4) | (swz << 30)));
  return d + (off + ((lbo >> 4) << 16));
}
__device__ __forceinline__ void mbar_init(uint32_t bar, uint32_t cnt) {
  asm volatile("mbarrier.init.shared::cta.b64 [%0], %1;" ::"r"(bar), "r"(cnt) : "memory");
}
__device__ __forceinline__ void mbar_expect(uint32_t bar, uint32_t tx) {
  asm volatile("mbarrier.arrive.expect_tx.shared::cta.b64 _, [%0], %1;" ::"r"(bar), "r"(tx) : "memory");
}
__device__ __forceinline__ bool mbar_test(uint32_t bar, uint32_t ph) {
  uint32_t ok;
  asm volatile("{\n.reg .pred p;\nmbarrier.test_wait.parity.shared::cta.b64 p, [%1], %2;\nselp.u32 %0, 1, 0, p;\n}\n"
               : "=r"(ok) : "r"(bar), "r"(ph) : "memory");
  return ok;
}
__device__ __forceinline__ void mbar_wait(uint32_t bar, uint32_t ph) {
  asm volatile("{\n.reg .pred p;\n.reg .u32 n;\nmov.u32 n, 0;\n"
               "LOOP:\nadd.u32 n, n, 1;\nmbarrier.try_wait.parity.shared::cta.b64 p, [%0], %1;\n@p bra DONE;\n"
               "setp.lt.u32 p, n, 0x1000000;\n@p bra LOOP;\ntrap;\n"
               "DONE:\n}\n" ::"r"(bar), "r"(ph) : "memory");
}
__device__ __forceinline__ void mbar_wait_math(uint32_t bar, uint32_t ph) {
  asm volatile("{\n.reg .pred p;\nLOOP:\nmbarrier.try_wait.parity.shared::cta.b64 p, [%0], %1;\n@!p bra LOOP;\n}\n" ::"r"(bar), "r"(ph) : "memory");
}
__device__ __forceinline__ void mbar_wait_long(uint32_t bar, uint32_t ph) {
  asm volatile("{\n.reg .pred p;\n.reg .u32 n;\nmov.u32 n, 0;\n"
               "LOOP:\nmbarrier.try_wait.parity.shared::cta.b64 p, [%0], %1, %2;\n@p bra DONE;\n"
               "add.u32 n, n, 1;\nsetp.lt.u32 p, n, 0x40000;\n@p bra LOOP;\ntrap;\n"
               "DONE:\n}\n" ::"r"(bar), "r"(ph), "r"(20000) : "memory");
}
__device__ __forceinline__ void mbar_arrive_cluster_if(bool on, uint32_t addr) {
  asm volatile("{\n.reg .pred p;\nsetp.ne.b32 p, %1, 0;\n@p mbarrier.arrive.shared::cluster.b64 _, [%0];\n}\n" ::"r"(addr), "r"((int)on) : "memory");
}
__device__ __forceinline__ void mbar_arrive_if(bool on, uint32_t addr) {
  asm volatile("{\n.reg .pred p;\nsetp.ne.b32 p, %1, 0;\n@p mbarrier.arrive.shared::cta.b64 _, [%0];\n}\n" ::"r"(addr), "r"((int)on) : "memory");
}
__device__ __forceinline__ void tma2d(uint32_t dst, const CUtensorMap* m, uint32_t bar, int c0, int c1) {
  asm volatile("cp.async.bulk.tensor.2d.shared::cluster.global.mbarrier::complete_tx::bytes [%0], [%1, {%3, %4}], [%2];"
               ::"r"(dst), "l"(m), "r"(bar), "r"(c0), "r"(c1) : "memory");
}
__device__ __forceinline__ void tma3d(uint32_t dst, const CUtensorMap* m, uint32_t bar, int c0, int c1, int c2) {
  asm volatile("cp.async.bulk.tensor.3d.shared::cluster.global.mbarrier::complete_tx::bytes [%0], [%1, {%3, %4, %5}], [%2];"
               ::"r"(dst), "l"(m), "r"(bar), "r"(c0), "r"(c1), "r"(c2) : "memory");
}
__device__ __forceinline__ void tma3d_mc(uint32_t dst, const CUtensorMap* m, uint32_t bar, int c0, int c1, int c2) {
  asm volatile("cp.async.bulk.tensor.3d.shared::cluster.global.mbarrier::complete_tx::bytes.multicast::cluster"
               " [%0], [%1, {%3, %4, %5}], [%2], %6;"
               ::"r"(dst), "l"(m), "r"(bar), "r"(c0), "r"(c1), "r"(c2), "h"((uint16_t)3) : "memory");
}
__device__ __forceinline__ void tma3d_store(const CUtensorMap* m, uint32_t src, int c0, int c1, int c2) {
  asm volatile("cp.async.bulk.tensor.3d.global.shared::cta.bulk_group [%0, {%2, %3, %4}], [%1];"
               ::"l"(m), "r"(src), "r"(c0), "r"(c1), "r"(c2) : "memory");
}
__device__ __forceinline__ void bar_sync(int id, int n) { asm volatile("bar.sync %0, %1;" ::"r"(id), "r"(n) : "memory"); }
__device__ __forceinline__ uint32_t pack_bf16(float lo, float hi) {
  uint32_t r;
  asm("cvt.rn.bf16x2.f32 %0, %1, %2;" : "=r"(r) : "f"(hi), "f"(lo));
  return r;
}
__device__ __forceinline__ float ex2(float x) {
  float y;
  asm("ex2.approx.ftz.f32 %0, %1;" : "=f"(y) : "f"(x));
  return y;
}
__device__ __forceinline__ float fadd(float a, float b) {
  float y;
  asm("add.f32 %0, %1, %2;" : "=f"(y) : "f"(a), "f"(b));
  return y;
}
__device__ __forceinline__ float rcp(float x) {
  float y;
  asm("rcp.approx.ftz.f32 %0, %1;" : "=f"(y) : "f"(x));
  return y;
}
__device__ __forceinline__ void stsm4(uint32_t addr, uint32_t a, uint32_t b, uint32_t c, uint32_t d) {
  asm volatile("stmatrix.sync.aligned.m8n8.x4.shared.b16 [%0], {%1, %2, %3, %4};" ::"r"(addr), "r"(a), "r"(b), "r"(c), "r"(d) : "memory");
}

__device__ __forceinline__ void tma4d_mc_hint(uint32_t dst, const CUtensorMap* m, uint32_t bar, int c3, uint64_t pol) {
  asm volatile("cp.async.bulk.tensor.4d.shared::cluster.global.mbarrier::complete_tx::bytes.multicast::cluster.L2::cache_hint"
               " [%0], [%1, {%3, %3, %3, %4}], [%2], %5, %6;"
               ::"r"(dst), "l"(m), "r"(bar), "r"(0), "r"(c3), "h"((uint16_t)3), "l"(pol) : "memory");
}
__device__ __forceinline__ void tma5d_mc(uint32_t dst, const CUtensorMap* m, uint32_t bar, int c2, int c4) {
  asm volatile("cp.async.bulk.tensor.5d.shared::cluster.global.mbarrier::complete_tx::bytes.multicast::cluster"
               " [%0], [%1, {%3, %3, %4, %3, %5}], [%2], %6;"
               ::"r"(dst), "l"(m), "r"(bar), "r"(0), "r"(c2), "r"(c4), "h"((uint16_t)3) : "memory");
}
__device__ __forceinline__ void bulk_load_hint(uint32_t dst, const void* src, uint32_t bytes, uint32_t bar, uint64_t pol) {
  asm volatile("cp.async.bulk.shared::cluster.global.mbarrier::complete_tx::bytes.L2::cache_hint [%0], [%1], %2, [%3], %4;"
               ::"r"(dst), "l"(src), "r"(bytes), "r"(bar), "l"(pol) : "memory");
}
__device__ __forceinline__ void stg2_if(bool on, void* p, uint32_t a, uint32_t b, uint32_t c, uint32_t d, uint32_t e, uint32_t f,
                                        uint32_t g, uint32_t h, uint64_t pol) {
  asm volatile("{\n.reg .pred p;\nsetp.ne.b32 p, %10, 0;\n"
               "@p st.global.L2::cache_hint.v4.b32 [%0], {%1, %2, %3, %4}, %9;\n"
               "@p st.global.L2::cache_hint.v4.b32 [%0 + 512], {%5, %6, %7, %8}, %9;\n}\n"
               ::"l"(p), "r"(a), "r"(b), "r"(c), "r"(d), "r"(e), "r"(f), "r"(g), "r"(h), "l"(pol), "r"((int)on) : "memory");
}
__device__ __forceinline__ uint64_t evict_first() {
  uint64_t p;
  asm("createpolicy.fractional.L2::evict_first.b64 %0, 1.0;" : "=l"(p));
  return p;
}
__device__ __forceinline__ bool elect() {
  uint32_t ok;
  asm volatile("{\n.reg .pred p;\nelect.sync _|p, 0xffffffff;\nselp.u32 %0, 1, 0, p;\n}\n" : "=r"(ok));
  return ok;
}
__device__ __forceinline__ void mbar_arrive(uint32_t bar) {
  asm volatile("mbarrier.arrive.shared::cta.b64 _, [%0];" ::"r"(bar) : "memory");
}
template <int OFF> __device__ __forceinline__ void lds2_if(bool on, uint32_t p, uint32_t* r) {
  asm volatile("{\n.reg .pred p;\nsetp.ne.b32 p, %9, 0;\n@p ld.shared.v4.b32 {%0, %1, %2, %3}, [%8 + %10];\n"
               "@p ld.shared.v4.b32 {%4, %5, %6, %7}, [%8 + %11];\n}\n"
               : "+r"(r[0]), "+r"(r[1]), "+r"(r[2]), "+r"(r[3]), "+r"(r[4]), "+r"(r[5]), "+r"(r[6]), "+r"(r[7])
               : "r"(p), "r"((int)on), "n"(OFF), "n"(OFF + 512) : "memory");
}
__device__ __forceinline__ void lds128(uint32_t p, uint32_t& a, uint32_t& b, uint32_t& c, uint32_t& d) {
  asm volatile("ld.shared.v4.b32 {%0, %1, %2, %3}, [%4];" : "=r"(a), "=r"(b), "=r"(c), "=r"(d) : "r"(p) : "memory");
}
__device__ __forceinline__ void wait_count(const unsigned int* p, uint32_t target) {
  asm volatile("{\n.reg .pred p;\n.reg .u32 n, v;\nmov.u32 n, 0;\n"
               "LOOP:\nld.acquire.gpu.global.u32 v, [%0];\nsetp.ge.u32 p, v, %1;\n@p bra DONE;\n"
               "nanosleep.u32 %2;\nadd.u32 n, n, 1;\nsetp.lt.u32 p, n, 0x400000;\n@p bra LOOP;\ntrap;\n"
               "DONE:\n}\n" ::"l"(p), "r"(target), "n"(300) : "memory");
}

__device__ __forceinline__ int o_wave(int a, int b, int i) {
  const int p = min(3, b - a - 1);
  return i < p ? b - 2 - i : i == p ? b - 1 : b - 1 - i;
}

struct Cursor {
  uint32_t n;
  __device__ __forceinline__ uint32_t off() const { return n & (8 * NBAR - 8); }
  __device__ __forceinline__ uint32_t ph() const { return (n / (8 * NBAR)) & 1; }
  __device__ __forceinline__ void next() { n += 8; }
};

constexpr float kScaleLog2 = 0.07216878364870322f * 1.4426950408889634f;
constexpr float kSumLimit = 1048576.0f;
constexpr float kMaxLag = 8.0f;

__global__ void __cluster_dims__(2, 1, 1) __launch_bounds__(384, 1)
fused_kernel(const __grid_constant__ Params P) {
  extern __shared__ uint8_t smem_raw[];
  const uint32_t sbase = (smem_u32(smem_raw) + 1023) & ~1023u;
  const uint32_t full0 = sbase + RING, empty0 = full0 + 8 * NBAR, odone = empty0 + 8 * NBAR, oready0 = odone + 8;
  const uint32_t fenced = oready0 + 64, hready0 = fenced + 8;
  const uint32_t rank = blockIdx.x & 1;
  const int role = blockIdx.x >> 1;
  const bool helper = role >= N_CL;
  const int team = helper ? 0 : role >> 2, nt = role & 3, blk = team >> 3;
  const uint32_t* prog = P.ops[helper ? N_TEAM + 2 * (role - N_CL) : team];
  auto q_role = [&](uint32_t op) { return helper ? (int)(((op >> 3) & 60) | ((op >> 12) & 3)) : role; };
  auto o_role = [&](uint32_t op) { return helper ? (int)(((op >> 26) & 56) | ((op >> 9) & 7)) : role; };
  const int wid = __shfl_sync(0xffffffffu, (int)(threadIdx.x >> 5), 0);
  const int wg = wid >> 2;

  const uint32_t op0 = P.first[helper ? N_TEAM + role - N_CL : team];
  if (__builtin_expect(wid == 8, 1)) {
    if (elect()) {
#pragma unroll
      for (int k = 0; k < EARLY; k++) mbar_init(full0 + 8 * k, 1);
      asm volatile("fence.mbarrier_init.release.cluster;" ::: "memory");
      if ((op0 & 3) == OP_Q) {
        const int qr = q_role(op0);
#pragma unroll
        for (int k = 0; k < EARLY; k++) {
          mbar_expect(full0 + 8 * k, SZ_WQ + SZ_A);
          tma2d(sbase + k * (SZ_WQ + SZ_A) + SZ_WQ, &P.x[qr >> 5], full0 + 8 * k, 64 * k, ((qr >> 2) & 7) * kSq + rank * 128);
          tma3d(sbase + k * (SZ_WQ + SZ_A), &P.wq[qr >> 5], full0 + 8 * k, 0, 64 * k, 3 * (4 * ((op0 >> 2) & 7) + (qr & 3)));
          tma3d(sbase + k * (SZ_WQ + SZ_A) + SZ_WQ / 2, &P.wq[qr >> 5], full0 + 8 * k, 0, 64 * k + 32, 3 * (4 * ((op0 >> 2) & 7) + (qr & 3)));
        }
      }
      asm volatile("prefetch.tensormap [%0];" ::"l"(&P.kv[blk]) : "memory");
      asm volatile("prefetch.tensormap [%0];" ::"l"(&P.kv[blk + 2]) : "memory");
    }
  } else if (threadIdx.x == 0) {
#pragma unroll
    for (int i = EARLY; i < 2 * NBAR + 10 + MAX_PARK; i++) mbar_init(full0 + 8 * i, i >= NBAR && i <= 2 * NBAR ? 16 : 1);
    asm volatile("fence.mbarrier_init.release.cluster;" ::: "memory");
  }
  __syncwarp();
  asm volatile("barrier.cluster.arrive.relaxed.aligned;\nbarrier.cluster.wait.aligned;" ::: "memory");

  if (wg == 2) {
    asm volatile("setmaxnreg.dec.sync.aligned.u32 24;");
    if (wid == 8) {
      Cursor tail{0u - 8}, head{0};
      int sh = 0;
      uint32_t cur = 0, used = 0;
      uint64_t fifo = 0;
      uint32_t oready = oready0;
      const uint64_t pol = evict_first();
      struct Load { uint32_t dst, bar, wbar, wph; int c0; const void* ptr; bool wait; };
      auto reserve = [&](uint32_t bytes, bool last, uint32_t half, int c0, const void* ptr) {
        uint32_t fp = bytes >> 12;
        if (cur + fp > (RING >> 12)) { fp += (RING >> 12) - cur; cur = 0; }
        used += fp;
        bool wait = false;
        while (used > (RING >> 12)) {
          wait = true;
          tail.next();
          used -= (uint32_t)fifo & 31;
          fifo >>= 5;
          sh -= 5;
        }
        fifo += (uint64_t)fp << sh;
        Load l{sbase + (cur << 12) + rank * half, full0 + head.off(), empty0 + tail.off(), tail.ph(), c0, ptr, wait};
        cur += bytes >> 12;
        sh += last ? 5 : 0;
        head.n += last ? 8 : 0;
        asm volatile("" : "+r"(l.dst), "+r"(l.bar), "+r"(l.c0), "+l"(l.ptr), "+r"(l.wbar), "+r"(l.wph));
        return l;
      };
      auto vacated = [&](const Load& l) { if (l.wait) mbar_wait(l.wbar, l.wph); };
      auto written = [&](uint32_t flag) {
        mbar_wait(flag, 0);
        asm volatile("fence.proxy.async.global;" ::: "memory");
      };
      for (int pc = 0;; pc++) {
        const uint32_t op = prog[pc];
        const int type = op & 3, a = (op >> 2) & 7;
        if (type == OP_END) break;
        if (type == OP_Q) {
          const int qr = q_role(op);
          const CUtensorMap *mw = &P.wq[qr >> 5], *mx = &P.x[qr >> 5];
          asm volatile("" : "+l"(mw), "+l"(mx));
          auto res_w = [&](int k) { return reserve(SZ_WQ, false, SZ_WQ / 2, 64 * k + 32 * rank, mw); };
          auto load_w = [&](const Load& w, int k) {
            vacated(w);
            if ((pc > 0 || k >= EARLY) && elect()) tma3d_mc(w.dst, (const CUtensorMap*)w.ptr, w.bar, 0, w.c0, 3 * (4 * a + (qr & 3)));
          };
          auto load_x = [&](const Load& x, int k) {
            vacated(x);
            if ((pc > 0 || k >= EARLY) && elect()) {
              tma2d(x.dst, (const CUtensorMap*)x.ptr, x.bar, x.c0, ((qr >> 2) & 7) * kSq + rank * 128);
              mbar_expect(x.bar, SZ_WQ + SZ_A);
            }
          };
#pragma unroll 1
          for (int k = 0; k < 10; k++) {
            load_w(res_w(k), k);
            load_x(reserve(SZ_A, true, 0, 64 * k, mx), k);
          }
        } else if (type == OP_A) {
          const uint32_t nop = prog[pc + 1];
          const int row8 = ((team & 7) * kH + nt) * (kSk / 8) + 4 * rank, wave8 = 4 * (kSk / 8);
          auto transit = [&]() {
            const Cursor c{head.n - 8 * (KV_TRANSIT + 1)};
            mbar_wait(full0 + c.off(), c.ph());
          };
          const char* map = (const char*)&P.kv[blk];
          asm volatile("" : "+l"(map));
          int t = (op & F_PARK) ? 1 : 0, c0 = row8 + a * wave8 + 8 * t, isv = 0;
#pragma unroll 1
          for (; t < 31; t++) {
            const Load l = reserve(SZ_KV, true, SZ_KV / 2, c0, map + isv);
            vacated(l);
            if (t >= KV_TRANSIT) transit();
            if (elect()) {
              tma4d_mc_hint(l.dst, (const CUtensorMap*)l.ptr, l.bar, l.c0, pol);
              mbar_expect(l.bar, SZ_KV);
            }
            isv = (t & 1) << 8;
            c0 += isv ? -8 : t ? 16 : 8;
          }
          const int next = (nop >> 2) & 7;
          if ((nop & 3) == OP_A) written((nop & F_HELP) ? hready0 + 8 * ((nop >> 10) & 3) : fenced);
#pragma unroll 1
          for (int i = (nop & 3) == OP_A ? 0 : 3; i < 4; i++) {
            const Load l = reserve(SZ_KV, true, i < 2 ? 0 : SZ_KV / 2, i == 3 ? c0 - 8 : row8 + next * wave8,
                                   i < 2 ? (const char*)&g_o[((team * 2 + rank) * 96 + 3 * (4 * next + nt)) * 1024 + i * (SZ_PARK / 16)] : map + ((i & 1) << 8));
            vacated(l);
            if (i < 2) {
              if (elect()) bulk_load_hint(l.dst, l.ptr, SZ_PARK, l.bar, pol);
              __syncwarp();
            } else {
              transit();
              if (elect()) tma4d_mc_hint(l.dst, (const CUtensorMap*)l.ptr, l.bar, l.c0, pol);
              __syncwarp();
            }
            if (elect()) mbar_expect(l.bar, SZ_KV);
          }
        } else {
          const int b = (op >> 5) & 15, ro = o_role(op);
          const CUtensorMap* mw = &P.wo[ro >> 5];
          const uint4* so = &g_o[((ro >> 2) * 2 + rank) * 96 * 1024];
          asm volatile("" : "+l"(mw), "+l"(so));
#pragma unroll 1
          for (int j = 0; j < b - a; j++) {
            const int w = o_wave(a, b, j);
            written(oready);
            oready += 8;
#pragma unroll 1
            for (int k = 12 * w; k < 12 * w + 12; k++) {
              const Load o = reserve(SZ_A, false, 0, 0, so + k * 1024);
              vacated(o);
              if (elect()) bulk_load_hint(o.dst, o.ptr, SZ_A, o.bar, pol);
              const Load w = reserve(SZ_WO, true, SZ_WO / 2, 8 * k + 4 * rank, mw);
              vacated(w);
              if (elect()) {
                tma5d_mc(w.dst, (const CUtensorMap*)w.ptr, w.bar, w.c0, 5 * (ro & 3));
                mbar_expect(w.bar, SZ_WO + SZ_A);
              }
            }
          }
          if ((op & F_LD) && (op & F_PARK)) written(hready0 + 8 * (MAX_PARK - 1));
#pragma unroll 1
          for (int i = (op & F_LD) ? 0 : 5; i < ((op & F_ST) ? 5 : 6); i++) {
            const Load l = reserve(i < 5 ? SZ_PART : SZ_OUT, i < 5, 0, 0, &g_part[(role * 2 + rank) * 5120 + i * (SZ_PART / 16)]);
            vacated(l);
            if (i < 5 && elect()) bulk_load_hint(l.dst, l.ptr, SZ_PART, l.bar, pol);
            if (elect()) mbar_expect(l.bar, i < 5 ? SZ_PART : 0);
          }
        }
      }
#pragma unroll 1
      for (Cursor c{head.n - 8 * NBAR}; c.n != head.n; c.next()) mbar_wait(empty0 + c.off(), c.ph());
    } else if (threadIdx.x == 288) {
      uint32_t ph = 0;
      bool first = true;
      for (int pc = 0;; pc++) {
        const uint32_t op = prog[pc];
        if ((op & 3) == OP_END) break;
        if ((op & 3) != OP_A && !helper) continue;
        mbar_wait_long(odone, ph);
        ph ^= 1;
        unsigned int* flag = !helper ? &g_done[(team * 2 + rank) * 8 + ((op >> 2) & 7)]
                             : (op & 3) == OP_Q ? &g_help[(q_role(op) * 2 + rank) * MAX_PARK + ((op >> 10) & 3)]
                                                : &g_help[(o_role(op) * 2 + rank) * MAX_PARK + MAX_PARK - 1];
        asm volatile("red.release.gpu.global.add.u32 [%0], 1;" ::"l"(flag) : "memory");
        if (first) mbar_arrive(fenced);
        first = false;
      }
    } else if (threadIdx.x == 320) {
      uint32_t oready = oready0;
      for (int pc = 0;; pc++) {
        const uint32_t op = prog[pc];
        if ((op & 3) == OP_END) break;
        if ((op & 3) == OP_O) {
          const int a = (op >> 2) & 7, b = (op >> 5) & 15;
#pragma unroll 1
          for (int i = 0; i < b - a; i++) {
            const int ci = ((o_role(op) >> 2) * 2 + rank) * 8 + o_wave(a, b, i);
            wait_count(&g_done[ci], 4);
            mbar_arrive(oready);
            oready += 8;
            if (atomicAdd(&g_seen[ci], 1u) == 3u) { g_seen[ci] = 0; g_done[ci] = 0; }
          }
        }
        if ((op & 3) != OP_Q && (op & F_HELP) && (op & F_PARK)) {
          unsigned int* flag = &g_help[(role * 2 + rank) * MAX_PARK + ((op >> 10) & 3)];
          wait_count(flag, 1);
          mbar_arrive(hready0 + 8 * ((op >> 10) & 3));
          *flag = 0;
        }
      }
    }
  } else {
    asm volatile("setmaxnreg.inc.sync.aligned.u32 240;");
    const int lane = threadIdx.x & 31, warp = wid & 3;
    uint32_t empty_rem;
    asm volatile("mapa.shared::cluster.u32 %0, %1, %2;" : "=r"(empty_rem) : "r"(empty0), "r"(lane & 1));
    auto release = [&](int slot) { mbar_arrive_cluster_if(lane < 2, empty_rem + slot); };
    Cursor r{0};
    const uint32_t ring16 = (sbase & 0x3FFFF) >> 4;
    uint32_t cur = ring16;
    bool rdy0 = false, rdy1 = false;
    auto probe1 = [&]() { rdy0 = mbar_test(full0 + r.off(), r.ph()); };
    auto probe2 = [&]() {
      Cursor n = r;
      rdy0 = mbar_test(full0 + n.off(), n.ph());
      n.next();
      rdy1 = mbar_test(full0 + n.off(), n.ph());
    };
    auto take = [&](bool rdy, uint32_t bytes, uint32_t& addr) {
      const int bi = r.off();
      if (!__all_sync(0xffffffffu, rdy)) mbar_wait_math(full0 + r.off(), r.ph());
      r.next();
      if (cur > ring16 + ((RING - bytes) >> 4)) cur = ring16;
      addr = cur;
      cur += bytes >> 4;
      return bi;
    };
    auto at = [&](uint32_t a16) {
      uint32_t a = sbase + (a16 - ring16) * 16;
      asm("" : "+r"(a));
      return a;
    };
    auto second = [&](uint32_t bytes) {
      if (cur > ring16 + ((RING - bytes) >> 4)) cur = ring16;
      cur += bytes >> 4;
      return cur - (bytes >> 4);
    };
    const int row = wg * 64 + warp * 16 + (lane >> 2);
    int img0 = (row * 4 + ((lane & 3) ^ ((row >> 1) & 3))) * 16;
    uint4* pend = nullptr;
    const uint64_t spol = evict_first();
    int pc = 0;
    uint32_t op = prog[0];
    auto enter = [&]() {
      r.n = op >> 12; cur = ring16 + (((op >> 20) & 63) << 8);
    };
    auto drain = [&](uint32_t (&t)[48], uint32_t c) {
      if (!(op & (3u << 26)) || c >= 6) return;
#pragma unroll
      for (int i = 0; i < 6; i++)
        stg2_if(c == i, pend + i * 512, t[8 * i], t[8 * i + 1], t[8 * i + 2], t[8 * i + 3],
                t[8 * i + 4], t[8 * i + 5], t[8 * i + 6], t[8 * i + 7], spol);
      if ((op & (1u << 26)) && c == 5) {
        __syncwarp();
        mbar_arrive_if(lane < 2, odone);
      }
    };
    float s[32], o[96], c[80];
    uint32_t q[48], pa[16], pb[16];
    float mc0, mc1, l0, l1;
    bool gen;
    auto soft = [&](float (&s)[32], uint32_t (&pout)[16], bool first) {
      if (first) { gen = false; mc0 = 0.f; mc1 = 0.f; }
      float b0, b1;
      for (;;) {
        if (gen) {
          float m0 = fmaxf(s[0], s[1]), m1 = fmaxf(s[2], s[3]);
#pragma unroll
          for (int i = 1; i < 8; i++) { m0 = fmaxf(m0, fmaxf(s[4 * i], s[4 * i + 1])); m1 = fmaxf(m1, fmaxf(s[4 * i + 2], s[4 * i + 3])); }
          m0 = fmaxf(m0, __shfl_xor_sync(0xffffffffu, m0, 1)); m1 = fmaxf(m1, __shfl_xor_sync(0xffffffffu, m1, 1));
          m0 = fmaxf(m0, __shfl_xor_sync(0xffffffffu, m0, 2)); m1 = fmaxf(m1, __shfl_xor_sync(0xffffffffu, m1, 2));
          if (first) {
            mc0 = m0; mc1 = m1;
          } else if (__any_sync(0xffffffffu, !(m0 <= mc0 + kMaxLag && m1 <= mc1 + kMaxLag))) {
            m0 = fmaxf(mc0, m0); m1 = fmaxf(mc1, m1);
            const float a0 = ex2(mc0 - m0), a1 = ex2(mc1 - m1);
            mc0 = m0; mc1 = m1;
            l0 *= a0; l1 *= a1;
            wg_wait<0>();
            fence_regs(o);
#pragma unroll
            for (int i = 0; i < 96; i++) o[i] *= i & 2 ? a1 : a0;
          }
#pragma unroll
          for (int i = 0; i < 32; i++) s[i] -= i & 2 ? mc1 : mc0;
        }
#pragma unroll
        for (int i = 0; i < 8; i++) {
          const float e1 = ex2(s[4 * i + 1]), e0 = ex2(s[4 * i]), e3 = ex2(s[4 * i + 3]), e2 = ex2(s[4 * i + 2]);
          pout[2 * i] = pack_bf16(e0, e1);
          b0 = i ? b0 + fadd(e1, e0) : fadd(e1, e0);
          pout[2 * i + 1] = pack_bf16(e2, e3);
          b1 = i ? b1 + fadd(e3, e2) : fadd(e3, e2);
        }
        if (!__any_sync(0xffffffffu, !gen && !(fmaxf(b0, b1) <= kSumLimit && (!first || fminf(b0, b1) >= 1.0f / kSumLimit)))) break;
        gen = __any_sync(0xffffffffu, true);
      }
      l0 = first ? b0 : l0 + b0;
      l1 = first ? b1 : l1 + b1;
    };
    auto qk = [&](float (&s)[32], uint32_t ak, int k0, int k1) {
#pragma unroll
      for (int kk = k0; kk < k1; kk++)
        wgmma_rs_n64<0>(s, q[4 * kk], q[4 * kk + 1], q[4 * kk + 2], q[4 * kk + 3], mk_desc(ak, 16, KV_SBO, 1, (kk >> 2) * KV_CH + (kk & 3) * 2), kk != 0);
      wg_commit();
    };
    auto pv = [&](uint32_t (&pin)[16], uint32_t av, int acc) {
#pragma unroll
      for (int kk = 0; kk < 4; kk++)
        wgmma_rs_n192<1>(o, pin[4 * kk], pin[4 * kk + 1], pin[4 * kk + 2], pin[4 * kk + 3], mk_desc(av, KV_CH * 16, KV_SBO, 1, kk * (KV_SBO / 8)), acc || (kk != 0));
      wg_commit();
    };
    auto xw = [&](uint32_t ad, int acc) {
      const uint32_t da = second(SZ_A) + wg * 512;
      wg_fence();
#pragma unroll
      for (int kk = 0; kk < 4; kk++)
        wgmma_ss_n192<1>(o, mk_desc(da, 16, 1024, 1, kk * 2), mk_desc(ad, 4096, 1024, 1, (kk & 1) * 128 + (kk >> 1) * 768), acc || kk != 0);
      wg_commit();
    };
    auto ow = [&](int acc, int prev) {
      uint32_t da;
      const int bi = take(rdy0, SZ_A, da);
      const uint32_t db = second(SZ_WO);
      da += wg * 256;
      wg_fence();
      wgmma_ss_n160<1>(c, mk_desc(da, 16, 512, 2), mk_desc(db, 2048, 512, 2), acc);
      wgmma_ss_n160<1>(c, mk_desc(da, 16, 512, 2, 2), mk_desc(db, 2048, 512, 2, 64), 1);
      wg_commit();
      if (acc == 1) { wg_wait<1>(); release(prev); }
      wgmma_ss_n160<1>(c, mk_desc(da, 16, 512, 2, 512), mk_desc(db, 2048, 512, 2, 640), 1);
      wgmma_ss_n160<1>(c, mk_desc(da, 16, 512, 2, 514), mk_desc(db, 2048, 512, 2, 704), 1);
      wg_commit();
      return bi;
    };
    auto st_part = [&](int i) {
      stg2_if(true, pend + i * 512, __float_as_uint(c[8 * i]), __float_as_uint(c[8 * i + 1]), __float_as_uint(c[8 * i + 2]), __float_as_uint(c[8 * i + 3]),
              __float_as_uint(c[8 * i + 4]), __float_as_uint(c[8 * i + 5]), __float_as_uint(c[8 * i + 6]), __float_as_uint(c[8 * i + 7]), spol);
    };
#pragma unroll
    for (int i = 0; i < 48; i++) q[i] = 0;
    enter();

    if ((op & 3) == OP_Q) {
      uint32_t ad;
      int bi0 = take(false, SZ_WQ, ad), k = 0, lag = 0;
      xw(ad, 0);
      for (;;) {
#pragma unroll 1
        for (;;) {
          drain(q, k - lag);
          probe1();
          wg_wait<0>();
          release(bi0);
          bi0 = take(rdy0, SZ_WQ, ad);
          if (++k == 8) break;
          xw(ad, 1);
        }
        if (wg) bar_sync(2, 256);
        xw(ad, 1);
        const int bi9 = take(false, SZ_WQ, ad);
        xw(ad, 1);
        if (!wg) asm volatile("bar.arrive 2, 256;" ::: "memory");
        k = 0; lag = 0;
        uint32_t nop = prog[++pc];
        wg_wait<1>();
        release(bi0);
        probe2();
        wg_wait<0>();
        fence_regs(o);
        release(bi9);
#pragma unroll
        for (int i = 0; i < 48; i++) q[i] = pack_bf16(o[2 * i] * kScaleLog2, o[2 * i + 1] * kScaleLog2);
        fence_regs(q);
        if (op & F_PARK) {
          const int qt = helper ? (op >> 5) & 15 : team, qm = helper ? (op >> 12) & 3 : nt;
          pend = (uint4*)((char*)&g_o[((qt * 2 + rank) * 96 + 3 * (4 * ((op >> 2) & 7) + qm)) * 1024] + img0);
          op = nop;
          enter();
          if ((op & 3) != OP_Q) break;
          const int b = take(rdy0, SZ_WQ, ad);
          xw(ad, 0);
          bi0 = take(rdy1, SZ_WQ, ad);
          xw(ad, 1);
          wg_wait<1>();
          release(b);
          k = 1; lag = 1;
          continue;
        }
        int wave = (op >> 2) & 7, sk1;
        uint32_t ak1;
        {
          float s0[32];
          const int sk0 = take(rdy0, SZ_KV, ad);
          wg_fence();
          qk(s0, ad, 0, 12);
          sk1 = take(rdy1, SZ_KV, ak1);
          wg_fence();
          qk(s, ak1, 0, S1A);
          probe1();
          wg_wait<1>();
          fence_regs(s0);
          release(sk0);
          soft(s0, pa, true);
        }
        float i0, i1;
        auto sums = [&]() {
          l0 += __shfl_xor_sync(0xffffffffu, l0, 1); l1 += __shfl_xor_sync(0xffffffffu, l1, 1);
          l0 += __shfl_xor_sync(0xffffffffu, l0, 2); l1 += __shfl_xor_sync(0xffffffffu, l1, 2);
          i0 = rcp(l0); i1 = rcp(l1);
          asm volatile("" : "+f"(i0), "+f"(i1));
        };
        auto target = [&]() {
          pend = (uint4*)((char*)&g_o[((team * 2 + rank) * 96 + 3 * (4 * wave + nt)) * 1024] + img0);
          asm volatile("" : "+l"(pend));
        };
        bool late = false;
#pragma unroll
        for (int i = 0; i < 16; i++) pb[i] = 0;
        for (;;) {
          nop = prog[++pc];
          {
            uint32_t av;
            const int sv = take(rdy0, SZ_KV, av);
            wg_fence();
            qk(s, ak1, S1A, 12);
            pv(pa, av, 0);
            if (late) {
              stg2_if(true, pend + 4 * 512, pb[0], pb[1], pb[2], pb[3], pb[4], pb[5], pb[6], pb[7], spol);
              stg2_if(true, pend + 5 * 512, pb[8], pb[9], pb[10], pb[11], pb[12], pb[13], pb[14], pb[15], spol);
              __syncwarp();
              mbar_arrive_if(lane < 2, odone);
            }
            probe2();
            wg_wait<1>();
            fence_regs(s);
            release(sk1);
            soft(s, pb, false);
            wg_wait<0>();
            fence_regs(o);
            release(sv);
          }
          auto step = [&](uint32_t (&pin)[16], uint32_t (&pout)[16], bool hook, bool unpark) {
            uint32_t ak, av;
            const int sk = take(rdy0, SZ_KV, ak), sv = take(rdy1, SZ_KV, av);
            wg_fence();
            qk(s, ak, 0, 12);
            pv(pin, av, 1);
            if (hook && unpark) { take(false, SZ_PARK, ak); take(false, SZ_PARK, av); }
            probe2();
            wg_wait<1>();
            fence_regs(s);
            release(sk);
            if (hook) {
              lds2_if<0>(unpark, img0 + at(ak), q);
              lds2_if<8192>(unpark, img0 + at(ak), q + 8);
              lds2_if<16384>(unpark, img0 + at(ak), q + 16);
              lds2_if<0>(unpark, img0 + at(av), q + 24);
              lds2_if<8192>(unpark, img0 + at(av), q + 32);
              lds2_if<16384>(unpark, img0 + at(av), q + 40);
            }
            soft(s, pout, false);
            wg_wait<0>();
            fence_regs(o);
            release(sv);
          };
          const int jpark = (nop & 3) == OP_A ? 6 : 7;
#pragma unroll 1
          for (int jj = 0; jj < 7; jj++) {
            step(pb, pa, false, false);
            step(pa, pb, true, jj == jpark);
          }
          if ((nop & 3) != OP_A) break;
          uint32_t ak, av;
          release(Cursor{r.n - 16}.off());
          release(Cursor{r.n - 8}.off());
          const int sk0 = take(rdy0, SZ_KV, ak), sv = take(rdy1, SZ_KV, av);
          wg_fence();
          qk(s, ak, 0, 8);
          sched_fence(img0, P.zero);
          sums();
          sched_fence(img0, P.zero);
          qk(s, ak, 8, 12);
          pv(pb, av, 1);
          probe2();
          wg_wait<1>();
          fence_regs(s);
          release(sk0);
          soft(s, pa, true);
          sk1 = take(rdy0, SZ_KV, ak1);
          rdy0 = rdy1;
          wg_wait<0>();
          target();
          fence_regs(o);
          release(sv);
          uint32_t t[48];
#pragma unroll
          for (int j = 0; j < 6; j++) {
#pragma unroll
            for (int i = 0; i < 4; i++) {
              t[8 * j + i] = pack_bf16(o[16 * j + 4 * i] * i0, o[16 * j + 4 * i + 1] * i0);
              t[8 * j + i + 4] = pack_bf16(o[16 * j + 4 * i + 2] * i1, o[16 * j + 4 * i + 3] * i1);
            }
            if (j < 4)
            stg2_if(true, pend + j * 512, t[8 * j], t[8 * j + 1], t[8 * j + 2], t[8 * j + 3], t[8 * j + 4], t[8 * j + 5], t[8 * j + 6], t[8 * j + 7], spol);
            if (j == 3) { wg_fence(); qk(s, ak1, 0, 4); }
            if (j == 5) { wg_fence(); qk(s, ak1, 4, S1A); }
            sched_fence(img0, P.zero);
          }
          if (P.zero) {
#pragma unroll
            for (int j = 0; j < 4; j++)
              stg2_if(true, pend, t[8 * j], t[8 * j + 1], t[8 * j + 2], t[8 * j + 3], t[8 * j + 4], t[8 * j + 5], t[8 * j + 6], t[8 * j + 7], spol);
          }
          late = true;
#pragma unroll
          for (int i = 0; i < 16; i++) pb[i] = t[32 + i];
          wave = (nop >> 2) & 7;
        }
        const int sv = take(rdy0, SZ_KV, ad);
        wg_fence();
        pv(pb, ad, 1);
        sums();
        target();
        op = nop;
        enter();
        rdy0 = rdy1;
        auto convert = [&](float (&u)[96], int j0, int j1) {
#pragma unroll
          for (int i = 4 * j0; i < 4 * j1; i++) {
            q[8 * (i >> 2) + (i & 3)] = pack_bf16(u[4 * i], u[4 * i + 1]);
            q[8 * (i >> 2) + (i & 3) + 4] = pack_bf16(u[4 * i + 2], u[4 * i + 3]);
          }
        };
        if ((op & 3) != OP_O) {
          if ((op & 3) == OP_Q) bi0 = take(rdy0, SZ_WQ, ad);
          wg_wait<0>();
          fence_regs(o);
          release(sv);
          float u[96];
#pragma unroll
          for (int i = 0; i < 96; i++) u[i] = o[i] * (i & 2 ? i1 : i0);
          if ((op & 3) != OP_Q) { convert(u, 0, 6); break; }
          fence_regs(u);
          xw(ad, 0);
          sched_fence(img0, P.zero);
          fence_regs(u);
          convert(u, 0, 1);
          stg2_if(true, pend, q[0], q[1], q[2], q[3], q[4], q[5], q[6], q[7], spol);
          probe1();
          wg_wait<0>();
          release(bi0);
          bi0 = take(rdy0, SZ_WQ, ad);
          xw(ad, 1);
          sched_fence(img0, P.zero);
          fence_regs(u);
          convert(u, 1, 6);
          k = 1;
          continue;
        }
        int bi = ow(0, 0);
        wg_wait<2>();
        fence_regs(o);
        release(sv);
#pragma unroll
        for (int j = 0; j < 6; j++) {
          uint32_t t[8];
#pragma unroll
          for (int i = 0; i < 4; i++) {
            t[i] = pack_bf16(o[16 * j + 4 * i] * i0, o[16 * j + 4 * i + 1] * i0);
            t[i + 4] = pack_bf16(o[16 * j + 4 * i + 2] * i1, o[16 * j + 4 * i + 3] * i1);
          }
          stg2_if(true, pend + j * 512, t[0], t[1], t[2], t[3], t[4], t[5], t[6], t[7], spol);
          if (j == 5) {
            __syncwarp();
            mbar_arrive_if(lane < 2, odone);
          }
          probe1();
          wg_wait<1>();
          bi = ow(1, bi);
          fence_regs(o);
        }
        {
          const int nk = 12 * (((op >> 5) & 15) - ((op >> 2) & 7)) - ((op & F_ST) ? 0 : 2);
#pragma unroll 1
          for (int k = 7; k < nk; k++) {
            probe1();
            wg_wait<1>();
            bi = ow(1, bi);
          }
        }
        if (!(op & F_ST)) {
          probe2();
          wg_wait<1>();
          if (wg) {
            wg_wait<0>();
            release(bi);
            bar_sync(2, 256);
          }
          bi0 = ow(2, 0);
          rdy0 = rdy1;
          const int b = ow(2, 0);
          if (!wg) asm volatile("bar.arrive 2, 256;" ::: "memory");
          wg_wait<4>();
          mbar_arrive_cluster_if(lane < 2 && !wg, empty_rem + bi);
          bi = b;
        }
        probe1();
        nop = prog[++pc];
        if (op & F_LD) {
          uint32_t t[80];
#pragma unroll
          for (int j = 0; j < 5; j++) {
            const int b = take(rdy0, SZ_PART, ad);
            probe1();
#pragma unroll
            for (int i = 4 * j; i < 4 * j + 4; i++)
              lds128(img0 + at(ad) + ((i >> 1) & 1) * 8192 + (i & 1) * 512, t[4 * i], t[4 * i + 1], t[4 * i + 2], t[4 * i + 3]);
            release(b);
          }
          wg_wait<0>();
          fence_regs(c);
#pragma unroll
          for (int i = 0; i < 80; i++) c[i] += __uint_as_float(t[i]);
        }
        if (!(op & F_ST)) {
          wg_wait<0>();
          fence_regs(c);
          release(bi0);
          release(bi);
          goto finish;
        }
        op = nop;
        enter();
        bi0 = take(rdy0, SZ_WQ, ad);
        xw(ad, 0);
        pend = (uint4*)((char*)&g_part[((team * 4 + nt) * 2 + rank) * 5120] + img0);
        probe1();
        wg_wait<1>();
        fence_regs(c);
        release(bi);
        st_part(0); st_part(1);
        wg_wait<0>();
        release(bi0);
        bi0 = take(rdy0, SZ_WQ, ad);
        xw(ad, 1);
        st_part(2); st_part(3);
#pragma unroll
        for (int i = 0; i < 48; i++) q[i] = __float_as_uint(c[32 + i]);
        pend += 4 * 512;
        k = 1; lag = 2;
      }
    }
    rdy0 = false;
    {
      uint32_t t[48];
#pragma unroll
      for (int i = 0; i < 48; i++) t[i] = q[i] ^ P.zero;
      while ((op & 3) == OP_O) {
        int bi = ow(0, 0);
#pragma unroll 1
        for (int k = 1; k < 12 * (int)(((op >> 5) & 15) - ((op >> 2) & 7)); k++) {
          drain(t, k - 1);
          probe1();
          wg_wait<1>();
          bi = ow(1, bi);
        }
        rdy0 = false;
        wg_wait<0>();
        fence_regs(c);
        pc++;
        release(bi);
        if (!(op & F_ST)) goto finish;
        pend = (uint4*)((char*)&g_part[((((op >> 26) & 56) | ((op >> 9) & 7)) * 2 + rank) * 5120] + img0);
#pragma unroll
        for (int i = 6; i < 10; i++) st_part(i);
#pragma unroll
        for (int i = 0; i < 48; i++) t[i] = __float_as_uint(c[i]) ^ P.zero;
        op = prog[pc];
        enter();
      }
      for (int i = 0; i < 6; i++) drain(t, i);
    }
    if (false) {
    finish:
      uint32_t ad;
      take(rdy0, SZ_OUT, ad);
      const uint32_t wstage = sbase + (ad - ring16) * 16 + (wg * 4 + warp) * 5120;
      const uint32_t sa = wstage + (lane & 15) * 64;
#pragma unroll
      for (int i = 0; i < 10; i++) {
        const int u = (i & 1) * 2 + (lane >> 4);
        stsm4(sa + (i >> 1) * 1024 + ((u ^ ((lane >> 1) & 3)) << 4), pack_bf16(c[8 * i], c[8 * i + 1]), pack_bf16(c[8 * i + 2], c[8 * i + 3]),
              pack_bf16(c[8 * i + 4], c[8 * i + 5]), pack_bf16(c[8 * i + 6], c[8 * i + 7]));
      }
      asm volatile("fence.proxy.async.shared::cta;" ::: "memory");
      __syncwarp();
      if (lane == 0) {
        tma3d_store(&P.out, wstage, 0, (team & 7) * kSq + rank * 128 + wg * 64 + warp * 16, blk * 20 + nt * 5);
        asm volatile("cp.async.bulk.commit_group;\ncp.async.bulk.wait_group.read 0;" ::: "memory");
      }
    }
  }
}

typedef CUresult (*EncodeFn)(CUtensorMap*, CUtensorMapDataType, cuuint32_t, void*, const cuuint64_t*, const cuuint64_t*,
                             const cuuint32_t*, const cuuint32_t*, CUtensorMapInterleave, CUtensorMapSwizzle,
                             CUtensorMapL2promotion, CUtensorMapFloatOOBfill);

void encode(EncodeFn fn, CUtensorMap* m, const void* ptr, int rank, const cuuint64_t* dims, const cuuint64_t* strides,
            const cuuint32_t* box, CUtensorMapSwizzle swz) {
  const cuuint32_t es[5] = {1, 1, 1, 1, 1};
  CUresult r = fn(m, CU_TENSOR_MAP_DATA_TYPE_BFLOAT16, rank, const_cast<void*>(ptr), dims, strides, box, es,
                  CU_TENSOR_MAP_INTERLEAVE_NONE, swz, CU_TENSOR_MAP_L2_PROMOTION_L2_128B, CU_TENSOR_MAP_FLOAT_OOB_FILL_NONE);
  if (r != CUDA_SUCCESS) fprintf(stderr, "cuTensorMapEncodeTiled failed: %d\n", (int)r);
}

void annotate(uint32_t* ops, int n, bool helper) {
  uint32_t items = 0, cur = 0, pend = 0;
  auto item = [&](uint32_t bytes, int count, uint32_t bytes2 = 0) {
    for (int i = 0; i < count; i++) {
      if (cur + bytes > RING) cur = 0;
      cur += bytes;
      if (cur + bytes2 > RING) cur = 0;
      cur += bytes2;
      items++;
    }
  };
  for (int i = 0; i <= n; i++) {
    const uint32_t op = ops[i];
    ops[i] |= (items % (2 * NBAR)) << 15 | (cur >> 12) << 20 | pend << 26;
    if ((op & 3) == OP_Q) { item(SZ_WQ, 10, SZ_A); pend = (op & F_PARK) ? (helper ? 1 : 2) : 0; }
    if ((op & 3) == OP_A) {
      item(SZ_KV, (op & F_PARK) ? 30 : 31);
      if ((ops[i + 1] & 3) == OP_A) { item(SZ_PARK, 2); item(SZ_KV, 1); }
      item(SZ_KV, 1);
      pend = 1;
    }
    if ((op & 3) == OP_O) {
      item(SZ_A, 12 * (((op >> 5) & 15) - ((op >> 2) & 7)), SZ_WO);
      if (op & F_LD) item(SZ_PART, 5);
      pend = (op & F_ST) ? (helper ? 1 : 2) : 0;
    }
  }
}

void compile_programs(const char* const* text, bool helpers, Params& P) {
  struct Req { int when, team, wave, slot; } req[N_TEAM * MAX_PARK];
  int n_req = 0;
  for (int t = 0; t < N_TEAM; t++) {
    uint32_t* ops = P.ops[t];
    int n = 0, flags[8] = {0, 0, 0, 0, 0, 0, 0, 0}, n_park = 0, last_o = -1, when = 0, given = 0;
    for (const char* s = text[t]; *s; s++) {
      const int a = s[1] - '0';
      if (*s == 'Q' || (*s == 'H' && !helpers)) { ops[n++] = OP_Q | a << 2; when += 10; }
      else if (*s == 'P') { flags[a] = F_PARK; ops[n++] = OP_Q | a << 2 | flags[a]; when += 10; }
      else if (*s == 'H') { req[n_req++] = {when, t, a, n_park}; flags[a] = F_PARK | F_HELP | n_park++ << 10; }
      else if (*s == 'A') { ops[n++] = OP_A | a << 2 | flags[a]; when += 32; }
      else if (*s == 'G') { given = a; if (helpers) req[n_req++] = {1000, t, 0, -a}; }
      else if (*s == 'O') {
        ops[n] = OP_O | a << 2 | (s[2] - '0') << 5;
        if (given) ops[n] = helpers ? ops[n] | F_LD | F_PARK | (MAX_PARK - 1) << 10 : ops[n] & ~(7u << 2);
        if (last_o >= 0) { ops[last_o] |= F_ST; ops[n] |= F_LD; }
        last_o = n++;
        when += 10 * (s[2] - s[1]);
      }
    }
    for (int i = n; i < MAX_OPS; i++) ops[i] = OP_END;
    annotate(ops, n, false);
  }
  for (int i = 1; i < n_req; i++)
    for (int j = i; j > 0 && req[j].when < req[j - 1].when; j--) { Req r = req[j]; req[j] = req[j - 1]; req[j - 1] = r; }
  for (int h = 0; h < N_HELP; h++) {
    uint32_t* ops = P.ops[N_TEAM + 2 * h];
    int n = 0;
    for (int i = 0; i < n_req; i++)
      for (int m = h; m < 4; m += N_HELP) {
        const uint32_t ro = 4 * req[i].team + m;
        ops[n++] = req[i].slot >= 0 ? OP_Q | req[i].wave << 2 | req[i].team << 5 | F_PARK | req[i].slot << 10 | m << 12
                                    : OP_O | -req[i].slot << 5 | F_ST | (ro & 7) << 9 | (ro >> 3) << 29;
      }
    for (int i = n; i < 2 * MAX_OPS; i++) ops[i] = OP_END;
    annotate(ops, n, true);
  }
  for (int i = 0; i < 32; i++) P.first[i] = i < N_TEAM ? P.ops[i][0] : i < N_TEAM + N_HELP ? P.ops[2 * i - N_TEAM][0] : 0;
}

const char* const kPrograms[N_TEAM] = {
  "Q0A0Q1A1H2A2O03Q3A3Q4A4Q5A5Q6A6Q7A7O38",
  "Q0A0Q1A1Q2A2Q3A3Q4A4O05Q5A5Q6A6H7A7O58",
  "Q0A0H1A1Q2A2Q3A3Q4A4O05Q5A5Q6A6Q7A7O58",
  "Q0A0Q1A1Q2A2O03Q3A3Q4A4Q5A5H6A6Q7A7O38",
  "Q0A0Q1A1Q2A2Q3A3O04Q4A4Q5A5Q6A6H7A7O48",
  "Q0A0Q1A1H2A2Q3A3Q4A4O05Q5A5Q6A6Q7A7O58",
  "Q0A0Q1A1Q2A2O03Q3A3Q4A4H5A5Q6A6Q7A7O38",
  "Q0A0Q1A1Q2A2O03Q3A3H4A4Q5A5Q6A6Q7A7O38",
  "P3Q0A0Q1A1Q2A2A3Q4A4Q5A5H6A6Q7A7O08",
  "P5P7Q0A0Q1A1Q2A2H3A3Q4A4A5Q6A6A7G1O18",
  "Q0A0Q1A1Q2A2O02Q3A3H4A4Q5A5Q6A6Q7A7O28",
  "P3P5Q0A0Q1A1Q2A2A3Q4A4A5Q6A6H7A7O08",
  "Q0A0Q1A1Q2A2Q3A3Q4A4Q5A5H6A6Q7A7O08",
  "P7Q0A0Q1A1Q2A2Q3A3Q4A4Q5A5Q6A6A7G1O18",
  "Q0A0Q1A1Q2A2H3A3Q4A4Q5A5Q6A6Q7A7O08",
  "P3Q0A0Q1A1Q2A2A3H4A4Q5A5Q6A6Q7A7O08",
};

const char* const* bench_programs() {
  return kPrograms;
}

}

extern "C" void kernel_launch(void* const* d_in, const int* in_sizes, int n_in, void* d_out, int out_size) {
  (void)in_sizes; (void)n_in; (void)out_size;
  static EncodeFn fn = nullptr;
  static int n_clusters = 0;
  if (!fn) {
    cudaDriverEntryPointQueryResult qr;
    void* f = nullptr;
    cudaGetDriverEntryPoint("cuTensorMapEncodeTiled", &f, cudaEnableDefault, &qr);
    fn = (EncodeFn)f;
    cudaFuncSetAttribute(fused_kernel, cudaFuncAttributeMaxDynamicSharedMemorySize, SMEM_BYTES);
    cudaLaunchConfig_t cfg = {};
    cfg.gridDim = dim3(132); cfg.blockDim = dim3(384); cfg.dynamicSmemBytes = SMEM_BYTES;
    cudaLaunchAttribute at[1];
    at[0].id = cudaLaunchAttributeClusterDimension; at[0].val.clusterDim.x = 2; at[0].val.clusterDim.y = 1; at[0].val.clusterDim.z = 1;
    cfg.attrs = at; cfg.numAttrs = 1;
    if (cudaOccupancyMaxActiveClusters(&n_clusters, fused_kernel, &cfg) != cudaSuccess || n_clusters < 1) n_clusters = 1;
    (void)cudaGetLastError();
  }
  Params P;
  const CUtensorMapSwizzle S128 = CU_TENSOR_MAP_SWIZZLE_128B, S64 = CU_TENSOR_MAP_SWIZZLE_64B;
  for (int blk = 0; blk < 2; blk++) {
    void* const* in = d_in + 5 * blk;
    { const cuuint64_t d[] = {kD, kB * kSq}, s[] = {kD * 2}; const cuuint32_t b[] = {64, 128};
      encode(fn, &P.x[blk], in[0], 2, d, s, b, S128); }
    { const cuuint64_t d[] = {64, 8, 3, (cuuint64_t)kB * kH * kSk / 8}, s[] = {kDh * 2, 128, 8 * kDh * 2}; const cuuint32_t b[] = {64, 8, 3, 4};
      encode(fn, &P.kv[blk], in[1], 4, d, s, b, S128);
      encode(fn, &P.kv[blk + 2], in[2], 4, d, s, b, S128); }
    { const cuuint64_t d[] = {64, kD, kHD / 64}, s[] = {kHD * 2, 128}; const cuuint32_t b[] = {64, 32, 3};
      encode(fn, &P.wq[blk], in[3], 3, d, s, b, S128); }
    { const cuuint64_t d[] = {32, 2, kHD / 8, 4, kD / 32}, s[] = {kD * 2, 8 * kD * 2, 2 * kD * 2, 64}; const cuuint32_t b[] = {32, 2, 4, 4, 5};
      encode(fn, &P.wo[blk], in[4], 5, d, s, b, S64); }
  }
  { const cuuint64_t d[] = {32, kB * kSq, 2 * kD / 32}, s[] = {2 * kD * 2, 64}; const cuuint32_t b[] = {32, 16, 5};
    encode(fn, &P.out, d_out, 3, d, s, b, S64); }

  P.zero = 0;
  if (n_clusters >= N_CL) {
    const bool helpers = n_clusters >= N_CL + N_HELP;
    compile_programs(bench_programs(), helpers, P);
    fused_kernel<<<2 * (N_CL + (helpers ? N_HELP : 0)), 384, SMEM_BYTES>>>(P);
  } else {
    for (int phase = 0; phase < 2; phase++) {
      const char* text[N_TEAM];
      for (int t = 0; t < N_TEAM; t++) text[t] = phase ? "O08" : "Q0A0Q1A1Q2A2Q3A3Q4A4Q5A5Q6A6Q7A7";
      compile_programs(text, false, P);
      fused_kernel<<<2 * N_CL, 384, SMEM_BYTES>>>(P);
    }
  }
}
```

```cpp
#include <cuda_runtime.h>
#include <cuda_bf16.h>
#include <cuda.h>
#include <stdint.h>
#include <stdio.h>

namespace {

constexpr int kB = 8, kSq = 256, kD = 640, kH = 32, kSk = 1024, kDh = 192;
constexpr int kHD = kH * kDh;
constexpr uint32_t RING = 224 * 1024;
constexpr uint32_t SZ_KV = 24576;
constexpr uint32_t SZ_WQ = 24576, SZ_WO = 20480, SZ_A = 16384;
constexpr uint32_t SZ_OUT = 40960;
constexpr uint32_t SZ_PARK = 24576;
constexpr uint32_t SZ_PART = 16384;
constexpr int NBAR = 16;
constexpr int KV_TRANSIT = 4;
constexpr int EARLY = 3;
constexpr int S1A = 7;
constexpr uint32_t KV_CH = 64, KV_SBO = 3072;
constexpr int SMEM_BYTES = RING + 512 + 1024;
constexpr int N_TEAM = 16, N_CL = 64, N_HELP = 2, N_QUAD = 30, MAX_OPS = 24, MAX_PARK = 4;
enum { OP_END = 0, OP_Q = 1, OP_A = 2, OP_O = 3, F_PARK = 1 << 9, F_LD = 1 << 12, F_ST = 1 << 13, F_HELP = 1 << 12 };

struct alignas(64) Params {
  uint32_t first[30], role0, quad;
  CUtensorMap x[4], wq[2], kv[4], wo[2], out;
  uint32_t ops[N_TEAM + 2 * N_HELP][MAX_OPS];
  uint32_t zero;
};

__device__ uint4 g_o[N_TEAM * 2 * 96 * 1024];
__device__ uint4 g_part[N_CL * 2 * 5 * 1024];
__device__ unsigned int g_done[N_TEAM * 2 * 8];
__device__ unsigned int g_help[N_CL * 2 * MAX_PARK];
__device__ unsigned int g_seen[N_TEAM * 2 * 8];

template <int TB>
__device__ __forceinline__ void wgmma_rs_n64(float (&d)[32], uint32_t a0, uint32_t a1, uint32_t a2, uint32_t a3, uint64_t db, int scale_d) {
  asm volatile("{\n.reg .pred p;\nsetp.ne.b32 p, %37, 0;\n"
    "wgmma.mma_async.sync.aligned.m64n64k16.f32.bf16.bf16 {%0, %1, %2, %3, %4, %5, %6, %7, %8, %9, %10, %11, %12, %13, %14, %15, %16, %17, %18, %19, %20, %21, %22, %23, %24, %25, %26, %27, %28, %29, %30, %31}, {%32, %33, %34, %35}, %36, p, 1, 1, %38;\n}\n"
    : "+f"(d[0]), "+f"(d[1]), "+f"(d[2]), "+f"(d[3]), "+f"(d[4]), "+f"(d[5]), "+f"(d[6]), "+f"(d[7]), "+f"(d[8]), "+f"(d[9]), "+f"(d[10]), "+f"(d[11]), "+f"(d[12]), "+f"(d[13]), "+f"(d[14]), "+f"(d[15]), "+f"(d[16]), "+f"(d[17]), "+f"(d[18]), "+f"(d[19]), "+f"(d[20]), "+f"(d[21]), "+f"(d[22]), "+f"(d[23]), "+f"(d[24]), "+f"(d[25]), "+f"(d[26]), "+f"(d[27]), "+f"(d[28]), "+f"(d[29]), "+f"(d[30]), "+f"(d[31])
    : "r"(a0), "r"(a1), "r"(a2), "r"(a3), "l"(db), "r"(scale_d), "n"(TB));
}
template <int TB, int TA = 0>
__device__ __forceinline__ void wgmma_ss_n160(float (&d)[80], uint64_t da, uint64_t db, int scale_d) {
  asm volatile("{\n.reg .pred p;\nsetp.ne.b32 p, %82, 0;\n"
    "wgmma.mma_async.sync.aligned.m64n160k16.f32.bf16.bf16 {%0, %1, %2, %3, %4, %5, %6, %7, %8, %9, %10, %11, %12, %13, %14, %15, %16, %17, %18, %19, %20, %21, %22, %23, %24, %25, %26, %27, %28, %29, %30, %31, %32, %33, %34, %35, %36, %37, %38, %39, %40, %41, %42, %43, %44, %45, %46, %47, %48, %49, %50, %51, %52, %53, %54, %55, %56, %57, %58, %59, %60, %61, %62, %63, %64, %65, %66, %67, %68, %69, %70, %71, %72, %73, %74, %75, %76, %77, %78, %79}, %80, %81, p, 1, 1, %83, %84;\n}\n"
    : "+f"(d[0]), "+f"(d[1]), "+f"(d[2]), "+f"(d[3]), "+f"(d[4]), "+f"(d[5]), "+f"(d[6]), "+f"(d[7]), "+f"(d[8]), "+f"(d[9]), "+f"(d[10]), "+f"(d[11]), "+f"(d[12]), "+f"(d[13]), "+f"(d[14]), "+f"(d[15]), "+f"(d[16]), "+f"(d[17]), "+f"(d[18]), "+f"(d[19]), "+f"(d[20]), "+f"(d[21]), "+f"(d[22]), "+f"(d[23]), "+f"(d[24]), "+f"(d[25]), "+f"(d[26]), "+f"(d[27]), "+f"(d[28]), "+f"(d[29]), "+f"(d[30]), "+f"(d[31]), "+f"(d[32]), "+f"(d[33]), "+f"(d[34]), "+f"(d[35]), "+f"(d[36]), "+f"(d[37]), "+f"(d[38]), "+f"(d[39]), "+f"(d[40]), "+f"(d[41]), "+f"(d[42]), "+f"(d[43]), "+f"(d[44]), "+f"(d[45]), "+f"(d[46]), "+f"(d[47]), "+f"(d[48]), "+f"(d[49]), "+f"(d[50]), "+f"(d[51]), "+f"(d[52]), "+f"(d[53]), "+f"(d[54]), "+f"(d[55]), "+f"(d[56]), "+f"(d[57]), "+f"(d[58]), "+f"(d[59]), "+f"(d[60]), "+f"(d[61]), "+f"(d[62]), "+f"(d[63]), "+f"(d[64]), "+f"(d[65]), "+f"(d[66]), "+f"(d[67]), "+f"(d[68]), "+f"(d[69]), "+f"(d[70]), "+f"(d[71]), "+f"(d[72]), "+f"(d[73]), "+f"(d[74]), "+f"(d[75]), "+f"(d[76]), "+f"(d[77]), "+f"(d[78]), "+f"(d[79])
    : "l"(da), "l"(db), "r"(scale_d), "n"(TA), "n"(TB));
}
template <int TB, int TA = 0>
__device__ __forceinline__ void wgmma_ss_n192(float (&d)[96], uint64_t da, uint64_t db, int scale_d) {
  asm volatile("{\n.reg .pred p;\nsetp.ne.b32 p, %98, 0;\n"
    "wgmma.mma_async.sync.aligned.m64n192k16.f32.bf16.bf16 {%0, %1, %2, %3, %4, %5, %6, %7, %8, %9, %10, %11, %12, %13, %14, %15, %16, %17, %18, %19, %20, %21, %22, %23, %24, %25, %26, %27, %28, %29, %30, %31, %32, %33, %34, %35, %36, %37, %38, %39, %40, %41, %42, %43, %44, %45, %46, %47, %48, %49, %50, %51, %52, %53, %54, %55, %56, %57, %58, %59, %60, %61, %62, %63, %64, %65, %66, %67, %68, %69, %70, %71, %72, %73, %74, %75, %76, %77, %78, %79, %80, %81, %82, %83, %84, %85, %86, %87, %88, %89, %90, %91, %92, %93, %94, %95}, %96, %97, p, 1, 1, %99, %100;\n}\n"
    : "+f"(d[0]), "+f"(d[1]), "+f"(d[2]), "+f"(d[3]), "+f"(d[4]), "+f"(d[5]), "+f"(d[6]), "+f"(d[7]), "+f"(d[8]), "+f"(d[9]), "+f"(d[10]), "+f"(d[11]), "+f"(d[12]), "+f"(d[13]), "+f"(d[14]), "+f"(d[15]), "+f"(d[16]), "+f"(d[17]), "+f"(d[18]), "+f"(d[19]), "+f"(d[20]), "+f"(d[21]), "+f"(d[22]), "+f"(d[23]), "+f"(d[24]), "+f"(d[25]), "+f"(d[26]), "+f"(d[27]), "+f"(d[28]), "+f"(d[29]), "+f"(d[30]), "+f"(d[31]), "+f"(d[32]), "+f"(d[33]), "+f"(d[34]), "+f"(d[35]), "+f"(d[36]), "+f"(d[37]), "+f"(d[38]), "+f"(d[39]), "+f"(d[40]), "+f"(d[41]), "+f"(d[42]), "+f"(d[43]), "+f"(d[44]), "+f"(d[45]), "+f"(d[46]), "+f"(d[47]), "+f"(d[48]), "+f"(d[49]), "+f"(d[50]), "+f"(d[51]), "+f"(d[52]), "+f"(d[53]), "+f"(d[54]), "+f"(d[55]), "+f"(d[56]), "+f"(d[57]), "+f"(d[58]), "+f"(d[59]), "+f"(d[60]), "+f"(d[61]), "+f"(d[62]), "+f"(d[63]), "+f"(d[64]), "+f"(d[65]), "+f"(d[66]), "+f"(d[67]), "+f"(d[68]), "+f"(d[69]), "+f"(d[70]), "+f"(d[71]), "+f"(d[72]), "+f"(d[73]), "+f"(d[74]), "+f"(d[75]), "+f"(d[76]), "+f"(d[77]), "+f"(d[78]), "+f"(d[79]), "+f"(d[80]), "+f"(d[81]), "+f"(d[82]), "+f"(d[83]), "+f"(d[84]), "+f"(d[85]), "+f"(d[86]), "+f"(d[87]), "+f"(d[88]), "+f"(d[89]), "+f"(d[90]), "+f"(d[91]), "+f"(d[92]), "+f"(d[93]), "+f"(d[94]), "+f"(d[95])
    : "l"(da), "l"(db), "r"(scale_d), "n"(TA), "n"(TB));
}
template <int TB>
__device__ __forceinline__ void wgmma_rs_n192(float (&d)[96], uint32_t a0, uint32_t a1, uint32_t a2, uint32_t a3, uint64_t db, int scale_d) {
  asm volatile("{\n.reg .pred p;\nsetp.ne.b32 p, %101, 0;\n"
    "wgmma.mma_async.sync.aligned.m64n192k16.f32.bf16.bf16 {%0, %1, %2, %3, %4, %5, %6, %7, %8, %9, %10, %11, %12, %13, %14, %15, %16, %17, %18, %19, %20, %21, %22, %23, %24, %25, %26, %27, %28, %29, %30, %31, %32, %33, %34, %35, %36, %37, %38, %39, %40, %41, %42, %43, %44, %45, %46, %47, %48, %49, %50, %51, %52, %53, %54, %55, %56, %57, %58, %59, %60, %61, %62, %63, %64, %65, %66, %67, %68, %69, %70, %71, %72, %73, %74, %75, %76, %77, %78, %79, %80, %81, %82, %83, %84, %85, %86, %87, %88, %89, %90, %91, %92, %93, %94, %95}, {%96, %97, %98, %99}, %100, p, 1, 1, %102;\n}\n"
    : "+f"(d[0]), "+f"(d[1]), "+f"(d[2]), "+f"(d[3]), "+f"(d[4]), "+f"(d[5]), "+f"(d[6]), "+f"(d[7]), "+f"(d[8]), "+f"(d[9]), "+f"(d[10]), "+f"(d[11]), "+f"(d[12]), "+f"(d[13]), "+f"(d[14]), "+f"(d[15]), "+f"(d[16]), "+f"(d[17]), "+f"(d[18]), "+f"(d[19]), "+f"(d[20]), "+f"(d[21]), "+f"(d[22]), "+f"(d[23]), "+f"(d[24]), "+f"(d[25]), "+f"(d[26]), "+f"(d[27]), "+f"(d[28]), "+f"(d[29]), "+f"(d[30]), "+f"(d[31]), "+f"(d[32]), "+f"(d[33]), "+f"(d[34]), "+f"(d[35]), "+f"(d[36]), "+f"(d[37]), "+f"(d[38]), "+f"(d[39]), "+f"(d[40]), "+f"(d[41]), "+f"(d[42]), "+f"(d[43]), "+f"(d[44]), "+f"(d[45]), "+f"(d[46]), "+f"(d[47]), "+f"(d[48]), "+f"(d[49]), "+f"(d[50]), "+f"(d[51]), "+f"(d[52]), "+f"(d[53]), "+f"(d[54]), "+f"(d[55]), "+f"(d[56]), "+f"(d[57]), "+f"(d[58]), "+f"(d[59]), "+f"(d[60]), "+f"(d[61]), "+f"(d[62]), "+f"(d[63]), "+f"(d[64]), "+f"(d[65]), "+f"(d[66]), "+f"(d[67]), "+f"(d[68]), "+f"(d[69]), "+f"(d[70]), "+f"(d[71]), "+f"(d[72]), "+f"(d[73]), "+f"(d[74]), "+f"(d[75]), "+f"(d[76]), "+f"(d[77]), "+f"(d[78]), "+f"(d[79]), "+f"(d[80]), "+f"(d[81]), "+f"(d[82]), "+f"(d[83]), "+f"(d[84]), "+f"(d[85]), "+f"(d[86]), "+f"(d[87]), "+f"(d[88]), "+f"(d[89]), "+f"(d[90]), "+f"(d[91]), "+f"(d[92]), "+f"(d[93]), "+f"(d[94]), "+f"(d[95])
    : "r"(a0), "r"(a1), "r"(a2), "r"(a3), "l"(db), "r"(scale_d), "n"(TB));
}

__device__ __forceinline__ uint32_t smem_u32(const void* p) { return (uint32_t)__cvta_generic_to_shared(p); }
__device__ __forceinline__ void wg_fence() { asm volatile("wgmma.fence.sync.aligned;" ::: "memory"); }
__device__ __forceinline__ void wg_commit() { asm volatile("wgmma.commit_group.sync.aligned;" ::: "memory"); }
template <int N> __device__ __forceinline__ void wg_wait() { asm volatile("wgmma.wait_group.sync.aligned %0;" ::"n"(N) : "memory"); }
__device__ __forceinline__ void sched_fence(int& keep, uint32_t zero) {
  asm volatile("{\n.reg .u32 c;\nmov.u32 c, %%clock;\nand.b32 c, c, %1;\nxor.b32 %0, %0, c;\n}\n" : "+r"(keep) : "r"(zero) : "memory");
}
template <int N> __device__ __forceinline__ void fence_regs(float (&r)[N]) {
#pragma unroll
  for (int i = 0; i < N; i++) asm volatile("" : "+f"(r[i])::"memory");
}
template <int N> __device__ __forceinline__ void fence_regs(uint32_t (&r)[N]) {
#pragma unroll
  for (int i = 0; i < N; i++) asm volatile("" : "+r"(r[i])::"memory");
}
__device__ __forceinline__ uint64_t mk_desc(uint32_t a16, uint32_t lbo, uint32_t sbo, uint32_t swz, uint32_t off = 0) {
  uint64_t d;
  asm("mov.b64 %0, {%1, %2};" : "=l"(d) : "r"(a16), "r"((sbo >> 4) | (swz << 30)));
  return d + (off + ((lbo >> 4) << 16));
}
__device__ __forceinline__ void mbar_init(uint32_t bar, uint32_t cnt) {
  asm volatile("mbarrier.init.shared::cta.b64 [%0], %1;" ::"r"(bar), "r"(cnt) : "memory");
}
__device__ __forceinline__ void mbar_expect(uint32_t bar, uint32_t tx) {
  asm volatile("mbarrier.arrive.expect_tx.shared::cta.b64 _, [%0], %1;" ::"r"(bar), "r"(tx) : "memory");
}
__device__ __forceinline__ bool mbar_test(uint32_t bar, uint32_t ph) {
  uint32_t ok;
  asm volatile("{\n.reg .pred p;\nmbarrier.test_wait.parity.shared::cta.b64 p, [%1], %2;\nselp.u32 %0, 1, 0, p;\n}\n"
               : "=r"(ok) : "r"(bar), "r"(ph) : "memory");
  return ok;
}
__device__ __forceinline__ void mbar_wait(uint32_t bar, uint32_t ph) {
  asm volatile("{\n.reg .pred p;\n.reg .u32 n;\nmov.u32 n, 0;\n"
               "LOOP:\nadd.u32 n, n, 1;\nmbarrier.try_wait.parity.shared::cta.b64 p, [%0], %1;\n@p bra DONE;\n"
               "setp.lt.u32 p, n, 0x1000000;\n@p bra LOOP;\ntrap;\n"
               "DONE:\n}\n" ::"r"(bar), "r"(ph) : "memory");
}
__device__ __forceinline__ void mbar_wait_math(uint32_t bar, uint32_t ph) {
  asm volatile("{\n.reg .pred p;\nLOOP:\nmbarrier.try_wait.parity.shared::cta.b64 p, [%0], %1;\n@!p bra LOOP;\n}\n" ::"r"(bar), "r"(ph) : "memory");
}
__device__ __forceinline__ void mbar_wait_long(uint32_t bar, uint32_t ph) {
  asm volatile("{\n.reg .pred p;\n.reg .u32 n;\nmov.u32 n, 0;\n"
               "LOOP:\nmbarrier.try_wait.parity.shared::cta.b64 p, [%0], %1, %2;\n@p bra DONE;\n"
               "add.u32 n, n, 1;\nsetp.lt.u32 p, n, 0x40000;\n@p bra LOOP;\ntrap;\n"
               "DONE:\n}\n" ::"r"(bar), "r"(ph), "r"(20000) : "memory");
}
__device__ __forceinline__ void mbar_arrive_cluster_if(bool on, uint32_t addr) {
  asm volatile("{\n.reg .pred p;\nsetp.ne.b32 p, %1, 0;\n@p mbarrier.arrive.shared::cluster.b64 _, [%0];\n}\n" ::"r"(addr), "r"((int)on) : "memory");
}
__device__ __forceinline__ void mbar_arrive_if(bool on, uint32_t addr) {
  asm volatile("{\n.reg .pred p;\nsetp.ne.b32 p, %1, 0;\n@p mbarrier.arrive.shared::cta.b64 _, [%0];\n}\n" ::"r"(addr), "r"((int)on) : "memory");
}
__device__ __forceinline__ void tma2d(uint32_t dst, const CUtensorMap* m, uint32_t bar, int c0, int c1) {
  asm volatile("cp.async.bulk.tensor.2d.shared::cluster.global.mbarrier::complete_tx::bytes [%0], [%1, {%3, %4}], [%2];"
               ::"r"(dst), "l"(m), "r"(bar), "r"(c0), "r"(c1) : "memory");
}
__device__ __forceinline__ void tma2d_mc(uint32_t dst, const CUtensorMap* m, uint32_t bar, int c0, int c1, uint16_t mask) {
  asm volatile("cp.async.bulk.tensor.2d.shared::cluster.global.mbarrier::complete_tx::bytes.multicast::cluster [%0], [%1, {%3, %4}], [%2], %5;"
               ::"r"(dst), "l"(m), "r"(bar), "r"(c0), "r"(c1), "h"(mask) : "memory");
}
__device__ __forceinline__ void bulk_load_mc(uint32_t dst, const void* src, uint32_t bytes, uint32_t bar, uint64_t pol, uint16_t mask) {
  asm volatile("cp.async.bulk.shared::cluster.global.mbarrier::complete_tx::bytes.multicast::cluster.L2::cache_hint [%0], [%1], %2, [%3], %5, %4;"
               ::"r"(dst), "l"(src), "r"(bytes), "r"(bar), "l"(pol), "h"(mask) : "memory");
}
__device__ __forceinline__ void tma3d(uint32_t dst, const CUtensorMap* m, uint32_t bar, int c0, int c1, int c2) {
  asm volatile("cp.async.bulk.tensor.3d.shared::cluster.global.mbarrier::complete_tx::bytes [%0], [%1, {%3, %4, %5}], [%2];"
               ::"r"(dst), "l"(m), "r"(bar), "r"(c0), "r"(c1), "r"(c2) : "memory");
}
__device__ __forceinline__ void tma3d_mc(uint32_t dst, const CUtensorMap* m, uint32_t bar, int c0, int c1, int c2, uint16_t mask) {
  asm volatile("cp.async.bulk.tensor.3d.shared::cluster.global.mbarrier::complete_tx::bytes.multicast::cluster"
               " [%0], [%1, {%3, %4, %5}], [%2], %6;"
               ::"r"(dst), "l"(m), "r"(bar), "r"(c0), "r"(c1), "r"(c2), "h"(mask) : "memory");
}
__device__ __forceinline__ void tma3d_store(const CUtensorMap* m, uint32_t src, int c0, int c1, int c2) {
  asm volatile("cp.async.bulk.tensor.3d.global.shared::cta.bulk_group [%0, {%2, %3, %4}], [%1];"
               ::"l"(m), "r"(src), "r"(c0), "r"(c1), "r"(c2) : "memory");
}
__device__ __forceinline__ void bar_sync(int id, int n) { asm volatile("bar.sync %0, %1;" ::"r"(id), "r"(n) : "memory"); }
__device__ __forceinline__ uint32_t pack_bf16(float lo, float hi) {
  uint32_t r;
  asm("cvt.rn.bf16x2.f32 %0, %1, %2;" : "=r"(r) : "f"(hi), "f"(lo));
  return r;
}
__device__ __forceinline__ float ex2(float x) {
  float y;
  asm("ex2.approx.ftz.f32 %0, %1;" : "=f"(y) : "f"(x));
  return y;
}
__device__ __forceinline__ float fadd(float a, float b) {
  float y;
  asm("add.f32 %0, %1, %2;" : "=f"(y) : "f"(a), "f"(b));
  return y;
}
__device__ __forceinline__ float rcp(float x) {
  float y;
  asm("rcp.approx.ftz.f32 %0, %1;" : "=f"(y) : "f"(x));
  return y;
}
__device__ __forceinline__ void stsm4(uint32_t addr, uint32_t a, uint32_t b, uint32_t c, uint32_t d) {
  asm volatile("stmatrix.sync.aligned.m8n8.x4.shared.b16 [%0], {%1, %2, %3, %4};" ::"r"(addr), "r"(a), "r"(b), "r"(c), "r"(d) : "memory");
}

__device__ __forceinline__ void tma4d_mc_hint(uint32_t dst, const CUtensorMap* m, uint32_t bar, int c3, uint64_t pol, uint16_t mask) {
  asm volatile("cp.async.bulk.tensor.4d.shared::cluster.global.mbarrier::complete_tx::bytes.multicast::cluster.L2::cache_hint"
               " [%0], [%1, {%3, %3, %3, %4}], [%2], %5, %6;"
               ::"r"(dst), "l"(m), "r"(bar), "r"(0), "r"(c3), "h"(mask), "l"(pol) : "memory");
}
__device__ __forceinline__ void tma5d_mc(uint32_t dst, const CUtensorMap* m, uint32_t bar, int c2, int c4, uint16_t mask) {
  asm volatile("cp.async.bulk.tensor.5d.shared::cluster.global.mbarrier::complete_tx::bytes.multicast::cluster"
               " [%0], [%1, {%3, %3, %4, %3, %5}], [%2], %6;"
               ::"r"(dst), "l"(m), "r"(bar), "r"(0), "r"(c2), "r"(c4), "h"(mask) : "memory");
}
__device__ __forceinline__ void bulk_load_hint(uint32_t dst, const void* src, uint32_t bytes, uint32_t bar, uint64_t pol) {
  asm volatile("cp.async.bulk.shared::cluster.global.mbarrier::complete_tx::bytes.L2::cache_hint [%0], [%1], %2, [%3], %4;"
               ::"r"(dst), "l"(src), "r"(bytes), "r"(bar), "l"(pol) : "memory");
}
__device__ __forceinline__ void stg2_if(bool on, void* p, uint32_t a, uint32_t b, uint32_t c, uint32_t d, uint32_t e, uint32_t f,
                                        uint32_t g, uint32_t h, uint64_t pol) {
  asm volatile("{\n.reg .pred p;\nsetp.ne.b32 p, %10, 0;\n"
               "@p st.global.L2::cache_hint.v4.b32 [%0], {%1, %2, %3, %4}, %9;\n"
               "@p st.global.L2::cache_hint.v4.b32 [%0 + 512], {%5, %6, %7, %8}, %9;\n}\n"
               ::"l"(p), "r"(a), "r"(b), "r"(c), "r"(d), "r"(e), "r"(f), "r"(g), "r"(h), "l"(pol), "r"((int)on) : "memory");
}
__device__ __forceinline__ uint64_t evict_first() {
  uint64_t p;
  asm("createpolicy.fractional.L2::evict_first.b64 %0, 1.0;" : "=l"(p));
  return p;
}
__device__ __forceinline__ bool elect() {
  uint32_t ok;
  asm volatile("{\n.reg .pred p;\nelect.sync _|p, 0xffffffff;\nselp.u32 %0, 1, 0, p;\n}\n" : "=r"(ok));
  return ok;
}
__device__ __forceinline__ void mbar_arrive(uint32_t bar) {
  asm volatile("mbarrier.arrive.shared::cta.b64 _, [%0];" ::"r"(bar) : "memory");
}
template <int OFF> __device__ __forceinline__ void lds2_if(bool on, uint32_t p, uint32_t* r) {
  asm volatile("{\n.reg .pred p;\nsetp.ne.b32 p, %9, 0;\n@p ld.shared.v4.b32 {%0, %1, %2, %3}, [%8 + %10];\n"
               "@p ld.shared.v4.b32 {%4, %5, %6, %7}, [%8 + %11];\n}\n"
               : "+r"(r[0]), "+r"(r[1]), "+r"(r[2]), "+r"(r[3]), "+r"(r[4]), "+r"(r[5]), "+r"(r[6]), "+r"(r[7])
               : "r"(p), "r"((int)on), "n"(OFF), "n"(OFF + 512) : "memory");
}
__device__ __forceinline__ void lds128(uint32_t p, uint32_t& a, uint32_t& b, uint32_t& c, uint32_t& d) {
  asm volatile("ld.shared.v4.b32 {%0, %1, %2, %3}, [%4];" : "=r"(a), "=r"(b), "=r"(c), "=r"(d) : "r"(p) : "memory");
}
__device__ __forceinline__ void wait_count(const unsigned int* p, uint32_t target) {
  asm volatile("{\n.reg .pred p;\n.reg .u32 n, v;\nmov.u32 n, 0;\n"
               "LOOP:\nld.acquire.gpu.global.u32 v, [%0];\nsetp.ge.u32 p, v, %1;\n@p bra DONE;\n"
               "nanosleep.u32 %2;\nadd.u32 n, n, 1;\nsetp.lt.u32 p, n, 0x400000;\n@p bra LOOP;\ntrap;\n"
               "DONE:\n}\n" ::"l"(p), "r"(target), "n"(300) : "memory");
}

__device__ __forceinline__ int o_wave(int a, int b, int i) {
  const int p = min(3, b - a - 1);
  return i < p ? b - 2 - i : i == p ? b - 1 : b - 1 - i;
}

struct Cursor {
  uint32_t n;
  __device__ __forceinline__ uint32_t off() const { return n & (8 * NBAR - 8); }
  __device__ __forceinline__ uint32_t ph() const { return (n / (8 * NBAR)) & 1; }
  __device__ __forceinline__ void next() { n += 8; }
};

constexpr float kScaleLog2 = 0.07216878364870322f * 1.4426950408889634f;
constexpr float kSumLimit = 1048576.0f;
constexpr float kMaxLag = 8.0f;

__global__ void __launch_bounds__(384, 1)
fused_kernel(const __grid_constant__ Params P) {
  extern __shared__ uint8_t smem_raw[];
  const uint32_t sbase = (smem_u32(smem_raw) + 1023) & ~1023u;
  const uint32_t full0 = sbase + RING, empty0 = full0 + 8 * NBAR, odone = empty0 + 8 * NBAR, oready0 = odone + 8;
  const uint32_t fenced = oready0 + 64, hready0 = fenced + 8;
  const uint32_t rank = blockIdx.x & 1;
  const int role = (blockIdx.x >> 1) + P.role0;
  const bool quad = P.quad;
  const uint32_t half = quad ? (blockIdx.x >> 1) & 1 : 0;
  asm volatile("griddepcontrol.launch_dependents;");
  const bool helper = role >= N_CL;
  const int team = helper ? 0 : role >> 2, nt = role & 3, blk = team >> 3;
  const uint32_t* prog = P.ops[helper ? N_TEAM + 2 * (role - N_CL) : team];
  auto q_role = [&](uint32_t op) { return helper ? (int)(((op >> 3) & 60) | ((op >> 12) & 3)) : role; };
  auto o_role = [&](uint32_t op) { return helper ? (int)(((op >> 26) & 56) | ((op >> 9) & 7)) : role; };
  const int wid = __shfl_sync(0xffffffffu, (int)(threadIdx.x >> 5), 0);
  const int wg = wid >> 2;

  const uint32_t op0 = P.first[helper ? N_TEAM + role - N_CL : team];
  if (__builtin_expect(wid == 8, 1)) {
    if (elect()) {
#pragma unroll
      for (int k = 0; k < EARLY; k++) mbar_init(full0 + 8 * k, 1);
      asm volatile("fence.mbarrier_init.release.cluster;" ::: "memory");
      if ((op0 & 3) == OP_Q) {
        const int qr = q_role(op0);
#pragma unroll
        for (int k = 0; k < EARLY; k++) {
          mbar_expect(full0 + 8 * k, SZ_WQ + SZ_A);
          tma2d(sbase + k * (SZ_WQ + SZ_A) + SZ_WQ, &P.x[qr >> 5], full0 + 8 * k, 64 * k, ((qr >> 2) & 7) * kSq + rank * 128);
          tma3d(sbase + k * (SZ_WQ + SZ_A), &P.wq[qr >> 5], full0 + 8 * k, 0, 64 * k, 3 * (4 * ((op0 >> 2) & 7) + (qr & 3)));
          tma3d(sbase + k * (SZ_WQ + SZ_A) + SZ_WQ / 2, &P.wq[qr >> 5], full0 + 8 * k, 0, 64 * k + 32, 3 * (4 * ((op0 >> 2) & 7) + (qr & 3)));
        }
      }
      asm volatile("prefetch.tensormap [%0];" ::"l"(&P.kv[blk]) : "memory");
      asm volatile("prefetch.tensormap [%0];" ::"l"(&P.kv[blk + 2]) : "memory");
    }
  } else if (threadIdx.x == 0) {
#pragma unroll
    for (int i = EARLY; i < 2 * NBAR + 10 + MAX_PARK; i++) mbar_init(full0 + 8 * i, i >= NBAR && i <= 2 * NBAR ? (quad ? 24 : 16) : 1);
    asm volatile("fence.mbarrier_init.release.cluster;" ::: "memory");
  }
  __syncwarp();
  asm volatile("barrier.cluster.arrive.relaxed.aligned;\nbarrier.cluster.wait.aligned;" ::: "memory");

  if (wg == 2) {
    asm volatile("setmaxnreg.dec.sync.aligned.u32 24;");
    if (wid == 8) {
      Cursor tail{0u - 8}, head{0};
      int sh = 0;
      uint32_t cur = 0, used = 0;
      uint64_t fifo = 0;
      uint32_t oready = oready0;
      const uint64_t pol = evict_first();
      const uint16_t pair = 3 << (2 * half), rows = (quad ? 5 : 1) << rank;
      const uint32_t piece = quad ? SZ_A / 2 : SZ_A;
      struct Load { uint32_t dst, bar, wbar, wph; int c0; const void* ptr; bool wait; };
      auto reserve = [&](uint32_t bytes, bool last, uint32_t off, int c0, const void* ptr) {
        uint32_t fp = bytes >> 12;
        if (cur + fp > (RING >> 12)) { fp += (RING >> 12) - cur; cur = 0; }
        used += fp;
        bool wait = false;
        while (used > (RING >> 12)) {
          wait = true;
          tail.next();
          used -= (uint32_t)fifo & 31;
          fifo >>= 5;
          sh -= 5;
        }
        fifo += (uint64_t)fp << sh;
        Load l{sbase + (cur << 12) + off, full0 + head.off(), empty0 + tail.off(), tail.ph(), c0, ptr, wait};
        cur += bytes >> 12;
        sh += last ? 5 : 0;
        head.n += last ? 8 : 0;
        asm volatile("" : "+r"(l.dst), "+r"(l.bar), "+r"(l.c0), "+l"(l.ptr), "+r"(l.wbar), "+r"(l.wph));
        return l;
      };
      auto vacated = [&](const Load& l) { if (l.wait) mbar_wait(l.wbar, l.wph); };
      auto written = [&](uint32_t flag) {
        mbar_wait(flag, 0);
        asm volatile("fence.proxy.async.global;" ::: "memory");
      };
      for (int pc = 0;; pc++) {
        const uint32_t op = prog[pc];
        const int type = op & 3, a = (op >> 2) & 7;
        if (type == OP_END) break;
        if (type == OP_Q) {
          const int qr = q_role(op);
          const CUtensorMap *mw = &P.wq[qr >> 5], *mx = &P.x[(qr >> 5) + (quad ? 2 : 0)];
          asm volatile("" : "+l"(mw), "+l"(mx));
          auto res_w = [&](int k) { return reserve(SZ_WQ, false, rank * (SZ_WQ / 2), 64 * k + 32 * rank, mw); };
          auto load_w = [&](const Load& w, int k) {
            vacated(w);
            if ((pc > 0 || k >= EARLY) && elect()) tma3d_mc(w.dst, (const CUtensorMap*)w.ptr, w.bar, 0, w.c0, 3 * (4 * a + (qr & 3)), pair);
          };
          auto load_x = [&](const Load& x, int k) {
            vacated(x);
            if ((pc > 0 || k >= EARLY) && elect()) {
              tma2d_mc(x.dst, (const CUtensorMap*)x.ptr, x.bar, x.c0, ((qr >> 2) & 7) * kSq + rank * 128 + half * 64, rows);
              mbar_expect(x.bar, SZ_WQ + SZ_A);
            }
          };
#pragma unroll 1
          for (int k = 0; k < 10; k++) {
            load_w(res_w(k), k);
            load_x(reserve(SZ_A, true, half * (SZ_A / 2), 64 * k, mx), k);
          }
        } else if (type == OP_A) {
          const uint32_t nop = prog[pc + 1];
          const int row8 = ((team & 7) * kH + nt) * (kSk / 8) + 4 * rank, wave8 = 4 * (kSk / 8);
          auto transit = [&]() {
            const Cursor c{head.n - 8 * (KV_TRANSIT + 1)};
            mbar_wait(full0 + c.off(), c.ph());
          };
          const char* map = (const char*)&P.kv[blk];
          asm volatile("" : "+l"(map));
          int t = (op & F_PARK) ? 1 : 0, c0 = row8 + a * wave8 + 8 * t, isv = 0;
#pragma unroll 1
          for (; t < 31; t++) {
            const Load l = reserve(SZ_KV, true, rank * (SZ_KV / 2), c0, map + isv);
            vacated(l);
            if (t >= KV_TRANSIT) transit();
            if (elect()) {
              tma4d_mc_hint(l.dst, (const CUtensorMap*)l.ptr, l.bar, l.c0, pol, pair);
              mbar_expect(l.bar, SZ_KV);
            }
            isv = (t & 1) << 8;
            c0 += isv ? -8 : t ? 16 : 8;
          }
          const int next = (nop >> 2) & 7;
          if ((nop & 3) == OP_A) written((nop & F_HELP) ? hready0 + 8 * ((nop >> 10) & 3) : fenced);
#pragma unroll 1
          for (int i = (nop & 3) == OP_A ? 0 : 3; i < 4; i++) {
            const Load l = reserve(SZ_KV, true, i < 2 ? 0 : rank * (SZ_KV / 2), i == 3 ? c0 - 8 : row8 + next * wave8,
                                   i < 2 ? (const char*)&g_o[((team * 2 + rank) * 96 + 3 * (4 * next + nt)) * 1024 + i * (SZ_PARK / 16)] : map + ((i & 1) << 8));
            vacated(l);
            if (i < 2) {
              if (elect()) bulk_load_hint(l.dst, l.ptr, SZ_PARK, l.bar, pol);
              __syncwarp();
            } else {
              transit();
              if (elect()) tma4d_mc_hint(l.dst, (const CUtensorMap*)l.ptr, l.bar, l.c0, pol, pair);
              __syncwarp();
            }
            if (elect()) mbar_expect(l.bar, SZ_KV);
          }
        } else {
          const int b = (op >> 5) & 15, ro = o_role(op);
          const CUtensorMap* mw = &P.wo[ro >> 5];
          const uint4* so = &g_o[((ro >> 2) * 2 + rank) * 96 * 1024 + half * 512];
          asm volatile("" : "+l"(mw), "+l"(so));
#pragma unroll 1
          for (int j = 0; j < b - a; j++) {
            const int w = o_wave(a, b, j);
            written(oready);
            oready += 8;
#pragma unroll 1
            for (int k = 12 * w; k < 12 * w + 12; k++) {
              const Load o = reserve(SZ_A, false, half * (SZ_A / 2), 0, so + k * 1024);
              vacated(o);
              if (elect()) bulk_load_mc(o.dst, o.ptr, piece, o.bar, pol, rows);
              const Load w = reserve(SZ_WO, true, rank * (SZ_WO / 2), 8 * k + 4 * rank, mw);
              vacated(w);
              if (elect()) {
                tma5d_mc(w.dst, (const CUtensorMap*)w.ptr, w.bar, w.c0, 5 * (ro & 3), pair);
                mbar_expect(w.bar, SZ_WO + SZ_A);
              }
            }
          }
          if ((op & F_LD) && (op & F_PARK)) written(hready0 + 8 * (MAX_PARK - 1));
#pragma unroll 1
          for (int i = (op & F_LD) ? 0 : 5; i < ((op & F_ST) ? 5 : 6); i++) {
            const Load l = reserve(i < 5 ? SZ_PART : SZ_OUT, i < 5, 0, 0, &g_part[(role * 2 + rank) * 5120 + i * (SZ_PART / 16)]);
            vacated(l);
            if (i < 5 && elect()) bulk_load_hint(l.dst, l.ptr, SZ_PART, l.bar, pol);
            if (elect()) mbar_expect(l.bar, i < 5 ? SZ_PART : 0);
          }
        }
      }
#pragma unroll 1
      for (Cursor c{head.n - 8 * NBAR}; c.n != head.n; c.next()) mbar_wait(empty0 + c.off(), c.ph());
    } else if (threadIdx.x == 288) {
      uint32_t ph = 0;
      bool first = true;
      for (int pc = 0;; pc++) {
        const uint32_t op = prog[pc];
        if ((op & 3) == OP_END) break;
        if ((op & 3) != OP_A && !helper) continue;
        mbar_wait_long(odone, ph);
        ph ^= 1;
        unsigned int* flag = !helper ? &g_done[(team * 2 + rank) * 8 + ((op >> 2) & 7)]
                             : (op & 3) == OP_Q ? &g_help[(q_role(op) * 2 + rank) * MAX_PARK + ((op >> 10) & 3)]
                                                : &g_help[(o_role(op) * 2 + rank) * MAX_PARK + MAX_PARK - 1];
        asm volatile("red.release.gpu.global.add.u32 [%0], 1;" ::"l"(flag) : "memory");
        if (first) mbar_arrive(fenced);
        first = false;
      }
    } else if (threadIdx.x == 320) {
      uint32_t oready = oready0;
      for (int pc = 0;; pc++) {
        const uint32_t op = prog[pc];
        if ((op & 3) == OP_END) break;
        if ((op & 3) == OP_O) {
          const int a = (op >> 2) & 7, b = (op >> 5) & 15;
#pragma unroll 1
          for (int i = 0; i < b - a; i++) {
            const int ci = ((o_role(op) >> 2) * 2 + rank) * 8 + o_wave(a, b, i);
            wait_count(&g_done[ci], 4);
            mbar_arrive(oready);
            oready += 8;
            if (atomicAdd(&g_seen[ci], 1u) == 3u) { g_seen[ci] = 0; g_done[ci] = 0; }
          }
        }
        if ((op & 3) != OP_Q && (op & F_HELP) && (op & F_PARK)) {
          unsigned int* flag = &g_help[(role * 2 + rank) * MAX_PARK + ((op >> 10) & 3)];
          wait_count(flag, 1);
          mbar_arrive(hready0 + 8 * ((op >> 10) & 3));
          *flag = 0;
        }
      }
    }
  } else {
    asm volatile("setmaxnreg.inc.sync.aligned.u32 240;");
    const int lane = threadIdx.x & 31, warp = wid & 3;
    uint32_t empty_rem;
    const bool tell = lane < (quad ? 3 : 2);
    asm volatile("mapa.shared::cluster.u32 %0, %1, %2;" : "=r"(empty_rem) : "r"(empty0), "r"((2 * half + rank) ^ (tell ? lane : 0)));
    auto release = [&](int slot) { mbar_arrive_cluster_if(tell, empty_rem + slot); };
    Cursor r{0};
    const uint32_t ring16 = (sbase & 0x3FFFF) >> 4;
    uint32_t cur = ring16;
    bool rdy0 = false, rdy1 = false;
    auto probe1 = [&]() { rdy0 = mbar_test(full0 + r.off(), r.ph()); };
    auto probe2 = [&]() {
      Cursor n = r;
      rdy0 = mbar_test(full0 + n.off(), n.ph());
      n.next();
      rdy1 = mbar_test(full0 + n.off(), n.ph());
    };
    auto take = [&](bool rdy, uint32_t bytes, uint32_t& addr) {
      const int bi = r.off();
      if (!__all_sync(0xffffffffu, rdy)) mbar_wait_math(full0 + r.off(), r.ph());
      r.next();
      if (cur > ring16 + ((RING - bytes) >> 4)) cur = ring16;
      addr = cur;
      cur += bytes >> 4;
      return bi;
    };
    auto at = [&](uint32_t a16) {
      uint32_t a = sbase + (a16 - ring16) * 16;
      asm("" : "+r"(a));
      return a;
    };
    auto second = [&](uint32_t bytes) {
      if (cur > ring16 + ((RING - bytes) >> 4)) cur = ring16;
      cur += bytes >> 4;
      return cur - (bytes >> 4);
    };
    const int row = wg * 64 + warp * 16 + (lane >> 2);
    int img0 = (row * 4 + ((lane & 3) ^ ((row >> 1) & 3))) * 16;
    uint4* pend = nullptr;
    const uint64_t spol = evict_first();
    int pc = 0;
    uint32_t op = prog[0];
    auto enter = [&]() {
      r.n = op >> 12; cur = ring16 + (((op >> 20) & 63) << 8);
    };
    auto drain = [&](uint32_t (&t)[48], uint32_t c) {
      if (!(op & (3u << 26)) || c >= 6) return;
#pragma unroll
      for (int i = 0; i < 6; i++)
        stg2_if(c == i, pend + i * 512, t[8 * i], t[8 * i + 1], t[8 * i + 2], t[8 * i + 3],
                t[8 * i + 4], t[8 * i + 5], t[8 * i + 6], t[8 * i + 7], spol);
      if ((op & (1u << 26)) && c == 5) {
        __syncwarp();
        mbar_arrive_if(tell, odone);
      }
    };
    float s[32], o[96], c[80];
    uint32_t q[48], pa[16], pb[16];
    float mc0, mc1, l0, l1;
    bool gen;
    auto soft = [&](float (&s)[32], uint32_t (&pout)[16], bool first) {
      if (first) { gen = false; mc0 = 0.f; mc1 = 0.f; }
      float b0, b1;
      for (;;) {
        if (gen) {
          float m0 = fmaxf(s[0], s[1]), m1 = fmaxf(s[2], s[3]);
#pragma unroll
          for (int i = 1; i < 8; i++) { m0 = fmaxf(m0, fmaxf(s[4 * i], s[4 * i + 1])); m1 = fmaxf(m1, fmaxf(s[4 * i + 2], s[4 * i + 3])); }
          m0 = fmaxf(m0, __shfl_xor_sync(0xffffffffu, m0, 1)); m1 = fmaxf(m1, __shfl_xor_sync(0xffffffffu, m1, 1));
          m0 = fmaxf(m0, __shfl_xor_sync(0xffffffffu, m0, 2)); m1 = fmaxf(m1, __shfl_xor_sync(0xffffffffu, m1, 2));
          if (first) {
            mc0 = m0; mc1 = m1;
          } else if (__any_sync(0xffffffffu, !(m0 <= mc0 + kMaxLag && m1 <= mc1 + kMaxLag))) {
            m0 = fmaxf(mc0, m0); m1 = fmaxf(mc1, m1);
            const float a0 = ex2(mc0 - m0), a1 = ex2(mc1 - m1);
            mc0 = m0; mc1 = m1;
            l0 *= a0; l1 *= a1;
            wg_wait<0>();
            fence_regs(o);
#pragma unroll
            for (int i = 0; i < 96; i++) o[i] *= i & 2 ? a1 : a0;
          }
#pragma unroll
          for (int i = 0; i < 32; i++) s[i] -= i & 2 ? mc1 : mc0;
        }
#pragma unroll
        for (int i = 0; i < 8; i++) {
          const float e1 = ex2(s[4 * i + 1]), e0 = ex2(s[4 * i]), e3 = ex2(s[4 * i + 3]), e2 = ex2(s[4 * i + 2]);
          pout[2 * i] = pack_bf16(e0, e1);
          b0 = i ? b0 + fadd(e1, e0) : fadd(e1, e0);
          pout[2 * i + 1] = pack_bf16(e2, e3);
          b1 = i ? b1 + fadd(e3, e2) : fadd(e3, e2);
        }
        if (!__any_sync(0xffffffffu, !gen && !(fmaxf(b0, b1) <= kSumLimit && (!first || fminf(b0, b1) >= 1.0f / kSumLimit)))) break;
        gen = __any_sync(0xffffffffu, true);
      }
      l0 = first ? b0 : l0 + b0;
      l1 = first ? b1 : l1 + b1;
    };
    auto qk = [&](float (&s)[32], uint32_t ak, int k0, int k1) {
#pragma unroll
      for (int kk = k0; kk < k1; kk++)
        wgmma_rs_n64<0>(s, q[4 * kk], q[4 * kk + 1], q[4 * kk + 2], q[4 * kk + 3], mk_desc(ak, 16, KV_SBO, 1, (kk >> 2) * KV_CH + (kk & 3) * 2), kk != 0);
      wg_commit();
    };
    auto pv = [&](uint32_t (&pin)[16], uint32_t av, int acc) {
#pragma unroll
      for (int kk = 0; kk < 4; kk++)
        wgmma_rs_n192<1>(o, pin[4 * kk], pin[4 * kk + 1], pin[4 * kk + 2], pin[4 * kk + 3], mk_desc(av, KV_CH * 16, KV_SBO, 1, kk * (KV_SBO / 8)), acc || (kk != 0));
      wg_commit();
    };
    auto xw = [&](uint32_t ad, int acc) {
      const uint32_t da = second(SZ_A) + wg * 512;
      wg_fence();
#pragma unroll
      for (int kk = 0; kk < 4; kk++)
        wgmma_ss_n192<1>(o, mk_desc(da, 16, 1024, 1, kk * 2), mk_desc(ad, 4096, 1024, 1, (kk & 1) * 128 + (kk >> 1) * 768), acc || kk != 0);
      wg_commit();
    };
    auto ow = [&](int acc, int prev) {
      uint32_t da;
      const int bi = take(rdy0, SZ_A, da);
      const uint32_t db = second(SZ_WO);
      da += wg * 256;
      wg_fence();
      wgmma_ss_n160<1>(c, mk_desc(da, 16, 512, 2), mk_desc(db, 2048, 512, 2), acc);
      wgmma_ss_n160<1>(c, mk_desc(da, 16, 512, 2, 2), mk_desc(db, 2048, 512, 2, 64), 1);
      wg_commit();
      if (acc == 1) { wg_wait<1>(); release(prev); }
      wgmma_ss_n160<1>(c, mk_desc(da, 16, 512, 2, 512), mk_desc(db, 2048, 512, 2, 640), 1);
      wgmma_ss_n160<1>(c, mk_desc(da, 16, 512, 2, 514), mk_desc(db, 2048, 512, 2, 704), 1);
      wg_commit();
      return bi;
    };
    auto st_part = [&](int i) {
      stg2_if(true, pend + i * 512, __float_as_uint(c[8 * i]), __float_as_uint(c[8 * i + 1]), __float_as_uint(c[8 * i + 2]), __float_as_uint(c[8 * i + 3]),
              __float_as_uint(c[8 * i + 4]), __float_as_uint(c[8 * i + 5]), __float_as_uint(c[8 * i + 6]), __float_as_uint(c[8 * i + 7]), spol);
    };
#pragma unroll
    for (int i = 0; i < 48; i++) q[i] = 0;
    enter();

    if ((op & 3) == OP_Q) {
      uint32_t ad;
      int bi0 = take(false, SZ_WQ, ad), k = 0, lag = 0;
      xw(ad, 0);
      for (;;) {
#pragma unroll 1
        for (;;) {
          drain(q, k - lag);
          probe1();
          wg_wait<0>();
          release(bi0);
          bi0 = take(rdy0, SZ_WQ, ad);
          if (++k == 8) break;
          xw(ad, 1);
        }
        if (wg) bar_sync(2, 256);
        xw(ad, 1);
        const int bi9 = take(false, SZ_WQ, ad);
        xw(ad, 1);
        if (!wg) asm volatile("bar.arrive 2, 256;" ::: "memory");
        k = 0; lag = 0;
        uint32_t nop = prog[++pc];
        wg_wait<1>();
        release(bi0);
        probe2();
        wg_wait<0>();
        fence_regs(o);
        release(bi9);
#pragma unroll
        for (int i = 0; i < 48; i++) q[i] = pack_bf16(o[2 * i] * kScaleLog2, o[2 * i + 1] * kScaleLog2);
        fence_regs(q);
        if (op & F_PARK) {
          const int qt = helper ? (op >> 5) & 15 : team, qm = helper ? (op >> 12) & 3 : nt;
          pend = (uint4*)((char*)&g_o[((qt * 2 + rank) * 96 + 3 * (4 * ((op >> 2) & 7) + qm)) * 1024] + img0);
          op = nop;
          enter();
          if ((op & 3) != OP_Q) break;
          const int b = take(rdy0, SZ_WQ, ad);
          xw(ad, 0);
          bi0 = take(rdy1, SZ_WQ, ad);
          xw(ad, 1);
          wg_wait<1>();
          release(b);
          k = 1; lag = 1;
          continue;
        }
        int wave = (op >> 2) & 7, sk1;
        uint32_t ak1;
        {
          float s0[32];
          const int sk0 = take(rdy0, SZ_KV, ad);
          wg_fence();
          qk(s0, ad, 0, 12);
          sk1 = take(rdy1, SZ_KV, ak1);
          wg_fence();
          qk(s, ak1, 0, S1A);
          probe1();
          wg_wait<1>();
          fence_regs(s0);
          release(sk0);
          soft(s0, pa, true);
        }
        float i0, i1;
        auto sums = [&]() {
          l0 += __shfl_xor_sync(0xffffffffu, l0, 1); l1 += __shfl_xor_sync(0xffffffffu, l1, 1);
          l0 += __shfl_xor_sync(0xffffffffu, l0, 2); l1 += __shfl_xor_sync(0xffffffffu, l1, 2);
          i0 = rcp(l0); i1 = rcp(l1);
          asm volatile("" : "+f"(i0), "+f"(i1));
        };
        auto target = [&]() {
          pend = (uint4*)((char*)&g_o[((team * 2 + rank) * 96 + 3 * (4 * wave + nt)) * 1024] + img0);
          asm volatile("" : "+l"(pend));
        };
        bool late = false;
#pragma unroll
        for (int i = 0; i < 16; i++) pb[i] = 0;
        for (;;) {
          nop = prog[++pc];
          {
            uint32_t av;
            const int sv = take(rdy0, SZ_KV, av);
            wg_fence();
            qk(s, ak1, S1A, 12);
            pv(pa, av, 0);
            if (late) {
              stg2_if(true, pend + 4 * 512, pb[0], pb[1], pb[2], pb[3], pb[4], pb[5], pb[6], pb[7], spol);
              stg2_if(true, pend + 5 * 512, pb[8], pb[9], pb[10], pb[11], pb[12], pb[13], pb[14], pb[15], spol);
              __syncwarp();
              mbar_arrive_if(tell, odone);
            }
            probe2();
            wg_wait<1>();
            fence_regs(s);
            release(sk1);
            soft(s, pb, false);
            wg_wait<0>();
            fence_regs(o);
            release(sv);
          }
          auto step = [&](uint32_t (&pin)[16], uint32_t (&pout)[16], bool hook, bool unpark) {
            uint32_t ak, av;
            const int sk = take(rdy0, SZ_KV, ak), sv = take(rdy1, SZ_KV, av);
            wg_fence();
            qk(s, ak, 0, 12);
            pv(pin, av, 1);
            if (hook && unpark) { take(false, SZ_PARK, ak); take(false, SZ_PARK, av); }
            probe2();
            wg_wait<1>();
            fence_regs(s);
            release(sk);
            if (hook) {
              lds2_if<0>(unpark, img0 + at(ak), q);
              lds2_if<8192>(unpark, img0 + at(ak), q + 8);
              lds2_if<16384>(unpark, img0 + at(ak), q + 16);
              lds2_if<0>(unpark, img0 + at(av), q + 24);
              lds2_if<8192>(unpark, img0 + at(av), q + 32);
              lds2_if<16384>(unpark, img0 + at(av), q + 40);
            }
            soft(s, pout, false);
            wg_wait<0>();
            fence_regs(o);
            release(sv);
          };
          const int jpark = (nop & 3) == OP_A ? 6 : 7;
#pragma unroll 1
          for (int jj = 0; jj < 7; jj++) {
            step(pb, pa, false, false);
            step(pa, pb, true, jj == jpark);
          }
          if ((nop & 3) != OP_A) break;
          uint32_t ak, av;
          release(Cursor{r.n - 16}.off());
          release(Cursor{r.n - 8}.off());
          const int sk0 = take(rdy0, SZ_KV, ak), sv = take(rdy1, SZ_KV, av);
          wg_fence();
          qk(s, ak, 0, 8);
          sched_fence(img0, P.zero);
          sums();
          sched_fence(img0, P.zero);
          qk(s, ak, 8, 12);
          pv(pb, av, 1);
          probe2();
          wg_wait<1>();
          fence_regs(s);
          release(sk0);
          soft(s, pa, true);
          sk1 = take(rdy0, SZ_KV, ak1);
          rdy0 = rdy1;
          wg_wait<0>();
          target();
          fence_regs(o);
          release(sv);
          uint32_t t[48];
#pragma unroll
          for (int j = 0; j < 6; j++) {
#pragma unroll
            for (int i = 0; i < 4; i++) {
              t[8 * j + i] = pack_bf16(o[16 * j + 4 * i] * i0, o[16 * j + 4 * i + 1] * i0);
              t[8 * j + i + 4] = pack_bf16(o[16 * j + 4 * i + 2] * i1, o[16 * j + 4 * i + 3] * i1);
            }
            if (j < 4)
            stg2_if(true, pend + j * 512, t[8 * j], t[8 * j + 1], t[8 * j + 2], t[8 * j + 3], t[8 * j + 4], t[8 * j + 5], t[8 * j + 6], t[8 * j + 7], spol);
            if (j == 3) { wg_fence(); qk(s, ak1, 0, 4); }
            if (j == 5) { wg_fence(); qk(s, ak1, 4, S1A); }
            sched_fence(img0, P.zero);
          }
          if (P.zero) {
#pragma unroll
            for (int j = 0; j < 4; j++)
              stg2_if(true, pend, t[8 * j], t[8 * j + 1], t[8 * j + 2], t[8 * j + 3], t[8 * j + 4], t[8 * j + 5], t[8 * j + 6], t[8 * j + 7], spol);
          }
          late = true;
#pragma unroll
          for (int i = 0; i < 16; i++) pb[i] = t[32 + i];
          wave = (nop >> 2) & 7;
        }
        const int sv = take(rdy0, SZ_KV, ad);
        wg_fence();
        pv(pb, ad, 1);
        sums();
        target();
        op = nop;
        enter();
        rdy0 = rdy1;
        auto convert = [&](float (&u)[96], int j0, int j1) {
#pragma unroll
          for (int i = 4 * j0; i < 4 * j1; i++) {
            q[8 * (i >> 2) + (i & 3)] = pack_bf16(u[4 * i], u[4 * i + 1]);
            q[8 * (i >> 2) + (i & 3) + 4] = pack_bf16(u[4 * i + 2], u[4 * i + 3]);
          }
        };
        if ((op & 3) != OP_O) {
          if ((op & 3) == OP_Q) bi0 = take(rdy0, SZ_WQ, ad);
          wg_wait<0>();
          fence_regs(o);
          release(sv);
          float u[96];
#pragma unroll
          for (int i = 0; i < 96; i++) u[i] = o[i] * (i & 2 ? i1 : i0);
          if ((op & 3) != OP_Q) { convert(u, 0, 6); break; }
          fence_regs(u);
          xw(ad, 0);
          sched_fence(img0, P.zero);
          fence_regs(u);
          convert(u, 0, 1);
          stg2_if(true, pend, q[0], q[1], q[2], q[3], q[4], q[5], q[6], q[7], spol);
          probe1();
          wg_wait<0>();
          release(bi0);
          bi0 = take(rdy0, SZ_WQ, ad);
          xw(ad, 1);
          sched_fence(img0, P.zero);
          fence_regs(u);
          convert(u, 1, 6);
          k = 1;
          continue;
        }
        int bi = ow(0, 0);
        wg_wait<2>();
        fence_regs(o);
        release(sv);
#pragma unroll
        for (int j = 0; j < 6; j++) {
          uint32_t t[8];
#pragma unroll
          for (int i = 0; i < 4; i++) {
            t[i] = pack_bf16(o[16 * j + 4 * i] * i0, o[16 * j + 4 * i + 1] * i0);
            t[i + 4] = pack_bf16(o[16 * j + 4 * i + 2] * i1, o[16 * j + 4 * i + 3] * i1);
          }
          stg2_if(true, pend + j * 512, t[0], t[1], t[2], t[3], t[4], t[5], t[6], t[7], spol);
          if (j == 5) {
            __syncwarp();
            mbar_arrive_if(tell, odone);
          }
          probe1();
          wg_wait<1>();
          bi = ow(1, bi);
          fence_regs(o);
        }
        {
          const int nk = 12 * (((op >> 5) & 15) - ((op >> 2) & 7)) - ((op & F_ST) ? 0 : 2);
#pragma unroll 1
          for (int k = 7; k < nk; k++) {
            probe1();
            wg_wait<1>();
            bi = ow(1, bi);
          }
        }
        if (!(op & F_ST)) {
          probe2();
          wg_wait<1>();
          if (wg) {
            wg_wait<0>();
            release(bi);
            bar_sync(2, 256);
          }
          bi0 = ow(2, 0);
          rdy0 = rdy1;
          const int b = ow(2, 0);
          if (!wg) asm volatile("bar.arrive 2, 256;" ::: "memory");
          wg_wait<4>();
          mbar_arrive_cluster_if(tell && !wg, empty_rem + bi);
          bi = b;
        }
        probe1();
        nop = prog[++pc];
        if (op & F_LD) {
          uint32_t t[80];
#pragma unroll
          for (int j = 0; j < 5; j++) {
            const int b = take(rdy0, SZ_PART, ad);
            probe1();
#pragma unroll
            for (int i = 4 * j; i < 4 * j + 4; i++)
              lds128(img0 + at(ad) + ((i >> 1) & 1) * 8192 + (i & 1) * 512, t[4 * i], t[4 * i + 1], t[4 * i + 2], t[4 * i + 3]);
            release(b);
          }
          wg_wait<0>();
          fence_regs(c);
#pragma unroll
          for (int i = 0; i < 80; i++) c[i] += __uint_as_float(t[i]);
        }
        if (!(op & F_ST)) {
          wg_wait<0>();
          fence_regs(c);
          release(bi0);
          release(bi);
          goto finish;
        }
        op = nop;
        enter();
        bi0 = take(rdy0, SZ_WQ, ad);
        xw(ad, 0);
        pend = (uint4*)((char*)&g_part[((team * 4 + nt) * 2 + rank) * 5120] + img0);
        probe1();
        wg_wait<1>();
        fence_regs(c);
        release(bi);
        st_part(0); st_part(1);
        wg_wait<0>();
        release(bi0);
        bi0 = take(rdy0, SZ_WQ, ad);
        xw(ad, 1);
        st_part(2); st_part(3);
#pragma unroll
        for (int i = 0; i < 48; i++) q[i] = __float_as_uint(c[32 + i]);
        pend += 4 * 512;
        k = 1; lag = 2;
      }
    }
    rdy0 = false;
    {
      uint32_t t[48];
#pragma unroll
      for (int i = 0; i < 48; i++) t[i] = q[i] ^ P.zero;
      while ((op & 3) == OP_O) {
        int bi = ow(0, 0);
#pragma unroll 1
        for (int k = 1; k < 12 * (int)(((op >> 5) & 15) - ((op >> 2) & 7)); k++) {
          drain(t, k - 1);
          probe1();
          wg_wait<1>();
          bi = ow(1, bi);
        }
        rdy0 = false;
        wg_wait<0>();
        fence_regs(c);
        pc++;
        release(bi);
        if (!(op & F_ST)) goto finish;
        pend = (uint4*)((char*)&g_part[((((op >> 26) & 56) | ((op >> 9) & 7)) * 2 + rank) * 5120] + img0);
#pragma unroll
        for (int i = 6; i < 10; i++) st_part(i);
#pragma unroll
        for (int i = 0; i < 48; i++) t[i] = __float_as_uint(c[i]) ^ P.zero;
        op = prog[pc];
        enter();
      }
      for (int i = 0; i < 6; i++) drain(t, i);
    }
    if (false) {
    finish:
      uint32_t ad;
      take(rdy0, SZ_OUT, ad);
      const uint32_t wstage = sbase + (ad - ring16) * 16 + (wg * 4 + warp) * 5120;
      const uint32_t sa = wstage + (lane & 15) * 64;
#pragma unroll
      for (int i = 0; i < 10; i++) {
        const int u = (i & 1) * 2 + (lane >> 4);
        stsm4(sa + (i >> 1) * 1024 + ((u ^ ((lane >> 1) & 3)) << 4), pack_bf16(c[8 * i], c[8 * i + 1]), pack_bf16(c[8 * i + 2], c[8 * i + 3]),
              pack_bf16(c[8 * i + 4], c[8 * i + 5]), pack_bf16(c[8 * i + 6], c[8 * i + 7]));
      }
      asm volatile("fence.proxy.async.shared::cta;" ::: "memory");
      __syncwarp();
      if (lane == 0) {
        tma3d_store(&P.out, wstage, 0, (team & 7) * kSq + rank * 128 + wg * 64 + warp * 16, blk * 20 + nt * 5);
        asm volatile("cp.async.bulk.commit_group;\ncp.async.bulk.wait_group.read 0;" ::: "memory");
      }
    }
  }
}

typedef CUresult (*EncodeFn)(CUtensorMap*, CUtensorMapDataType, cuuint32_t, void*, const cuuint64_t*, const cuuint64_t*,
                             const cuuint32_t*, const cuuint32_t*, CUtensorMapInterleave, CUtensorMapSwizzle,
                             CUtensorMapL2promotion, CUtensorMapFloatOOBfill);

void encode(EncodeFn fn, CUtensorMap* m, const void* ptr, int rank, const cuuint64_t* dims, const cuuint64_t* strides,
            const cuuint32_t* box, CUtensorMapSwizzle swz) {
  const cuuint32_t es[5] = {1, 1, 1, 1, 1};
  CUresult r = fn(m, CU_TENSOR_MAP_DATA_TYPE_BFLOAT16, rank, const_cast<void*>(ptr), dims, strides, box, es,
                  CU_TENSOR_MAP_INTERLEAVE_NONE, swz, CU_TENSOR_MAP_L2_PROMOTION_L2_128B, CU_TENSOR_MAP_FLOAT_OOB_FILL_NONE);
  if (r != CUDA_SUCCESS) fprintf(stderr, "cuTensorMapEncodeTiled failed: %d\n", (int)r);
}

void annotate(uint32_t* ops, int n, bool helper) {
  uint32_t items = 0, cur = 0, pend = 0;
  auto item = [&](uint32_t bytes, int count, uint32_t bytes2 = 0) {
    for (int i = 0; i < count; i++) {
      if (cur + bytes > RING) cur = 0;
      cur += bytes;
      if (cur + bytes2 > RING) cur = 0;
      cur += bytes2;
      items++;
    }
  };
  for (int i = 0; i <= n; i++) {
    const uint32_t op = ops[i];
    ops[i] |= (items % (2 * NBAR)) << 15 | (cur >> 12) << 20 | pend << 26;
    if ((op & 3) == OP_Q) { item(SZ_WQ, 10, SZ_A); pend = (op & F_PARK) ? (helper ? 1 : 2) : 0; }
    if ((op & 3) == OP_A) {
      item(SZ_KV, (op & F_PARK) ? 30 : 31);
      if ((ops[i + 1] & 3) == OP_A) { item(SZ_PARK, 2); item(SZ_KV, 1); }
      item(SZ_KV, 1);
      pend = 1;
    }
    if ((op & 3) == OP_O) {
      item(SZ_A, 12 * (((op >> 5) & 15) - ((op >> 2) & 7)), SZ_WO);
      if (op & F_LD) item(SZ_PART, 5);
      pend = (op & F_ST) ? (helper ? 1 : 2) : 0;
    }
  }
}

void compile_programs(const char* const* text, bool helpers, Params& P) {
  struct Req { int when, team, wave, slot; } req[N_TEAM * MAX_PARK];
  int n_req = 0;
  for (int t = 0; t < N_TEAM; t++) {
    uint32_t* ops = P.ops[t];
    int n = 0, flags[8] = {0, 0, 0, 0, 0, 0, 0, 0}, n_park = 0, last_o = -1, when = 0, given = 0;
    for (const char* s = text[t]; *s; s++) {
      const int a = s[1] - '0';
      if (*s == 'Q' || (*s == 'H' && !helpers)) { ops[n++] = OP_Q | a << 2; when += 10; }
      else if (*s == 'P') { flags[a] = F_PARK; ops[n++] = OP_Q | a << 2 | flags[a]; when += 10; }
      else if (*s == 'H') { req[n_req++] = {when, t, a, n_park}; flags[a] = F_PARK | F_HELP | n_park++ << 10; }
      else if (*s == 'A') { ops[n++] = OP_A | a << 2 | flags[a]; when += 32; }
      else if (*s == 'G') { given = a; if (helpers) req[n_req++] = {1000, t, 0, -a}; }
      else if (*s == 'O') {
        ops[n] = OP_O | a << 2 | (s[2] - '0') << 5;
        if (given) ops[n] = helpers ? ops[n] | F_LD | F_PARK | (MAX_PARK - 1) << 10 : ops[n] & ~(7u << 2);
        if (last_o >= 0) { ops[last_o] |= F_ST; ops[n] |= F_LD; }
        last_o = n++;
        when += 10 * (s[2] - s[1]);
      }
    }
    for (int i = n; i < MAX_OPS; i++) ops[i] = OP_END;
    annotate(ops, n, false);
  }
  for (int i = 1; i < n_req; i++)
    for (int j = i; j > 0 && req[j].when < req[j - 1].when; j--) { Req r = req[j]; req[j] = req[j - 1]; req[j - 1] = r; }
  for (int h = 0; h < N_HELP; h++) {
    uint32_t* ops = P.ops[N_TEAM + 2 * h];
    int n = 0;
    for (int i = 0; i < n_req; i++)
      for (int m = h; m < 4; m += N_HELP) {
        const uint32_t ro = 4 * req[i].team + m;
        ops[n++] = req[i].slot >= 0 ? OP_Q | req[i].wave << 2 | req[i].team << 5 | F_PARK | req[i].slot << 10 | m << 12
                                    : OP_O | -req[i].slot << 5 | F_ST | (ro & 7) << 9 | (ro >> 3) << 29;
      }
    for (int i = n; i < 2 * MAX_OPS; i++) ops[i] = OP_END;
    annotate(ops, n, true);
  }
  for (int i = 0; i < 30; i++) P.first[i] = i < N_TEAM ? P.ops[i][0] : i < N_TEAM + N_HELP ? P.ops[2 * i - N_TEAM][0] : 0;
}

const char* const kPrograms[N_TEAM] = {
  "Q0A0Q1A1H2A2O03Q3A3Q4A4Q5A5Q6A6Q7A7O38",
  "Q0A0Q1A1Q2A2Q3A3Q4A4O05Q5A5Q6A6H7A7O58",
  "Q0A0H1A1Q2A2Q3A3Q4A4O05Q5A5Q6A6Q7A7O58",
  "Q0A0Q1A1Q2A2O03Q3A3Q4A4Q5A5H6A6Q7A7O38",
  "Q0A0Q1A1Q2A2Q3A3O04Q4A4Q5A5Q6A6H7A7O48",
  "Q0A0Q1A1H2A2Q3A3Q4A4O05Q5A5Q6A6Q7A7O58",
  "Q0A0Q1A1Q2A2O03Q3A3Q4A4H5A5Q6A6Q7A7O38",
  "Q0A0Q1A1Q2A2O03Q3A3H4A4Q5A5Q6A6Q7A7O38",
  "P3Q0A0Q1A1Q2A2A3Q4A4Q5A5H6A6Q7A7O08",
  "P5P7Q0A0Q1A1Q2A2H3A3Q4A4A5Q6A6A7G1O18",
  "Q0A0Q1A1Q2A2O02Q3A3H4A4Q5A5Q6A6Q7A7O28",
  "P3P5Q0A0Q1A1Q2A2A3Q4A4A5Q6A6H7A7O08",
  "Q0A0Q1A1Q2A2Q3A3Q4A4Q5A5H6A6Q7A7O08",
  "P7Q0A0Q1A1Q2A2Q3A3Q4A4Q5A5Q6A6A7G1O18",
  "Q0A0Q1A1Q2A2H3A3Q4A4Q5A5Q6A6Q7A7O08",
  "P3Q0A0Q1A1Q2A2A3H4A4Q5A5Q6A6Q7A7O08",
};

cudaLaunchConfig_t config(int clusters, int size, cudaLaunchAttribute* at) {
  cudaLaunchConfig_t cfg = {};
  cfg.gridDim = dim3(clusters * size); cfg.blockDim = dim3(384); cfg.dynamicSmemBytes = SMEM_BYTES; cfg.stream = cudaStreamPerThread;
  at[0].id = cudaLaunchAttributeClusterDimension; at[0].val.clusterDim.x = size; at[0].val.clusterDim.y = 1; at[0].val.clusterDim.z = 1;
  at[1].id = cudaLaunchAttributeProgrammaticStreamSerialization; at[1].val.programmaticStreamSerializationAllowed = 1;
  cfg.attrs = at; cfg.numAttrs = 1;
  return cfg;
}

void launch(Params& P, int role0, int clusters, int size, bool overlap) {
  cudaLaunchAttribute at[2];
  cudaLaunchConfig_t cfg = config(clusters, size, at);
  cfg.numAttrs = overlap ? 2 : 1;
  P.role0 = role0; P.quad = size == 4;
  cudaLaunchKernelEx(&cfg, fused_kernel, P);
}

const char* const* bench_programs() {
  return kPrograms;
}

}

extern "C" void kernel_launch(void* const* d_in, const int* in_sizes, int n_in, void* d_out, int out_size) {
  (void)in_sizes; (void)n_in; (void)out_size;
  static EncodeFn fn = nullptr;
  static int n_clusters = 0, n_quads = 0;
  if (!fn) {
    cudaDriverEntryPointQueryResult qr;
    void* f = nullptr;
    cudaGetDriverEntryPoint("cuTensorMapEncodeTiled", &f, cudaEnableDefault, &qr);
    fn = (EncodeFn)f;
    cudaFuncSetAttribute(fused_kernel, cudaFuncAttributeMaxDynamicSharedMemorySize, SMEM_BYTES);
    cudaLaunchAttribute at[2];
    cudaLaunchConfig_t cfg = config(N_CL + N_HELP, 2, at);
    if (cudaOccupancyMaxActiveClusters(&n_clusters, fused_kernel, &cfg) != cudaSuccess || n_clusters < 1) n_clusters = 1;
    cfg = config(N_QUAD, 4, at);
    if (cudaOccupancyMaxActiveClusters(&n_quads, fused_kernel, &cfg) != cudaSuccess) n_quads = 0;
    (void)cudaGetLastError();
  }
  Params P;
  const CUtensorMapSwizzle S128 = CU_TENSOR_MAP_SWIZZLE_128B, S64 = CU_TENSOR_MAP_SWIZZLE_64B;
  for (int blk = 0; blk < 2; blk++) {
    void* const* in = d_in + 5 * blk;
    { const cuuint64_t d[] = {kD, kB * kSq}, s[] = {kD * 2}; const cuuint32_t b[] = {64, 128};
      encode(fn, &P.x[blk], in[0], 2, d, s, b, S128);
      const cuuint32_t b2[] = {64, 64};
      encode(fn, &P.x[2 + blk], in[0], 2, d, s, b2, S128); }
    { const cuuint64_t d[] = {64, 8, 3, (cuuint64_t)kB * kH * kSk / 8}, s[] = {kDh * 2, 128, 8 * kDh * 2}; const cuuint32_t b[] = {64, 8, 3, 4};
      encode(fn, &P.kv[blk], in[1], 4, d, s, b, S128);
      encode(fn, &P.kv[blk + 2], in[2], 4, d, s, b, S128); }
    { const cuuint64_t d[] = {64, kD, kHD / 64}, s[] = {kHD * 2, 128}; const cuuint32_t b[] = {64, 32, 3};
      encode(fn, &P.wq[blk], in[3], 3, d, s, b, S128); }
    { const cuuint64_t d[] = {32, 2, kHD / 8, 4, kD / 32}, s[] = {kD * 2, 8 * kD * 2, 2 * kD * 2, 64}; const cuuint32_t b[] = {32, 2, 4, 4, 5};
      encode(fn, &P.wo[blk], in[4], 5, d, s, b, S64); }
  }
  { const cuuint64_t d[] = {32, kB * kSq, 2 * kD / 32}, s[] = {2 * kD * 2, 64}; const cuuint32_t b[] = {32, 16, 5};
    encode(fn, &P.out, d_out, 3, d, s, b, S64); }

  P.zero = 0;
  if (n_clusters >= N_CL) {
    const bool helpers = n_clusters >= N_CL + N_HELP;
    compile_programs(bench_programs(), helpers, P);
    if (helpers && n_quads >= N_QUAD) {
      launch(P, 0, N_QUAD, 4, false);
      launch(P, 2 * N_QUAD, N_CL + N_HELP - 2 * N_QUAD, 2, true);
    } else {
      launch(P, 0, N_CL + (helpers ? N_HELP : 0), 2, false);
    }
  } else {
    for (int phase = 0; phase < 2; phase++) {
      const char* text[N_TEAM];
      for (int t = 0; t < N_TEAM; t++) text[t] = phase ? "O08" : "Q0A0Q1A1Q2A2Q3A3Q4A4Q5A5Q6A6Q7A7";
      compile_programs(text, false, P);
      launch(P, 0, N_CL, 2, false);
    }
  }
}
```

```cpp
#include <cuda_runtime.h>
#include <cuda_bf16.h>
#include <cuda.h>
#include <stdint.h>
#include <stdio.h>

namespace {

constexpr int kB = 8, kSq = 256, kD = 640, kH = 32, kSk = 1024, kDh = 192;
constexpr int kHD = kH * kDh;
constexpr uint32_t RING = 224 * 1024;
constexpr uint32_t SZ_KV = 24576;
constexpr uint32_t SZ_WQ = 24576, SZ_WO = 20480, SZ_A = 16384;
constexpr uint32_t SZ_OUT = 40960;
constexpr uint32_t SZ_PARK = 24576;
constexpr uint32_t SZ_PART = 16384;
constexpr int NBAR = 16;
constexpr int KV_TRANSIT = 4;
constexpr int EARLY = 3;
constexpr int S1A = 7;
constexpr uint32_t KV_CH = 64, KV_SBO = 3072;
constexpr int SMEM_BYTES = RING + 512 + 1024;
constexpr int N_TEAM = 16, N_CL = 64, N_HELP = 2, MAX_OPS = 24, MAX_PARK = 4;
#define WIDE_ 4
constexpr int WIDE = WIDE_, N_WIDE = 60;
enum { OP_END = 0, OP_Q = 1, OP_A = 2, OP_O = 3, F_PARK = 1 << 9, F_LD = 1 << 12, F_ST = 1 << 13, F_HELP = 1 << 12 };

struct alignas(64) Params {
  uint32_t first[30], role0, wide;
  CUtensorMap x[4], wq[2], kv[4], wo[2], out;
  uint32_t ops[N_TEAM + 2 * N_HELP][MAX_OPS];
  uint32_t zero;
};

__device__ uint4 g_o[N_TEAM * 2 * 96 * 1024];
__device__ uint4 g_part[N_CL * 2 * 5 * 1024];
__device__ unsigned int g_done[N_TEAM * 2 * 8];
__device__ unsigned int g_help[N_CL * 2 * MAX_PARK];
__device__ unsigned int g_seen[N_TEAM * 2 * 8];

template <int TB>
__device__ __forceinline__ void wgmma_rs_n64(float (&d)[32], uint32_t a0, uint32_t a1, uint32_t a2, uint32_t a3, uint64_t db, int scale_d) {
  asm volatile("{\n.reg .pred p;\nsetp.ne.b32 p, %37, 0;\n"
    "wgmma.mma_async.sync.aligned.m64n64k16.f32.bf16.bf16 {%0, %1, %2, %3, %4, %5, %6, %7, %8, %9, %10, %11, %12, %13, %14, %15, %16, %17, %18, %19, %20, %21, %22, %23, %24, %25, %26, %27, %28, %29, %30, %31}, {%32, %33, %34, %35}, %36, p, 1, 1, %38;\n}\n"
    : "+f"(d[0]), "+f"(d[1]), "+f"(d[2]), "+f"(d[3]), "+f"(d[4]), "+f"(d[5]), "+f"(d[6]), "+f"(d[7]), "+f"(d[8]), "+f"(d[9]), "+f"(d[10]), "+f"(d[11]), "+f"(d[12]), "+f"(d[13]), "+f"(d[14]), "+f"(d[15]), "+f"(d[16]), "+f"(d[17]), "+f"(d[18]), "+f"(d[19]), "+f"(d[20]), "+f"(d[21]), "+f"(d[22]), "+f"(d[23]), "+f"(d[24]), "+f"(d[25]), "+f"(d[26]), "+f"(d[27]), "+f"(d[28]), "+f"(d[29]), "+f"(d[30]), "+f"(d[31])
    : "r"(a0), "r"(a1), "r"(a2), "r"(a3), "l"(db), "r"(scale_d), "n"(TB));
}
template <int TB, int TA = 0>
__device__ __forceinline__ void wgmma_ss_n160(float (&d)[80], uint64_t da, uint64_t db, int scale_d) {
  asm volatile("{\n.reg .pred p;\nsetp.ne.b32 p, %82, 0;\n"
    "wgmma.mma_async.sync.aligned.m64n160k16.f32.bf16.bf16 {%0, %1, %2, %3, %4, %5, %6, %7, %8, %9, %10, %11, %12, %13, %14, %15, %16, %17, %18, %19, %20, %21, %22, %23, %24, %25, %26, %27, %28, %29, %30, %31, %32, %33, %34, %35, %36, %37, %38, %39, %40, %41, %42, %43, %44, %45, %46, %47, %48, %49, %50, %51, %52, %53, %54, %55, %56, %57, %58, %59, %60, %61, %62, %63, %64, %65, %66, %67, %68, %69, %70, %71, %72, %73, %74, %75, %76, %77, %78, %79}, %80, %81, p, 1, 1, %83, %84;\n}\n"
    : "+f"(d[0]), "+f"(d[1]), "+f"(d[2]), "+f"(d[3]), "+f"(d[4]), "+f"(d[5]), "+f"(d[6]), "+f"(d[7]), "+f"(d[8]), "+f"(d[9]), "+f"(d[10]), "+f"(d[11]), "+f"(d[12]), "+f"(d[13]), "+f"(d[14]), "+f"(d[15]), "+f"(d[16]), "+f"(d[17]), "+f"(d[18]), "+f"(d[19]), "+f"(d[20]), "+f"(d[21]), "+f"(d[22]), "+f"(d[23]), "+f"(d[24]), "+f"(d[25]), "+f"(d[26]), "+f"(d[27]), "+f"(d[28]), "+f"(d[29]), "+f"(d[30]), "+f"(d[31]), "+f"(d[32]), "+f"(d[33]), "+f"(d[34]), "+f"(d[35]), "+f"(d[36]), "+f"(d[37]), "+f"(d[38]), "+f"(d[39]), "+f"(d[40]), "+f"(d[41]), "+f"(d[42]), "+f"(d[43]), "+f"(d[44]), "+f"(d[45]), "+f"(d[46]), "+f"(d[47]), "+f"(d[48]), "+f"(d[49]), "+f"(d[50]), "+f"(d[51]), "+f"(d[52]), "+f"(d[53]), "+f"(d[54]), "+f"(d[55]), "+f"(d[56]), "+f"(d[57]), "+f"(d[58]), "+f"(d[59]), "+f"(d[60]), "+f"(d[61]), "+f"(d[62]), "+f"(d[63]), "+f"(d[64]), "+f"(d[65]), "+f"(d[66]), "+f"(d[67]), "+f"(d[68]), "+f"(d[69]), "+f"(d[70]), "+f"(d[71]), "+f"(d[72]), "+f"(d[73]), "+f"(d[74]), "+f"(d[75]), "+f"(d[76]), "+f"(d[77]), "+f"(d[78]), "+f"(d[79])
    : "l"(da), "l"(db), "r"(scale_d), "n"(TA), "n"(TB));
}
template <int TB, int TA = 0>
__device__ __forceinline__ void wgmma_ss_n192(float (&d)[96], uint64_t da, uint64_t db, int scale_d) {
  asm volatile("{\n.reg .pred p;\nsetp.ne.b32 p, %98, 0;\n"
    "wgmma.mma_async.sync.aligned.m64n192k16.f32.bf16.bf16 {%0, %1, %2, %3, %4, %5, %6, %7, %8, %9, %10, %11, %12, %13, %14, %15, %16, %17, %18, %19, %20, %21, %22, %23, %24, %25, %26, %27, %28, %29, %30, %31, %32, %33, %34, %35, %36, %37, %38, %39, %40, %41, %42, %43, %44, %45, %46, %47, %48, %49, %50, %51, %52, %53, %54, %55, %56, %57, %58, %59, %60, %61, %62, %63, %64, %65, %66, %67, %68, %69, %70, %71, %72, %73, %74, %75, %76, %77, %78, %79, %80, %81, %82, %83, %84, %85, %86, %87, %88, %89, %90, %91, %92, %93, %94, %95}, %96, %97, p, 1, 1, %99, %100;\n}\n"
    : "+f"(d[0]), "+f"(d[1]), "+f"(d[2]), "+f"(d[3]), "+f"(d[4]), "+f"(d[5]), "+f"(d[6]), "+f"(d[7]), "+f"(d[8]), "+f"(d[9]), "+f"(d[10]), "+f"(d[11]), "+f"(d[12]), "+f"(d[13]), "+f"(d[14]), "+f"(d[15]), "+f"(d[16]), "+f"(d[17]), "+f"(d[18]), "+f"(d[19]), "+f"(d[20]), "+f"(d[21]), "+f"(d[22]), "+f"(d[23]), "+f"(d[24]), "+f"(d[25]), "+f"(d[26]), "+f"(d[27]), "+f"(d[28]), "+f"(d[29]), "+f"(d[30]), "+f"(d[31]), "+f"(d[32]), "+f"(d[33]), "+f"(d[34]), "+f"(d[35]), "+f"(d[36]), "+f"(d[37]), "+f"(d[38]), "+f"(d[39]), "+f"(d[40]), "+f"(d[41]), "+f"(d[42]), "+f"(d[43]), "+f"(d[44]), "+f"(d[45]), "+f"(d[46]), "+f"(d[47]), "+f"(d[48]), "+f"(d[49]), "+f"(d[50]), "+f"(d[51]), "+f"(d[52]), "+f"(d[53]), "+f"(d[54]), "+f"(d[55]), "+f"(d[56]), "+f"(d[57]), "+f"(d[58]), "+f"(d[59]), "+f"(d[60]), "+f"(d[61]), "+f"(d[62]), "+f"(d[63]), "+f"(d[64]), "+f"(d[65]), "+f"(d[66]), "+f"(d[67]), "+f"(d[68]), "+f"(d[69]), "+f"(d[70]), "+f"(d[71]), "+f"(d[72]), "+f"(d[73]), "+f"(d[74]), "+f"(d[75]), "+f"(d[76]), "+f"(d[77]), "+f"(d[78]), "+f"(d[79]), "+f"(d[80]), "+f"(d[81]), "+f"(d[82]), "+f"(d[83]), "+f"(d[84]), "+f"(d[85]), "+f"(d[86]), "+f"(d[87]), "+f"(d[88]), "+f"(d[89]), "+f"(d[90]), "+f"(d[91]), "+f"(d[92]), "+f"(d[93]), "+f"(d[94]), "+f"(d[95])
    : "l"(da), "l"(db), "r"(scale_d), "n"(TA), "n"(TB));
}
template <int TB>
__device__ __forceinline__ void wgmma_rs_n192(float (&d)[96], uint32_t a0, uint32_t a1, uint32_t a2, uint32_t a3, uint64_t db, int scale_d) {
  asm volatile("{\n.reg .pred p;\nsetp.ne.b32 p, %101, 0;\n"
    "wgmma.mma_async.sync.aligned.m64n192k16.f32.bf16.bf16 {%0, %1, %2, %3, %4, %5, %6, %7, %8, %9, %10, %11, %12, %13, %14, %15, %16, %17, %18, %19, %20, %21, %22, %23, %24, %25, %26, %27, %28, %29, %30, %31, %32, %33, %34, %35, %36, %37, %38, %39, %40, %41, %42, %43, %44, %45, %46, %47, %48, %49, %50, %51, %52, %53, %54, %55, %56, %57, %58, %59, %60, %61, %62, %63, %64, %65, %66, %67, %68, %69, %70, %71, %72, %73, %74, %75, %76, %77, %78, %79, %80, %81, %82, %83, %84, %85, %86, %87, %88, %89, %90, %91, %92, %93, %94, %95}, {%96, %97, %98, %99}, %100, p, 1, 1, %102;\n}\n"
    : "+f"(d[0]), "+f"(d[1]), "+f"(d[2]), "+f"(d[3]), "+f"(d[4]), "+f"(d[5]), "+f"(d[6]), "+f"(d[7]), "+f"(d[8]), "+f"(d[9]), "+f"(d[10]), "+f"(d[11]), "+f"(d[12]), "+f"(d[13]), "+f"(d[14]), "+f"(d[15]), "+f"(d[16]), "+f"(d[17]), "+f"(d[18]), "+f"(d[19]), "+f"(d[20]), "+f"(d[21]), "+f"(d[22]), "+f"(d[23]), "+f"(d[24]), "+f"(d[25]), "+f"(d[26]), "+f"(d[27]), "+f"(d[28]), "+f"(d[29]), "+f"(d[30]), "+f"(d[31]), "+f"(d[32]), "+f"(d[33]), "+f"(d[34]), "+f"(d[35]), "+f"(d[36]), "+f"(d[37]), "+f"(d[38]), "+f"(d[39]), "+f"(d[40]), "+f"(d[41]), "+f"(d[42]), "+f"(d[43]), "+f"(d[44]), "+f"(d[45]), "+f"(d[46]), "+f"(d[47]), "+f"(d[48]), "+f"(d[49]), "+f"(d[50]), "+f"(d[51]), "+f"(d[52]), "+f"(d[53]), "+f"(d[54]), "+f"(d[55]), "+f"(d[56]), "+f"(d[57]), "+f"(d[58]), "+f"(d[59]), "+f"(d[60]), "+f"(d[61]), "+f"(d[62]), "+f"(d[63]), "+f"(d[64]), "+f"(d[65]), "+f"(d[66]), "+f"(d[67]), "+f"(d[68]), "+f"(d[69]), "+f"(d[70]), "+f"(d[71]), "+f"(d[72]), "+f"(d[73]), "+f"(d[74]), "+f"(d[75]), "+f"(d[76]), "+f"(d[77]), "+f"(d[78]), "+f"(d[79]), "+f"(d[80]), "+f"(d[81]), "+f"(d[82]), "+f"(d[83]), "+f"(d[84]), "+f"(d[85]), "+f"(d[86]), "+f"(d[87]), "+f"(d[88]), "+f"(d[89]), "+f"(d[90]), "+f"(d[91]), "+f"(d[92]), "+f"(d[93]), "+f"(d[94]), "+f"(d[95])
    : "r"(a0), "r"(a1), "r"(a2), "r"(a3), "l"(db), "r"(scale_d), "n"(TB));
}

__device__ __forceinline__ uint32_t smem_u32(const void* p) { return (uint32_t)__cvta_generic_to_shared(p); }
__device__ __forceinline__ void wg_fence() { asm volatile("wgmma.fence.sync.aligned;" ::: "memory"); }
__device__ __forceinline__ void wg_commit() { asm volatile("wgmma.commit_group.sync.aligned;" ::: "memory"); }
template <int N> __device__ __forceinline__ void wg_wait() { asm volatile("wgmma.wait_group.sync.aligned %0;" ::"n"(N) : "memory"); }
__device__ __forceinline__ void sched_fence(int& keep, uint32_t zero) {
  asm volatile("{\n.reg .u32 c;\nmov.u32 c, %%clock;\nand.b32 c, c, %1;\nxor.b32 %0, %0, c;\n}\n" : "+r"(keep) : "r"(zero) : "memory");
}
template <int N> __device__ __forceinline__ void fence_regs(float (&r)[N]) {
#pragma unroll
  for (int i = 0; i < N; i++) asm volatile("" : "+f"(r[i])::"memory");
}
template <int N> __device__ __forceinline__ void fence_regs(uint32_t (&r)[N]) {
#pragma unroll
  for (int i = 0; i < N; i++) asm volatile("" : "+r"(r[i])::"memory");
}
__device__ __forceinline__ uint64_t mk_desc(uint32_t a16, uint32_t lbo, uint32_t sbo, uint32_t swz, uint32_t off = 0) {
  uint64_t d;
  asm("mov.b64 %0, {%1, %2};" : "=l"(d) : "r"(a16), "r"((sbo >> 4) | (swz << 30)));
  return d + (off + ((lbo >> 4) << 16));
}
__device__ __forceinline__ void mbar_init(uint32_t bar, uint32_t cnt) {
  asm volatile("mbarrier.init.shared::cta.b64 [%0], %1;" ::"r"(bar), "r"(cnt) : "memory");
}
__device__ __forceinline__ void mbar_expect(uint32_t bar, uint32_t tx) {
  asm volatile("mbarrier.arrive.expect_tx.shared::cta.b64 _, [%0], %1;" ::"r"(bar), "r"(tx) : "memory");
}
__device__ __forceinline__ bool mbar_test(uint32_t bar, uint32_t ph) {
  uint32_t ok;
  asm volatile("{\n.reg .pred p;\nmbarrier.test_wait.parity.shared::cta.b64 p, [%1], %2;\nselp.u32 %0, 1, 0, p;\n}\n"
               : "=r"(ok) : "r"(bar), "r"(ph) : "memory");
  return ok;
}
__device__ __forceinline__ void mbar_wait(uint32_t bar, uint32_t ph) {
  asm volatile("{\n.reg .pred p;\n.reg .u32 n;\nmov.u32 n, 0;\n"
               "LOOP:\nadd.u32 n, n, 1;\nmbarrier.try_wait.parity.shared::cta.b64 p, [%0], %1;\n@p bra DONE;\n"
               "setp.lt.u32 p, n, 0x1000000;\n@p bra LOOP;\ntrap;\n"
               "DONE:\n}\n" ::"r"(bar), "r"(ph) : "memory");
}
__device__ __forceinline__ void mbar_wait_math(uint32_t bar, uint32_t ph) {
  asm volatile("{\n.reg .pred p;\nLOOP:\nmbarrier.try_wait.parity.shared::cta.b64 p, [%0], %1;\n@!p bra LOOP;\n}\n" ::"r"(bar), "r"(ph) : "memory");
}
__device__ __forceinline__ void mbar_wait_long(uint32_t bar, uint32_t ph) {
  asm volatile("{\n.reg .pred p;\n.reg .u32 n;\nmov.u32 n, 0;\n"
               "LOOP:\nmbarrier.try_wait.parity.shared::cta.b64 p, [%0], %1, %2;\n@p bra DONE;\n"
               "add.u32 n, n, 1;\nsetp.lt.u32 p, n, 0x40000;\n@p bra LOOP;\ntrap;\n"
               "DONE:\n}\n" ::"r"(bar), "r"(ph), "r"(20000) : "memory");
}
__device__ __forceinline__ void mbar_arrive_cluster_if(bool on, uint32_t addr) {
  asm volatile("{\n.reg .pred p;\nsetp.ne.b32 p, %1, 0;\n@p mbarrier.arrive.shared::cluster.b64 _, [%0];\n}\n" ::"r"(addr), "r"((int)on) : "memory");
}
__device__ __forceinline__ void mbar_arrive_if(bool on, uint32_t addr) {
  asm volatile("{\n.reg .pred p;\nsetp.ne.b32 p, %1, 0;\n@p mbarrier.arrive.shared::cta.b64 _, [%0];\n}\n" ::"r"(addr), "r"((int)on) : "memory");
}
__device__ __forceinline__ void tma2d(uint32_t dst, const CUtensorMap* m, uint32_t bar, int c0, int c1) {
  asm volatile("cp.async.bulk.tensor.2d.shared::cluster.global.mbarrier::complete_tx::bytes [%0], [%1, {%3, %4}], [%2];"
               ::"r"(dst), "l"(m), "r"(bar), "r"(c0), "r"(c1) : "memory");
}
__device__ __forceinline__ void tma2d_mc(uint32_t dst, const CUtensorMap* m, uint32_t bar, int c0, int c1, uint16_t mask) {
  asm volatile("cp.async.bulk.tensor.2d.shared::cluster.global.mbarrier::complete_tx::bytes.multicast::cluster [%0], [%1, {%3, %4}], [%2], %5;"
               ::"r"(dst), "l"(m), "r"(bar), "r"(c0), "r"(c1), "h"(mask) : "memory");
}
__device__ __forceinline__ void bulk_load_mc(uint32_t dst, const void* src, uint32_t bytes, uint32_t bar, uint64_t pol, uint16_t mask) {
  asm volatile("cp.async.bulk.shared::cluster.global.mbarrier::complete_tx::bytes.multicast::cluster.L2::cache_hint [%0], [%1], %2, [%3], %5, %4;"
               ::"r"(dst), "l"(src), "r"(bytes), "r"(bar), "l"(pol), "h"(mask) : "memory");
}
__device__ __forceinline__ void tma3d(uint32_t dst, const CUtensorMap* m, uint32_t bar, int c0, int c1, int c2) {
  asm volatile("cp.async.bulk.tensor.3d.shared::cluster.global.mbarrier::complete_tx::bytes [%0], [%1, {%3, %4, %5}], [%2];"
               ::"r"(dst), "l"(m), "r"(bar), "r"(c0), "r"(c1), "r"(c2) : "memory");
}
__device__ __forceinline__ void tma3d_mc(uint32_t dst, const CUtensorMap* m, uint32_t bar, int c0, int c1, int c2, uint16_t mask) {
  asm volatile("cp.async.bulk.tensor.3d.shared::cluster.global.mbarrier::complete_tx::bytes.multicast::cluster"
               " [%0], [%1, {%3, %4, %5}], [%2], %6;"
               ::"r"(dst), "l"(m), "r"(bar), "r"(c0), "r"(c1), "r"(c2), "h"(mask) : "memory");
}
__device__ __forceinline__ void tma3d_store(const CUtensorMap* m, uint32_t src, int c0, int c1, int c2) {
  asm volatile("cp.async.bulk.tensor.3d.global.shared::cta.bulk_group [%0, {%2, %3, %4}], [%1];"
               ::"l"(m), "r"(src), "r"(c0), "r"(c1), "r"(c2) : "memory");
}
__device__ __forceinline__ void bar_sync(int id, int n) { asm volatile("bar.sync %0, %1;" ::"r"(id), "r"(n) : "memory"); }
__device__ __forceinline__ uint32_t pack_bf16(float lo, float hi) {
  uint32_t r;
  asm("cvt.rn.bf16x2.f32 %0, %1, %2;" : "=r"(r) : "f"(hi), "f"(lo));
  return r;
}
__device__ __forceinline__ float ex2(float x) {
  float y;
  asm("ex2.approx.ftz.f32 %0, %1;" : "=f"(y) : "f"(x));
  return y;
}
__device__ __forceinline__ float fadd(float a, float b) {
  float y;
  asm("add.f32 %0, %1, %2;" : "=f"(y) : "f"(a), "f"(b));
  return y;
}
__device__ __forceinline__ float rcp(float x) {
  float y;
  asm("rcp.approx.ftz.f32 %0, %1;" : "=f"(y) : "f"(x));
  return y;
}
__device__ __forceinline__ void stsm4(uint32_t addr, uint32_t a, uint32_t b, uint32_t c, uint32_t d) {
  asm volatile("stmatrix.sync.aligned.m8n8.x4.shared.b16 [%0], {%1, %2, %3, %4};" ::"r"(addr), "r"(a), "r"(b), "r"(c), "r"(d) : "memory");
}

__device__ __forceinline__ void tma4d_mc_hint(uint32_t dst, const CUtensorMap* m, uint32_t bar, int c3, uint64_t pol, uint16_t mask) {
  asm volatile("cp.async.bulk.tensor.4d.shared::cluster.global.mbarrier::complete_tx::bytes.multicast::cluster.L2::cache_hint"
               " [%0], [%1, {%3, %3, %3, %4}], [%2], %5, %6;"
               ::"r"(dst), "l"(m), "r"(bar), "r"(0), "r"(c3), "h"(mask), "l"(pol) : "memory");
}
__device__ __forceinline__ void tma5d_mc(uint32_t dst, const CUtensorMap* m, uint32_t bar, int c2, int c4, uint16_t mask) {
  asm volatile("cp.async.bulk.tensor.5d.shared::cluster.global.mbarrier::complete_tx::bytes.multicast::cluster"
               " [%0], [%1, {%3, %3, %4, %3, %5}], [%2], %6;"
               ::"r"(dst), "l"(m), "r"(bar), "r"(0), "r"(c2), "r"(c4), "h"(mask) : "memory");
}
__device__ __forceinline__ void bulk_load_hint(uint32_t dst, const void* src, uint32_t bytes, uint32_t bar, uint64_t pol) {
  asm volatile("cp.async.bulk.shared::cluster.global.mbarrier::complete_tx::bytes.L2::cache_hint [%0], [%1], %2, [%3], %4;"
               ::"r"(dst), "l"(src), "r"(bytes), "r"(bar), "l"(pol) : "memory");
}
__device__ __forceinline__ void stg2_if(bool on, void* p, uint32_t a, uint32_t b, uint32_t c, uint32_t d, uint32_t e, uint32_t f,
                                        uint32_t g, uint32_t h, uint64_t pol) {
  asm volatile("{\n.reg .pred p;\nsetp.ne.b32 p, %10, 0;\n"
               "@p st.global.L2::cache_hint.v4.b32 [%0], {%1, %2, %3, %4}, %9;\n"
               "@p st.global.L2::cache_hint.v4.b32 [%0 + 512], {%5, %6, %7, %8}, %9;\n}\n"
               ::"l"(p), "r"(a), "r"(b), "r"(c), "r"(d), "r"(e), "r"(f), "r"(g), "r"(h), "l"(pol), "r"((int)on) : "memory");
}
__device__ __forceinline__ uint64_t evict_first() {
  uint64_t p;
  asm("createpolicy.fractional.L2::evict_first.b64 %0, 1.0;" : "=l"(p));
  return p;
}
__device__ __forceinline__ bool elect() {
  uint32_t ok;
  asm volatile("{\n.reg .pred p;\nelect.sync _|p, 0xffffffff;\nselp.u32 %0, 1, 0, p;\n}\n" : "=r"(ok));
  return ok;
}
__device__ __forceinline__ void mbar_arrive(uint32_t bar) {
  asm volatile("mbarrier.arrive.shared::cta.b64 _, [%0];" ::"r"(bar) : "memory");
}
template <int OFF> __device__ __forceinline__ void lds2_if(bool on, uint32_t p, uint32_t* r) {
  asm volatile("{\n.reg .pred p;\nsetp.ne.b32 p, %9, 0;\n@p ld.shared.v4.b32 {%0, %1, %2, %3}, [%8 + %10];\n"
               "@p ld.shared.v4.b32 {%4, %5, %6, %7}, [%8 + %11];\n}\n"
               : "+r"(r[0]), "+r"(r[1]), "+r"(r[2]), "+r"(r[3]), "+r"(r[4]), "+r"(r[5]), "+r"(r[6]), "+r"(r[7])
               : "r"(p), "r"((int)on), "n"(OFF), "n"(OFF + 512) : "memory");
}
__device__ __forceinline__ void lds128(uint32_t p, uint32_t& a, uint32_t& b, uint32_t& c, uint32_t& d) {
  asm volatile("ld.shared.v4.b32 {%0, %1, %2, %3}, [%4];" : "=r"(a), "=r"(b), "=r"(c), "=r"(d) : "r"(p) : "memory");
}
__device__ __forceinline__ void wait_count(const unsigned int* p, uint32_t target) {
  asm volatile("{\n.reg .pred p;\n.reg .u32 n, v;\nmov.u32 n, 0;\n"
               "LOOP:\nld.acquire.gpu.global.u32 v, [%0];\nsetp.ge.u32 p, v, %1;\n@p bra DONE;\n"
               "nanosleep.u32 %2;\nadd.u32 n, n, 1;\nsetp.lt.u32 p, n, 0x400000;\n@p bra LOOP;\ntrap;\n"
               "DONE:\n}\n" ::"l"(p), "r"(target), "n"(300) : "memory");
}

__device__ __forceinline__ int o_wave(int a, int b, int i) {
  const int p = min(3, b - a - 1);
  return i < p ? b - 2 - i : i == p ? b - 1 : b - 1 - i;
}

struct Cursor {
  uint32_t n;
  __device__ __forceinline__ uint32_t off() const { return n & (8 * NBAR - 8); }
  __device__ __forceinline__ uint32_t ph() const { return (n / (8 * NBAR)) & 1; }
  __device__ __forceinline__ void next() { n += 8; }
};

constexpr float kScaleLog2 = 0.07216878364870322f * 1.4426950408889634f;
constexpr float kSumLimit = 1048576.0f;
constexpr float kMaxLag = 8.0f;

__global__ void __launch_bounds__(384, 1)
fused_kernel(const __grid_constant__ Params P) {
  extern __shared__ uint8_t smem_raw[];
  const uint32_t sbase = (smem_u32(smem_raw) + 1023) & ~1023u;
  const uint32_t full0 = sbase + RING, empty0 = full0 + 8 * NBAR, odone = empty0 + 8 * NBAR, oready0 = odone + 8;
  const uint32_t fenced = oready0 + 64, hready0 = fenced + 8;
  const uint32_t rank = blockIdx.x & 1;
  const int role = (blockIdx.x >> 1) + P.role0;
  const bool wide = P.wide;
  const uint32_t sub = wide ? (blockIdx.x >> 1) & (WIDE - 1) : 0;
  asm volatile("griddepcontrol.launch_dependents;");
  const bool helper = role >= N_CL;
  const int team = helper ? 0 : role >> 2, nt = role & 3, blk = team >> 3;
  const uint32_t* prog = P.ops[helper ? N_TEAM + 2 * (role - N_CL) : team];
  auto q_role = [&](uint32_t op) { return helper ? (int)(((op >> 3) & 60) | ((op >> 12) & 3)) : role; };
  auto o_role = [&](uint32_t op) { return helper ? (int)(((op >> 26) & 56) | ((op >> 9) & 7)) : role; };
  const int wid = __shfl_sync(0xffffffffu, (int)(threadIdx.x >> 5), 0);
  const int wg = wid >> 2;

  const uint32_t op0 = P.first[helper ? N_TEAM + role - N_CL : team];
  if (__builtin_expect(wid == 8, 1)) {
    if (elect()) {
#pragma unroll
      for (int k = 0; k < EARLY; k++) mbar_init(full0 + 8 * k, 1);
      asm volatile("fence.mbarrier_init.release.cluster;" ::: "memory");
      if ((op0 & 3) == OP_Q) {
        const int qr = q_role(op0);
#pragma unroll
        for (int k = 0; k < EARLY; k++) {
          mbar_expect(full0 + 8 * k, SZ_WQ + SZ_A);
          tma2d(sbase + k * (SZ_WQ + SZ_A) + SZ_WQ, &P.x[qr >> 5], full0 + 8 * k, 64 * k, ((qr >> 2) & 7) * kSq + rank * 128);
          tma3d(sbase + k * (SZ_WQ + SZ_A), &P.wq[qr >> 5], full0 + 8 * k, 0, 64 * k, 3 * (4 * ((op0 >> 2) & 7) + (qr & 3)));
          tma3d(sbase + k * (SZ_WQ + SZ_A) + SZ_WQ / 2, &P.wq[qr >> 5], full0 + 8 * k, 0, 64 * k + 32, 3 * (4 * ((op0 >> 2) & 7) + (qr & 3)));
        }
      }
      asm volatile("prefetch.tensormap [%0];" ::"l"(&P.kv[blk]) : "memory");
      asm volatile("prefetch.tensormap [%0];" ::"l"(&P.kv[blk + 2]) : "memory");
    }
  } else if (threadIdx.x == 0) {
#pragma unroll
    for (int i = EARLY; i < 2 * NBAR + 10 + MAX_PARK; i++) mbar_init(full0 + 8 * i, i >= NBAR && i <= 2 * NBAR ? (wide ? 8 * WIDE + 8 : 16) : 1);
    asm volatile("fence.mbarrier_init.release.cluster;" ::: "memory");
  }
  __syncwarp();
  asm volatile("barrier.cluster.arrive.relaxed.aligned;\nbarrier.cluster.wait.aligned;" ::: "memory");

  if (wg == 2) {
    asm volatile("setmaxnreg.dec.sync.aligned.u32 24;");
    if (wid == 8) {
      Cursor tail{0u - 8}, head{0};
      int sh = 0;
      uint32_t cur = 0, used = 0;
      uint64_t fifo = 0;
      uint32_t oready = oready0;
      const uint64_t pol = evict_first();
      const uint16_t pair = 3 << (2 * sub), rows = (wide ? 0x55 >> (8 - 2 * WIDE) : 1) << rank;
      const uint32_t piece = wide ? SZ_A / WIDE : SZ_A;
      struct Load { uint32_t dst, bar, wbar, wph; int c0; const void* ptr; bool wait; };
      auto reserve = [&](uint32_t bytes, bool last, uint32_t off, int c0, const void* ptr) {
        uint32_t fp = bytes >> 12;
        if (cur + fp > (RING >> 12)) { fp += (RING >> 12) - cur; cur = 0; }
        used += fp;
        bool wait = false;
        while (used > (RING >> 12)) {
          wait = true;
          tail.next();
          used -= (uint32_t)fifo & 31;
          fifo >>= 5;
          sh -= 5;
        }
        fifo += (uint64_t)fp << sh;
        Load l{sbase + (cur << 12) + off, full0 + head.off(), empty0 + tail.off(), tail.ph(), c0, ptr, wait};
        cur += bytes >> 12;
        sh += last ? 5 : 0;
        head.n += last ? 8 : 0;
        asm volatile("" : "+r"(l.dst), "+r"(l.bar), "+r"(l.c0), "+l"(l.ptr), "+r"(l.wbar), "+r"(l.wph));
        return l;
      };
      auto vacated = [&](const Load& l) { if (l.wait) mbar_wait(l.wbar, l.wph); };
      auto written = [&](uint32_t flag) {
        mbar_wait(flag, 0);
        asm volatile("fence.proxy.async.global;" ::: "memory");
      };
      for (int pc = 0;; pc++) {
        const uint32_t op = prog[pc];
        const int type = op & 3, a = (op >> 2) & 7;
        if (type == OP_END) break;
        if (type == OP_Q) {
          const int qr = q_role(op);
          const CUtensorMap *mw = &P.wq[qr >> 5], *mx = &P.x[(qr >> 5) + (wide ? 2 : 0)];
          asm volatile("" : "+l"(mw), "+l"(mx));
          auto res_w = [&](int k) { return reserve(SZ_WQ, false, rank * (SZ_WQ / 2), 64 * k + 32 * rank, mw); };
          auto load_w = [&](const Load& w, int k) {
            vacated(w);
            if ((pc > 0 || k >= EARLY) && elect()) tma3d_mc(w.dst, (const CUtensorMap*)w.ptr, w.bar, 0, w.c0, 3 * (4 * a + (qr & 3)), pair);
          };
          auto load_x = [&](const Load& x, int k) {
            vacated(x);
            if ((pc > 0 || k >= EARLY) && elect()) {
              tma2d_mc(x.dst, (const CUtensorMap*)x.ptr, x.bar, x.c0, ((qr >> 2) & 7) * kSq + rank * 128 + sub * (128 / WIDE), rows);
              mbar_expect(x.bar, SZ_WQ + SZ_A);
            }
          };
#pragma unroll 1
          for (int k = 0; k < 10; k++) {
            load_w(res_w(k), k);
            load_x(reserve(SZ_A, true, sub * (SZ_A / WIDE), 64 * k, mx), k);
          }
        } else if (type == OP_A) {
          const uint32_t nop = prog[pc + 1];
          const int row8 = ((team & 7) * kH + nt) * (kSk / 8) + 4 * rank, wave8 = 4 * (kSk / 8);
          auto transit = [&]() {
            const Cursor c{head.n - 8 * (KV_TRANSIT + 1)};
            mbar_wait(full0 + c.off(), c.ph());
          };
          const char* map = (const char*)&P.kv[blk];
          asm volatile("" : "+l"(map));
          int t = (op & F_PARK) ? 1 : 0, c0 = row8 + a * wave8 + 8 * t, isv = 0;
#pragma unroll 1
          for (; t < 31; t++) {
            const Load l = reserve(SZ_KV, true, rank * (SZ_KV / 2), c0, map + isv);
            vacated(l);
            if (t >= KV_TRANSIT) transit();
            if (elect()) {
              tma4d_mc_hint(l.dst, (const CUtensorMap*)l.ptr, l.bar, l.c0, pol, pair);
              mbar_expect(l.bar, SZ_KV);
            }
            isv = (t & 1) << 8;
            c0 += isv ? -8 : t ? 16 : 8;
          }
          const int next = (nop >> 2) & 7;
          if ((nop & 3) == OP_A) written((nop & F_HELP) ? hready0 + 8 * ((nop >> 10) & 3) : fenced);
#pragma unroll 1
          for (int i = (nop & 3) == OP_A ? 0 : 3; i < 4; i++) {
            const Load l = reserve(SZ_KV, true, i < 2 ? 0 : rank * (SZ_KV / 2), i == 3 ? c0 - 8 : row8 + next * wave8,
                                   i < 2 ? (const char*)&g_o[((team * 2 + rank) * 96 + 3 * (4 * next + nt)) * 1024 + i * (SZ_PARK / 16)] : map + ((i & 1) << 8));
            vacated(l);
            if (i < 2) {
              if (elect()) bulk_load_hint(l.dst, l.ptr, SZ_PARK, l.bar, pol);
              __syncwarp();
            } else {
              transit();
              if (elect()) tma4d_mc_hint(l.dst, (const CUtensorMap*)l.ptr, l.bar, l.c0, pol, pair);
              __syncwarp();
            }
            if (elect()) mbar_expect(l.bar, SZ_KV);
          }
        } else {
          const int b = (op >> 5) & 15, ro = o_role(op);
          const CUtensorMap* mw = &P.wo[ro >> 5];
          const uint4* so = &g_o[((ro >> 2) * 2 + rank) * 96 * 1024 + sub * (1024 / WIDE)];
          asm volatile("" : "+l"(mw), "+l"(so));
#pragma unroll 1
          for (int j = 0; j < b - a; j++) {
            const int w = o_wave(a, b, j);
            written(oready);
            oready += 8;
#pragma unroll 1
            for (int k = 12 * w; k < 12 * w + 12; k++) {
              const Load o = reserve(SZ_A, false, sub * (SZ_A / WIDE), 0, so + k * 1024);
              vacated(o);
              if (elect()) bulk_load_mc(o.dst, o.ptr, piece, o.bar, pol, rows);
              const Load w = reserve(SZ_WO, true, rank * (SZ_WO / 2), 8 * k + 4 * rank, mw);
              vacated(w);
              if (elect()) {
                tma5d_mc(w.dst, (const CUtensorMap*)w.ptr, w.bar, w.c0, 5 * (ro & 3), pair);
                mbar_expect(w.bar, SZ_WO + SZ_A);
              }
            }
          }
          if ((op & F_LD) && (op & F_PARK)) written(hready0 + 8 * (MAX_PARK - 1));
#pragma unroll 1
          for (int i = (op & F_LD) ? 0 : 5; i < ((op & F_ST) ? 5 : 6); i++) {
            const Load l = reserve(i < 5 ? SZ_PART : SZ_OUT, i < 5, 0, 0, &g_part[(role * 2 + rank) * 5120 + i * (SZ_PART / 16)]);
            vacated(l);
            if (i < 5 && elect()) bulk_load_hint(l.dst, l.ptr, SZ_PART, l.bar, pol);
            if (elect()) mbar_expect(l.bar, i < 5 ? SZ_PART : 0);
          }
        }
      }
#pragma unroll 1
      for (Cursor c{head.n - 8 * NBAR}; c.n != head.n; c.next()) mbar_wait(empty0 + c.off(), c.ph());
    } else if (threadIdx.x == 288) {
      uint32_t ph = 0;
      bool first = true;
      for (int pc = 0;; pc++) {
        const uint32_t op = prog[pc];
        if ((op & 3) == OP_END) break;
        if ((op & 3) != OP_A && !helper) continue;
        mbar_wait_long(odone, ph);
        ph ^= 1;
        unsigned int* flag = !helper ? &g_done[(team * 2 + rank) * 8 + ((op >> 2) & 7)]
                             : (op & 3) == OP_Q ? &g_help[(q_role(op) * 2 + rank) * MAX_PARK + ((op >> 10) & 3)]
                                                : &g_help[(o_role(op) * 2 + rank) * MAX_PARK + MAX_PARK - 1];
        asm volatile("red.release.gpu.global.add.u32 [%0], 1;" ::"l"(flag) : "memory");
        if (first) mbar_arrive(fenced);
        first = false;
      }
    } else if (threadIdx.x == 320) {
      uint32_t oready = oready0;
      for (int pc = 0;; pc++) {
        const uint32_t op = prog[pc];
        if ((op & 3) == OP_END) break;
        if ((op & 3) == OP_O) {
          const int a = (op >> 2) & 7, b = (op >> 5) & 15;
#pragma unroll 1
          for (int i = 0; i < b - a; i++) {
            const int ci = ((o_role(op) >> 2) * 2 + rank) * 8 + o_wave(a, b, i);
            wait_count(&g_done[ci], 4);
            mbar_arrive(oready);
            oready += 8;
            if (atomicAdd(&g_seen[ci], 1u) == 3u) { g_seen[ci] = 0; g_done[ci] = 0; }
          }
        }
        if ((op & 3) != OP_Q && (op & F_HELP) && (op & F_PARK)) {
          unsigned int* flag = &g_help[(role * 2 + rank) * MAX_PARK + ((op >> 10) & 3)];
          wait_count(flag, 1);
          mbar_arrive(hready0 + 8 * ((op >> 10) & 3));
          *flag = 0;
        }
      }
    }
  } else {
    asm volatile("setmaxnreg.inc.sync.aligned.u32 240;");
    const int lane = threadIdx.x & 31, warp = wid & 3;
    uint32_t empty_rem;
    const bool tell = lane < (wide ? WIDE + 1 : 2);
    asm volatile("mapa.shared::cluster.u32 %0, %1, %2;" : "=r"(empty_rem) : "r"(empty0), "r"((2 * sub + rank) ^ (!tell ? 0 : lane < 2 ? lane : 2 * lane - 2)));
    auto release = [&](int slot) { mbar_arrive_cluster_if(tell, empty_rem + slot); };
    Cursor r{0};
    const uint32_t ring16 = (sbase & 0x3FFFF) >> 4;
    uint32_t cur = ring16;
    bool rdy0 = false, rdy1 = false;
    auto probe1 = [&]() { rdy0 = mbar_test(full0 + r.off(), r.ph()); };
    auto probe2 = [&]() {
      Cursor n = r;
      rdy0 = mbar_test(full0 + n.off(), n.ph());
      n.next();
      rdy1 = mbar_test(full0 + n.off(), n.ph());
    };
    auto take = [&](bool rdy, uint32_t bytes, uint32_t& addr) {
      const int bi = r.off();
      if (!__all_sync(0xffffffffu, rdy)) mbar_wait_math(full0 + r.off(), r.ph());
      r.next();
      if (cur > ring16 + ((RING - bytes) >> 4)) cur = ring16;
      addr = cur;
      cur += bytes >> 4;
      return bi;
    };
    auto at = [&](uint32_t a16) {
      uint32_t a = sbase + (a16 - ring16) * 16;
      asm("" : "+r"(a));
      return a;
    };
    auto second = [&](uint32_t bytes) {
      if (cur > ring16 + ((RING - bytes) >> 4)) cur = ring16;
      cur += bytes >> 4;
      return cur - (bytes >> 4);
    };
    const int row = wg * 64 + warp * 16 + (lane >> 2);
    int img0 = (row * 4 + ((lane & 3) ^ ((row >> 1) & 3))) * 16;
    uint4* pend = nullptr;
    const uint64_t spol = evict_first();
    int pc = 0;
    uint32_t op = prog[0];
    auto enter = [&]() {
      r.n = op >> 12; cur = ring16 + (((op >> 20) & 63) << 8);
    };
    auto drain = [&](uint32_t (&t)[48], uint32_t c) {
      if (!(op & (3u << 26)) || c >= 6) return;
#pragma unroll
      for (int i = 0; i < 6; i++)
        stg2_if(c == i, pend + i * 512, t[8 * i], t[8 * i + 1], t[8 * i + 2], t[8 * i + 3],
                t[8 * i + 4], t[8 * i + 5], t[8 * i + 6], t[8 * i + 7], spol);
      if ((op & (1u << 26)) && c == 5) {
        __syncwarp();
        mbar_arrive_if(tell, odone);
      }
    };
    float s[32], o[96], c[80];
    uint32_t q[48], pa[16], pb[16];
    float mc0, mc1, l0, l1;
    bool gen;
    auto soft = [&](float (&s)[32], uint32_t (&pout)[16], bool first) {
      if (first) { gen = false; mc0 = 0.f; mc1 = 0.f; }
      float b0, b1;
      for (;;) {
        if (gen) {
          float m0 = fmaxf(s[0], s[1]), m1 = fmaxf(s[2], s[3]);
#pragma unroll
          for (int i = 1; i < 8; i++) { m0 = fmaxf(m0, fmaxf(s[4 * i], s[4 * i + 1])); m1 = fmaxf(m1, fmaxf(s[4 * i + 2], s[4 * i + 3])); }
          m0 = fmaxf(m0, __shfl_xor_sync(0xffffffffu, m0, 1)); m1 = fmaxf(m1, __shfl_xor_sync(0xffffffffu, m1, 1));
          m0 = fmaxf(m0, __shfl_xor_sync(0xffffffffu, m0, 2)); m1 = fmaxf(m1, __shfl_xor_sync(0xffffffffu, m1, 2));
          if (first) {
            mc0 = m0; mc1 = m1;
          } else if (__any_sync(0xffffffffu, !(m0 <= mc0 + kMaxLag && m1 <= mc1 + kMaxLag))) {
            m0 = fmaxf(mc0, m0); m1 = fmaxf(mc1, m1);
            const float a0 = ex2(mc0 - m0), a1 = ex2(mc1 - m1);
            mc0 = m0; mc1 = m1;
            l0 *= a0; l1 *= a1;
            wg_wait<0>();
            fence_regs(o);
#pragma unroll
            for (int i = 0; i < 96; i++) o[i] *= i & 2 ? a1 : a0;
          }
#pragma unroll
          for (int i = 0; i < 32; i++) s[i] -= i & 2 ? mc1 : mc0;
        }
#pragma unroll
        for (int i = 0; i < 8; i++) {
          const float e1 = ex2(s[4 * i + 1]), e0 = ex2(s[4 * i]), e3 = ex2(s[4 * i + 3]), e2 = ex2(s[4 * i + 2]);
          pout[2 * i] = pack_bf16(e0, e1);
          b0 = i ? b0 + fadd(e1, e0) : fadd(e1, e0);
          pout[2 * i + 1] = pack_bf16(e2, e3);
          b1 = i ? b1 + fadd(e3, e2) : fadd(e3, e2);
        }
        if (!__any_sync(0xffffffffu, !gen && !(fmaxf(b0, b1) <= kSumLimit && (!first || fminf(b0, b1) >= 1.0f / kSumLimit)))) break;
        gen = __any_sync(0xffffffffu, true);
      }
      l0 = first ? b0 : l0 + b0;
      l1 = first ? b1 : l1 + b1;
    };
    auto qk = [&](float (&s)[32], uint32_t ak, int k0, int k1) {
#pragma unroll
      for (int kk = k0; kk < k1; kk++)
        wgmma_rs_n64<0>(s, q[4 * kk], q[4 * kk + 1], q[4 * kk + 2], q[4 * kk + 3], mk_desc(ak, 16, KV_SBO, 1, (kk >> 2) * KV_CH + (kk & 3) * 2), kk != 0);
      wg_commit();
    };
    auto pv = [&](uint32_t (&pin)[16], uint32_t av, int acc) {
#pragma unroll
      for (int kk = 0; kk < 4; kk++)
        wgmma_rs_n192<1>(o, pin[4 * kk], pin[4 * kk + 1], pin[4 * kk + 2], pin[4 * kk + 3], mk_desc(av, KV_CH * 16, KV_SBO, 1, kk * (KV_SBO / 8)), acc || (kk != 0));
      wg_commit();
    };
    auto xw = [&](uint32_t ad, int acc) {
      const uint32_t da = second(SZ_A) + wg * 512;
      wg_fence();
#pragma unroll
      for (int kk = 0; kk < 4; kk++)
        wgmma_ss_n192<1>(o, mk_desc(da, 16, 1024, 1, kk * 2), mk_desc(ad, 4096, 1024, 1, (kk & 1) * 128 + (kk >> 1) * 768), acc || kk != 0);
      wg_commit();
    };
    auto ow = [&](int acc, int prev) {
      uint32_t da;
      const int bi = take(rdy0, SZ_A, da);
      const uint32_t db = second(SZ_WO);
      da += wg * 256;
      wg_fence();
      wgmma_ss_n160<1>(c, mk_desc(da, 16, 512, 2), mk_desc(db, 2048, 512, 2), acc);
      wgmma_ss_n160<1>(c, mk_desc(da, 16, 512, 2, 2), mk_desc(db, 2048, 512, 2, 64), 1);
      wg_commit();
      if (acc == 1) { wg_wait<1>(); release(prev); }
      wgmma_ss_n160<1>(c, mk_desc(da, 16, 512, 2, 512), mk_desc(db, 2048, 512, 2, 640), 1);
      wgmma_ss_n160<1>(c, mk_desc(da, 16, 512, 2, 514), mk_desc(db, 2048, 512, 2, 704), 1);
      wg_commit();
      return bi;
    };
    auto st_part = [&](int i) {
      stg2_if(true, pend + i * 512, __float_as_uint(c[8 * i]), __float_as_uint(c[8 * i + 1]), __float_as_uint(c[8 * i + 2]), __float_as_uint(c[8 * i + 3]),
              __float_as_uint(c[8 * i + 4]), __float_as_uint(c[8 * i + 5]), __float_as_uint(c[8 * i + 6]), __float_as_uint(c[8 * i + 7]), spol);
    };
#pragma unroll
    for (int i = 0; i < 48; i++) q[i] = 0;
    enter();

    if ((op & 3) == OP_Q) {
      uint32_t ad;
      int bi0 = take(false, SZ_WQ, ad), k = 0, lag = 0;
      xw(ad, 0);
      for (;;) {
#pragma unroll 1
        for (;;) {
          drain(q, k - lag);
          probe1();
          wg_wait<0>();
          release(bi0);
          bi0 = take(rdy0, SZ_WQ, ad);
          if (++k == 8) break;
          xw(ad, 1);
        }
        if (wg) bar_sync(2, 256);
        xw(ad, 1);
        const int bi9 = take(false, SZ_WQ, ad);
        xw(ad, 1);
        if (!wg) asm volatile("bar.arrive 2, 256;" ::: "memory");
        k = 0; lag = 0;
        uint32_t nop = prog[++pc];
        wg_wait<1>();
        release(bi0);
        probe2();
        wg_wait<0>();
        fence_regs(o);
        release(bi9);
#pragma unroll
        for (int i = 0; i < 48; i++) q[i] = pack_bf16(o[2 * i] * kScaleLog2, o[2 * i + 1] * kScaleLog2);
        fence_regs(q);
        if (op & F_PARK) {
          const int qt = helper ? (op >> 5) & 15 : team, qm = helper ? (op >> 12) & 3 : nt;
          pend = (uint4*)((char*)&g_o[((qt * 2 + rank) * 96 + 3 * (4 * ((op >> 2) & 7) + qm)) * 1024] + img0);
          op = nop;
          enter();
          if ((op & 3) != OP_Q) break;
          const int b = take(rdy0, SZ_WQ, ad);
          xw(ad, 0);
          bi0 = take(rdy1, SZ_WQ, ad);
          xw(ad, 1);
          wg_wait<1>();
          release(b);
          k = 1; lag = 1;
          continue;
        }
        int wave = (op >> 2) & 7, sk1;
        uint32_t ak1;
        {
          float s0[32];
          const int sk0 = take(rdy0, SZ_KV, ad);
          wg_fence();
          qk(s0, ad, 0, 12);
          sk1 = take(rdy1, SZ_KV, ak1);
          wg_fence();
          qk(s, ak1, 0, S1A);
          probe1();
          wg_wait<1>();
          fence_regs(s0);
          release(sk0);
          soft(s0, pa, true);
        }
        float i0, i1;
        auto sums = [&]() {
          l0 += __shfl_xor_sync(0xffffffffu, l0, 1); l1 += __shfl_xor_sync(0xffffffffu, l1, 1);
          l0 += __shfl_xor_sync(0xffffffffu, l0, 2); l1 += __shfl_xor_sync(0xffffffffu, l1, 2);
          i0 = rcp(l0); i1 = rcp(l1);
          asm volatile("" : "+f"(i0), "+f"(i1));
        };
        auto target = [&]() {
          pend = (uint4*)((char*)&g_o[((team * 2 + rank) * 96 + 3 * (4 * wave + nt)) * 1024] + img0);
          asm volatile("" : "+l"(pend));
        };
        bool late = false;
#pragma unroll
        for (int i = 0; i < 16; i++) pb[i] = 0;
        for (;;) {
          nop = prog[++pc];
          {
            uint32_t av;
            const int sv = take(rdy0, SZ_KV, av);
            wg_fence();
            qk(s, ak1, S1A, 12);
            pv(pa, av, 0);
            if (late) {
              stg2_if(true, pend + 4 * 512, pb[0], pb[1], pb[2], pb[3], pb[4], pb[5], pb[6], pb[7], spol);
              stg2_if(true, pend + 5 * 512, pb[8], pb[9], pb[10], pb[11], pb[12], pb[13], pb[14], pb[15], spol);
              __syncwarp();
              mbar_arrive_if(tell, odone);
            }
            probe2();
            wg_wait<1>();
            fence_regs(s);
            release(sk1);
            soft(s, pb, false);
            wg_wait<0>();
            fence_regs(o);
            release(sv);
          }
          auto step = [&](uint32_t (&pin)[16], uint32_t (&pout)[16], bool hook, bool unpark) {
            uint32_t ak, av;
            const int sk = take(rdy0, SZ_KV, ak), sv = take(rdy1, SZ_KV, av);
            wg_fence();
            qk(s, ak, 0, 12);
            pv(pin, av, 1);
            if (hook && unpark) { take(false, SZ_PARK, ak); take(false, SZ_PARK, av); }
            probe2();
            wg_wait<1>();
            fence_regs(s);
            release(sk);
            if (hook) {
              lds2_if<0>(unpark, img0 + at(ak), q);
              lds2_if<8192>(unpark, img0 + at(ak), q + 8);
              lds2_if<16384>(unpark, img0 + at(ak), q + 16);
              lds2_if<0>(unpark, img0 + at(av), q + 24);
              lds2_if<8192>(unpark, img0 + at(av), q + 32);
              lds2_if<16384>(unpark, img0 + at(av), q + 40);
            }
            soft(s, pout, false);
            wg_wait<0>();
            fence_regs(o);
            release(sv);
          };
          const int jpark = (nop & 3) == OP_A ? 6 : 7;
#pragma unroll 1
          for (int jj = 0; jj < 7; jj++) {
            step(pb, pa, false, false);
            step(pa, pb, true, jj == jpark);
          }
          if ((nop & 3) != OP_A) break;
          uint32_t ak, av;
          release(Cursor{r.n - 16}.off());
          release(Cursor{r.n - 8}.off());
          const int sk0 = take(rdy0, SZ_KV, ak), sv = take(rdy1, SZ_KV, av);
          wg_fence();
          qk(s, ak, 0, 8);
          sched_fence(img0, P.zero);
          sums();
          sched_fence(img0, P.zero);
          qk(s, ak, 8, 12);
          pv(pb, av, 1);
          probe2();
          wg_wait<1>();
          fence_regs(s);
          release(sk0);
          soft(s, pa, true);
          sk1 = take(rdy0, SZ_KV, ak1);
          rdy0 = rdy1;
          wg_wait<0>();
          target();
          fence_regs(o);
          release(sv);
          uint32_t t[48];
#pragma unroll
          for (int j = 0; j < 6; j++) {
#pragma unroll
            for (int i = 0; i < 4; i++) {
              t[8 * j + i] = pack_bf16(o[16 * j + 4 * i] * i0, o[16 * j + 4 * i + 1] * i0);
              t[8 * j + i + 4] = pack_bf16(o[16 * j + 4 * i + 2] * i1, o[16 * j + 4 * i + 3] * i1);
            }
            if (j < 4)
            stg2_if(true, pend + j * 512, t[8 * j], t[8 * j + 1], t[8 * j + 2], t[8 * j + 3], t[8 * j + 4], t[8 * j + 5], t[8 * j + 6], t[8 * j + 7], spol);
            if (j == 3) { wg_fence(); qk(s, ak1, 0, 4); }
            if (j == 5) { wg_fence(); qk(s, ak1, 4, S1A); }
            sched_fence(img0, P.zero);
          }
          if (P.zero) {
#pragma unroll
            for (int j = 0; j < 4; j++)
              stg2_if(true, pend, t[8 * j], t[8 * j + 1], t[8 * j + 2], t[8 * j + 3], t[8 * j + 4], t[8 * j + 5], t[8 * j + 6], t[8 * j + 7], spol);
          }
          late = true;
#pragma unroll
          for (int i = 0; i < 16; i++) pb[i] = t[32 + i];
          wave = (nop >> 2) & 7;
        }
        const int sv = take(rdy0, SZ_KV, ad);
        wg_fence();
        pv(pb, ad, 1);
        sums();
        target();
        op = nop;
        enter();
        rdy0 = rdy1;
        auto convert = [&](float (&u)[96], int j0, int j1) {
#pragma unroll
          for (int i = 4 * j0; i < 4 * j1; i++) {
            q[8 * (i >> 2) + (i & 3)] = pack_bf16(u[4 * i], u[4 * i + 1]);
            q[8 * (i >> 2) + (i & 3) + 4] = pack_bf16(u[4 * i + 2], u[4 * i + 3]);
          }
        };
        if ((op & 3) != OP_O) {
          if ((op & 3) == OP_Q) bi0 = take(rdy0, SZ_WQ, ad);
          wg_wait<0>();
          fence_regs(o);
          release(sv);
          float u[96];
#pragma unroll
          for (int i = 0; i < 96; i++) u[i] = o[i] * (i & 2 ? i1 : i0);
          if ((op & 3) != OP_Q) { convert(u, 0, 6); break; }
          fence_regs(u);
          xw(ad, 0);
          sched_fence(img0, P.zero);
          fence_regs(u);
          convert(u, 0, 1);
          stg2_if(true, pend, q[0], q[1], q[2], q[3], q[4], q[5], q[6], q[7], spol);
          probe1();
          wg_wait<0>();
          release(bi0);
          bi0 = take(rdy0, SZ_WQ, ad);
          xw(ad, 1);
          sched_fence(img0, P.zero);
          fence_regs(u);
          convert(u, 1, 6);
          k = 1;
          continue;
        }
        int bi = ow(0, 0);
        wg_wait<2>();
        fence_regs(o);
        release(sv);
#pragma unroll
        for (int j = 0; j < 6; j++) {
          uint32_t t[8];
#pragma unroll
          for (int i = 0; i < 4; i++) {
            t[i] = pack_bf16(o[16 * j + 4 * i] * i0, o[16 * j + 4 * i + 1] * i0);
            t[i + 4] = pack_bf16(o[16 * j + 4 * i + 2] * i1, o[16 * j + 4 * i + 3] * i1);
          }
          stg2_if(true, pend + j * 512, t[0], t[1], t[2], t[3], t[4], t[5], t[6], t[7], spol);
          if (j == 5) {
            __syncwarp();
            mbar_arrive_if(tell, odone);
          }
          probe1();
          wg_wait<1>();
          bi = ow(1, bi);
          fence_regs(o);
        }
        {
          const int nk = 12 * (((op >> 5) & 15) - ((op >> 2) & 7)) - ((op & F_ST) ? 0 : 2);
#pragma unroll 1
          for (int k = 7; k < nk; k++) {
            probe1();
            wg_wait<1>();
            bi = ow(1, bi);
          }
        }
        if (!(op & F_ST)) {
          probe2();
          wg_wait<1>();
          if (wg) {
            wg_wait<0>();
            release(bi);
            bar_sync(2, 256);
          }
          bi0 = ow(2, 0);
          rdy0 = rdy1;
          const int b = ow(2, 0);
          if (!wg) asm volatile("bar.arrive 2, 256;" ::: "memory");
          wg_wait<4>();
          mbar_arrive_cluster_if(tell && !wg, empty_rem + bi);
          bi = b;
        }
        probe1();
        nop = prog[++pc];
        if (op & F_LD) {
          uint32_t t[80];
#pragma unroll
          for (int j = 0; j < 5; j++) {
            const int b = take(rdy0, SZ_PART, ad);
            probe1();
#pragma unroll
            for (int i = 4 * j; i < 4 * j + 4; i++)
              lds128(img0 + at(ad) + ((i >> 1) & 1) * 8192 + (i & 1) * 512, t[4 * i], t[4 * i + 1], t[4 * i + 2], t[4 * i + 3]);
            release(b);
          }
          wg_wait<0>();
          fence_regs(c);
#pragma unroll
          for (int i = 0; i < 80; i++) c[i] += __uint_as_float(t[i]);
        }
        if (!(op & F_ST)) {
          wg_wait<0>();
          fence_regs(c);
          release(bi0);
          release(bi);
          goto finish;
        }
        op = nop;
        enter();
        bi0 = take(rdy0, SZ_WQ, ad);
        xw(ad, 0);
        pend = (uint4*)((char*)&g_part[((team * 4 + nt) * 2 + rank) * 5120] + img0);
        probe1();
        wg_wait<1>();
        fence_regs(c);
        release(bi);
        st_part(0); st_part(1);
        wg_wait<0>();
        release(bi0);
        bi0 = take(rdy0, SZ_WQ, ad);
        xw(ad, 1);
        st_part(2); st_part(3);
#pragma unroll
        for (int i = 0; i < 48; i++) q[i] = __float_as_uint(c[32 + i]);
        pend += 4 * 512;
        k = 1; lag = 2;
      }
    }
    rdy0 = false;
    {
      uint32_t t[48];
#pragma unroll
      for (int i = 0; i < 48; i++) t[i] = q[i] ^ P.zero;
      while ((op & 3) == OP_O) {
        int bi = ow(0, 0);
#pragma unroll 1
        for (int k = 1; k < 12 * (int)(((op >> 5) & 15) - ((op >> 2) & 7)); k++) {
          drain(t, k - 1);
          probe1();
          wg_wait<1>();
          bi = ow(1, bi);
        }
        rdy0 = false;
        wg_wait<0>();
        fence_regs(c);
        pc++;
        release(bi);
        if (!(op & F_ST)) goto finish;
        pend = (uint4*)((char*)&g_part[((((op >> 26) & 56) | ((op >> 9) & 7)) * 2 + rank) * 5120] + img0);
#pragma unroll
        for (int i = 6; i < 10; i++) st_part(i);
#pragma unroll
        for (int i = 0; i < 48; i++) t[i] = __float_as_uint(c[i]) ^ P.zero;
        op = prog[pc];
        enter();
      }
      for (int i = 0; i < 6; i++) drain(t, i);
    }
    if (false) {
    finish:
      uint32_t ad;
      take(rdy0, SZ_OUT, ad);
      const uint32_t wstage = sbase + (ad - ring16) * 16 + (wg * 4 + warp) * 5120;
      const uint32_t sa = wstage + (lane & 15) * 64;
#pragma unroll
      for (int i = 0; i < 10; i++) {
        const int u = (i & 1) * 2 + (lane >> 4);
        stsm4(sa + (i >> 1) * 1024 + ((u ^ ((lane >> 1) & 3)) << 4), pack_bf16(c[8 * i], c[8 * i + 1]), pack_bf16(c[8 * i + 2], c[8 * i + 3]),
              pack_bf16(c[8 * i + 4], c[8 * i + 5]), pack_bf16(c[8 * i + 6], c[8 * i + 7]));
      }
      asm volatile("fence.proxy.async.shared::cta;" ::: "memory");
      __syncwarp();
      if (lane == 0) {
        tma3d_store(&P.out, wstage, 0, (team & 7) * kSq + rank * 128 + wg * 64 + warp * 16, blk * 20 + nt * 5);
        asm volatile("cp.async.bulk.commit_group;\ncp.async.bulk.wait_group.read 0;" ::: "memory");
      }
    }
  }
}

typedef CUresult (*EncodeFn)(CUtensorMap*, CUtensorMapDataType, cuuint32_t, void*, const cuuint64_t*, const cuuint64_t*,
                             const cuuint32_t*, const cuuint32_t*, CUtensorMapInterleave, CUtensorMapSwizzle,
                             CUtensorMapL2promotion, CUtensorMapFloatOOBfill);

void encode(EncodeFn fn, CUtensorMap* m, const void* ptr, int rank, const cuuint64_t* dims, const cuuint64_t* strides,
            const cuuint32_t* box, CUtensorMapSwizzle swz) {
  const cuuint32_t es[5] = {1, 1, 1, 1, 1};
  CUresult r = fn(m, CU_TENSOR_MAP_DATA_TYPE_BFLOAT16, rank, const_cast<void*>(ptr), dims, strides, box, es,
                  CU_TENSOR_MAP_INTERLEAVE_NONE, swz, CU_TENSOR_MAP_L2_PROMOTION_L2_128B, CU_TENSOR_MAP_FLOAT_OOB_FILL_NONE);
  if (r != CUDA_SUCCESS) fprintf(stderr, "cuTensorMapEncodeTiled failed: %d\n", (int)r);
}

void annotate(uint32_t* ops, int n, bool helper) {
  uint32_t items = 0, cur = 0, pend = 0;
  auto item = [&](uint32_t bytes, int count, uint32_t bytes2 = 0) {
    for (int i = 0; i < count; i++) {
      if (cur + bytes > RING) cur = 0;
      cur += bytes;
      if (cur + bytes2 > RING) cur = 0;
      cur += bytes2;
      items++;
    }
  };
  for (int i = 0; i <= n; i++) {
    const uint32_t op = ops[i];
    ops[i] |= (items % (2 * NBAR)) << 15 | (cur >> 12) << 20 | pend << 26;
    if ((op & 3) == OP_Q) { item(SZ_WQ, 10, SZ_A); pend = (op & F_PARK) ? (helper ? 1 : 2) : 0; }
    if ((op & 3) == OP_A) {
      item(SZ_KV, (op & F_PARK) ? 30 : 31);
      if ((ops[i + 1] & 3) == OP_A) { item(SZ_PARK, 2); item(SZ_KV, 1); }
      item(SZ_KV, 1);
      pend = 1;
    }
    if ((op & 3) == OP_O) {
      item(SZ_A, 12 * (((op >> 5) & 15) - ((op >> 2) & 7)), SZ_WO);
      if (op & F_LD) item(SZ_PART, 5);
      pend = (op & F_ST) ? (helper ? 1 : 2) : 0;
    }
  }
}

void compile_programs(const char* const* text, bool helpers, Params& P) {
  struct Req { int when, team, wave, slot; } req[N_TEAM * MAX_PARK];
  int n_req = 0;
  for (int t = 0; t < N_TEAM; t++) {
    uint32_t* ops = P.ops[t];
    int n = 0, flags[8] = {0, 0, 0, 0, 0, 0, 0, 0}, n_park = 0, last_o = -1, when = 0, given = 0;
    for (const char* s = text[t]; *s; s++) {
      const int a = s[1] - '0';
      if (*s == 'Q' || (*s == 'H' && !helpers)) { ops[n++] = OP_Q | a << 2; when += 10; }
      else if (*s == 'P') { flags[a] = F_PARK; ops[n++] = OP_Q | a << 2 | flags[a]; when += 10; }
      else if (*s == 'H') { req[n_req++] = {when, t, a, n_park}; flags[a] = F_PARK | F_HELP | n_park++ << 10; }
      else if (*s == 'A') { ops[n++] = OP_A | a << 2 | flags[a]; when += 32; }
      else if (*s == 'G') { given = a; if (helpers) req[n_req++] = {1000, t, 0, -a}; }
      else if (*s == 'O') {
        ops[n] = OP_O | a << 2 | (s[2] - '0') << 5;
        if (given) ops[n] = helpers ? ops[n] | F_LD | F_PARK | (MAX_PARK - 1) << 10 : ops[n] & ~(7u << 2);
        if (last_o >= 0) { ops[last_o] |= F_ST; ops[n] |= F_LD; }
        last_o = n++;
        when += 10 * (s[2] - s[1]);
      }
    }
    for (int i = n; i < MAX_OPS; i++) ops[i] = OP_END;
    annotate(ops, n, false);
  }
  for (int i = 1; i < n_req; i++)
    for (int j = i; j > 0 && req[j].when < req[j - 1].when; j--) { Req r = req[j]; req[j] = req[j - 1]; req[j - 1] = r; }
  for (int h = 0; h < N_HELP; h++) {
    uint32_t* ops = P.ops[N_TEAM + 2 * h];
    int n = 0;
    for (int i = 0; i < n_req; i++)
      for (int m = h; m < 4; m += N_HELP) {
        const uint32_t ro = 4 * req[i].team + m;
        ops[n++] = req[i].slot >= 0 ? OP_Q | req[i].wave << 2 | req[i].team << 5 | F_PARK | req[i].slot << 10 | m << 12
                                    : OP_O | -req[i].slot << 5 | F_ST | (ro & 7) << 9 | (ro >> 3) << 29;
      }
    for (int i = n; i < 2 * MAX_OPS; i++) ops[i] = OP_END;
    annotate(ops, n, true);
  }
  for (int i = 0; i < 30; i++) P.first[i] = i < N_TEAM ? P.ops[i][0] : i < N_TEAM + N_HELP ? P.ops[2 * i - N_TEAM][0] : 0;
}

const char* const kPrograms[N_TEAM] = {
  "Q0A0Q1A1Q2A2Q3A3Q4A4O05Q5A5Q6A6H7A7O58",
  "Q0A0Q1A1H2A2Q3A3O03Q4A4Q5A5Q6A6Q7A7O38",
  "Q0A0H1A1Q2A2O03Q3A3Q4A4Q5A5Q6A6Q7A7O38",
  "Q0A0Q1A1Q2A2Q3A3Q4A4O05Q5A5Q6A6H7A7O58",
  "Q0A0Q1A1Q2A2Q3A3Q4A4O05Q5A5Q6A6H7A7O58",
  "Q0A0Q1A1H2A2O03Q3A3Q4A4Q5A5Q6A6Q7A7O38",
  "Q0A0Q1A1Q2A2O03Q3A3Q4A4H5A5Q6A6Q7A7O38",
  "Q0A0Q1A1Q2A2O03Q3A3H4A4Q5A5Q6A6Q7A7O38",
  "P3Q0A0Q1A1Q2A2A3Q4A4Q5A5Q6A6H7A7O08",
  "Q0A0Q1A1Q2A2Q3A3H4A4Q5A5Q6A6Q7A7O08",
  "P3P7Q0A0Q1A1Q2A2A3Q4A4H5A5Q6A6A7G1O18",
  "Q0A0Q1A1Q2A2H3A3Q4A4Q5A5Q6A6Q7A7O08",
  "P3Q0A0Q1A1Q2A2A3Q4A4Q5A5H6A6Q7A7O08",
  "P7Q0A0Q1A1Q2A2Q3A3Q4A4Q5A5Q6A6A7G1O18",
  "Q0A0Q1A1Q2A2H3A3Q4A4Q5A5Q6A6Q7A7O08",
  "P3Q0A0Q1A1Q2A2A3H4A4Q5A5Q6A6Q7A7G1O18",
};

cudaLaunchConfig_t config(int clusters, int size, cudaLaunchAttribute* at) {
  cudaLaunchConfig_t cfg = {};
  cfg.gridDim = dim3(clusters * size); cfg.blockDim = dim3(384); cfg.dynamicSmemBytes = SMEM_BYTES; cfg.stream = cudaStreamPerThread;
  at[0].id = cudaLaunchAttributeClusterDimension; at[0].val.clusterDim.x = size; at[0].val.clusterDim.y = 1; at[0].val.clusterDim.z = 1;
  at[1].id = cudaLaunchAttributeProgrammaticStreamSerialization; at[1].val.programmaticStreamSerializationAllowed = 1;
  cfg.attrs = at; cfg.numAttrs = 1;
  return cfg;
}

void launch(Params& P, int role0, int clusters, int size, bool overlap) {
  cudaLaunchAttribute at[2];
  cudaLaunchConfig_t cfg = config(clusters, size, at);
  cfg.numAttrs = overlap ? 2 : 1;
  P.role0 = role0; P.wide = size > 2;
  cudaLaunchKernelEx(&cfg, fused_kernel, P);
}

const char* const* bench_programs() {
  return kPrograms;
}

}

extern "C" void kernel_launch(void* const* d_in, const int* in_sizes, int n_in, void* d_out, int out_size) {
  (void)in_sizes; (void)n_in; (void)out_size;
  static EncodeFn fn = nullptr;
  static int n_clusters = 0, n_wide = 0;
  if (!fn) {
    cudaDriverEntryPointQueryResult qr;
    void* f = nullptr;
    cudaGetDriverEntryPoint("cuTensorMapEncodeTiled", &f, cudaEnableDefault, &qr);
    fn = (EncodeFn)f;
    cudaFuncSetAttribute(fused_kernel, cudaFuncAttributeMaxDynamicSharedMemorySize, SMEM_BYTES);
    cudaLaunchAttribute at[2];
    cudaLaunchConfig_t cfg = config(N_CL + N_HELP, 2, at);
    if (cudaOccupancyMaxActiveClusters(&n_clusters, fused_kernel, &cfg) != cudaSuccess || n_clusters < 1) n_clusters = 1;
    cfg = config(N_WIDE / WIDE, 2 * WIDE, at);
    if (cudaOccupancyMaxActiveClusters(&n_wide, fused_kernel, &cfg) != cudaSuccess) n_wide = 0;
    (void)cudaGetLastError();
  }
  Params P;
  const CUtensorMapSwizzle S128 = CU_TENSOR_MAP_SWIZZLE_128B, S64 = CU_TENSOR_MAP_SWIZZLE_64B;
  for (int blk = 0; blk < 2; blk++) {
    void* const* in = d_in + 5 * blk;
    { const cuuint64_t d[] = {kD, kB * kSq}, s[] = {kD * 2}; const cuuint32_t b[] = {64, 128};
      encode(fn, &P.x[blk], in[0], 2, d, s, b, S128);
      const cuuint32_t b2[] = {64, 128 / WIDE};
      encode(fn, &P.x[2 + blk], in[0], 2, d, s, b2, S128); }
    { const cuuint64_t d[] = {64, 8, 3, (cuuint64_t)kB * kH * kSk / 8}, s[] = {kDh * 2, 128, 8 * kDh * 2}; const cuuint32_t b[] = {64, 8, 3, 4};
      encode(fn, &P.kv[blk], in[1], 4, d, s, b, S128);
      encode(fn, &P.kv[blk + 2], in[2], 4, d, s, b, S128); }
    { const cuuint64_t d[] = {64, kD, kHD / 64}, s[] = {kHD * 2, 128}; const cuuint32_t b[] = {64, 32, 3};
      encode(fn, &P.wq[blk], in[3], 3, d, s, b, S128); }
    { const cuuint64_t d[] = {32, 2, kHD / 8, 4, kD / 32}, s[] = {kD * 2, 8 * kD * 2, 2 * kD * 2, 64}; const cuuint32_t b[] = {32, 2, 4, 4, 5};
      encode(fn, &P.wo[blk], in[4], 5, d, s, b, S64); }
  }
  { const cuuint64_t d[] = {32, kB * kSq, 2 * kD / 32}, s[] = {2 * kD * 2, 64}; const cuuint32_t b[] = {32, 16, 5};
    encode(fn, &P.out, d_out, 3, d, s, b, S64); }

  P.zero = 0;
  if (n_clusters >= N_CL) {
    const bool helpers = n_clusters >= N_CL + N_HELP;
    compile_programs(bench_programs(), helpers, P);
    if (helpers && n_wide >= N_WIDE / WIDE) {
      launch(P, 0, N_WIDE / WIDE, 2 * WIDE, false);
      launch(P, N_WIDE, N_CL + N_HELP - N_WIDE, 2, true);
    } else {
      launch(P, 0, N_CL + (helpers ? N_HELP : 0), 2, false);
    }
  } else {
    for (int phase = 0; phase < 2; phase++) {
      const char* text[N_TEAM];
      for (int t = 0; t < N_TEAM; t++) text[t] = phase ? "O08" : "Q0A0Q1A1Q2A2Q3A3Q4A4Q5A5Q6A6Q7A7";
      compile_programs(text, false, P);
      launch(P, 0, N_CL, 2, false);
    }
  }
}
```

```cpp
#include <cuda_runtime.h>
#include <cuda_bf16.h>
#include <cuda.h>
#include <stdint.h>
#include <stdio.h>

namespace {

constexpr int kB = 8, kSq = 256, kD = 640, kH = 32, kSk = 1024, kDh = 192;
constexpr int kHD = kH * kDh;
constexpr uint32_t RING = 224 * 1024;
constexpr uint32_t SZ_KV = 24576;
constexpr uint32_t SZ_WQ = 24576, SZ_WO = 20480, SZ_A = 16384;
constexpr uint32_t SZ_OUT = 40960;
constexpr uint32_t SZ_PARK = 24576;
constexpr uint32_t SZ_PART = 16384;
constexpr int NBAR = 16;
constexpr int KV_TRANSIT = 4;
constexpr int EARLY = 3;
constexpr int S1A = 7;
constexpr uint32_t KV_CH = 64, KV_SBO = 3072;
constexpr int SMEM_BYTES = RING + 512 + 1024;
constexpr int N_TEAM = 16, N_CL = 64, N_HELP = 2, MAX_OPS = 20, MAX_PARK = 4;
constexpr int N_ROWS = N_TEAM + 2 * N_HELP;
#define WIDE_ 4
constexpr int WIDE = WIDE_, N_WIDE = 60;
enum { OP_END = 0, OP_Q = 1, OP_A = 2, OP_O = 3, F_PARK = 1 << 9, F_LD = 1 << 12, F_ST = 1 << 13, F_HELP = 1 << 12 };

struct alignas(64) Params {
  uint32_t first[30], role0, wide;
  CUtensorMap x[4], wq[2], kv[4], wo[2], out;
  uint32_t ops[2 * N_ROWS][MAX_OPS];
  uint32_t zero;
};

__device__ uint4 g_o[N_TEAM * 2 * 96 * 1024];
__device__ uint4 g_part[N_CL * 2 * 5 * 1024];
__device__ unsigned int g_done[N_TEAM * 2 * 8];
__device__ unsigned int g_help[N_CL * 2 * MAX_PARK];
__device__ unsigned int g_meet[2];
__device__ unsigned int g_seen[N_TEAM * 2 * 8];

template <int TB>
__device__ __forceinline__ void wgmma_rs_n64(float (&d)[32], uint32_t a0, uint32_t a1, uint32_t a2, uint32_t a3, uint64_t db, int scale_d) {
  asm volatile("{\n.reg .pred p;\nsetp.ne.b32 p, %37, 0;\n"
    "wgmma.mma_async.sync.aligned.m64n64k16.f32.bf16.bf16 {%0, %1, %2, %3, %4, %5, %6, %7, %8, %9, %10, %11, %12, %13, %14, %15, %16, %17, %18, %19, %20, %21, %22, %23, %24, %25, %26, %27, %28, %29, %30, %31}, {%32, %33, %34, %35}, %36, p, 1, 1, %38;\n}\n"
    : "+f"(d[0]), "+f"(d[1]), "+f"(d[2]), "+f"(d[3]), "+f"(d[4]), "+f"(d[5]), "+f"(d[6]), "+f"(d[7]), "+f"(d[8]), "+f"(d[9]), "+f"(d[10]), "+f"(d[11]), "+f"(d[12]), "+f"(d[13]), "+f"(d[14]), "+f"(d[15]), "+f"(d[16]), "+f"(d[17]), "+f"(d[18]), "+f"(d[19]), "+f"(d[20]), "+f"(d[21]), "+f"(d[22]), "+f"(d[23]), "+f"(d[24]), "+f"(d[25]), "+f"(d[26]), "+f"(d[27]), "+f"(d[28]), "+f"(d[29]), "+f"(d[30]), "+f"(d[31])
    : "r"(a0), "r"(a1), "r"(a2), "r"(a3), "l"(db), "r"(scale_d), "n"(TB));
}
template <int TB, int TA = 0>
__device__ __forceinline__ void wgmma_ss_n160(float (&d)[80], uint64_t da, uint64_t db, int scale_d) {
  asm volatile("{\n.reg .pred p;\nsetp.ne.b32 p, %82, 0;\n"
    "wgmma.mma_async.sync.aligned.m64n160k16.f32.bf16.bf16 {%0, %1, %2, %3, %4, %5, %6, %7, %8, %9, %10, %11, %12, %13, %14, %15, %16, %17, %18, %19, %20, %21, %22, %23, %24, %25, %26, %27, %28, %29, %30, %31, %32, %33, %34, %35, %36, %37, %38, %39, %40, %41, %42, %43, %44, %45, %46, %47, %48, %49, %50, %51, %52, %53, %54, %55, %56, %57, %58, %59, %60, %61, %62, %63, %64, %65, %66, %67, %68, %69, %70, %71, %72, %73, %74, %75, %76, %77, %78, %79}, %80, %81, p, 1, 1, %83, %84;\n}\n"
    : "+f"(d[0]), "+f"(d[1]), "+f"(d[2]), "+f"(d[3]), "+f"(d[4]), "+f"(d[5]), "+f"(d[6]), "+f"(d[7]), "+f"(d[8]), "+f"(d[9]), "+f"(d[10]), "+f"(d[11]), "+f"(d[12]), "+f"(d[13]), "+f"(d[14]), "+f"(d[15]), "+f"(d[16]), "+f"(d[17]), "+f"(d[18]), "+f"(d[19]), "+f"(d[20]), "+f"(d[21]), "+f"(d[22]), "+f"(d[23]), "+f"(d[24]), "+f"(d[25]), "+f"(d[26]), "+f"(d[27]), "+f"(d[28]), "+f"(d[29]), "+f"(d[30]), "+f"(d[31]), "+f"(d[32]), "+f"(d[33]), "+f"(d[34]), "+f"(d[35]), "+f"(d[36]), "+f"(d[37]), "+f"(d[38]), "+f"(d[39]), "+f"(d[40]), "+f"(d[41]), "+f"(d[42]), "+f"(d[43]), "+f"(d[44]), "+f"(d[45]), "+f"(d[46]), "+f"(d[47]), "+f"(d[48]), "+f"(d[49]), "+f"(d[50]), "+f"(d[51]), "+f"(d[52]), "+f"(d[53]), "+f"(d[54]), "+f"(d[55]), "+f"(d[56]), "+f"(d[57]), "+f"(d[58]), "+f"(d[59]), "+f"(d[60]), "+f"(d[61]), "+f"(d[62]), "+f"(d[63]), "+f"(d[64]), "+f"(d[65]), "+f"(d[66]), "+f"(d[67]), "+f"(d[68]), "+f"(d[69]), "+f"(d[70]), "+f"(d[71]), "+f"(d[72]), "+f"(d[73]), "+f"(d[74]), "+f"(d[75]), "+f"(d[76]), "+f"(d[77]), "+f"(d[78]), "+f"(d[79])
    : "l"(da), "l"(db), "r"(scale_d), "n"(TA), "n"(TB));
}
template <int TB, int TA = 0>
__device__ __forceinline__ void wgmma_ss_n192(float (&d)[96], uint64_t da, uint64_t db, int scale_d) {
  asm volatile("{\n.reg .pred p;\nsetp.ne.b32 p, %98, 0;\n"
    "wgmma.mma_async.sync.aligned.m64n192k16.f32.bf16.bf16 {%0, %1, %2, %3, %4, %5, %6, %7, %8, %9, %10, %11, %12, %13, %14, %15, %16, %17, %18, %19, %20, %21, %22, %23, %24, %25, %26, %27, %28, %29, %30, %31, %32, %33, %34, %35, %36, %37, %38, %39, %40, %41, %42, %43, %44, %45, %46, %47, %48, %49, %50, %51, %52, %53, %54, %55, %56, %57, %58, %59, %60, %61, %62, %63, %64, %65, %66, %67, %68, %69, %70, %71, %72, %73, %74, %75, %76, %77, %78, %79, %80, %81, %82, %83, %84, %85, %86, %87, %88, %89, %90, %91, %92, %93, %94, %95}, %96, %97, p, 1, 1, %99, %100;\n}\n"
    : "+f"(d[0]), "+f"(d[1]), "+f"(d[2]), "+f"(d[3]), "+f"(d[4]), "+f"(d[5]), "+f"(d[6]), "+f"(d[7]), "+f"(d[8]), "+f"(d[9]), "+f"(d[10]), "+f"(d[11]), "+f"(d[12]), "+f"(d[13]), "+f"(d[14]), "+f"(d[15]), "+f"(d[16]), "+f"(d[17]), "+f"(d[18]), "+f"(d[19]), "+f"(d[20]), "+f"(d[21]), "+f"(d[22]), "+f"(d[23]), "+f"(d[24]), "+f"(d[25]), "+f"(d[26]), "+f"(d[27]), "+f"(d[28]), "+f"(d[29]), "+f"(d[30]), "+f"(d[31]), "+f"(d[32]), "+f"(d[33]), "+f"(d[34]), "+f"(d[35]), "+f"(d[36]), "+f"(d[37]), "+f"(d[38]), "+f"(d[39]), "+f"(d[40]), "+f"(d[41]), "+f"(d[42]), "+f"(d[43]), "+f"(d[44]), "+f"(d[45]), "+f"(d[46]), "+f"(d[47]), "+f"(d[48]), "+f"(d[49]), "+f"(d[50]), "+f"(d[51]), "+f"(d[52]), "+f"(d[53]), "+f"(d[54]), "+f"(d[55]), "+f"(d[56]), "+f"(d[57]), "+f"(d[58]), "+f"(d[59]), "+f"(d[60]), "+f"(d[61]), "+f"(d[62]), "+f"(d[63]), "+f"(d[64]), "+f"(d[65]), "+f"(d[66]), "+f"(d[67]), "+f"(d[68]), "+f"(d[69]), "+f"(d[70]), "+f"(d[71]), "+f"(d[72]), "+f"(d[73]), "+f"(d[74]), "+f"(d[75]), "+f"(d[76]), "+f"(d[77]), "+f"(d[78]), "+f"(d[79]), "+f"(d[80]), "+f"(d[81]), "+f"(d[82]), "+f"(d[83]), "+f"(d[84]), "+f"(d[85]), "+f"(d[86]), "+f"(d[87]), "+f"(d[88]), "+f"(d[89]), "+f"(d[90]), "+f"(d[91]), "+f"(d[92]), "+f"(d[93]), "+f"(d[94]), "+f"(d[95])
    : "l"(da), "l"(db), "r"(scale_d), "n"(TA), "n"(TB));
}
template <int TB>
__device__ __forceinline__ void wgmma_rs_n192(float (&d)[96], uint32_t a0, uint32_t a1, uint32_t a2, uint32_t a3, uint64_t db, int scale_d) {
  asm volatile("{\n.reg .pred p;\nsetp.ne.b32 p, %101, 0;\n"
    "wgmma.mma_async.sync.aligned.m64n192k16.f32.bf16.bf16 {%0, %1, %2, %3, %4, %5, %6, %7, %8, %9, %10, %11, %12, %13, %14, %15, %16, %17, %18, %19, %20, %21, %22, %23, %24, %25, %26, %27, %28, %29, %30, %31, %32, %33, %34, %35, %36, %37, %38, %39, %40, %41, %42, %43, %44, %45, %46, %47, %48, %49, %50, %51, %52, %53, %54, %55, %56, %57, %58, %59, %60, %61, %62, %63, %64, %65, %66, %67, %68, %69, %70, %71, %72, %73, %74, %75, %76, %77, %78, %79, %80, %81, %82, %83, %84, %85, %86, %87, %88, %89, %90, %91, %92, %93, %94, %95}, {%96, %97, %98, %99}, %100, p, 1, 1, %102;\n}\n"
    : "+f"(d[0]), "+f"(d[1]), "+f"(d[2]), "+f"(d[3]), "+f"(d[4]), "+f"(d[5]), "+f"(d[6]), "+f"(d[7]), "+f"(d[8]), "+f"(d[9]), "+f"(d[10]), "+f"(d[11]), "+f"(d[12]), "+f"(d[13]), "+f"(d[14]), "+f"(d[15]), "+f"(d[16]), "+f"(d[17]), "+f"(d[18]), "+f"(d[19]), "+f"(d[20]), "+f"(d[21]), "+f"(d[22]), "+f"(d[23]), "+f"(d[24]), "+f"(d[25]), "+f"(d[26]), "+f"(d[27]), "+f"(d[28]), "+f"(d[29]), "+f"(d[30]), "+f"(d[31]), "+f"(d[32]), "+f"(d[33]), "+f"(d[34]), "+f"(d[35]), "+f"(d[36]), "+f"(d[37]), "+f"(d[38]), "+f"(d[39]), "+f"(d[40]), "+f"(d[41]), "+f"(d[42]), "+f"(d[43]), "+f"(d[44]), "+f"(d[45]), "+f"(d[46]), "+f"(d[47]), "+f"(d[48]), "+f"(d[49]), "+f"(d[50]), "+f"(d[51]), "+f"(d[52]), "+f"(d[53]), "+f"(d[54]), "+f"(d[55]), "+f"(d[56]), "+f"(d[57]), "+f"(d[58]), "+f"(d[59]), "+f"(d[60]), "+f"(d[61]), "+f"(d[62]), "+f"(d[63]), "+f"(d[64]), "+f"(d[65]), "+f"(d[66]), "+f"(d[67]), "+f"(d[68]), "+f"(d[69]), "+f"(d[70]), "+f"(d[71]), "+f"(d[72]), "+f"(d[73]), "+f"(d[74]), "+f"(d[75]), "+f"(d[76]), "+f"(d[77]), "+f"(d[78]), "+f"(d[79]), "+f"(d[80]), "+f"(d[81]), "+f"(d[82]), "+f"(d[83]), "+f"(d[84]), "+f"(d[85]), "+f"(d[86]), "+f"(d[87]), "+f"(d[88]), "+f"(d[89]), "+f"(d[90]), "+f"(d[91]), "+f"(d[92]), "+f"(d[93]), "+f"(d[94]), "+f"(d[95])
    : "r"(a0), "r"(a1), "r"(a2), "r"(a3), "l"(db), "r"(scale_d), "n"(TB));
}

__device__ __forceinline__ uint32_t smem_u32(const void* p) { return (uint32_t)__cvta_generic_to_shared(p); }
__device__ __forceinline__ void wg_fence() { asm volatile("wgmma.fence.sync.aligned;" ::: "memory"); }
__device__ __forceinline__ void wg_commit() { asm volatile("wgmma.commit_group.sync.aligned;" ::: "memory"); }
template <int N> __device__ __forceinline__ void wg_wait() { asm volatile("wgmma.wait_group.sync.aligned %0;" ::"n"(N) : "memory"); }
__device__ __forceinline__ void sched_fence(int& keep, uint32_t zero) {
  asm volatile("{\n.reg .u32 c;\nmov.u32 c, %%clock;\nand.b32 c, c, %1;\nxor.b32 %0, %0, c;\n}\n" : "+r"(keep) : "r"(zero) : "memory");
}
template <int N> __device__ __forceinline__ void fence_regs(float (&r)[N]) {
#pragma unroll
  for (int i = 0; i < N; i++) asm volatile("" : "+f"(r[i])::"memory");
}
template <int N> __device__ __forceinline__ void fence_regs(uint32_t (&r)[N]) {
#pragma unroll
  for (int i = 0; i < N; i++) asm volatile("" : "+r"(r[i])::"memory");
}
__device__ __forceinline__ uint64_t mk_desc(uint32_t a16, uint32_t lbo, uint32_t sbo, uint32_t swz, uint32_t off = 0) {
  uint64_t d;
  asm("mov.b64 %0, {%1, %2};" : "=l"(d) : "r"(a16), "r"((sbo >> 4) | (swz << 30)));
  return d + (off + ((lbo >> 4) << 16));
}
__device__ __forceinline__ void mbar_init(uint32_t bar, uint32_t cnt) {
  asm volatile("mbarrier.init.shared::cta.b64 [%0], %1;" ::"r"(bar), "r"(cnt) : "memory");
}
__device__ __forceinline__ void mbar_expect(uint32_t bar, uint32_t tx) {
  asm volatile("mbarrier.arrive.expect_tx.shared::cta.b64 _, [%0], %1;" ::"r"(bar), "r"(tx) : "memory");
}
__device__ __forceinline__ bool mbar_test(uint32_t bar, uint32_t ph) {
  uint32_t ok;
  asm volatile("{\n.reg .pred p;\nmbarrier.test_wait.parity.shared::cta.b64 p, [%1], %2;\nselp.u32 %0, 1, 0, p;\n}\n"
               : "=r"(ok) : "r"(bar), "r"(ph) : "memory");
  return ok;
}
__device__ __forceinline__ void mbar_wait(uint32_t bar, uint32_t ph) {
  asm volatile("{\n.reg .pred p;\n.reg .u32 n;\nmov.u32 n, 0;\n"
               "LOOP:\nadd.u32 n, n, 1;\nmbarrier.try_wait.parity.shared::cta.b64 p, [%0], %1;\n@p bra DONE;\n"
               "setp.lt.u32 p, n, 0x1000000;\n@p bra LOOP;\ntrap;\n"
               "DONE:\n}\n" ::"r"(bar), "r"(ph) : "memory");
}
__device__ __forceinline__ void mbar_wait_math(uint32_t bar, uint32_t ph) {
  asm volatile("{\n.reg .pred p;\nLOOP:\nmbarrier.try_wait.parity.shared::cta.b64 p, [%0], %1;\n@!p bra LOOP;\n}\n" ::"r"(bar), "r"(ph) : "memory");
}
__device__ __forceinline__ void mbar_wait_long(uint32_t bar, uint32_t ph) {
  asm volatile("{\n.reg .pred p;\n.reg .u32 n;\nmov.u32 n, 0;\n"
               "LOOP:\nmbarrier.try_wait.parity.shared::cta.b64 p, [%0], %1, %2;\n@p bra DONE;\n"
               "add.u32 n, n, 1;\nsetp.lt.u32 p, n, 0x40000;\n@p bra LOOP;\ntrap;\n"
               "DONE:\n}\n" ::"r"(bar), "r"(ph), "r"(20000) : "memory");
}
__device__ __forceinline__ void mbar_arrive_cluster_if(bool on, uint32_t addr) {
  asm volatile("{\n.reg .pred p;\nsetp.ne.b32 p, %1, 0;\n@p mbarrier.arrive.shared::cluster.b64 _, [%0];\n}\n" ::"r"(addr), "r"((int)on) : "memory");
}
__device__ __forceinline__ void mbar_arrive_if(bool on, uint32_t addr) {
  asm volatile("{\n.reg .pred p;\nsetp.ne.b32 p, %1, 0;\n@p mbarrier.arrive.shared::cta.b64 _, [%0];\n}\n" ::"r"(addr), "r"((int)on) : "memory");
}
__device__ __forceinline__ void tma2d(uint32_t dst, const CUtensorMap* m, uint32_t bar, int c0, int c1) {
  asm volatile("cp.async.bulk.tensor.2d.shared::cluster.global.mbarrier::complete_tx::bytes [%0], [%1, {%3, %4}], [%2];"
               ::"r"(dst), "l"(m), "r"(bar), "r"(c0), "r"(c1) : "memory");
}
__device__ __forceinline__ void tma2d_mc(uint32_t dst, const CUtensorMap* m, uint32_t bar, int c0, int c1, uint16_t mask) {
  asm volatile("cp.async.bulk.tensor.2d.shared::cluster.global.mbarrier::complete_tx::bytes.multicast::cluster [%0], [%1, {%3, %4}], [%2], %5;"
               ::"r"(dst), "l"(m), "r"(bar), "r"(c0), "r"(c1), "h"(mask) : "memory");
}
__device__ __forceinline__ void bulk_load_mc(uint32_t dst, const void* src, uint32_t bytes, uint32_t bar, uint64_t pol, uint16_t mask) {
  asm volatile("cp.async.bulk.shared::cluster.global.mbarrier::complete_tx::bytes.multicast::cluster.L2::cache_hint [%0], [%1], %2, [%3], %5, %4;"
               ::"r"(dst), "l"(src), "r"(bytes), "r"(bar), "l"(pol), "h"(mask) : "memory");
}
__device__ __forceinline__ void tma3d(uint32_t dst, const CUtensorMap* m, uint32_t bar, int c0, int c1, int c2) {
  asm volatile("cp.async.bulk.tensor.3d.shared::cluster.global.mbarrier::complete_tx::bytes [%0], [%1, {%3, %4, %5}], [%2];"
               ::"r"(dst), "l"(m), "r"(bar), "r"(c0), "r"(c1), "r"(c2) : "memory");
}
__device__ __forceinline__ void tma3d_mc(uint32_t dst, const CUtensorMap* m, uint32_t bar, int c0, int c1, int c2, uint16_t mask) {
  asm volatile("cp.async.bulk.tensor.3d.shared::cluster.global.mbarrier::complete_tx::bytes.multicast::cluster"
               " [%0], [%1, {%3, %4, %5}], [%2], %6;"
               ::"r"(dst), "l"(m), "r"(bar), "r"(c0), "r"(c1), "r"(c2), "h"(mask) : "memory");
}
__device__ __forceinline__ void tma3d_store(const CUtensorMap* m, uint32_t src, int c0, int c1, int c2) {
  asm volatile("cp.async.bulk.tensor.3d.global.shared::cta.bulk_group [%0, {%2, %3, %4}], [%1];"
               ::"l"(m), "r"(src), "r"(c0), "r"(c1), "r"(c2) : "memory");
}
__device__ __forceinline__ void bar_sync(int id, int n) { asm volatile("bar.sync %0, %1;" ::"r"(id), "r"(n) : "memory"); }
__device__ __forceinline__ uint32_t pack_bf16(float lo, float hi) {
  uint32_t r;
  asm("cvt.rn.bf16x2.f32 %0, %1, %2;" : "=r"(r) : "f"(hi), "f"(lo));
  return r;
}
__device__ __forceinline__ float ex2(float x) {
  float y;
  asm("ex2.approx.ftz.f32 %0, %1;" : "=f"(y) : "f"(x));
  return y;
}
__device__ __forceinline__ float fadd(float a, float b) {
  float y;
  asm("add.f32 %0, %1, %2;" : "=f"(y) : "f"(a), "f"(b));
  return y;
}
__device__ __forceinline__ float rcp(float x) {
  float y;
  asm("rcp.approx.ftz.f32 %0, %1;" : "=f"(y) : "f"(x));
  return y;
}
__device__ __forceinline__ void stsm4(uint32_t addr, uint32_t a, uint32_t b, uint32_t c, uint32_t d) {
  asm volatile("stmatrix.sync.aligned.m8n8.x4.shared.b16 [%0], {%1, %2, %3, %4};" ::"r"(addr), "r"(a), "r"(b), "r"(c), "r"(d) : "memory");
}

__device__ __forceinline__ void tma4d_mc_hint(uint32_t dst, const CUtensorMap* m, uint32_t bar, int c3, uint64_t pol, uint16_t mask) {
  asm volatile("cp.async.bulk.tensor.4d.shared::cluster.global.mbarrier::complete_tx::bytes.multicast::cluster.L2::cache_hint"
               " [%0], [%1, {%3, %3, %3, %4}], [%2], %5, %6;"
               ::"r"(dst), "l"(m), "r"(bar), "r"(0), "r"(c3), "h"(mask), "l"(pol) : "memory");
}
__device__ __forceinline__ void tma5d_mc(uint32_t dst, const CUtensorMap* m, uint32_t bar, int c2, int c4, uint16_t mask) {
  asm volatile("cp.async.bulk.tensor.5d.shared::cluster.global.mbarrier::complete_tx::bytes.multicast::cluster"
               " [%0], [%1, {%3, %3, %4, %3, %5}], [%2], %6;"
               ::"r"(dst), "l"(m), "r"(bar), "r"(0), "r"(c2), "r"(c4), "h"(mask) : "memory");
}
__device__ __forceinline__ void bulk_load_hint(uint32_t dst, const void* src, uint32_t bytes, uint32_t bar, uint64_t pol) {
  asm volatile("cp.async.bulk.shared::cluster.global.mbarrier::complete_tx::bytes.L2::cache_hint [%0], [%1], %2, [%3], %4;"
               ::"r"(dst), "l"(src), "r"(bytes), "r"(bar), "l"(pol) : "memory");
}
__device__ __forceinline__ void stg2_if(bool on, void* p, uint32_t a, uint32_t b, uint32_t c, uint32_t d, uint32_t e, uint32_t f,
                                        uint32_t g, uint32_t h, uint64_t pol) {
  asm volatile("{\n.reg .pred p;\nsetp.ne.b32 p, %10, 0;\n"
               "@p st.global.L2::cache_hint.v4.b32 [%0], {%1, %2, %3, %4}, %9;\n"
               "@p st.global.L2::cache_hint.v4.b32 [%0 + 512], {%5, %6, %7, %8}, %9;\n}\n"
               ::"l"(p), "r"(a), "r"(b), "r"(c), "r"(d), "r"(e), "r"(f), "r"(g), "r"(h), "l"(pol), "r"((int)on) : "memory");
}
__device__ __forceinline__ uint64_t evict_first() {
  uint64_t p;
  asm("createpolicy.fractional.L2::evict_first.b64 %0, 1.0;" : "=l"(p));
  return p;
}
__device__ __forceinline__ bool elect() {
  uint32_t ok;
  asm volatile("{\n.reg .pred p;\nelect.sync _|p, 0xffffffff;\nselp.u32 %0, 1, 0, p;\n}\n" : "=r"(ok));
  return ok;
}
__device__ __forceinline__ void mbar_arrive(uint32_t bar) {
  asm volatile("mbarrier.arrive.shared::cta.b64 _, [%0];" ::"r"(bar) : "memory");
}
template <int OFF> __device__ __forceinline__ void lds2_if(bool on, uint32_t p, uint32_t* r) {
  asm volatile("{\n.reg .pred p;\nsetp.ne.b32 p, %9, 0;\n@p ld.shared.v4.b32 {%0, %1, %2, %3}, [%8 + %10];\n"
               "@p ld.shared.v4.b32 {%4, %5, %6, %7}, [%8 + %11];\n}\n"
               : "+r"(r[0]), "+r"(r[1]), "+r"(r[2]), "+r"(r[3]), "+r"(r[4]), "+r"(r[5]), "+r"(r[6]), "+r"(r[7])
               : "r"(p), "r"((int)on), "n"(OFF), "n"(OFF + 512) : "memory");
}
__device__ __forceinline__ void lds128(uint32_t p, uint32_t& a, uint32_t& b, uint32_t& c, uint32_t& d) {
  asm volatile("ld.shared.v4.b32 {%0, %1, %2, %3}, [%4];" : "=r"(a), "=r"(b), "=r"(c), "=r"(d) : "r"(p) : "memory");
}
__device__ __forceinline__ void wait_count(const unsigned int* p, uint32_t target) {
  asm volatile("{\n.reg .pred p;\n.reg .u32 n, v;\nmov.u32 n, 0;\n"
               "LOOP:\nld.acquire.gpu.global.u32 v, [%0];\nsetp.ge.u32 p, v, %1;\n@p bra DONE;\n"
               "nanosleep.u32 %2;\nadd.u32 n, n, 1;\nsetp.lt.u32 p, n, 0x400000;\n@p bra LOOP;\ntrap;\n"
               "DONE:\n}\n" ::"l"(p), "r"(target), "n"(300) : "memory");
}

__device__ __forceinline__ int o_wave(int a, int b, int i) {
  const int p = min(3, b - a - 1);
  return i < p ? b - 2 - i : i == p ? b - 1 : b - 1 - i;
}

struct Cursor {
  uint32_t n;
  __device__ __forceinline__ uint32_t off() const { return n & (8 * NBAR - 8); }
  __device__ __forceinline__ uint32_t ph() const { return (n / (8 * NBAR)) & 1; }
  __device__ __forceinline__ void next() { n += 8; }
};

constexpr float kScaleLog2 = 0.07216878364870322f * 1.4426950408889634f;
constexpr float kSumLimit = 1048576.0f;
constexpr float kMaxLag = 8.0f;

__global__ void __launch_bounds__(384, 1)
fused_kernel(const __grid_constant__ Params P) {
  extern __shared__ uint8_t smem_raw[];
  const uint32_t sbase = (smem_u32(smem_raw) + 1023) & ~1023u;
  const uint32_t full0 = sbase + RING, empty0 = full0 + 8 * NBAR, odone = empty0 + 8 * NBAR, oready0 = odone + 8;
  const uint32_t fenced = oready0 + 64, hready0 = fenced + 8, met = hready0 + 8 * MAX_PARK;
  const uint32_t rank = blockIdx.x & 1;
  const int role = (blockIdx.x >> 1) + P.role0;
  const bool wide = P.wide;
  const uint32_t sub = wide ? (blockIdx.x >> 1) & (WIDE - 1) : 0;
  asm volatile("griddepcontrol.launch_dependents;");
  const bool helper = role >= N_CL;
  const int team = helper ? 0 : role >> 2, nt = role & 3, blk = team >> 3;
  const uint32_t* prog = P.ops[helper ? N_TEAM + 2 * (role - N_CL) : team];
  auto q_role = [&](uint32_t op) { return helper ? (int)(((op >> 3) & 60) | ((op >> 12) & 3)) : role; };
  auto o_role = [&](uint32_t op) { return helper ? (int)(((op >> 26) & 56) | ((op >> 9) & 7)) : role; };
  auto alone = [&]() {
    uint32_t v;
    mbar_wait(met, 0);
    asm volatile("ld.shared.u32 %0, [%1];" : "=r"(v) : "r"(met + 8) : "memory");
    return v;
  };
  const int wid = __shfl_sync(0xffffffffu, (int)(threadIdx.x >> 5), 0);
  const int wg = wid >> 2;

  const uint32_t op0 = P.first[helper ? N_TEAM + role - N_CL : team];
  if (__builtin_expect(wid == 8, 1)) {
    if (elect()) {
#pragma unroll
      for (int k = 0; k < EARLY; k++) mbar_init(full0 + 8 * k, 1);
      asm volatile("fence.mbarrier_init.release.cluster;" ::: "memory");
      if ((op0 & 3) == OP_Q) {
        const int qr = q_role(op0);
#pragma unroll
        for (int k = 0; k < EARLY; k++) {
          mbar_expect(full0 + 8 * k, SZ_WQ + SZ_A);
          tma2d(sbase + k * (SZ_WQ + SZ_A) + SZ_WQ, &P.x[qr >> 5], full0 + 8 * k, 64 * k, ((qr >> 2) & 7) * kSq + rank * 128);
          tma3d(sbase + k * (SZ_WQ + SZ_A), &P.wq[qr >> 5], full0 + 8 * k, 0, 64 * k, 3 * (4 * ((op0 >> 2) & 7) + (qr & 3)));
          tma3d(sbase + k * (SZ_WQ + SZ_A) + SZ_WQ / 2, &P.wq[qr >> 5], full0 + 8 * k, 0, 64 * k + 32, 3 * (4 * ((op0 >> 2) & 7) + (qr & 3)));
        }
      }
      asm volatile("prefetch.tensormap [%0];" ::"l"(&P.kv[blk]) : "memory");
      asm volatile("prefetch.tensormap [%0];" ::"l"(&P.kv[blk + 2]) : "memory");
    }
  } else if (threadIdx.x == 0) {
#pragma unroll
    for (int i = EARLY; i < 2 * NBAR + 11 + MAX_PARK; i++) mbar_init(full0 + 8 * i, i >= NBAR && i <= 2 * NBAR ? (wide ? 8 * WIDE + 8 : 16) : 1);
    asm volatile("fence.mbarrier_init.release.cluster;" ::: "memory");
  }
  __syncwarp();
  asm volatile("barrier.cluster.arrive.relaxed.aligned;\nbarrier.cluster.wait.aligned;" ::: "memory");

  if (wg == 2) {
    asm volatile("setmaxnreg.dec.sync.aligned.u32 24;");
    if (wid == 8) {
      Cursor tail{0u - 8}, head{0};
      int sh = 0;
      uint32_t cur = 0, used = 0;
      uint64_t fifo = 0;
      uint32_t oready = oready0;
      const uint64_t pol = evict_first();
      const uint16_t pair = 3 << (2 * sub), rows = (wide ? 0x55 >> (8 - 2 * WIDE) : 1) << rank;
      const uint32_t piece = wide ? SZ_A / WIDE : SZ_A;
      struct Load { uint32_t dst, bar, wbar, wph; int c0; const void* ptr; bool wait; };
      auto reserve = [&](uint32_t bytes, bool last, uint32_t off, int c0, const void* ptr) {
        uint32_t fp = bytes >> 12;
        if (cur + fp > (RING >> 12)) { fp += (RING >> 12) - cur; cur = 0; }
        used += fp;
        bool wait = false;
        while (used > (RING >> 12)) {
          wait = true;
          tail.next();
          used -= (uint32_t)fifo & 31;
          fifo >>= 5;
          sh -= 5;
        }
        fifo += (uint64_t)fp << sh;
        Load l{sbase + (cur << 12) + off, full0 + head.off(), empty0 + tail.off(), tail.ph(), c0, ptr, wait};
        cur += bytes >> 12;
        sh += last ? 5 : 0;
        head.n += last ? 8 : 0;
        asm volatile("" : "+r"(l.dst), "+r"(l.bar), "+r"(l.c0), "+l"(l.ptr), "+r"(l.wbar), "+r"(l.wph));
        return l;
      };
      auto vacated = [&](const Load& l) { if (l.wait) mbar_wait(l.wbar, l.wph); };
      auto written = [&](uint32_t flag) {
        mbar_wait(flag, 0);
        asm volatile("fence.proxy.async.global;" ::: "memory");
      };
      for (int pc = 0;; pc++) {
        if (pc == 1) prog += __shfl_sync(0xffffffffu, alone(), 0);
        const uint32_t op = prog[pc];
        const int type = op & 3, a = (op >> 2) & 7;
        if (type == OP_END) break;
        if (type == OP_Q) {
          const int qr = q_role(op);
          const CUtensorMap *mw = &P.wq[qr >> 5], *mx = &P.x[(qr >> 5) + (wide ? 2 : 0)];
          asm volatile("" : "+l"(mw), "+l"(mx));
          auto res_w = [&](int k) { return reserve(SZ_WQ, false, rank * (SZ_WQ / 2), 64 * k + 32 * rank, mw); };
          auto load_w = [&](const Load& w, int k) {
            vacated(w);
            if ((pc > 0 || k >= EARLY) && elect()) tma3d_mc(w.dst, (const CUtensorMap*)w.ptr, w.bar, 0, w.c0, 3 * (4 * a + (qr & 3)), pair);
          };
          auto load_x = [&](const Load& x, int k) {
            vacated(x);
            if ((pc > 0 || k >= EARLY) && elect()) {
              tma2d_mc(x.dst, (const CUtensorMap*)x.ptr, x.bar, x.c0, ((qr >> 2) & 7) * kSq + rank * 128 + sub * (128 / WIDE), rows);
              mbar_expect(x.bar, SZ_WQ + SZ_A);
            }
          };
#pragma unroll 1
          for (int k = 0; k < 10; k++) {
            load_w(res_w(k), k);
            load_x(reserve(SZ_A, true, sub * (SZ_A / WIDE), 64 * k, mx), k);
          }
        } else if (type == OP_A) {
          const uint32_t nop = prog[pc + 1];
          const int row8 = ((team & 7) * kH + nt) * (kSk / 8) + 4 * rank, wave8 = 4 * (kSk / 8);
          auto transit = [&]() {
            const Cursor c{head.n - 8 * (KV_TRANSIT + 1)};
            mbar_wait(full0 + c.off(), c.ph());
          };
          const char* map = (const char*)&P.kv[blk];
          asm volatile("" : "+l"(map));
          int t = (op & F_PARK) ? 1 : 0, c0 = row8 + a * wave8 + 8 * t, isv = 0;
#pragma unroll 1
          for (; t < 31; t++) {
            const Load l = reserve(SZ_KV, true, rank * (SZ_KV / 2), c0, map + isv);
            vacated(l);
            if (t >= KV_TRANSIT) transit();
            if (elect()) {
              tma4d_mc_hint(l.dst, (const CUtensorMap*)l.ptr, l.bar, l.c0, pol, pair);
              mbar_expect(l.bar, SZ_KV);
            }
            isv = (t & 1) << 8;
            c0 += isv ? -8 : t ? 16 : 8;
          }
          const int next = (nop >> 2) & 7;
          if ((nop & 3) == OP_A) written((nop & F_HELP) ? hready0 + 8 * ((nop >> 10) & 3) : fenced);
#pragma unroll 1
          for (int i = (nop & 3) == OP_A ? 0 : 3; i < 4; i++) {
            const Load l = reserve(SZ_KV, true, i < 2 ? 0 : rank * (SZ_KV / 2), i == 3 ? c0 - 8 : row8 + next * wave8,
                                   i < 2 ? (const char*)&g_o[((team * 2 + rank) * 96 + 3 * (4 * next + nt)) * 1024 + i * (SZ_PARK / 16)] : map + ((i & 1) << 8));
            vacated(l);
            if (i < 2) {
              if (elect()) bulk_load_hint(l.dst, l.ptr, SZ_PARK, l.bar, pol);
              __syncwarp();
            } else {
              transit();
              if (elect()) tma4d_mc_hint(l.dst, (const CUtensorMap*)l.ptr, l.bar, l.c0, pol, pair);
              __syncwarp();
            }
            if (elect()) mbar_expect(l.bar, SZ_KV);
          }
        } else {
          const int b = (op >> 5) & 15, ro = o_role(op);
          const CUtensorMap* mw = &P.wo[ro >> 5];
          const uint4* so = &g_o[((ro >> 2) * 2 + rank) * 96 * 1024 + sub * (1024 / WIDE)];
          asm volatile("" : "+l"(mw), "+l"(so));
#pragma unroll 1
          for (int j = 0; j < b - a; j++) {
            const int w = o_wave(a, b, j);
            written(oready);
            oready += 8;
#pragma unroll 1
            for (int k = 12 * w; k < 12 * w + 12; k++) {
              const Load o = reserve(SZ_A, false, sub * (SZ_A / WIDE), 0, so + k * 1024);
              vacated(o);
              if (elect()) bulk_load_mc(o.dst, o.ptr, piece, o.bar, pol, rows);
              const Load w = reserve(SZ_WO, true, rank * (SZ_WO / 2), 8 * k + 4 * rank, mw);
              vacated(w);
              if (elect()) {
                tma5d_mc(w.dst, (const CUtensorMap*)w.ptr, w.bar, w.c0, 5 * (ro & 3), pair);
                mbar_expect(w.bar, SZ_WO + SZ_A);
              }
            }
          }
          if ((op & F_LD) && (op & F_PARK)) written(hready0 + 8 * (MAX_PARK - 1));
#pragma unroll 1
          for (int i = (op & F_LD) ? 0 : 5; i < ((op & F_ST) ? 5 : 6); i++) {
            const Load l = reserve(i < 5 ? SZ_PART : SZ_OUT, i < 5, 0, 0, &g_part[(role * 2 + rank) * 5120 + i * (SZ_PART / 16)]);
            vacated(l);
            if (i < 5 && elect()) bulk_load_hint(l.dst, l.ptr, SZ_PART, l.bar, pol);
            if (elect()) mbar_expect(l.bar, i < 5 ? SZ_PART : 0);
          }
        }
      }
#pragma unroll 1
      for (Cursor c{head.n - 8 * NBAR}; c.n != head.n; c.next()) mbar_wait(empty0 + c.off(), c.ph());
    } else if (threadIdx.x == 288) {
      uint32_t ph = 0;
      bool first = true;
      prog += alone();
      for (int pc = 0;; pc++) {
        const uint32_t op = prog[pc];
        if ((op & 3) == OP_END) break;
        if ((op & 3) != OP_A && !helper) continue;
        mbar_wait_long(odone, ph);
        ph ^= 1;
        unsigned int* flag = !helper ? &g_done[(team * 2 + rank) * 8 + ((op >> 2) & 7)]
                             : (op & 3) == OP_Q ? &g_help[(q_role(op) * 2 + rank) * MAX_PARK + ((op >> 10) & 3)]
                                                : &g_help[(o_role(op) * 2 + rank) * MAX_PARK + MAX_PARK - 1];
        asm volatile("red.release.gpu.global.add.u32 [%0], 1;" ::"l"(flag) : "memory");
        if (first) mbar_arrive(fenced);
        first = false;
      }
    } else if (threadIdx.x == 320) {
      uint32_t meet = 1;
      if (wide || P.role0) {
        meet = 0;
        for (int n = 0; wide && !meet && n < 300; n++) {
          __nanosleep(100);
          asm volatile("ld.relaxed.gpu.global.u32 %0, [%1];" : "=r"(meet) : "l"(&g_meet[0]) : "memory");
        }
        if (!meet && !(meet = atomicCAS(&g_meet[0], 0u, wide ? 2u : 1u))) meet = wide ? 2 : 1;
        if (atomicAdd(&g_meet[1], 1u) == 2 * (N_CL + N_HELP) - 1) { g_meet[0] = 0; g_meet[1] = 0; }
      }
      prog += (meet - 1) * (N_ROWS * MAX_OPS);
      asm volatile("st.shared.u32 [%0], %1;" ::"r"(met + 8), "r"((meet - 1) * (N_ROWS * MAX_OPS)) : "memory");
      mbar_arrive(met);
      uint32_t oready = oready0;
      for (int pc = 0;; pc++) {
        const uint32_t op = prog[pc];
        if ((op & 3) == OP_END) break;
        if ((op & 3) == OP_O) {
          const int a = (op >> 2) & 7, b = (op >> 5) & 15;
#pragma unroll 1
          for (int i = 0; i < b - a; i++) {
            const int ci = ((o_role(op) >> 2) * 2 + rank) * 8 + o_wave(a, b, i);
            wait_count(&g_done[ci], 4);
            mbar_arrive(oready);
            oready += 8;
            if (atomicAdd(&g_seen[ci], 1u) == 3u) { g_seen[ci] = 0; g_done[ci] = 0; }
          }
        }
        if ((op & 3) != OP_Q && (op & F_HELP) && (op & F_PARK)) {
          unsigned int* flag = &g_help[(role * 2 + rank) * MAX_PARK + ((op >> 10) & 3)];
          wait_count(flag, 1);
          mbar_arrive(hready0 + 8 * ((op >> 10) & 3));
          *flag = 0;
        }
      }
    }
  } else {
    asm volatile("setmaxnreg.inc.sync.aligned.u32 240;");
    const int lane = threadIdx.x & 31, warp = wid & 3;
    uint32_t empty_rem;
    const bool tell = lane < (wide ? WIDE + 1 : 2);
    asm volatile("mapa.shared::cluster.u32 %0, %1, %2;" : "=r"(empty_rem) : "r"(empty0), "r"((2 * sub + rank) ^ (!tell ? 0 : lane < 2 ? lane : 2 * lane - 2)));
    auto release = [&](int slot) { mbar_arrive_cluster_if(tell, empty_rem + slot); };
    Cursor r{0};
    const uint32_t ring16 = (sbase & 0x3FFFF) >> 4;
    uint32_t cur = ring16;
    bool rdy0 = false, rdy1 = false;
    auto probe1 = [&]() { rdy0 = mbar_test(full0 + r.off(), r.ph()); };
    auto probe2 = [&]() {
      Cursor n = r;
      rdy0 = mbar_test(full0 + n.off(), n.ph());
      n.next();
      rdy1 = mbar_test(full0 + n.off(), n.ph());
    };
    auto take = [&](bool rdy, uint32_t bytes, uint32_t& addr) {
      const int bi = r.off();
      if (!__all_sync(0xffffffffu, rdy)) mbar_wait_math(full0 + r.off(), r.ph());
      r.next();
      if (cur > ring16 + ((RING - bytes) >> 4)) cur = ring16;
      addr = cur;
      cur += bytes >> 4;
      return bi;
    };
    auto at = [&](uint32_t a16) {
      uint32_t a = sbase + (a16 - ring16) * 16;
      asm("" : "+r"(a));
      return a;
    };
    auto second = [&](uint32_t bytes) {
      if (cur > ring16 + ((RING - bytes) >> 4)) cur = ring16;
      cur += bytes >> 4;
      return cur - (bytes >> 4);
    };
    const int row = wg * 64 + warp * 16 + (lane >> 2);
    int img0 = (row * 4 + ((lane & 3) ^ ((row >> 1) & 3))) * 16;
    uint4* pend = nullptr;
    const uint64_t spol = evict_first();
    int pc = 0;
    uint32_t op = prog[0];
    auto enter = [&]() {
      r.n = op >> 12; cur = ring16 + (((op >> 20) & 63) << 8);
    };
    auto drain = [&](uint32_t (&t)[48], uint32_t c) {
      if (!(op & (3u << 26)) || c >= 6) return;
#pragma unroll
      for (int i = 0; i < 6; i++)
        stg2_if(c == i, pend + i * 512, t[8 * i], t[8 * i + 1], t[8 * i + 2], t[8 * i + 3],
                t[8 * i + 4], t[8 * i + 5], t[8 * i + 6], t[8 * i + 7], spol);
      if ((op & (1u << 26)) && c == 5) {
        __syncwarp();
        mbar_arrive_if(tell, odone);
      }
    };
    float s[32], o[96], c[80];
    uint32_t q[48], pa[16], pb[16];
    float mc0, mc1, l0, l1;
    bool gen;
    auto soft = [&](float (&s)[32], uint32_t (&pout)[16], bool first) {
      if (first) { gen = false; mc0 = 0.f; mc1 = 0.f; }
      float b0, b1;
      for (;;) {
        if (gen) {
          float m0 = fmaxf(s[0], s[1]), m1 = fmaxf(s[2], s[3]);
#pragma unroll
          for (int i = 1; i < 8; i++) { m0 = fmaxf(m0, fmaxf(s[4 * i], s[4 * i + 1])); m1 = fmaxf(m1, fmaxf(s[4 * i + 2], s[4 * i + 3])); }
          m0 = fmaxf(m0, __shfl_xor_sync(0xffffffffu, m0, 1)); m1 = fmaxf(m1, __shfl_xor_sync(0xffffffffu, m1, 1));
          m0 = fmaxf(m0, __shfl_xor_sync(0xffffffffu, m0, 2)); m1 = fmaxf(m1, __shfl_xor_sync(0xffffffffu, m1, 2));
          if (first) {
            mc0 = m0; mc1 = m1;
          } else if (__any_sync(0xffffffffu, !(m0 <= mc0 + kMaxLag && m1 <= mc1 + kMaxLag))) {
            m0 = fmaxf(mc0, m0); m1 = fmaxf(mc1, m1);
            const float a0 = ex2(mc0 - m0), a1 = ex2(mc1 - m1);
            mc0 = m0; mc1 = m1;
            l0 *= a0; l1 *= a1;
            wg_wait<0>();
            fence_regs(o);
#pragma unroll
            for (int i = 0; i < 96; i++) o[i] *= i & 2 ? a1 : a0;
          }
#pragma unroll
          for (int i = 0; i < 32; i++) s[i] -= i & 2 ? mc1 : mc0;
        }
#pragma unroll
        for (int i = 0; i < 8; i++) {
          const float e1 = ex2(s[4 * i + 1]), e0 = ex2(s[4 * i]), e3 = ex2(s[4 * i + 3]), e2 = ex2(s[4 * i + 2]);
          pout[2 * i] = pack_bf16(e0, e1);
          b0 = i ? b0 + fadd(e1, e0) : fadd(e1, e0);
          pout[2 * i + 1] = pack_bf16(e2, e3);
          b1 = i ? b1 + fadd(e3, e2) : fadd(e3, e2);
        }
        if (!__any_sync(0xffffffffu, !gen && !(fmaxf(b0, b1) <= kSumLimit && (!first || fminf(b0, b1) >= 1.0f / kSumLimit)))) break;
        gen = __any_sync(0xffffffffu, true);
      }
      l0 = first ? b0 : l0 + b0;
      l1 = first ? b1 : l1 + b1;
    };
    auto qk = [&](float (&s)[32], uint32_t ak, int k0, int k1) {
#pragma unroll
      for (int kk = k0; kk < k1; kk++)
        wgmma_rs_n64<0>(s, q[4 * kk], q[4 * kk + 1], q[4 * kk + 2], q[4 * kk + 3], mk_desc(ak, 16, KV_SBO, 1, (kk >> 2) * KV_CH + (kk & 3) * 2), kk != 0);
      wg_commit();
    };
    auto pv = [&](uint32_t (&pin)[16], uint32_t av, int acc) {
#pragma unroll
      for (int kk = 0; kk < 4; kk++)
        wgmma_rs_n192<1>(o, pin[4 * kk], pin[4 * kk + 1], pin[4 * kk + 2], pin[4 * kk + 3], mk_desc(av, KV_CH * 16, KV_SBO, 1, kk * (KV_SBO / 8)), acc || (kk != 0));
      wg_commit();
    };
    auto xw = [&](uint32_t ad, int acc) {
      const uint32_t da = second(SZ_A) + wg * 512;
      wg_fence();
#pragma unroll
      for (int kk = 0; kk < 4; kk++)
        wgmma_ss_n192<1>(o, mk_desc(da, 16, 1024, 1, kk * 2), mk_desc(ad, 4096, 1024, 1, (kk & 1) * 128 + (kk >> 1) * 768), acc || kk != 0);
      wg_commit();
    };
    auto ow = [&](int acc, int prev) {
      uint32_t da;
      const int bi = take(rdy0, SZ_A, da);
      const uint32_t db = second(SZ_WO);
      da += wg * 256;
      wg_fence();
      wgmma_ss_n160<1>(c, mk_desc(da, 16, 512, 2), mk_desc(db, 2048, 512, 2), acc);
      wgmma_ss_n160<1>(c, mk_desc(da, 16, 512, 2, 2), mk_desc(db, 2048, 512, 2, 64), 1);
      wg_commit();
      if (acc == 1) { wg_wait<1>(); release(prev); }
      wgmma_ss_n160<1>(c, mk_desc(da, 16, 512, 2, 512), mk_desc(db, 2048, 512, 2, 640), 1);
      wgmma_ss_n160<1>(c, mk_desc(da, 16, 512, 2, 514), mk_desc(db, 2048, 512, 2, 704), 1);
      wg_commit();
      return bi;
    };
    auto st_part = [&](int i) {
      stg2_if(true, pend + i * 512, __float_as_uint(c[8 * i]), __float_as_uint(c[8 * i + 1]), __float_as_uint(c[8 * i + 2]), __float_as_uint(c[8 * i + 3]),
              __float_as_uint(c[8 * i + 4]), __float_as_uint(c[8 * i + 5]), __float_as_uint(c[8 * i + 6]), __float_as_uint(c[8 * i + 7]), spol);
    };
#pragma unroll
    for (int i = 0; i < 48; i++) q[i] = 0;
    enter();

    if ((op & 3) == OP_Q) {
      uint32_t ad;
      int bi0 = take(false, SZ_WQ, ad), k = 0, lag = 0;
      xw(ad, 0);
      for (;;) {
#pragma unroll 1
        for (;;) {
          drain(q, k - lag);
          probe1();
          wg_wait<0>();
          release(bi0);
          bi0 = take(rdy0, SZ_WQ, ad);
          if (++k == 8) break;
          xw(ad, 1);
        }
        if (wg) bar_sync(2, 256);
        xw(ad, 1);
        const int bi9 = take(false, SZ_WQ, ad);
        xw(ad, 1);
        if (!wg) asm volatile("bar.arrive 2, 256;" ::: "memory");
        k = 0; lag = 0;
        if (pc == 0) prog += __shfl_sync(0xffffffffu, alone(), 0);
        uint32_t nop = prog[++pc];
        wg_wait<1>();
        release(bi0);
        probe2();
        wg_wait<0>();
        fence_regs(o);
        release(bi9);
#pragma unroll
        for (int i = 0; i < 48; i++) q[i] = pack_bf16(o[2 * i] * kScaleLog2, o[2 * i + 1] * kScaleLog2);
        fence_regs(q);
        if (op & F_PARK) {
          const int qt = helper ? (op >> 5) & 15 : team, qm = helper ? (op >> 12) & 3 : nt;
          pend = (uint4*)((char*)&g_o[((qt * 2 + rank) * 96 + 3 * (4 * ((op >> 2) & 7) + qm)) * 1024] + img0);
          op = nop;
          enter();
          if ((op & 3) != OP_Q) break;
          const int b = take(rdy0, SZ_WQ, ad);
          xw(ad, 0);
          bi0 = take(rdy1, SZ_WQ, ad);
          xw(ad, 1);
          wg_wait<1>();
          release(b);
          k = 1; lag = 1;
          continue;
        }
        int wave = (op >> 2) & 7, sk1;
        uint32_t ak1;
        {
          float s0[32];
          const int sk0 = take(rdy0, SZ_KV, ad);
          wg_fence();
          qk(s0, ad, 0, 12);
          sk1 = take(rdy1, SZ_KV, ak1);
          wg_fence();
          qk(s, ak1, 0, S1A);
          probe1();
          wg_wait<1>();
          fence_regs(s0);
          release(sk0);
          soft(s0, pa, true);
        }
        float i0, i1;
        auto sums = [&]() {
          l0 += __shfl_xor_sync(0xffffffffu, l0, 1); l1 += __shfl_xor_sync(0xffffffffu, l1, 1);
          l0 += __shfl_xor_sync(0xffffffffu, l0, 2); l1 += __shfl_xor_sync(0xffffffffu, l1, 2);
          i0 = rcp(l0); i1 = rcp(l1);
          asm volatile("" : "+f"(i0), "+f"(i1));
        };
        auto target = [&]() {
          pend = (uint4*)((char*)&g_o[((team * 2 + rank) * 96 + 3 * (4 * wave + nt)) * 1024] + img0);
          asm volatile("" : "+l"(pend));
        };
        bool late = false;
#pragma unroll
        for (int i = 0; i < 16; i++) pb[i] = 0;
        for (;;) {
          nop = prog[++pc];
          {
            uint32_t av;
            const int sv = take(rdy0, SZ_KV, av);
            wg_fence();
            qk(s, ak1, S1A, 12);
            pv(pa, av, 0);
            if (late) {
              stg2_if(true, pend + 4 * 512, pb[0], pb[1], pb[2], pb[3], pb[4], pb[5], pb[6], pb[7], spol);
              stg2_if(true, pend + 5 * 512, pb[8], pb[9], pb[10], pb[11], pb[12], pb[13], pb[14], pb[15], spol);
              __syncwarp();
              mbar_arrive_if(tell, odone);
            }
            probe2();
            wg_wait<1>();
            fence_regs(s);
            release(sk1);
            soft(s, pb, false);
            wg_wait<0>();
            fence_regs(o);
            release(sv);
          }
          auto step = [&](uint32_t (&pin)[16], uint32_t (&pout)[16], bool hook, bool unpark) {
            uint32_t ak, av;
            const int sk = take(rdy0, SZ_KV, ak), sv = take(rdy1, SZ_KV, av);
            wg_fence();
            qk(s, ak, 0, 12);
            pv(pin, av, 1);
            if (hook && unpark) { take(false, SZ_PARK, ak); take(false, SZ_PARK, av); }
            probe2();
            wg_wait<1>();
            fence_regs(s);
            release(sk);
            if (hook) {
              lds2_if<0>(unpark, img0 + at(ak), q);
              lds2_if<8192>(unpark, img0 + at(ak), q + 8);
              lds2_if<16384>(unpark, img0 + at(ak), q + 16);
              lds2_if<0>(unpark, img0 + at(av), q + 24);
              lds2_if<8192>(unpark, img0 + at(av), q + 32);
              lds2_if<16384>(unpark, img0 + at(av), q + 40);
            }
            soft(s, pout, false);
            wg_wait<0>();
            fence_regs(o);
            release(sv);
          };
          const int jpark = (nop & 3) == OP_A ? 6 : 7;
#pragma unroll 1
          for (int jj = 0; jj < 7; jj++) {
            step(pb, pa, false, false);
            step(pa, pb, true, jj == jpark);
          }
          if ((nop & 3) != OP_A) break;
          uint32_t ak, av;
          release(Cursor{r.n - 16}.off());
          release(Cursor{r.n - 8}.off());
          const int sk0 = take(rdy0, SZ_KV, ak), sv = take(rdy1, SZ_KV, av);
          wg_fence();
          qk(s, ak, 0, 8);
          sched_fence(img0, P.zero);
          sums();
          sched_fence(img0, P.zero);
          qk(s, ak, 8, 12);
          pv(pb, av, 1);
          probe2();
          wg_wait<1>();
          fence_regs(s);
          release(sk0);
          soft(s, pa, true);
          sk1 = take(rdy0, SZ_KV, ak1);
          rdy0 = rdy1;
          wg_wait<0>();
          target();
          fence_regs(o);
          release(sv);
          uint32_t t[48];
#pragma unroll
          for (int j = 0; j < 6; j++) {
#pragma unroll
            for (int i = 0; i < 4; i++) {
              t[8 * j + i] = pack_bf16(o[16 * j + 4 * i] * i0, o[16 * j + 4 * i + 1] * i0);
              t[8 * j + i + 4] = pack_bf16(o[16 * j + 4 * i + 2] * i1, o[16 * j + 4 * i + 3] * i1);
            }
            if (j < 4)
            stg2_if(true, pend + j * 512, t[8 * j], t[8 * j + 1], t[8 * j + 2], t[8 * j + 3], t[8 * j + 4], t[8 * j + 5], t[8 * j + 6], t[8 * j + 7], spol);
            if (j == 3) { wg_fence(); qk(s, ak1, 0, 4); }
            if (j == 5) { wg_fence(); qk(s, ak1, 4, S1A); }
            sched_fence(img0, P.zero);
          }
          if (P.zero) {
#pragma unroll
            for (int j = 0; j < 4; j++)
              stg2_if(true, pend, t[8 * j], t[8 * j + 1], t[8 * j + 2], t[8 * j + 3], t[8 * j + 4], t[8 * j + 5], t[8 * j + 6], t[8 * j + 7], spol);
          }
          late = true;
#pragma unroll
          for (int i = 0; i < 16; i++) pb[i] = t[32 + i];
          wave = (nop >> 2) & 7;
        }
        const int sv = take(rdy0, SZ_KV, ad);
        wg_fence();
        pv(pb, ad, 1);
        sums();
        target();
        op = nop;
        enter();
        rdy0 = rdy1;
        auto convert = [&](float (&u)[96], int j0, int j1) {
#pragma unroll
          for (int i = 4 * j0; i < 4 * j1; i++) {
            q[8 * (i >> 2) + (i & 3)] = pack_bf16(u[4 * i], u[4 * i + 1]);
            q[8 * (i >> 2) + (i & 3) + 4] = pack_bf16(u[4 * i + 2], u[4 * i + 3]);
          }
        };
        if ((op & 3) != OP_O) {
          if ((op & 3) == OP_Q) bi0 = take(rdy0, SZ_WQ, ad);
          wg_wait<0>();
          fence_regs(o);
          release(sv);
          float u[96];
#pragma unroll
          for (int i = 0; i < 96; i++) u[i] = o[i] * (i & 2 ? i1 : i0);
          if ((op & 3) != OP_Q) { convert(u, 0, 6); break; }
          fence_regs(u);
          xw(ad, 0);
          sched_fence(img0, P.zero);
          fence_regs(u);
          convert(u, 0, 1);
          stg2_if(true, pend, q[0], q[1], q[2], q[3], q[4], q[5], q[6], q[7], spol);
          probe1();
          wg_wait<0>();
          release(bi0);
          bi0 = take(rdy0, SZ_WQ, ad);
          xw(ad, 1);
          sched_fence(img0, P.zero);
          fence_regs(u);
          convert(u, 1, 6);
          k = 1;
          continue;
        }
        int bi = ow(0, 0);
        wg_wait<2>();
        fence_regs(o);
        release(sv);
#pragma unroll
        for (int j = 0; j < 6; j++) {
          uint32_t t[8];
#pragma unroll
          for (int i = 0; i < 4; i++) {
            t[i] = pack_bf16(o[16 * j + 4 * i] * i0, o[16 * j + 4 * i + 1] * i0);
            t[i + 4] = pack_bf16(o[16 * j + 4 * i + 2] * i1, o[16 * j + 4 * i + 3] * i1);
          }
          stg2_if(true, pend + j * 512, t[0], t[1], t[2], t[3], t[4], t[5], t[6], t[7], spol);
          if (j == 5) {
            __syncwarp();
            mbar_arrive_if(tell, odone);
          }
          probe1();
          wg_wait<1>();
          bi = ow(1, bi);
          fence_regs(o);
        }
        {
          const int nk = 12 * (((op >> 5) & 15) - ((op >> 2) & 7)) - ((op & F_ST) ? 0 : 2);
#pragma unroll 1
          for (int k = 7; k < nk; k++) {
            probe1();
            wg_wait<1>();
            bi = ow(1, bi);
          }
        }
        if (!(op & F_ST)) {
          probe2();
          wg_wait<1>();
          if (wg) {
            wg_wait<0>();
            release(bi);
            bar_sync(2, 256);
          }
          bi0 = ow(2, 0);
          rdy0 = rdy1;
          const int b = ow(2, 0);
          if (!wg) asm volatile("bar.arrive 2, 256;" ::: "memory");
          wg_wait<4>();
          mbar_arrive_cluster_if(tell && !wg, empty_rem + bi);
          bi = b;
        }
        probe1();
        nop = prog[++pc];
        if (op & F_LD) {
          uint32_t t[80];
#pragma unroll
          for (int j = 0; j < 5; j++) {
            const int b = take(rdy0, SZ_PART, ad);
            probe1();
#pragma unroll
            for (int i = 4 * j; i < 4 * j + 4; i++)
              lds128(img0 + at(ad) + ((i >> 1) & 1) * 8192 + (i & 1) * 512, t[4 * i], t[4 * i + 1], t[4 * i + 2], t[4 * i + 3]);
            release(b);
          }
          wg_wait<0>();
          fence_regs(c);
#pragma unroll
          for (int i = 0; i < 80; i++) c[i] += __uint_as_float(t[i]);
        }
        if (!(op & F_ST)) {
          wg_wait<0>();
          fence_regs(c);
          release(bi0);
          release(bi);
          goto finish;
        }
        op = nop;
        enter();
        bi0 = take(rdy0, SZ_WQ, ad);
        xw(ad, 0);
        pend = (uint4*)((char*)&g_part[((team * 4 + nt) * 2 + rank) * 5120] + img0);
        probe1();
        wg_wait<1>();
        fence_regs(c);
        release(bi);
        st_part(0); st_part(1);
        wg_wait<0>();
        release(bi0);
        bi0 = take(rdy0, SZ_WQ, ad);
        xw(ad, 1);
        st_part(2); st_part(3);
#pragma unroll
        for (int i = 0; i < 48; i++) q[i] = __float_as_uint(c[32 + i]);
        pend += 4 * 512;
        k = 1; lag = 2;
      }
    }
    rdy0 = false;
    {
      uint32_t t[48];
#pragma unroll
      for (int i = 0; i < 48; i++) t[i] = q[i] ^ P.zero;
      while ((op & 3) == OP_O) {
        int bi = ow(0, 0);
#pragma unroll 1
        for (int k = 1; k < 12 * (int)(((op >> 5) & 15) - ((op >> 2) & 7)); k++) {
          drain(t, k - 1);
          probe1();
          wg_wait<1>();
          bi = ow(1, bi);
        }
        rdy0 = false;
        wg_wait<0>();
        fence_regs(c);
        pc++;
        release(bi);
        if (!(op & F_ST)) goto finish;
        pend = (uint4*)((char*)&g_part[((((op >> 26) & 56) | ((op >> 9) & 7)) * 2 + rank) * 5120] + img0);
#pragma unroll
        for (int i = 6; i < 10; i++) st_part(i);
#pragma unroll
        for (int i = 0; i < 48; i++) t[i] = __float_as_uint(c[i]) ^ P.zero;
        op = prog[pc];
        enter();
      }
      for (int i = 0; i < 6; i++) drain(t, i);
    }
    if (false) {
    finish:
      uint32_t ad;
      take(rdy0, SZ_OUT, ad);
      const uint32_t wstage = sbase + (ad - ring16) * 16 + (wg * 4 + warp) * 5120;
      const uint32_t sa = wstage + (lane & 15) * 64;
#pragma unroll
      for (int i = 0; i < 10; i++) {
        const int u = (i & 1) * 2 + (lane >> 4);
        stsm4(sa + (i >> 1) * 1024 + ((u ^ ((lane >> 1) & 3)) << 4), pack_bf16(c[8 * i], c[8 * i + 1]), pack_bf16(c[8 * i + 2], c[8 * i + 3]),
              pack_bf16(c[8 * i + 4], c[8 * i + 5]), pack_bf16(c[8 * i + 6], c[8 * i + 7]));
      }
      asm volatile("fence.proxy.async.shared::cta;" ::: "memory");
      __syncwarp();
      if (lane == 0) {
        tma3d_store(&P.out, wstage, 0, (team & 7) * kSq + rank * 128 + wg * 64 + warp * 16, blk * 20 + nt * 5);
        asm volatile("cp.async.bulk.commit_group;\ncp.async.bulk.wait_group.read 0;" ::: "memory");
      }
    }
  }
}

typedef CUresult (*EncodeFn)(CUtensorMap*, CUtensorMapDataType, cuuint32_t, void*, const cuuint64_t*, const cuuint64_t*,
                             const cuuint32_t*, const cuuint32_t*, CUtensorMapInterleave, CUtensorMapSwizzle,
                             CUtensorMapL2promotion, CUtensorMapFloatOOBfill);

void encode(EncodeFn fn, CUtensorMap* m, const void* ptr, int rank, const cuuint64_t* dims, const cuuint64_t* strides,
            const cuuint32_t* box, CUtensorMapSwizzle swz) {
  const cuuint32_t es[5] = {1, 1, 1, 1, 1};
  CUresult r = fn(m, CU_TENSOR_MAP_DATA_TYPE_BFLOAT16, rank, const_cast<void*>(ptr), dims, strides, box, es,
                  CU_TENSOR_MAP_INTERLEAVE_NONE, swz, CU_TENSOR_MAP_L2_PROMOTION_L2_128B, CU_TENSOR_MAP_FLOAT_OOB_FILL_NONE);
  if (r != CUDA_SUCCESS) fprintf(stderr, "cuTensorMapEncodeTiled failed: %d\n", (int)r);
}

void annotate(uint32_t* ops, int n, bool helper) {
  uint32_t items = 0, cur = 0, pend = 0;
  auto item = [&](uint32_t bytes, int count, uint32_t bytes2 = 0) {
    for (int i = 0; i < count; i++) {
      if (cur + bytes > RING) cur = 0;
      cur += bytes;
      if (cur + bytes2 > RING) cur = 0;
      cur += bytes2;
      items++;
    }
  };
  for (int i = 0; i <= n; i++) {
    const uint32_t op = ops[i];
    ops[i] |= (items % (2 * NBAR)) << 15 | (cur >> 12) << 20 | pend << 26;
    if ((op & 3) == OP_Q) { item(SZ_WQ, 10, SZ_A); pend = (op & F_PARK) ? (helper ? 1 : 2) : 0; }
    if ((op & 3) == OP_A) {
      item(SZ_KV, (op & F_PARK) ? 30 : 31);
      if ((ops[i + 1] & 3) == OP_A) { item(SZ_PARK, 2); item(SZ_KV, 1); }
      item(SZ_KV, 1);
      pend = 1;
    }
    if ((op & 3) == OP_O) {
      item(SZ_A, 12 * (((op >> 5) & 15) - ((op >> 2) & 7)), SZ_WO);
      if (op & F_LD) item(SZ_PART, 5);
      pend = (op & F_ST) ? (helper ? 1 : 2) : 0;
    }
  }
}

void compile_programs(const char* const* text, bool helpers, uint32_t (*rows)[MAX_OPS]) {
  struct Req { int when, team, wave, slot; } req[N_TEAM * MAX_PARK];
  int n_req = 0;
  for (int t = 0; t < N_TEAM; t++) {
    uint32_t* ops = rows[t];
    int n = 0, flags[8] = {0, 0, 0, 0, 0, 0, 0, 0}, n_park = 0, last_o = -1, when = 0, given = 0;
    for (const char* s = text[t]; *s; s++) {
      const int a = s[1] - '0';
      if (*s == 'Q' || (*s == 'H' && !helpers)) { ops[n++] = OP_Q | a << 2; when += 10; }
      else if (*s == 'P') { flags[a] = F_PARK; ops[n++] = OP_Q | a << 2 | flags[a]; when += 10; }
      else if (*s == 'H') { req[n_req++] = {when, t, a, n_park}; flags[a] = F_PARK | F_HELP | n_park++ << 10; }
      else if (*s == 'A') { ops[n++] = OP_A | a << 2 | flags[a]; when += 32; }
      else if (*s == 'G') { given = a; if (helpers) req[n_req++] = {1000, t, 0, -a}; }
      else if (*s == 'O') {
        ops[n] = OP_O | a << 2 | (s[2] - '0') << 5;
        if (given) ops[n] = helpers ? ops[n] | F_LD | F_PARK | (MAX_PARK - 1) << 10 : ops[n] & ~(7u << 2);
        if (last_o >= 0) { ops[last_o] |= F_ST; ops[n] |= F_LD; }
        last_o = n++;
        when += 10 * (s[2] - s[1]);
      }
    }
    for (int i = n; i < MAX_OPS; i++) ops[i] = OP_END;
    annotate(ops, n, false);
  }
  for (int i = 1; i < n_req; i++)
    for (int j = i; j > 0 && req[j].when < req[j - 1].when; j--) { Req r = req[j]; req[j] = req[j - 1]; req[j - 1] = r; }
  for (int h = 0; h < N_HELP; h++) {
    uint32_t* ops = rows[N_TEAM + 2 * h];
    int n = 0;
    for (int i = 0; i < n_req; i++)
      for (int m = h; m < 4; m += N_HELP) {
        const uint32_t ro = 4 * req[i].team + m;
        ops[n++] = req[i].slot >= 0 ? OP_Q | req[i].wave << 2 | req[i].team << 5 | F_PARK | req[i].slot << 10 | m << 12
                                    : OP_O | -req[i].slot << 5 | F_ST | (ro & 7) << 9 | (ro >> 3) << 29;
      }
    for (int i = n; i < 2 * MAX_OPS; i++) ops[i] = OP_END;
    annotate(ops, n, true);
  }
}

const char* const kPrograms[N_TEAM] = {
  "Q0A0Q1A1Q2A2Q3A3Q4A4O05Q5A5Q6A6H7A7O58",
  "Q0A0Q1A1H2A2Q3A3O03Q4A4Q5A5Q6A6Q7A7O38",
  "Q0A0H1A1Q2A2O03Q3A3Q4A4Q5A5Q6A6Q7A7O38",
  "Q0A0Q1A1Q2A2Q3A3Q4A4O05Q5A5Q6A6H7A7O58",
  "Q0A0Q1A1Q2A2Q3A3Q4A4O05Q5A5Q6A6H7A7O58",
  "Q0A0Q1A1H2A2O03Q3A3Q4A4Q5A5Q6A6Q7A7O38",
  "Q0A0Q1A1Q2A2O03Q3A3Q4A4H5A5Q6A6Q7A7O38",
  "Q0A0Q1A1Q2A2O03Q3A3H4A4Q5A5Q6A6Q7A7O38",
  "P3Q0A0Q1A1Q2A2A3Q4A4Q5A5Q6A6H7A7O08",
  "Q0A0Q1A1Q2A2Q3A3H4A4Q5A5Q6A6Q7A7O08",
  "P3P7Q0A0Q1A1Q2A2A3Q4A4H5A5Q6A6A7G1O18",
  "Q0A0Q1A1Q2A2H3A3Q4A4Q5A5Q6A6Q7A7O08",
  "P3Q0A0Q1A1Q2A2A3Q4A4Q5A5H6A6Q7A7O08",
  "P7Q0A0Q1A1Q2A2Q3A3Q4A4Q5A5Q6A6A7G1O18",
  "Q0A0Q1A1Q2A2H3A3Q4A4Q5A5Q6A6Q7A7O08",
  "P3Q0A0Q1A1Q2A2A3H4A4Q5A5Q6A6Q7A7G1O18",
};

cudaLaunchConfig_t config(int clusters, int size, cudaLaunchAttribute* at) {
  cudaLaunchConfig_t cfg = {};
  cfg.gridDim = dim3(clusters * size); cfg.blockDim = dim3(384); cfg.dynamicSmemBytes = SMEM_BYTES; cfg.stream = cudaStreamPerThread;
  at[0].id = cudaLaunchAttributeClusterDimension; at[0].val.clusterDim.x = size; at[0].val.clusterDim.y = 1; at[0].val.clusterDim.z = 1;
  at[1].id = cudaLaunchAttributeProgrammaticStreamSerialization; at[1].val.programmaticStreamSerializationAllowed = 1;
  cfg.attrs = at; cfg.numAttrs = 1;
  return cfg;
}

void launch(Params& P, int role0, int clusters, int size, bool overlap) {
  cudaLaunchAttribute at[2];
  cudaLaunchConfig_t cfg = config(clusters, size, at);
  cfg.numAttrs = overlap ? 2 : 1;
  for (int i = 0; i < 30; i++) P.first[i] = i < N_TEAM ? P.ops[i][0] : i < N_TEAM + N_HELP ? P.ops[2 * i - N_TEAM][0] : 0;
  P.role0 = role0; P.wide = size > 2;
  cudaLaunchKernelEx(&cfg, fused_kernel, P);
}

const char* const* bench_programs() {
  return kPrograms;
}

}

extern "C" void kernel_launch(void* const* d_in, const int* in_sizes, int n_in, void* d_out, int out_size) {
  (void)in_sizes; (void)n_in; (void)out_size;
  static EncodeFn fn = nullptr;
  static int n_clusters = 0, n_wide = 0;
  if (!fn) {
    cudaDriverEntryPointQueryResult qr;
    void* f = nullptr;
    cudaGetDriverEntryPoint("cuTensorMapEncodeTiled", &f, cudaEnableDefault, &qr);
    fn = (EncodeFn)f;
    cudaFuncSetAttribute(fused_kernel, cudaFuncAttributeMaxDynamicSharedMemorySize, SMEM_BYTES);
    cudaLaunchAttribute at[2];
    cudaLaunchConfig_t cfg = config(N_CL + N_HELP, 2, at);
    if (cudaOccupancyMaxActiveClusters(&n_clusters, fused_kernel, &cfg) != cudaSuccess || n_clusters < 1) n_clusters = 1;
    cfg = config(N_WIDE / WIDE, 2 * WIDE, at);
    if (cudaOccupancyMaxActiveClusters(&n_wide, fused_kernel, &cfg) != cudaSuccess) n_wide = 0;
    (void)cudaGetLastError();
  }
  Params P;
  const CUtensorMapSwizzle S128 = CU_TENSOR_MAP_SWIZZLE_128B, S64 = CU_TENSOR_MAP_SWIZZLE_64B;
  for (int blk = 0; blk < 2; blk++) {
    void* const* in = d_in + 5 * blk;
    { const cuuint64_t d[] = {kD, kB * kSq}, s[] = {kD * 2}; const cuuint32_t b[] = {64, 128};
      encode(fn, &P.x[blk], in[0], 2, d, s, b, S128);
      const cuuint32_t b2[] = {64, 128 / WIDE};
      encode(fn, &P.x[2 + blk], in[0], 2, d, s, b2, S128); }
    { const cuuint64_t d[] = {64, 8, 3, (cuuint64_t)kB * kH * kSk / 8}, s[] = {kDh * 2, 128, 8 * kDh * 2}; const cuuint32_t b[] = {64, 8, 3, 4};
      encode(fn, &P.kv[blk], in[1], 4, d, s, b, S128);
      encode(fn, &P.kv[blk + 2], in[2], 4, d, s, b, S128); }
    { const cuuint64_t d[] = {64, kD, kHD / 64}, s[] = {kHD * 2, 128}; const cuuint32_t b[] = {64, 32, 3};
      encode(fn, &P.wq[blk], in[3], 3, d, s, b, S128); }
    { const cuuint64_t d[] = {32, 2, kHD / 8, 4, kD / 32}, s[] = {kD * 2, 8 * kD * 2, 2 * kD * 2, 64}; const cuuint32_t b[] = {32, 2, 4, 4, 5};
      encode(fn, &P.wo[blk], in[4], 5, d, s, b, S64); }
  }
  { const cuuint64_t d[] = {32, kB * kSq, 2 * kD / 32}, s[] = {2 * kD * 2, 64}; const cuuint32_t b[] = {32, 16, 5};
    encode(fn, &P.out, d_out, 3, d, s, b, S64); }

  P.zero = 0;
  compile_programs(bench_programs(), false, P.ops + N_ROWS);
  if (n_clusters >= N_CL) {
    const bool helpers = n_clusters >= N_CL + N_HELP;
    compile_programs(bench_programs(), helpers, P.ops);
    if (helpers && n_wide >= N_WIDE / WIDE) {
      launch(P, 0, N_WIDE / WIDE, 2 * WIDE, false);
      launch(P, N_WIDE, N_CL + N_HELP - N_WIDE, 2, true);
    } else {
      launch(P, 0, N_CL + (helpers ? N_HELP : 0), 2, false);
    }
  } else {
    for (int phase = 0; phase < 2; phase++) {
      const char* text[N_TEAM];
      for (int t = 0; t < N_TEAM; t++) text[t] = phase ? "O08" : "Q0A0Q1A1Q2A2Q3A3Q4A4Q5A5Q6A6Q7A7";
      compile_programs(text, false, P.ops);
      launch(P, 0, N_CL, 2, false);
    }
  }
}
```

```cpp
#include <cuda_runtime.h>
#include <cuda_bf16.h>
#include <cuda.h>
#include <stdint.h>
#include <stdio.h>

#define KVT 4
#define EAR 3
#define LAG 3
namespace {

constexpr int kB = 8, kSq = 256, kD = 640, kH = 32, kSk = 1024, kDh = 192;
constexpr int kHD = kH * kDh;
constexpr uint32_t RING = 224 * 1024;
constexpr uint32_t SZ_KV = 24576;
constexpr uint32_t SZ_WQ = 24576, SZ_WO = 20480, SZ_A = 16384;
constexpr uint32_t SZ_OUT = 40960;
constexpr uint32_t SZ_PARK = 24576;
constexpr uint32_t SZ_PART = 16384;
constexpr int NBAR = 16;
constexpr int KV_TRANSIT = KVT;
constexpr int EARLY = EAR;
constexpr int S1A = 7;
constexpr uint32_t KV_CH = 64, KV_SBO = 3072;
constexpr int SMEM_BYTES = RING + 512 + 1024;
constexpr int N_TEAM = 16, N_CL = 64, N_HELP = 2, MAX_OPS = 20, MAX_PARK = 4;
constexpr int N_ROWS = N_TEAM + 2 * N_HELP;
#define WIDE_ 4
constexpr int WIDE = WIDE_, N_WIDE = 60;
enum { OP_END = 0, OP_Q = 1, OP_A = 2, OP_O = 3, F_PARK = 1 << 9, F_LD = 1 << 12, F_ST = 1 << 13, F_HELP = 1 << 12 };

struct alignas(64) Params {
  uint32_t first[30], role0, wide;
  CUtensorMap x[4], wq[2], kv[4], wo[2], out;
  uint32_t ops[2 * N_ROWS][MAX_OPS];
  uint32_t zero;
};

__device__ uint4 g_o[N_TEAM * 2 * 96 * 1024];
__device__ uint4 g_part[N_CL * 2 * 5 * 1024];
__device__ unsigned int g_done[N_TEAM * 2 * 8];
__device__ unsigned int g_help[N_CL * 2 * MAX_PARK];
__device__ unsigned int g_meet[2];
__device__ unsigned int g_seen[N_TEAM * 2 * 8];

template <int TB>
__device__ __forceinline__ void wgmma_rs_n64(float (&d)[32], uint32_t a0, uint32_t a1, uint32_t a2, uint32_t a3, uint64_t db, int scale_d) {
  asm volatile("{\n.reg .pred p;\nsetp.ne.b32 p, %37, 0;\n"
    "wgmma.mma_async.sync.aligned.m64n64k16.f32.bf16.bf16 {%0, %1, %2, %3, %4, %5, %6, %7, %8, %9, %10, %11, %12, %13, %14, %15, %16, %17, %18, %19, %20, %21, %22, %23, %24, %25, %26, %27, %28, %29, %30, %31}, {%32, %33, %34, %35}, %36, p, 1, 1, %38;\n}\n"
    : "+f"(d[0]), "+f"(d[1]), "+f"(d[2]), "+f"(d[3]), "+f"(d[4]), "+f"(d[5]), "+f"(d[6]), "+f"(d[7]), "+f"(d[8]), "+f"(d[9]), "+f"(d[10]), "+f"(d[11]), "+f"(d[12]), "+f"(d[13]), "+f"(d[14]), "+f"(d[15]), "+f"(d[16]), "+f"(d[17]), "+f"(d[18]), "+f"(d[19]), "+f"(d[20]), "+f"(d[21]), "+f"(d[22]), "+f"(d[23]), "+f"(d[24]), "+f"(d[25]), "+f"(d[26]), "+f"(d[27]), "+f"(d[28]), "+f"(d[29]), "+f"(d[30]), "+f"(d[31])
    : "r"(a0), "r"(a1), "r"(a2), "r"(a3), "l"(db), "r"(scale_d), "n"(TB));
}
template <int TB, int TA = 0>
__device__ __forceinline__ void wgmma_ss_n160(float (&d)[80], uint64_t da, uint64_t db, int scale_d) {
  asm volatile("{\n.reg .pred p;\nsetp.ne.b32 p, %82, 0;\n"
    "wgmma.mma_async.sync.aligned.m64n160k16.f32.bf16.bf16 {%0, %1, %2, %3, %4, %5, %6, %7, %8, %9, %10, %11, %12, %13, %14, %15, %16, %17, %18, %19, %20, %21, %22, %23, %24, %25, %26, %27, %28, %29, %30, %31, %32, %33, %34, %35, %36, %37, %38, %39, %40, %41, %42, %43, %44, %45, %46, %47, %48, %49, %50, %51, %52, %53, %54, %55, %56, %57, %58, %59, %60, %61, %62, %63, %64, %65, %66, %67, %68, %69, %70, %71, %72, %73, %74, %75, %76, %77, %78, %79}, %80, %81, p, 1, 1, %83, %84;\n}\n"
    : "+f"(d[0]), "+f"(d[1]), "+f"(d[2]), "+f"(d[3]), "+f"(d[4]), "+f"(d[5]), "+f"(d[6]), "+f"(d[7]), "+f"(d[8]), "+f"(d[9]), "+f"(d[10]), "+f"(d[11]), "+f"(d[12]), "+f"(d[13]), "+f"(d[14]), "+f"(d[15]), "+f"(d[16]), "+f"(d[17]), "+f"(d[18]), "+f"(d[19]), "+f"(d[20]), "+f"(d[21]), "+f"(d[22]), "+f"(d[23]), "+f"(d[24]), "+f"(d[25]), "+f"(d[26]), "+f"(d[27]), "+f"(d[28]), "+f"(d[29]), "+f"(d[30]), "+f"(d[31]), "+f"(d[32]), "+f"(d[33]), "+f"(d[34]), "+f"(d[35]), "+f"(d[36]), "+f"(d[37]), "+f"(d[38]), "+f"(d[39]), "+f"(d[40]), "+f"(d[41]), "+f"(d[42]), "+f"(d[43]), "+f"(d[44]), "+f"(d[45]), "+f"(d[46]), "+f"(d[47]), "+f"(d[48]), "+f"(d[49]), "+f"(d[50]), "+f"(d[51]), "+f"(d[52]), "+f"(d[53]), "+f"(d[54]), "+f"(d[55]), "+f"(d[56]), "+f"(d[57]), "+f"(d[58]), "+f"(d[59]), "+f"(d[60]), "+f"(d[61]), "+f"(d[62]), "+f"(d[63]), "+f"(d[64]), "+f"(d[65]), "+f"(d[66]), "+f"(d[67]), "+f"(d[68]), "+f"(d[69]), "+f"(d[70]), "+f"(d[71]), "+f"(d[72]), "+f"(d[73]), "+f"(d[74]), "+f"(d[75]), "+f"(d[76]), "+f"(d[77]), "+f"(d[78]), "+f"(d[79])
    : "l"(da), "l"(db), "r"(scale_d), "n"(TA), "n"(TB));
}
template <int TB, int TA = 0>
__device__ __forceinline__ void wgmma_ss_n192(float (&d)[96], uint64_t da, uint64_t db, int scale_d) {
  asm volatile("{\n.reg .pred p;\nsetp.ne.b32 p, %98, 0;\n"
    "wgmma.mma_async.sync.aligned.m64n192k16.f32.bf16.bf16 {%0, %1, %2, %3, %4, %5, %6, %7, %8, %9, %10, %11, %12, %13, %14, %15, %16, %17, %18, %19, %20, %21, %22, %23, %24, %25, %26, %27, %28, %29, %30, %31, %32, %33, %34, %35, %36, %37, %38, %39, %40, %41, %42, %43, %44, %45, %46, %47, %48, %49, %50, %51, %52, %53, %54, %55, %56, %57, %58, %59, %60, %61, %62, %63, %64, %65, %66, %67, %68, %69, %70, %71, %72, %73, %74, %75, %76, %77, %78, %79, %80, %81, %82, %83, %84, %85, %86, %87, %88, %89, %90, %91, %92, %93, %94, %95}, %96, %97, p, 1, 1, %99, %100;\n}\n"
    : "+f"(d[0]), "+f"(d[1]), "+f"(d[2]), "+f"(d[3]), "+f"(d[4]), "+f"(d[5]), "+f"(d[6]), "+f"(d[7]), "+f"(d[8]), "+f"(d[9]), "+f"(d[10]), "+f"(d[11]), "+f"(d[12]), "+f"(d[13]), "+f"(d[14]), "+f"(d[15]), "+f"(d[16]), "+f"(d[17]), "+f"(d[18]), "+f"(d[19]), "+f"(d[20]), "+f"(d[21]), "+f"(d[22]), "+f"(d[23]), "+f"(d[24]), "+f"(d[25]), "+f"(d[26]), "+f"(d[27]), "+f"(d[28]), "+f"(d[29]), "+f"(d[30]), "+f"(d[31]), "+f"(d[32]), "+f"(d[33]), "+f"(d[34]), "+f"(d[35]), "+f"(d[36]), "+f"(d[37]), "+f"(d[38]), "+f"(d[39]), "+f"(d[40]), "+f"(d[41]), "+f"(d[42]), "+f"(d[43]), "+f"(d[44]), "+f"(d[45]), "+f"(d[46]), "+f"(d[47]), "+f"(d[48]), "+f"(d[49]), "+f"(d[50]), "+f"(d[51]), "+f"(d[52]), "+f"(d[53]), "+f"(d[54]), "+f"(d[55]), "+f"(d[56]), "+f"(d[57]), "+f"(d[58]), "+f"(d[59]), "+f"(d[60]), "+f"(d[61]), "+f"(d[62]), "+f"(d[63]), "+f"(d[64]), "+f"(d[65]), "+f"(d[66]), "+f"(d[67]), "+f"(d[68]), "+f"(d[69]), "+f"(d[70]), "+f"(d[71]), "+f"(d[72]), "+f"(d[73]), "+f"(d[74]), "+f"(d[75]), "+f"(d[76]), "+f"(d[77]), "+f"(d[78]), "+f"(d[79]), "+f"(d[80]), "+f"(d[81]), "+f"(d[82]), "+f"(d[83]), "+f"(d[84]), "+f"(d[85]), "+f"(d[86]), "+f"(d[87]), "+f"(d[88]), "+f"(d[89]), "+f"(d[90]), "+f"(d[91]), "+f"(d[92]), "+f"(d[93]), "+f"(d[94]), "+f"(d[95])
    : "l"(da), "l"(db), "r"(scale_d), "n"(TA), "n"(TB));
}
template <int TB>
__device__ __forceinline__ void wgmma_rs_n192(float (&d)[96], uint32_t a0, uint32_t a1, uint32_t a2, uint32_t a3, uint64_t db, int scale_d) {
  asm volatile("{\n.reg .pred p;\nsetp.ne.b32 p, %101, 0;\n"
    "wgmma.mma_async.sync.aligned.m64n192k16.f32.bf16.bf16 {%0, %1, %2, %3, %4, %5, %6, %7, %8, %9, %10, %11, %12, %13, %14, %15, %16, %17, %18, %19, %20, %21, %22, %23, %24, %25, %26, %27, %28, %29, %30, %31, %32, %33, %34, %35, %36, %37, %38, %39, %40, %41, %42, %43, %44, %45, %46, %47, %48, %49, %50, %51, %52, %53, %54, %55, %56, %57, %58, %59, %60, %61, %62, %63, %64, %65, %66, %67, %68, %69, %70, %71, %72, %73, %74, %75, %76, %77, %78, %79, %80, %81, %82, %83, %84, %85, %86, %87, %88, %89, %90, %91, %92, %93, %94, %95}, {%96, %97, %98, %99}, %100, p, 1, 1, %102;\n}\n"
    : "+f"(d[0]), "+f"(d[1]), "+f"(d[2]), "+f"(d[3]), "+f"(d[4]), "+f"(d[5]), "+f"(d[6]), "+f"(d[7]), "+f"(d[8]), "+f"(d[9]), "+f"(d[10]), "+f"(d[11]), "+f"(d[12]), "+f"(d[13]), "+f"(d[14]), "+f"(d[15]), "+f"(d[16]), "+f"(d[17]), "+f"(d[18]), "+f"(d[19]), "+f"(d[20]), "+f"(d[21]), "+f"(d[22]), "+f"(d[23]), "+f"(d[24]), "+f"(d[25]), "+f"(d[26]), "+f"(d[27]), "+f"(d[28]), "+f"(d[29]), "+f"(d[30]), "+f"(d[31]), "+f"(d[32]), "+f"(d[33]), "+f"(d[34]), "+f"(d[35]), "+f"(d[36]), "+f"(d[37]), "+f"(d[38]), "+f"(d[39]), "+f"(d[40]), "+f"(d[41]), "+f"(d[42]), "+f"(d[43]), "+f"(d[44]), "+f"(d[45]), "+f"(d[46]), "+f"(d[47]), "+f"(d[48]), "+f"(d[49]), "+f"(d[50]), "+f"(d[51]), "+f"(d[52]), "+f"(d[53]), "+f"(d[54]), "+f"(d[55]), "+f"(d[56]), "+f"(d[57]), "+f"(d[58]), "+f"(d[59]), "+f"(d[60]), "+f"(d[61]), "+f"(d[62]), "+f"(d[63]), "+f"(d[64]), "+f"(d[65]), "+f"(d[66]), "+f"(d[67]), "+f"(d[68]), "+f"(d[69]), "+f"(d[70]), "+f"(d[71]), "+f"(d[72]), "+f"(d[73]), "+f"(d[74]), "+f"(d[75]), "+f"(d[76]), "+f"(d[77]), "+f"(d[78]), "+f"(d[79]), "+f"(d[80]), "+f"(d[81]), "+f"(d[82]), "+f"(d[83]), "+f"(d[84]), "+f"(d[85]), "+f"(d[86]), "+f"(d[87]), "+f"(d[88]), "+f"(d[89]), "+f"(d[90]), "+f"(d[91]), "+f"(d[92]), "+f"(d[93]), "+f"(d[94]), "+f"(d[95])
    : "r"(a0), "r"(a1), "r"(a2), "r"(a3), "l"(db), "r"(scale_d), "n"(TB));
}

__device__ __forceinline__ uint32_t smem_u32(const void* p) { return (uint32_t)__cvta_generic_to_shared(p); }
__device__ __forceinline__ void wg_fence() { asm volatile("wgmma.fence.sync.aligned;" ::: "memory"); }
__device__ __forceinline__ void wg_commit() { asm volatile("wgmma.commit_group.sync.aligned;" ::: "memory"); }
template <int N> __device__ __forceinline__ void wg_wait() { asm volatile("wgmma.wait_group.sync.aligned %0;" ::"n"(N) : "memory"); }
__device__ __forceinline__ void sched_fence(int& keep, uint32_t zero) {
  asm volatile("{\n.reg .u32 c;\nmov.u32 c, %%clock;\nand.b32 c, c, %1;\nxor.b32 %0, %0, c;\n}\n" : "+r"(keep) : "r"(zero) : "memory");
}
template <int N> __device__ __forceinline__ void fence_regs(float (&r)[N]) {
#pragma unroll
  for (int i = 0; i < N; i++) asm volatile("" : "+f"(r[i])::"memory");
}
template <int N> __device__ __forceinline__ void fence_regs(uint32_t (&r)[N]) {
#pragma unroll
  for (int i = 0; i < N; i++) asm volatile("" : "+r"(r[i])::"memory");
}
__device__ __forceinline__ uint64_t mk_desc(uint32_t a16, uint32_t lbo, uint32_t sbo, uint32_t swz, uint32_t off = 0) {
  uint64_t d;
  asm("mov.b64 %0, {%1, %2};" : "=l"(d) : "r"(a16), "r"((sbo >> 4) | (swz << 30)));
  return d + (off + ((lbo >> 4) << 16));
}
__device__ __forceinline__ void mbar_init(uint32_t bar, uint32_t cnt) {
  asm volatile("mbarrier.init.shared::cta.b64 [%0], %1;" ::"r"(bar), "r"(cnt) : "memory");
}
__device__ __forceinline__ void mbar_expect(uint32_t bar, uint32_t tx) {
  asm volatile("mbarrier.arrive.expect_tx.shared::cta.b64 _, [%0], %1;" ::"r"(bar), "r"(tx) : "memory");
}
__device__ __forceinline__ bool mbar_test(uint32_t bar, uint32_t ph) {
  uint32_t ok;
  asm volatile("{\n.reg .pred p;\nmbarrier.test_wait.parity.shared::cta.b64 p, [%1], %2;\nselp.u32 %0, 1, 0, p;\n}\n"
               : "=r"(ok) : "r"(bar), "r"(ph) : "memory");
  return ok;
}
__device__ __forceinline__ void mbar_wait(uint32_t bar, uint32_t ph) {
  asm volatile("{\n.reg .pred p;\n.reg .u32 n;\nmov.u32 n, 0;\n"
               "LOOP:\nadd.u32 n, n, 1;\nmbarrier.try_wait.parity.shared::cta.b64 p, [%0], %1;\n@p bra DONE;\n"
               "setp.lt.u32 p, n, 0x1000000;\n@p bra LOOP;\ntrap;\n"
               "DONE:\n}\n" ::"r"(bar), "r"(ph) : "memory");
}
__device__ __forceinline__ void mbar_wait_math(uint32_t bar, uint32_t ph) {
  asm volatile("{\n.reg .pred p;\nLOOP:\nmbarrier.try_wait.parity.shared::cta.b64 p, [%0], %1;\n@!p bra LOOP;\n}\n" ::"r"(bar), "r"(ph) : "memory");
}
__device__ __forceinline__ void mbar_wait_long(uint32_t bar, uint32_t ph) {
  asm volatile("{\n.reg .pred p;\n.reg .u32 n;\nmov.u32 n, 0;\n"
               "LOOP:\nmbarrier.try_wait.parity.shared::cta.b64 p, [%0], %1, %2;\n@p bra DONE;\n"
               "add.u32 n, n, 1;\nsetp.lt.u32 p, n, 0x40000;\n@p bra LOOP;\ntrap;\n"
               "DONE:\n}\n" ::"r"(bar), "r"(ph), "r"(20000) : "memory");
}
__device__ __forceinline__ void mbar_arrive_cluster_if(bool on, uint32_t addr) {
  asm volatile("{\n.reg .pred p;\nsetp.ne.b32 p, %1, 0;\n@p mbarrier.arrive.shared::cluster.b64 _, [%0];\n}\n" ::"r"(addr), "r"((int)on) : "memory");
}
__device__ __forceinline__ void mbar_arrive_if(bool on, uint32_t addr) {
  asm volatile("{\n.reg .pred p;\nsetp.ne.b32 p, %1, 0;\n@p mbarrier.arrive.shared::cta.b64 _, [%0];\n}\n" ::"r"(addr), "r"((int)on) : "memory");
}
__device__ __forceinline__ void tma2d(uint32_t dst, const CUtensorMap* m, uint32_t bar, int c0, int c1) {
  asm volatile("cp.async.bulk.tensor.2d.shared::cluster.global.mbarrier::complete_tx::bytes [%0], [%1, {%3, %4}], [%2];"
               ::"r"(dst), "l"(m), "r"(bar), "r"(c0), "r"(c1) : "memory");
}
__device__ __forceinline__ void tma2d_mc(uint32_t dst, const CUtensorMap* m, uint32_t bar, int c0, int c1, uint16_t mask) {
  asm volatile("cp.async.bulk.tensor.2d.shared::cluster.global.mbarrier::complete_tx::bytes.multicast::cluster [%0], [%1, {%3, %4}], [%2], %5;"
               ::"r"(dst), "l"(m), "r"(bar), "r"(c0), "r"(c1), "h"(mask) : "memory");
}
__device__ __forceinline__ void bulk_load_mc(uint32_t dst, const void* src, uint32_t bytes, uint32_t bar, uint64_t pol, uint16_t mask) {
  asm volatile("cp.async.bulk.shared::cluster.global.mbarrier::complete_tx::bytes.multicast::cluster.L2::cache_hint [%0], [%1], %2, [%3], %5, %4;"
               ::"r"(dst), "l"(src), "r"(bytes), "r"(bar), "l"(pol), "h"(mask) : "memory");
}
__device__ __forceinline__ void tma3d(uint32_t dst, const CUtensorMap* m, uint32_t bar, int c0, int c1, int c2) {
  asm volatile("cp.async.bulk.tensor.3d.shared::cluster.global.mbarrier::complete_tx::bytes [%0], [%1, {%3, %4, %5}], [%2];"
               ::"r"(dst), "l"(m), "r"(bar), "r"(c0), "r"(c1), "r"(c2) : "memory");
}
__device__ __forceinline__ void tma3d_mc(uint32_t dst, const CUtensorMap* m, uint32_t bar, int c0, int c1, int c2, uint16_t mask) {
  asm volatile("cp.async.bulk.tensor.3d.shared::cluster.global.mbarrier::complete_tx::bytes.multicast::cluster"
               " [%0], [%1, {%3, %4, %5}], [%2], %6;"
               ::"r"(dst), "l"(m), "r"(bar), "r"(c0), "r"(c1), "r"(c2), "h"(mask) : "memory");
}
__device__ __forceinline__ void tma3d_store(const CUtensorMap* m, uint32_t src, int c0, int c1, int c2) {
  asm volatile("cp.async.bulk.tensor.3d.global.shared::cta.bulk_group [%0, {%2, %3, %4}], [%1];"
               ::"l"(m), "r"(src), "r"(c0), "r"(c1), "r"(c2) : "memory");
}
__device__ __forceinline__ void bar_sync(int id, int n) { asm volatile("bar.sync %0, %1;" ::"r"(id), "r"(n) : "memory"); }
__device__ __forceinline__ uint32_t pack_bf16(float lo, float hi) {
  uint32_t r;
  asm("cvt.rn.bf16x2.f32 %0, %1, %2;" : "=r"(r) : "f"(hi), "f"(lo));
  return r;
}
__device__ __forceinline__ float ex2(float x) {
  float y;
  asm("ex2.approx.ftz.f32 %0, %1;" : "=f"(y) : "f"(x));
  return y;
}
__device__ __forceinline__ float fadd(float a, float b) {
  float y;
  asm("add.f32 %0, %1, %2;" : "=f"(y) : "f"(a), "f"(b));
  return y;
}
__device__ __forceinline__ float rcp(float x) {
  float y;
  asm("rcp.approx.ftz.f32 %0, %1;" : "=f"(y) : "f"(x));
  return y;
}
__device__ __forceinline__ void stsm4(uint32_t addr, uint32_t a, uint32_t b, uint32_t c, uint32_t d) {
  asm volatile("stmatrix.sync.aligned.m8n8.x4.shared.b16 [%0], {%1, %2, %3, %4};" ::"r"(addr), "r"(a), "r"(b), "r"(c), "r"(d) : "memory");
}

__device__ __forceinline__ void tma4d_mc_hint(uint32_t dst, const CUtensorMap* m, uint32_t bar, int c3, uint64_t pol, uint16_t mask) {
  asm volatile("cp.async.bulk.tensor.4d.shared::cluster.global.mbarrier::complete_tx::bytes.multicast::cluster.L2::cache_hint"
               " [%0], [%1, {%3, %3, %3, %4}], [%2], %5, %6;"
               ::"r"(dst), "l"(m), "r"(bar), "r"(0), "r"(c3), "h"(mask), "l"(pol) : "memory");
}
__device__ __forceinline__ void tma5d_mc(uint32_t dst, const CUtensorMap* m, uint32_t bar, int c2, int c4, uint16_t mask) {
  asm volatile("cp.async.bulk.tensor.5d.shared::cluster.global.mbarrier::complete_tx::bytes.multicast::cluster"
               " [%0], [%1, {%3, %3, %4, %3, %5}], [%2], %6;"
               ::"r"(dst), "l"(m), "r"(bar), "r"(0), "r"(c2), "r"(c4), "h"(mask) : "memory");
}
__device__ __forceinline__ void bulk_load_hint(uint32_t dst, const void* src, uint32_t bytes, uint32_t bar, uint64_t pol) {
  asm volatile("cp.async.bulk.shared::cluster.global.mbarrier::complete_tx::bytes.L2::cache_hint [%0], [%1], %2, [%3], %4;"
               ::"r"(dst), "l"(src), "r"(bytes), "r"(bar), "l"(pol) : "memory");
}
__device__ __forceinline__ void stg2_if(bool on, void* p, uint32_t a, uint32_t b, uint32_t c, uint32_t d, uint32_t e, uint32_t f,
                                        uint32_t g, uint32_t h, uint64_t pol) {
  asm volatile("{\n.reg .pred p;\nsetp.ne.b32 p, %10, 0;\n"
               "@p st.global.L2::cache_hint.v4.b32 [%0], {%1, %2, %3, %4}, %9;\n"
               "@p st.global.L2::cache_hint.v4.b32 [%0 + 512], {%5, %6, %7, %8}, %9;\n}\n"
               ::"l"(p), "r"(a), "r"(b), "r"(c), "r"(d), "r"(e), "r"(f), "r"(g), "r"(h), "l"(pol), "r"((int)on) : "memory");
}
__device__ __forceinline__ uint64_t evict_first() {
  uint64_t p;
  asm("createpolicy.fractional.L2::evict_first.b64 %0, 1.0;" : "=l"(p));
  return p;
}
__device__ __forceinline__ bool elect() {
  uint32_t ok;
  asm volatile("{\n.reg .pred p;\nelect.sync _|p, 0xffffffff;\nselp.u32 %0, 1, 0, p;\n}\n" : "=r"(ok));
  return ok;
}
__device__ __forceinline__ void mbar_arrive(uint32_t bar) {
  asm volatile("mbarrier.arrive.shared::cta.b64 _, [%0];" ::"r"(bar) : "memory");
}
template <int OFF> __device__ __forceinline__ void lds2_if(bool on, uint32_t p, uint32_t* r) {
  asm volatile("{\n.reg .pred p;\nsetp.ne.b32 p, %9, 0;\n@p ld.shared.v4.b32 {%0, %1, %2, %3}, [%8 + %10];\n"
               "@p ld.shared.v4.b32 {%4, %5, %6, %7}, [%8 + %11];\n}\n"
               : "+r"(r[0]), "+r"(r[1]), "+r"(r[2]), "+r"(r[3]), "+r"(r[4]), "+r"(r[5]), "+r"(r[6]), "+r"(r[7])
               : "r"(p), "r"((int)on), "n"(OFF), "n"(OFF + 512) : "memory");
}
__device__ __forceinline__ void lds128(uint32_t p, uint32_t& a, uint32_t& b, uint32_t& c, uint32_t& d) {
  asm volatile("ld.shared.v4.b32 {%0, %1, %2, %3}, [%4];" : "=r"(a), "=r"(b), "=r"(c), "=r"(d) : "r"(p) : "memory");
}
__device__ __forceinline__ void wait_count(const unsigned int* p, uint32_t target) {
  asm volatile("{\n.reg .pred p;\n.reg .u32 n, v;\nmov.u32 n, 0;\n"
               "LOOP:\nld.acquire.gpu.global.u32 v, [%0];\nsetp.ge.u32 p, v, %1;\n@p bra DONE;\n"
               "nanosleep.u32 %2;\nadd.u32 n, n, 1;\nsetp.lt.u32 p, n, 0x400000;\n@p bra LOOP;\ntrap;\n"
               "DONE:\n}\n" ::"l"(p), "r"(target), "n"(300) : "memory");
}

__device__ __forceinline__ int o_wave(int a, int b, int i) {
  const int p = min(LAG, b - a - 1);
  return i < p ? b - 2 - i : i == p ? b - 1 : b - 1 - i;
}

struct Cursor {
  uint32_t n;
  __device__ __forceinline__ uint32_t off() const { return n & (8 * NBAR - 8); }
  __device__ __forceinline__ uint32_t ph() const { return (n / (8 * NBAR)) & 1; }
  __device__ __forceinline__ void next() { n += 8; }
};

constexpr float kScaleLog2 = 0.07216878364870322f * 1.4426950408889634f;
constexpr float kSumLimit = 1048576.0f;
constexpr float kMaxLag = 8.0f;

__global__ void __launch_bounds__(384, 1)
fused_kernel(const __grid_constant__ Params P) {
  extern __shared__ uint8_t smem_raw[];
  const uint32_t sbase = (smem_u32(smem_raw) + 1023) & ~1023u;
  const uint32_t full0 = sbase + RING, empty0 = full0 + 8 * NBAR, odone = empty0 + 8 * NBAR, oready0 = odone + 8;
  const uint32_t fenced = oready0 + 64, hready0 = fenced + 8, met = hready0 + 8 * MAX_PARK;
  const uint32_t rank = blockIdx.x & 1;
  const int role = (blockIdx.x >> 1) + P.role0;
  const bool wide = P.wide;
  const uint32_t sub = wide ? (blockIdx.x >> 1) & (WIDE - 1) : 0;
  asm volatile("griddepcontrol.launch_dependents;");
  const bool helper = role >= N_CL;
  const int team = helper ? 0 : role >> 2, nt = role & 3, blk = team >> 3;
  const uint32_t* prog = P.ops[helper ? N_TEAM + 2 * (role - N_CL) : team];
  auto q_role = [&](uint32_t op) { return helper ? (int)(((op >> 3) & 60) | ((op >> 12) & 3)) : role; };
  auto o_role = [&](uint32_t op) { return helper ? (int)(((op >> 26) & 56) | ((op >> 9) & 7)) : role; };
  auto alone = [&]() {
    uint32_t v;
    mbar_wait(met, 0);
    asm volatile("ld.shared.u32 %0, [%1];" : "=r"(v) : "r"(met + 8) : "memory");
    return v;
  };
  const int wid = __shfl_sync(0xffffffffu, (int)(threadIdx.x >> 5), 0);
  const int wg = wid >> 2;

  const uint32_t op0 = P.first[helper ? N_TEAM + role - N_CL : team];
  if (__builtin_expect(wid == 8, 1)) {
    if (elect()) {
#pragma unroll
      for (int k = 0; k < EARLY; k++) mbar_init(full0 + 8 * k, 1);
      asm volatile("fence.mbarrier_init.release.cluster;" ::: "memory");
      if ((op0 & 3) == OP_Q) {
        const int qr = q_role(op0);
#pragma unroll
        for (int k = 0; k < EARLY; k++) {
          mbar_expect(full0 + 8 * k, SZ_WQ + SZ_A);
          tma2d(sbase + k * (SZ_WQ + SZ_A) + SZ_WQ, &P.x[qr >> 5], full0 + 8 * k, 64 * k, ((qr >> 2) & 7) * kSq + rank * 128);
          tma3d(sbase + k * (SZ_WQ + SZ_A), &P.wq[qr >> 5], full0 + 8 * k, 0, 64 * k, 3 * (4 * ((op0 >> 2) & 7) + (qr & 3)));
          tma3d(sbase + k * (SZ_WQ + SZ_A) + SZ_WQ / 2, &P.wq[qr >> 5], full0 + 8 * k, 0, 64 * k + 32, 3 * (4 * ((op0 >> 2) & 7) + (qr & 3)));
        }
      }
      asm volatile("prefetch.tensormap [%0];" ::"l"(&P.kv[blk]) : "memory");
      asm volatile("prefetch.tensormap [%0];" ::"l"(&P.kv[blk + 2]) : "memory");
    }
  } else if (threadIdx.x == 0) {
#pragma unroll
    for (int i = EARLY; i < 2 * NBAR + 11 + MAX_PARK; i++) mbar_init(full0 + 8 * i, i >= NBAR && i <= 2 * NBAR ? (wide ? 8 * WIDE + 8 : 16) : 1);
    asm volatile("fence.mbarrier_init.release.cluster;" ::: "memory");
  }
  __syncwarp();
  asm volatile("barrier.cluster.arrive.relaxed.aligned;\nbarrier.cluster.wait.aligned;" ::: "memory");

  if (wg == 2) {
    asm volatile("setmaxnreg.dec.sync.aligned.u32 24;");
    if (wid == 8) {
      Cursor tail{0u - 8}, head{0};
      int sh = 0;
      uint32_t cur = 0, used = 0;
      uint64_t fifo = 0;
      uint32_t oready = oready0;
      const uint64_t pol = evict_first();
      const uint16_t pair = 3 << (2 * sub), rows = (wide ? 0x55 >> (8 - 2 * WIDE) : 1) << rank;
      const uint32_t piece = wide ? SZ_A / WIDE : SZ_A;
      struct Load { uint32_t dst, bar, wbar, wph; int c0; const void* ptr; bool wait; };
      auto reserve = [&](uint32_t bytes, bool last, uint32_t off, int c0, const void* ptr) {
        uint32_t fp = bytes >> 12;
        if (cur + fp > (RING >> 12)) { fp += (RING >> 12) - cur; cur = 0; }
        used += fp;
        bool wait = false;
        while (used > (RING >> 12)) {
          wait = true;
          tail.next();
          used -= (uint32_t)fifo & 31;
          fifo >>= 5;
          sh -= 5;
        }
        fifo += (uint64_t)fp << sh;
        Load l{sbase + (cur << 12) + off, full0 + head.off(), empty0 + tail.off(), tail.ph(), c0, ptr, wait};
        cur += bytes >> 12;
        sh += last ? 5 : 0;
        head.n += last ? 8 : 0;
        asm volatile("" : "+r"(l.dst), "+r"(l.bar), "+r"(l.c0), "+l"(l.ptr), "+r"(l.wbar), "+r"(l.wph));
        return l;
      };
      auto vacated = [&](const Load& l) { if (l.wait) mbar_wait(l.wbar, l.wph); };
      auto written = [&](uint32_t flag) {
        mbar_wait(flag, 0);
        asm volatile("fence.proxy.async.global;" ::: "memory");
      };
      for (int pc = 0;; pc++) {
        if (pc == 1) prog += __shfl_sync(0xffffffffu, alone(), 0);
        const uint32_t op = prog[pc];
        const int type = op & 3, a = (op >> 2) & 7;
        if (type == OP_END) break;
        if (type == OP_Q) {
          const int qr = q_role(op);
          const CUtensorMap *mw = &P.wq[qr >> 5], *mx = &P.x[(qr >> 5) + (wide ? 2 : 0)];
          asm volatile("" : "+l"(mw), "+l"(mx));
          auto res_w = [&](int k) { return reserve(SZ_WQ, false, rank * (SZ_WQ / 2), 64 * k + 32 * rank, mw); };
          auto load_w = [&](const Load& w, int k) {
            vacated(w);
            if ((pc > 0 || k >= EARLY) && elect()) tma3d_mc(w.dst, (const CUtensorMap*)w.ptr, w.bar, 0, w.c0, 3 * (4 * a + (qr & 3)), pair);
          };
          auto load_x = [&](const Load& x, int k) {
            vacated(x);
            if ((pc > 0 || k >= EARLY) && elect()) {
              tma2d_mc(x.dst, (const CUtensorMap*)x.ptr, x.bar, x.c0, ((qr >> 2) & 7) * kSq + rank * 128 + sub * (128 / WIDE), rows);
              mbar_expect(x.bar, SZ_WQ + SZ_A);
            }
          };
#pragma unroll 1
          for (int k = 0; k < 10; k++) {
            load_w(res_w(k), k);
            load_x(reserve(SZ_A, true, sub * (SZ_A / WIDE), 64 * k, mx), k);
          }
        } else if (type == OP_A) {
          const uint32_t nop = prog[pc + 1];
          const int row8 = ((team & 7) * kH + nt) * (kSk / 8) + 4 * rank, wave8 = 4 * (kSk / 8);
          auto transit = [&]() {
            const Cursor c{head.n - 8 * (KV_TRANSIT + 1)};
            mbar_wait(full0 + c.off(), c.ph());
          };
          const char* map = (const char*)&P.kv[blk];
          asm volatile("" : "+l"(map));
          int t = (op & F_PARK) ? 1 : 0, c0 = row8 + a * wave8 + 8 * t, isv = 0;
#pragma unroll 1
          for (; t < 31; t++) {
            const Load l = reserve(SZ_KV, true, rank * (SZ_KV / 2), c0, map + isv);
            vacated(l);
            if (t >= KV_TRANSIT) transit();
            if (elect()) {
              tma4d_mc_hint(l.dst, (const CUtensorMap*)l.ptr, l.bar, l.c0, pol, pair);
              mbar_expect(l.bar, SZ_KV);
            }
            isv = (t & 1) << 8;
            c0 += isv ? -8 : t ? 16 : 8;
          }
          const int next = (nop >> 2) & 7;
          if ((nop & 3) == OP_A) written((nop & F_HELP) ? hready0 + 8 * ((nop >> 10) & 3) : fenced);
#pragma unroll 1
          for (int i = (nop & 3) == OP_A ? 0 : 3; i < 4; i++) {
            const Load l = reserve(SZ_KV, true, i < 2 ? 0 : rank * (SZ_KV / 2), i == 3 ? c0 - 8 : row8 + next * wave8,
                                   i < 2 ? (const char*)&g_o[((team * 2 + rank) * 96 + 3 * (4 * next + nt)) * 1024 + i * (SZ_PARK / 16)] : map + ((i & 1) << 8));
            vacated(l);
            if (i < 2) {
              if (elect()) bulk_load_hint(l.dst, l.ptr, SZ_PARK, l.bar, pol);
              __syncwarp();
            } else {
              transit();
              if (elect()) tma4d_mc_hint(l.dst, (const CUtensorMap*)l.ptr, l.bar, l.c0, pol, pair);
              __syncwarp();
            }
            if (elect()) mbar_expect(l.bar, SZ_KV);
          }
        } else {
          const int b = (op >> 5) & 15, ro = o_role(op);
          const CUtensorMap* mw = &P.wo[ro >> 5];
          const uint4* so = &g_o[((ro >> 2) * 2 + rank) * 96 * 1024 + sub * (1024 / WIDE)];
          asm volatile("" : "+l"(mw), "+l"(so));
#pragma unroll 1
          for (int j = 0; j < b - a; j++) {
            const int w = o_wave(a, b, j);
            written(oready);
            oready += 8;
#pragma unroll 1
            for (int k = 12 * w; k < 12 * w + 12; k++) {
              const Load o = reserve(SZ_A, false, sub * (SZ_A / WIDE), 0, so + k * 1024);
              vacated(o);
              if (elect()) bulk_load_mc(o.dst, o.ptr, piece, o.bar, pol, rows);
              const Load w = reserve(SZ_WO, true, rank * (SZ_WO / 2), 8 * k + 4 * rank, mw);
              vacated(w);
              if (elect()) {
                tma5d_mc(w.dst, (const CUtensorMap*)w.ptr, w.bar, w.c0, 5 * (ro & 3), pair);
                mbar_expect(w.bar, SZ_WO + SZ_A);
              }
            }
          }
          if ((op & F_LD) && (op & F_PARK)) written(hready0 + 8 * (MAX_PARK - 1));
#pragma unroll 1
          for (int i = (op & F_LD) ? 0 : 5; i < ((op & F_ST) ? 5 : 6); i++) {
            const Load l = reserve(i < 5 ? SZ_PART : SZ_OUT, i < 5, 0, 0, &g_part[(role * 2 + rank) * 5120 + i * (SZ_PART / 16)]);
            vacated(l);
            if (i < 5 && elect()) bulk_load_hint(l.dst, l.ptr, SZ_PART, l.bar, pol);
            if (elect()) mbar_expect(l.bar, i < 5 ? SZ_PART : 0);
          }
        }
      }
#pragma unroll 1
      for (Cursor c{head.n - 8 * NBAR}; c.n != head.n; c.next()) mbar_wait(empty0 + c.off(), c.ph());
    } else if (threadIdx.x == 288) {
      uint32_t ph = 0;
      bool first = true;
      prog += alone();
      for (int pc = 0;; pc++) {
        const uint32_t op = prog[pc];
        if ((op & 3) == OP_END) break;
        if ((op & 3) != OP_A && !helper) continue;
        mbar_wait_long(odone, ph);
        ph ^= 1;
        unsigned int* flag = !helper ? &g_done[(team * 2 + rank) * 8 + ((op >> 2) & 7)]
                             : (op & 3) == OP_Q ? &g_help[(q_role(op) * 2 + rank) * MAX_PARK + ((op >> 10) & 3)]
                                                : &g_help[(o_role(op) * 2 + rank) * MAX_PARK + MAX_PARK - 1];
        asm volatile("red.release.gpu.global.add.u32 [%0], 1;" ::"l"(flag) : "memory");
        if (first) mbar_arrive(fenced);
        first = false;
      }
    } else if (threadIdx.x == 320) {
      uint32_t meet = 1;
      if (wide || P.role0) {
        meet = 0;
        for (int n = 0; wide && !meet && n < 300; n++) {
          __nanosleep(100);
          asm volatile("ld.relaxed.gpu.global.u32 %0, [%1];" : "=r"(meet) : "l"(&g_meet[0]) : "memory");
        }
        if (!meet && !(meet = atomicCAS(&g_meet[0], 0u, wide ? 2u : 1u))) meet = wide ? 2 : 1;
        if (atomicAdd(&g_meet[1], 1u) == 2 * (N_CL + N_HELP) - 1) { g_meet[0] = 0; g_meet[1] = 0; }
      }
      prog += (meet - 1) * (N_ROWS * MAX_OPS);
      asm volatile("st.shared.u32 [%0], %1;" ::"r"(met + 8), "r"((meet - 1) * (N_ROWS * MAX_OPS)) : "memory");
      mbar_arrive(met);
      uint32_t oready = oready0;
      for (int pc = 0;; pc++) {
        const uint32_t op = prog[pc];
        if ((op & 3) == OP_END) break;
        if ((op & 3) == OP_O) {
          const int a = (op >> 2) & 7, b = (op >> 5) & 15;
#pragma unroll 1
          for (int i = 0; i < b - a; i++) {
            const int ci = ((o_role(op) >> 2) * 2 + rank) * 8 + o_wave(a, b, i);
            wait_count(&g_done[ci], 4);
            mbar_arrive(oready);
            oready += 8;
            if (atomicAdd(&g_seen[ci], 1u) == 3u) { g_seen[ci] = 0; g_done[ci] = 0; }
          }
        }
        if ((op & 3) != OP_Q && (op & F_HELP) && (op & F_PARK)) {
          unsigned int* flag = &g_help[(role * 2 + rank) * MAX_PARK + ((op >> 10) & 3)];
          wait_count(flag, 1);
          mbar_arrive(hready0 + 8 * ((op >> 10) & 3));
          *flag = 0;
        }
      }
    }
  } else {
    asm volatile("setmaxnreg.inc.sync.aligned.u32 240;");
    const int lane = threadIdx.x & 31, warp = wid & 3;
    uint32_t empty_rem;
    const bool tell = lane < (wide ? WIDE + 1 : 2);
    asm volatile("mapa.shared::cluster.u32 %0, %1, %2;" : "=r"(empty_rem) : "r"(empty0), "r"((2 * sub + rank) ^ (!tell ? 0 : lane < 2 ? lane : 2 * lane - 2)));
    auto release = [&](int slot) { mbar_arrive_cluster_if(tell, empty_rem + slot); };
    Cursor r{0};
    const uint32_t ring16 = (sbase & 0x3FFFF) >> 4;
    uint32_t cur = ring16;
    bool rdy0 = false, rdy1 = false;
    auto probe1 = [&]() { rdy0 = mbar_test(full0 + r.off(), r.ph()); };
    auto probe2 = [&]() {
      Cursor n = r;
      rdy0 = mbar_test(full0 + n.off(), n.ph());
      n.next();
      rdy1 = mbar_test(full0 + n.off(), n.ph());
    };
    auto take = [&](bool rdy, uint32_t bytes, uint32_t& addr) {
      const int bi = r.off();
      if (!__all_sync(0xffffffffu, rdy)) mbar_wait_math(full0 + r.off(), r.ph());
      r.next();
      if (cur > ring16 + ((RING - bytes) >> 4)) cur = ring16;
      addr = cur;
      cur += bytes >> 4;
      return bi;
    };
    auto at = [&](uint32_t a16) {
      uint32_t a = sbase + (a16 - ring16) * 16;
      asm("" : "+r"(a));
      return a;
    };
    auto second = [&](uint32_t bytes) {
      if (cur > ring16 + ((RING - bytes) >> 4)) cur = ring16;
      cur += bytes >> 4;
      return cur - (bytes >> 4);
    };
    const int row = wg * 64 + warp * 16 + (lane >> 2);
    int img0 = (row * 4 + ((lane & 3) ^ ((row >> 1) & 3))) * 16;
    uint4* pend = nullptr;
    const uint64_t spol = evict_first();
    int pc = 0;
    uint32_t op = prog[0];
    auto enter = [&]() {
      r.n = op >> 12; cur = ring16 + (((op >> 20) & 63) << 8);
    };
    auto drain = [&](uint32_t (&t)[48], uint32_t c) {
      if (!(op & (3u << 26)) || c >= 6) return;
#pragma unroll
      for (int i = 0; i < 6; i++)
        stg2_if(c == i, pend + i * 512, t[8 * i], t[8 * i + 1], t[8 * i + 2], t[8 * i + 3],
                t[8 * i + 4], t[8 * i + 5], t[8 * i + 6], t[8 * i + 7], spol);
      if ((op & (1u << 26)) && c == 5) {
        __syncwarp();
        mbar_arrive_if(tell, odone);
      }
    };
    float s[32], o[96], c[80];
    uint32_t q[48], pa[16], pb[16];
    float mc0, mc1, l0, l1;
    bool gen;
    auto soft = [&](float (&s)[32], uint32_t (&pout)[16], bool first) {
      if (first) { gen = false; mc0 = 0.f; mc1 = 0.f; }
      float b0, b1;
      for (;;) {
        if (gen) {
          float m0 = fmaxf(s[0], s[1]), m1 = fmaxf(s[2], s[3]);
#pragma unroll
          for (int i = 1; i < 8; i++) { m0 = fmaxf(m0, fmaxf(s[4 * i], s[4 * i + 1])); m1 = fmaxf(m1, fmaxf(s[4 * i + 2], s[4 * i + 3])); }
          m0 = fmaxf(m0, __shfl_xor_sync(0xffffffffu, m0, 1)); m1 = fmaxf(m1, __shfl_xor_sync(0xffffffffu, m1, 1));
          m0 = fmaxf(m0, __shfl_xor_sync(0xffffffffu, m0, 2)); m1 = fmaxf(m1, __shfl_xor_sync(0xffffffffu, m1, 2));
          if (first) {
            mc0 = m0; mc1 = m1;
          } else if (__any_sync(0xffffffffu, !(m0 <= mc0 + kMaxLag && m1 <= mc1 + kMaxLag))) {
            m0 = fmaxf(mc0, m0); m1 = fmaxf(mc1, m1);
            const float a0 = ex2(mc0 - m0), a1 = ex2(mc1 - m1);
            mc0 = m0; mc1 = m1;
            l0 *= a0; l1 *= a1;
            wg_wait<0>();
            fence_regs(o);
#pragma unroll
            for (int i = 0; i < 96; i++) o[i] *= i & 2 ? a1 : a0;
          }
#pragma unroll
          for (int i = 0; i < 32; i++) s[i] -= i & 2 ? mc1 : mc0;
        }
#pragma unroll
        for (int i = 0; i < 8; i++) {
          const float e1 = ex2(s[4 * i + 1]), e0 = ex2(s[4 * i]), e3 = ex2(s[4 * i + 3]), e2 = ex2(s[4 * i + 2]);
          pout[2 * i] = pack_bf16(e0, e1);
          b0 = i ? b0 + fadd(e1, e0) : fadd(e1, e0);
          pout[2 * i + 1] = pack_bf16(e2, e3);
          b1 = i ? b1 + fadd(e3, e2) : fadd(e3, e2);
        }
        if (!__any_sync(0xffffffffu, !gen && !(fmaxf(b0, b1) <= kSumLimit && (!first || fminf(b0, b1) >= 1.0f / kSumLimit)))) break;
        gen = __any_sync(0xffffffffu, true);
      }
      l0 = first ? b0 : l0 + b0;
      l1 = first ? b1 : l1 + b1;
    };
    auto qk = [&](float (&s)[32], uint32_t ak, int k0, int k1) {
#pragma unroll
      for (int kk = k0; kk < k1; kk++)
        wgmma_rs_n64<0>(s, q[4 * kk], q[4 * kk + 1], q[4 * kk + 2], q[4 * kk + 3], mk_desc(ak, 16, KV_SBO, 1, (kk >> 2) * KV_CH + (kk & 3) * 2), kk != 0);
      wg_commit();
    };
    auto pv = [&](uint32_t (&pin)[16], uint32_t av, int acc) {
#pragma unroll
      for (int kk = 0; kk < 4; kk++)
        wgmma_rs_n192<1>(o, pin[4 * kk], pin[4 * kk + 1], pin[4 * kk + 2], pin[4 * kk + 3], mk_desc(av, KV_CH * 16, KV_SBO, 1, kk * (KV_SBO / 8)), acc || (kk != 0));
      wg_commit();
    };
    auto xw = [&](uint32_t ad, int acc) {
      const uint32_t da = second(SZ_A) + wg * 512;
      wg_fence();
#pragma unroll
      for (int kk = 0; kk < 4; kk++)
        wgmma_ss_n192<1>(o, mk_desc(da, 16, 1024, 1, kk * 2), mk_desc(ad, 4096, 1024, 1, (kk & 1) * 128 + (kk >> 1) * 768), acc || kk != 0);
      wg_commit();
    };
    auto ow = [&](int acc, int prev) {
      uint32_t da;
      const int bi = take(rdy0, SZ_A, da);
      const uint32_t db = second(SZ_WO);
      da += wg * 256;
      wg_fence();
      wgmma_ss_n160<1>(c, mk_desc(da, 16, 512, 2), mk_desc(db, 2048, 512, 2), acc);
      wgmma_ss_n160<1>(c, mk_desc(da, 16, 512, 2, 2), mk_desc(db, 2048, 512, 2, 64), 1);
      wg_commit();
      if (acc == 1) { wg_wait<1>(); release(prev); }
      wgmma_ss_n160<1>(c, mk_desc(da, 16, 512, 2, 512), mk_desc(db, 2048, 512, 2, 640), 1);
      wgmma_ss_n160<1>(c, mk_desc(da, 16, 512, 2, 514), mk_desc(db, 2048, 512, 2, 704), 1);
      wg_commit();
      return bi;
    };
    auto st_part = [&](int i) {
      stg2_if(true, pend + i * 512, __float_as_uint(c[8 * i]), __float_as_uint(c[8 * i + 1]), __float_as_uint(c[8 * i + 2]), __float_as_uint(c[8 * i + 3]),
              __float_as_uint(c[8 * i + 4]), __float_as_uint(c[8 * i + 5]), __float_as_uint(c[8 * i + 6]), __float_as_uint(c[8 * i + 7]), spol);
    };
#pragma unroll
    for (int i = 0; i < 48; i++) q[i] = 0;
    enter();

    if ((op & 3) == OP_Q) {
      uint32_t ad;
      int bi0 = take(false, SZ_WQ, ad), k = 0, lag = 0;
      xw(ad, 0);
      for (;;) {
#pragma unroll 1
        for (;;) {
          drain(q, k - lag);
          probe1();
          wg_wait<0>();
          release(bi0);
          bi0 = take(rdy0, SZ_WQ, ad);
          if (++k == 8) break;
          xw(ad, 1);
        }
        if (wg) bar_sync(2, 256);
        xw(ad, 1);
        const int bi9 = take(false, SZ_WQ, ad);
        xw(ad, 1);
        if (!wg) asm volatile("bar.arrive 2, 256;" ::: "memory");
        k = 0; lag = 0;
        if (pc == 0) prog += __shfl_sync(0xffffffffu, alone(), 0);
        uint32_t nop = prog[++pc];
        wg_wait<1>();
        release(bi0);
        probe2();
        wg_wait<0>();
        fence_regs(o);
        release(bi9);
#pragma unroll
        for (int i = 0; i < 48; i++) q[i] = pack_bf16(o[2 * i] * kScaleLog2, o[2 * i + 1] * kScaleLog2);
        fence_regs(q);
        if (op & F_PARK) {
          const int qt = helper ? (op >> 5) & 15 : team, qm = helper ? (op >> 12) & 3 : nt;
          pend = (uint4*)((char*)&g_o[((qt * 2 + rank) * 96 + 3 * (4 * ((op >> 2) & 7) + qm)) * 1024] + img0);
          op = nop;
          enter();
          if ((op & 3) != OP_Q) break;
          const int b = take(rdy0, SZ_WQ, ad);
          xw(ad, 0);
          bi0 = take(rdy1, SZ_WQ, ad);
          xw(ad, 1);
          wg_wait<1>();
          release(b);
          k = 1; lag = 1;
          continue;
        }
        int wave = (op >> 2) & 7, sk1;
        uint32_t ak1;
        {
          float s0[32];
          const int sk0 = take(rdy0, SZ_KV, ad);
          wg_fence();
          qk(s0, ad, 0, 12);
          sk1 = take(rdy1, SZ_KV, ak1);
          wg_fence();
          qk(s, ak1, 0, S1A);
          probe1();
          wg_wait<1>();
          fence_regs(s0);
          release(sk0);
          soft(s0, pa, true);
        }
        float i0, i1;
        auto sums = [&]() {
          l0 += __shfl_xor_sync(0xffffffffu, l0, 1); l1 += __shfl_xor_sync(0xffffffffu, l1, 1);
          l0 += __shfl_xor_sync(0xffffffffu, l0, 2); l1 += __shfl_xor_sync(0xffffffffu, l1, 2);
          i0 = rcp(l0); i1 = rcp(l1);
          asm volatile("" : "+f"(i0), "+f"(i1));
        };
        auto target = [&]() {
          pend = (uint4*)((char*)&g_o[((team * 2 + rank) * 96 + 3 * (4 * wave + nt)) * 1024] + img0);
          asm volatile("" : "+l"(pend));
        };
        bool late = false;
#pragma unroll
        for (int i = 0; i < 16; i++) pb[i] = 0;
        for (;;) {
          nop = prog[++pc];
          {
            uint32_t av;
            const int sv = take(rdy0, SZ_KV, av);
            wg_fence();
            qk(s, ak1, S1A, 12);
            pv(pa, av, 0);
            if (late) {
              stg2_if(true, pend + 4 * 512, pb[0], pb[1], pb[2], pb[3], pb[4], pb[5], pb[6], pb[7], spol);
              stg2_if(true, pend + 5 * 512, pb[8], pb[9], pb[10], pb[11], pb[12], pb[13], pb[14], pb[15], spol);
              __syncwarp();
              mbar_arrive_if(tell, odone);
            }
            probe2();
            wg_wait<1>();
            fence_regs(s);
            release(sk1);
            soft(s, pb, false);
            wg_wait<0>();
            fence_regs(o);
            release(sv);
          }
          auto step = [&](uint32_t (&pin)[16], uint32_t (&pout)[16], bool hook, bool unpark) {
            uint32_t ak, av;
            const int sk = take(rdy0, SZ_KV, ak), sv = take(rdy1, SZ_KV, av);
            wg_fence();
            qk(s, ak, 0, 12);
            pv(pin, av, 1);
            if (hook && unpark) { take(false, SZ_PARK, ak); take(false, SZ_PARK, av); }
            probe2();
            wg_wait<1>();
            fence_regs(s);
            release(sk);
            if (hook) {
              lds2_if<0>(unpark, img0 + at(ak), q);
              lds2_if<8192>(unpark, img0 + at(ak), q + 8);
              lds2_if<16384>(unpark, img0 + at(ak), q + 16);
              lds2_if<0>(unpark, img0 + at(av), q + 24);
              lds2_if<8192>(unpark, img0 + at(av), q + 32);
              lds2_if<16384>(unpark, img0 + at(av), q + 40);
            }
            soft(s, pout, false);
            wg_wait<0>();
            fence_regs(o);
            release(sv);
          };
          const int jpark = (nop & 3) == OP_A ? 6 : 7;
#pragma unroll 1
          for (int jj = 0; jj < 7; jj++) {
            step(pb, pa, false, false);
            step(pa, pb, true, jj == jpark);
          }
          if ((nop & 3) != OP_A) break;
          uint32_t ak, av;
          release(Cursor{r.n - 16}.off());
          release(Cursor{r.n - 8}.off());
          const int sk0 = take(rdy0, SZ_KV, ak), sv = take(rdy1, SZ_KV, av);
          wg_fence();
          qk(s, ak, 0, 8);
          sched_fence(img0, P.zero);
          sums();
          sched_fence(img0, P.zero);
          qk(s, ak, 8, 12);
          pv(pb, av, 1);
          probe2();
          wg_wait<1>();
          fence_regs(s);
          release(sk0);
          soft(s, pa, true);
          sk1 = take(rdy0, SZ_KV, ak1);
          rdy0 = rdy1;
          wg_wait<0>();
          target();
          fence_regs(o);
          release(sv);
          uint32_t t[48];
#pragma unroll
          for (int j = 0; j < 6; j++) {
#pragma unroll
            for (int i = 0; i < 4; i++) {
              t[8 * j + i] = pack_bf16(o[16 * j + 4 * i] * i0, o[16 * j + 4 * i + 1] * i0);
              t[8 * j + i + 4] = pack_bf16(o[16 * j + 4 * i + 2] * i1, o[16 * j + 4 * i + 3] * i1);
            }
            if (j < 4)
            stg2_if(true, pend + j * 512, t[8 * j], t[8 * j + 1], t[8 * j + 2], t[8 * j + 3], t[8 * j + 4], t[8 * j + 5], t[8 * j + 6], t[8 * j + 7], spol);
            if (j == 3) { wg_fence(); qk(s, ak1, 0, 4); }
            if (j == 5) { wg_fence(); qk(s, ak1, 4, S1A); }
            sched_fence(img0, P.zero);
          }
          if (P.zero) {
#pragma unroll
            for (int j = 0; j < 4; j++)
              stg2_if(true, pend, t[8 * j], t[8 * j + 1], t[8 * j + 2], t[8 * j + 3], t[8 * j + 4], t[8 * j + 5], t[8 * j + 6], t[8 * j + 7], spol);
          }
          late = true;
#pragma unroll
          for (int i = 0; i < 16; i++) pb[i] = t[32 + i];
          wave = (nop >> 2) & 7;
        }
        const int sv = take(rdy0, SZ_KV, ad);
        wg_fence();
        pv(pb, ad, 1);
        sums();
        target();
        op = nop;
        enter();
        rdy0 = rdy1;
        auto convert = [&](float (&u)[96], int j0, int j1) {
#pragma unroll
          for (int i = 4 * j0; i < 4 * j1; i++) {
            q[8 * (i >> 2) + (i & 3)] = pack_bf16(u[4 * i], u[4 * i + 1]);
            q[8 * (i >> 2) + (i & 3) + 4] = pack_bf16(u[4 * i + 2], u[4 * i + 3]);
          }
        };
        if ((op & 3) != OP_O) {
          if ((op & 3) == OP_Q) bi0 = take(rdy0, SZ_WQ, ad);
          wg_wait<0>();
          fence_regs(o);
          release(sv);
          float u[96];
#pragma unroll
          for (int i = 0; i < 96; i++) u[i] = o[i] * (i & 2 ? i1 : i0);
          if ((op & 3) != OP_Q) { convert(u, 0, 6); break; }
          fence_regs(u);
          xw(ad, 0);
          sched_fence(img0, P.zero);
          fence_regs(u);
          convert(u, 0, 1);
          stg2_if(true, pend, q[0], q[1], q[2], q[3], q[4], q[5], q[6], q[7], spol);
          probe1();
          wg_wait<0>();
          release(bi0);
          bi0 = take(rdy0, SZ_WQ, ad);
          xw(ad, 1);
          sched_fence(img0, P.zero);
          fence_regs(u);
          convert(u, 1, 6);
          k = 1;
          continue;
        }
        int bi = ow(0, 0);
        wg_wait<2>();
        fence_regs(o);
        release(sv);
#pragma unroll
        for (int j = 0; j < 6; j++) {
          uint32_t t[8];
#pragma unroll
          for (int i = 0; i < 4; i++) {
            t[i] = pack_bf16(o[16 * j + 4 * i] * i0, o[16 * j + 4 * i + 1] * i0);
            t[i + 4] = pack_bf16(o[16 * j + 4 * i + 2] * i1, o[16 * j + 4 * i + 3] * i1);
          }
          stg2_if(true, pend + j * 512, t[0], t[1], t[2], t[3], t[4], t[5], t[6], t[7], spol);
          if (j == 5) {
            __syncwarp();
            mbar_arrive_if(tell, odone);
          }
          probe1();
          wg_wait<1>();
          bi = ow(1, bi);
          fence_regs(o);
        }
        {
          const int nk = 12 * (((op >> 5) & 15) - ((op >> 2) & 7)) - ((op & F_ST) ? 0 : 2);
#pragma unroll 1
          for (int k = 7; k < nk; k++) {
            probe1();
            wg_wait<1>();
            bi = ow(1, bi);
          }
        }
        if (!(op & F_ST)) {
          probe2();
          wg_wait<1>();
          if (wg) {
            wg_wait<0>();
            release(bi);
            bar_sync(2, 256);
          }
          bi0 = ow(2, 0);
          rdy0 = rdy1;
          const int b = ow(2, 0);
          if (!wg) asm volatile("bar.arrive 2, 256;" ::: "memory");
          wg_wait<4>();
          mbar_arrive_cluster_if(tell && !wg, empty_rem + bi);
          bi = b;
        }
        probe1();
        nop = prog[++pc];
        if (op & F_LD) {
          uint32_t t[80];
#pragma unroll
          for (int j = 0; j < 5; j++) {
            const int b = take(rdy0, SZ_PART, ad);
            probe1();
#pragma unroll
            for (int i = 4 * j; i < 4 * j + 4; i++)
              lds128(img0 + at(ad) + ((i >> 1) & 1) * 8192 + (i & 1) * 512, t[4 * i], t[4 * i + 1], t[4 * i + 2], t[4 * i + 3]);
            release(b);
          }
          wg_wait<0>();
          fence_regs(c);
#pragma unroll
          for (int i = 0; i < 80; i++) c[i] += __uint_as_float(t[i]);
        }
        if (!(op & F_ST)) {
          wg_wait<0>();
          fence_regs(c);
          release(bi0);
          release(bi);
          goto finish;
        }
        op = nop;
        enter();
        bi0 = take(rdy0, SZ_WQ, ad);
        xw(ad, 0);
        pend = (uint4*)((char*)&g_part[((team * 4 + nt) * 2 + rank) * 5120] + img0);
        probe1();
        wg_wait<1>();
        fence_regs(c);
        release(bi);
        st_part(0); st_part(1);
        wg_wait<0>();
        release(bi0);
        bi0 = take(rdy0, SZ_WQ, ad);
        xw(ad, 1);
        st_part(2); st_part(3);
#pragma unroll
        for (int i = 0; i < 48; i++) q[i] = __float_as_uint(c[32 + i]);
        pend += 4 * 512;
        k = 1; lag = 2;
      }
    }
    rdy0 = false;
    {
      uint32_t t[48];
#pragma unroll
      for (int i = 0; i < 48; i++) t[i] = q[i] ^ P.zero;
      while ((op & 3) == OP_O) {
        int bi = ow(0, 0);
#pragma unroll 1
        for (int k = 1; k < 12 * (int)(((op >> 5) & 15) - ((op >> 2) & 7)); k++) {
          drain(t, k - 1);
          probe1();
          wg_wait<1>();
          bi = ow(1, bi);
        }
        rdy0 = false;
        wg_wait<0>();
        fence_regs(c);
        pc++;
        release(bi);
        if (!(op & F_ST)) goto finish;
        pend = (uint4*)((char*)&g_part[((((op >> 26) & 56) | ((op >> 9) & 7)) * 2 + rank) * 5120] + img0);
#pragma unroll
        for (int i = 6; i < 10; i++) st_part(i);
#pragma unroll
        for (int i = 0; i < 48; i++) t[i] = __float_as_uint(c[i]) ^ P.zero;
        op = prog[pc];
        enter();
      }
      for (int i = 0; i < 6; i++) drain(t, i);
    }
    if (false) {
    finish:
      uint32_t ad;
      take(rdy0, SZ_OUT, ad);
      const uint32_t wstage = sbase + (ad - ring16) * 16 + (wg * 4 + warp) * 5120;
      const uint32_t sa = wstage + (lane & 15) * 64;
#pragma unroll
      for (int i = 0; i < 10; i++) {
        const int u = (i & 1) * 2 + (lane >> 4);
        stsm4(sa + (i >> 1) * 1024 + ((u ^ ((lane >> 1) & 3)) << 4), pack_bf16(c[8 * i], c[8 * i + 1]), pack_bf16(c[8 * i + 2], c[8 * i + 3]),
              pack_bf16(c[8 * i + 4], c[8 * i + 5]), pack_bf16(c[8 * i + 6], c[8 * i + 7]));
      }
      asm volatile("fence.proxy.async.shared::cta;" ::: "memory");
      __syncwarp();
      if (lane == 0) {
        tma3d_store(&P.out, wstage, 0, (team & 7) * kSq + rank * 128 + wg * 64 + warp * 16, blk * 20 + nt * 5);
        asm volatile("cp.async.bulk.commit_group;\ncp.async.bulk.wait_group.read 0;" ::: "memory");
      }
    }
  }
}

typedef CUresult (*EncodeFn)(CUtensorMap*, CUtensorMapDataType, cuuint32_t, void*, const cuuint64_t*, const cuuint64_t*,
                             const cuuint32_t*, const cuuint32_t*, CUtensorMapInterleave, CUtensorMapSwizzle,
                             CUtensorMapL2promotion, CUtensorMapFloatOOBfill);

void encode(EncodeFn fn, CUtensorMap* m, const void* ptr, int rank, const cuuint64_t* dims, const cuuint64_t* strides,
            const cuuint32_t* box, CUtensorMapSwizzle swz) {
  const cuuint32_t es[5] = {1, 1, 1, 1, 1};
  CUresult r = fn(m, CU_TENSOR_MAP_DATA_TYPE_BFLOAT16, rank, const_cast<void*>(ptr), dims, strides, box, es,
                  CU_TENSOR_MAP_INTERLEAVE_NONE, swz, CU_TENSOR_MAP_L2_PROMOTION_L2_128B, CU_TENSOR_MAP_FLOAT_OOB_FILL_NONE);
  if (r != CUDA_SUCCESS) fprintf(stderr, "cuTensorMapEncodeTiled failed: %d\n", (int)r);
}

void annotate(uint32_t* ops, int n, bool helper) {
  uint32_t items = 0, cur = 0, pend = 0;
  auto item = [&](uint32_t bytes, int count, uint32_t bytes2 = 0) {
    for (int i = 0; i < count; i++) {
      if (cur + bytes > RING) cur = 0;
      cur += bytes;
      if (cur + bytes2 > RING) cur = 0;
      cur += bytes2;
      items++;
    }
  };
  for (int i = 0; i <= n; i++) {
    const uint32_t op = ops[i];
    ops[i] |= (items % (2 * NBAR)) << 15 | (cur >> 12) << 20 | pend << 26;
    if ((op & 3) == OP_Q) { item(SZ_WQ, 10, SZ_A); pend = (op & F_PARK) ? (helper ? 1 : 2) : 0; }
    if ((op & 3) == OP_A) {
      item(SZ_KV, (op & F_PARK) ? 30 : 31);
      if ((ops[i + 1] & 3) == OP_A) { item(SZ_PARK, 2); item(SZ_KV, 1); }
      item(SZ_KV, 1);
      pend = 1;
    }
    if ((op & 3) == OP_O) {
      item(SZ_A, 12 * (((op >> 5) & 15) - ((op >> 2) & 7)), SZ_WO);
      if (op & F_LD) item(SZ_PART, 5);
      pend = (op & F_ST) ? (helper ? 1 : 2) : 0;
    }
  }
}

void compile_programs(const char* const* text, bool helpers, uint32_t (*rows)[MAX_OPS]) {
  struct Req { int when, team, wave, slot; } req[N_TEAM * MAX_PARK];
  int n_req = 0;
  for (int t = 0; t < N_TEAM; t++) {
    uint32_t* ops = rows[t];
    int n = 0, flags[8] = {0, 0, 0, 0, 0, 0, 0, 0}, n_park = 0, last_o = -1, when = 0, given = 0;
    for (const char* s = text[t]; *s; s++) {
      const int a = s[1] - '0';
      if (*s == 'Q' || (*s == 'H' && !helpers)) { ops[n++] = OP_Q | a << 2; when += 10; }
      else if (*s == 'P') { flags[a] = F_PARK; ops[n++] = OP_Q | a << 2 | flags[a]; when += 10; }
      else if (*s == 'H') { req[n_req++] = {when, t, a, n_park}; flags[a] = F_PARK | F_HELP | n_park++ << 10; }
      else if (*s == 'A') { ops[n++] = OP_A | a << 2 | flags[a]; when += 32; }
      else if (*s == 'G') { given = a; if (helpers) req[n_req++] = {1000, t, 0, -a}; }
      else if (*s == 'O') {
        ops[n] = OP_O | a << 2 | (s[2] - '0') << 5;
        if (given) ops[n] = helpers ? ops[n] | F_LD | F_PARK | (MAX_PARK - 1) << 10 : ops[n] & ~(7u << 2);
        if (last_o >= 0) { ops[last_o] |= F_ST; ops[n] |= F_LD; }
        last_o = n++;
        when += 10 * (s[2] - s[1]);
      }
    }
    for (int i = n; i < MAX_OPS; i++) ops[i] = OP_END;
    annotate(ops, n, false);
  }
  for (int i = 1; i < n_req; i++)
    for (int j = i; j > 0 && req[j].when < req[j - 1].when; j--) { Req r = req[j]; req[j] = req[j - 1]; req[j - 1] = r; }
  for (int h = 0; h < N_HELP; h++) {
    uint32_t* ops = rows[N_TEAM + 2 * h];
    int n = 0;
    for (int i = 0; i < n_req; i++)
      for (int m = h; m < 4; m += N_HELP) {
        const uint32_t ro = 4 * req[i].team + m;
        ops[n++] = req[i].slot >= 0 ? OP_Q | req[i].wave << 2 | req[i].team << 5 | F_PARK | req[i].slot << 10 | m << 12
                                    : OP_O | -req[i].slot << 5 | F_ST | (ro & 7) << 9 | (ro >> 3) << 29;
      }
    for (int i = n; i < 2 * MAX_OPS; i++) ops[i] = OP_END;
    annotate(ops, n, true);
  }
}

const char* const kPrograms[N_TEAM] = {
  "Q0A0Q1A1Q2A2Q3A3Q4A4O05Q5A5Q6A6H7A7O58",
  "Q0A0Q1A1H2A2Q3A3O03Q4A4Q5A5Q6A6Q7A7O38",
  "Q0A0H1A1Q2A2O03Q3A3Q4A4Q5A5Q6A6Q7A7O38",
  "Q0A0Q1A1Q2A2Q3A3Q4A4O05Q5A5Q6A6H7A7O58",
  "Q0A0Q1A1Q2A2Q3A3Q4A4O05Q5A5Q6A6H7A7O58",
  "Q0A0Q1A1H2A2O03Q3A3Q4A4Q5A5Q6A6Q7A7O38",
  "Q0A0Q1A1Q2A2O03Q3A3Q4A4H5A5Q6A6Q7A7O38",
  "Q0A0Q1A1Q2A2O03Q3A3H4A4Q5A5Q6A6Q7A7O38",
  "P3Q0A0Q1A1Q2A2A3Q4A4Q5A5Q6A6H7A7O08",
  "Q0A0Q1A1Q2A2Q3A3H4A4Q5A5Q6A6Q7A7O08",
  "P3P7Q0A0Q1A1Q2A2A3Q4A4H5A5Q6A6A7G1O18",
  "Q0A0Q1A1Q2A2H3A3Q4A4Q5A5Q6A6Q7A7O08",
  "P3Q0A0Q1A1Q2A2A3Q4A4Q5A5H6A6Q7A7O08",
  "P7Q0A0Q1A1Q2A2Q3A3Q4A4Q5A5Q6A6A7G1O18",
  "Q0A0Q1A1Q2A2H3A3Q4A4Q5A5Q6A6Q7A7O08",
  "P3Q0A0Q1A1Q2A2A3H4A4Q5A5Q6A6Q7A7G1O18",
};

cudaLaunchConfig_t config(int clusters, int size, cudaLaunchAttribute* at) {
  cudaLaunchConfig_t cfg = {};
  cfg.gridDim = dim3(clusters * size); cfg.blockDim = dim3(384); cfg.dynamicSmemBytes = SMEM_BYTES; cfg.stream = cudaStreamPerThread;
  at[0].id = cudaLaunchAttributeClusterDimension; at[0].val.clusterDim.x = size; at[0].val.clusterDim.y = 1; at[0].val.clusterDim.z = 1;
  at[1].id = cudaLaunchAttributeProgrammaticStreamSerialization; at[1].val.programmaticStreamSerializationAllowed = 1;
  cfg.attrs = at; cfg.numAttrs = 1;
  return cfg;
}

void launch(Params& P, int role0, int clusters, int size, bool overlap) {
  cudaLaunchAttribute at[2];
  cudaLaunchConfig_t cfg = config(clusters, size, at);
  cfg.numAttrs = overlap ? 2 : 1;
  for (int i = 0; i < 30; i++) P.first[i] = i < N_TEAM ? P.ops[i][0] : i < N_TEAM + N_HELP ? P.ops[2 * i - N_TEAM][0] : 0;
  P.role0 = role0; P.wide = size > 2;
  cudaLaunchKernelEx(&cfg, fused_kernel, P);
}

const char* const* bench_programs() {
  return kPrograms;
}

}

extern "C" void kernel_launch(void* const* d_in, const int* in_sizes, int n_in, void* d_out, int out_size) {
  (void)in_sizes; (void)n_in; (void)out_size;
  static EncodeFn fn = nullptr;
  static int n_clusters = 0, n_wide = 0;
  if (!fn) {
    cudaDriverEntryPointQueryResult qr;
    void* f = nullptr;
    cudaGetDriverEntryPoint("cuTensorMapEncodeTiled", &f, cudaEnableDefault, &qr);
    fn = (EncodeFn)f;
    cudaFuncSetAttribute(fused_kernel, cudaFuncAttributeMaxDynamicSharedMemorySize, SMEM_BYTES);
    cudaLaunchAttribute at[2];
    cudaLaunchConfig_t cfg = config(N_CL + N_HELP, 2, at);
    if (cudaOccupancyMaxActiveClusters(&n_clusters, fused_kernel, &cfg) != cudaSuccess || n_clusters < 1) n_clusters = 1;
    cfg = config(N_WIDE / WIDE, 2 * WIDE, at);
    if (cudaOccupancyMaxActiveClusters(&n_wide, fused_kernel, &cfg) != cudaSuccess) n_wide = 0;
    (void)cudaGetLastError();
  }
  Params P;
  const CUtensorMapSwizzle S128 = CU_TENSOR_MAP_SWIZZLE_128B, S64 = CU_TENSOR_MAP_SWIZZLE_64B;
  for (int blk = 0; blk < 2; blk++) {
    void* const* in = d_in + 5 * blk;
    { const cuuint64_t d[] = {kD, kB * kSq}, s[] = {kD * 2}; const cuuint32_t b[] = {64, 128};
      encode(fn, &P.x[blk], in[0], 2, d, s, b, S128);
      const cuuint32_t b2[] = {64, 128 / WIDE};
      encode(fn, &P.x[2 + blk], in[0], 2, d, s, b2, S128); }
    { const cuuint64_t d[] = {64, 8, 3, (cuuint64_t)kB * kH * kSk / 8}, s[] = {kDh * 2, 128, 8 * kDh * 2}; const cuuint32_t b[] = {64, 8, 3, 4};
      encode(fn, &P.kv[blk], in[1], 4, d, s, b, S128);
      encode(fn, &P.kv[blk + 2], in[2], 4, d, s, b, S128); }
    { const cuuint64_t d[] = {64, kD, kHD / 64}, s[] = {kHD * 2, 128}; const cuuint32_t b[] = {64, 32, 3};
      encode(fn, &P.wq[blk], in[3], 3, d, s, b, S128); }
    { const cuuint64_t d[] = {32, 2, kHD / 8, 4, kD / 32}, s[] = {kD * 2, 8 * kD * 2, 2 * kD * 2, 64}; const cuuint32_t b[] = {32, 2, 4, 4, 5};
      encode(fn, &P.wo[blk], in[4], 5, d, s, b, S64); }
  }
  { const cuuint64_t d[] = {32, kB * kSq, 2 * kD / 32}, s[] = {2 * kD * 2, 64}; const cuuint32_t b[] = {32, 16, 5};
    encode(fn, &P.out, d_out, 3, d, s, b, S64); }

  P.zero = 0;
  compile_programs(bench_programs(), false, P.ops + N_ROWS);
  if (n_clusters >= N_CL) {
    const bool helpers = n_clusters >= N_CL + N_HELP;
    compile_programs(bench_programs(), helpers, P.ops);
    if (helpers && n_wide >= N_WIDE / WIDE) {
      launch(P, 0, N_WIDE / WIDE, 2 * WIDE, false);
      launch(P, N_WIDE, N_CL + N_HELP - N_WIDE, 2, true);
    } else {
      launch(P, 0, N_CL + (helpers ? N_HELP : 0), 2, false);
    }
  } else {
    for (int phase = 0; phase < 2; phase++) {
      const char* text[N_TEAM];
      for (int t = 0; t < N_TEAM; t++) text[t] = phase ? "O08" : "Q0A0Q1A1Q2A2Q3A3Q4A4Q5A5Q6A6Q7A7";
      compile_programs(text, false, P.ops);
      launch(P, 0, N_CL, 2, false);
    }
  }
}
```

```cpp
#include <cuda_runtime.h>
#include <cuda_bf16.h>
#include <cuda.h>
#include <stdint.h>
#include <stdio.h>

namespace {

constexpr int kB = 8, kSq = 256, kD = 640, kH = 32, kSk = 1024, kDh = 192;
constexpr int kHD = kH * kDh;
constexpr uint32_t RING = 224 * 1024;
constexpr uint32_t SZ_KV = 24576;
constexpr uint32_t SZ_WQ = 24576, SZ_WO = 20480, SZ_A = 16384;
constexpr uint32_t SZ_OUT = 40960;
constexpr uint32_t SZ_PARK = 24576;
constexpr uint32_t SZ_PART = 16384;
constexpr int NBAR = 16;
constexpr int KV_TRANSIT = 4;
constexpr int EARLY = 3;
constexpr int S1A = 7;
constexpr uint32_t KV_CH = 64, KV_SBO = 3072;
constexpr int SMEM_BYTES = RING + 512 + 1024;
constexpr int N_TEAM = 16, N_CL = 64, N_HELP = 2, MAX_OPS = 20, MAX_PARK = 4;
constexpr int N_ROWS = N_TEAM + 2 * N_HELP;
#define WIDE_ 4
constexpr int WIDE = WIDE_, N_WIDE = 60;
enum { OP_END = 0, OP_Q = 1, OP_A = 2, OP_O = 3, F_PARK = 1 << 9, F_LD = 1 << 12, F_ST = 1 << 13, F_HELP = 1 << 12 };

struct alignas(64) Params {
  uint32_t first[30], role0, wide;
  CUtensorMap x[4], wq[2], kv[4], wo[2], out;
  uint32_t ops[2 * N_ROWS][MAX_OPS];
  uint32_t zero;
};

__device__ uint4 g_o[N_TEAM * 2 * 120 * 1024];
__device__ unsigned int g_done[N_TEAM * 2 * 8];
__device__ unsigned int g_help[N_CL * 2 * MAX_PARK];
__device__ unsigned int g_meet[2];
__device__ unsigned int g_seen[N_TEAM * 2 * 8];

template <int TB>
__device__ __forceinline__ void wgmma_rs_n64(float (&d)[32], uint32_t a0, uint32_t a1, uint32_t a2, uint32_t a3, uint64_t db, int scale_d) {
  asm volatile("{\n.reg .pred p;\nsetp.ne.b32 p, %37, 0;\n"
    "wgmma.mma_async.sync.aligned.m64n64k16.f32.bf16.bf16 {%0, %1, %2, %3, %4, %5, %6, %7, %8, %9, %10, %11, %12, %13, %14, %15, %16, %17, %18, %19, %20, %21, %22, %23, %24, %25, %26, %27, %28, %29, %30, %31}, {%32, %33, %34, %35}, %36, p, 1, 1, %38;\n}\n"
    : "+f"(d[0]), "+f"(d[1]), "+f"(d[2]), "+f"(d[3]), "+f"(d[4]), "+f"(d[5]), "+f"(d[6]), "+f"(d[7]), "+f"(d[8]), "+f"(d[9]), "+f"(d[10]), "+f"(d[11]), "+f"(d[12]), "+f"(d[13]), "+f"(d[14]), "+f"(d[15]), "+f"(d[16]), "+f"(d[17]), "+f"(d[18]), "+f"(d[19]), "+f"(d[20]), "+f"(d[21]), "+f"(d[22]), "+f"(d[23]), "+f"(d[24]), "+f"(d[25]), "+f"(d[26]), "+f"(d[27]), "+f"(d[28]), "+f"(d[29]), "+f"(d[30]), "+f"(d[31])
    : "r"(a0), "r"(a1), "r"(a2), "r"(a3), "l"(db), "r"(scale_d), "n"(TB));
}
template <int TB, int TA = 0>
__device__ __forceinline__ void wgmma_ss_n160(float (&d)[80], uint64_t da, uint64_t db, int scale_d) {
  asm volatile("{\n.reg .pred p;\nsetp.ne.b32 p, %82, 0;\n"
    "wgmma.mma_async.sync.aligned.m64n160k16.f32.bf16.bf16 {%0, %1, %2, %3, %4, %5, %6, %7, %8, %9, %10, %11, %12, %13, %14, %15, %16, %17, %18, %19, %20, %21, %22, %23, %24, %25, %26, %27, %28, %29, %30, %31, %32, %33, %34, %35, %36, %37, %38, %39, %40, %41, %42, %43, %44, %45, %46, %47, %48, %49, %50, %51, %52, %53, %54, %55, %56, %57, %58, %59, %60, %61, %62, %63, %64, %65, %66, %67, %68, %69, %70, %71, %72, %73, %74, %75, %76, %77, %78, %79}, %80, %81, p, 1, 1, %83, %84;\n}\n"
    : "+f"(d[0]), "+f"(d[1]), "+f"(d[2]), "+f"(d[3]), "+f"(d[4]), "+f"(d[5]), "+f"(d[6]), "+f"(d[7]), "+f"(d[8]), "+f"(d[9]), "+f"(d[10]), "+f"(d[11]), "+f"(d[12]), "+f"(d[13]), "+f"(d[14]), "+f"(d[15]), "+f"(d[16]), "+f"(d[17]), "+f"(d[18]), "+f"(d[19]), "+f"(d[20]), "+f"(d[21]), "+f"(d[22]), "+f"(d[23]), "+f"(d[24]), "+f"(d[25]), "+f"(d[26]), "+f"(d[27]), "+f"(d[28]), "+f"(d[29]), "+f"(d[30]), "+f"(d[31]), "+f"(d[32]), "+f"(d[33]), "+f"(d[34]), "+f"(d[35]), "+f"(d[36]), "+f"(d[37]), "+f"(d[38]), "+f"(d[39]), "+f"(d[40]), "+f"(d[41]), "+f"(d[42]), "+f"(d[43]), "+f"(d[44]), "+f"(d[45]), "+f"(d[46]), "+f"(d[47]), "+f"(d[48]), "+f"(d[49]), "+f"(d[50]), "+f"(d[51]), "+f"(d[52]), "+f"(d[53]), "+f"(d[54]), "+f"(d[55]), "+f"(d[56]), "+f"(d[57]), "+f"(d[58]), "+f"(d[59]), "+f"(d[60]), "+f"(d[61]), "+f"(d[62]), "+f"(d[63]), "+f"(d[64]), "+f"(d[65]), "+f"(d[66]), "+f"(d[67]), "+f"(d[68]), "+f"(d[69]), "+f"(d[70]), "+f"(d[71]), "+f"(d[72]), "+f"(d[73]), "+f"(d[74]), "+f"(d[75]), "+f"(d[76]), "+f"(d[77]), "+f"(d[78]), "+f"(d[79])
    : "l"(da), "l"(db), "r"(scale_d), "n"(TA), "n"(TB));
}
template <int TB, int TA = 0>
__device__ __forceinline__ void wgmma_ss_n192(float (&d)[96], uint64_t da, uint64_t db, int scale_d) {
  asm volatile("{\n.reg .pred p;\nsetp.ne.b32 p, %98, 0;\n"
    "wgmma.mma_async.sync.aligned.m64n192k16.f32.bf16.bf16 {%0, %1, %2, %3, %4, %5, %6, %7, %8, %9, %10, %11, %12, %13, %14, %15, %16, %17, %18, %19, %20, %21, %22, %23, %24, %25, %26, %27, %28, %29, %30, %31, %32, %33, %34, %35, %36, %37, %38, %39, %40, %41, %42, %43, %44, %45, %46, %47, %48, %49, %50, %51, %52, %53, %54, %55, %56, %57, %58, %59, %60, %61, %62, %63, %64, %65, %66, %67, %68, %69, %70, %71, %72, %73, %74, %75, %76, %77, %78, %79, %80, %81, %82, %83, %84, %85, %86, %87, %88, %89, %90, %91, %92, %93, %94, %95}, %96, %97, p, 1, 1, %99, %100;\n}\n"
    : "+f"(d[0]), "+f"(d[1]), "+f"(d[2]), "+f"(d[3]), "+f"(d[4]), "+f"(d[5]), "+f"(d[6]), "+f"(d[7]), "+f"(d[8]), "+f"(d[9]), "+f"(d[10]), "+f"(d[11]), "+f"(d[12]), "+f"(d[13]), "+f"(d[14]), "+f"(d[15]), "+f"(d[16]), "+f"(d[17]), "+f"(d[18]), "+f"(d[19]), "+f"(d[20]), "+f"(d[21]), "+f"(d[22]), "+f"(d[23]), "+f"(d[24]), "+f"(d[25]), "+f"(d[26]), "+f"(d[27]), "+f"(d[28]), "+f"(d[29]), "+f"(d[30]), "+f"(d[31]), "+f"(d[32]), "+f"(d[33]), "+f"(d[34]), "+f"(d[35]), "+f"(d[36]), "+f"(d[37]), "+f"(d[38]), "+f"(d[39]), "+f"(d[40]), "+f"(d[41]), "+f"(d[42]), "+f"(d[43]), "+f"(d[44]), "+f"(d[45]), "+f"(d[46]), "+f"(d[47]), "+f"(d[48]), "+f"(d[49]), "+f"(d[50]), "+f"(d[51]), "+f"(d[52]), "+f"(d[53]), "+f"(d[54]), "+f"(d[55]), "+f"(d[56]), "+f"(d[57]), "+f"(d[58]), "+f"(d[59]), "+f"(d[60]), "+f"(d[61]), "+f"(d[62]), "+f"(d[63]), "+f"(d[64]), "+f"(d[65]), "+f"(d[66]), "+f"(d[67]), "+f"(d[68]), "+f"(d[69]), "+f"(d[70]), "+f"(d[71]), "+f"(d[72]), "+f"(d[73]), "+f"(d[74]), "+f"(d[75]), "+f"(d[76]), "+f"(d[77]), "+f"(d[78]), "+f"(d[79]), "+f"(d[80]), "+f"(d[81]), "+f"(d[82]), "+f"(d[83]), "+f"(d[84]), "+f"(d[85]), "+f"(d[86]), "+f"(d[87]), "+f"(d[88]), "+f"(d[89]), "+f"(d[90]), "+f"(d[91]), "+f"(d[92]), "+f"(d[93]), "+f"(d[94]), "+f"(d[95])
    : "l"(da), "l"(db), "r"(scale_d), "n"(TA), "n"(TB));
}
template <int TB>
__device__ __forceinline__ void wgmma_rs_n192(float (&d)[96], uint32_t a0, uint32_t a1, uint32_t a2, uint32_t a3, uint64_t db, int scale_d) {
  asm volatile("{\n.reg .pred p;\nsetp.ne.b32 p, %101, 0;\n"
    "wgmma.mma_async.sync.aligned.m64n192k16.f32.bf16.bf16 {%0, %1, %2, %3, %4, %5, %6, %7, %8, %9, %10, %11, %12, %13, %14, %15, %16, %17, %18, %19, %20, %21, %22, %23, %24, %25, %26, %27, %28, %29, %30, %31, %32, %33, %34, %35, %36, %37, %38, %39, %40, %41, %42, %43, %44, %45, %46, %47, %48, %49, %50, %51, %52, %53, %54, %55, %56, %57, %58, %59, %60, %61, %62, %63, %64, %65, %66, %67, %68, %69, %70, %71, %72, %73, %74, %75, %76, %77, %78, %79, %80, %81, %82, %83, %84, %85, %86, %87, %88, %89, %90, %91, %92, %93, %94, %95}, {%96, %97, %98, %99}, %100, p, 1, 1, %102;\n}\n"
    : "+f"(d[0]), "+f"(d[1]), "+f"(d[2]), "+f"(d[3]), "+f"(d[4]), "+f"(d[5]), "+f"(d[6]), "+f"(d[7]), "+f"(d[8]), "+f"(d[9]), "+f"(d[10]), "+f"(d[11]), "+f"(d[12]), "+f"(d[13]), "+f"(d[14]), "+f"(d[15]), "+f"(d[16]), "+f"(d[17]), "+f"(d[18]), "+f"(d[19]), "+f"(d[20]), "+f"(d[21]), "+f"(d[22]), "+f"(d[23]), "+f"(d[24]), "+f"(d[25]), "+f"(d[26]), "+f"(d[27]), "+f"(d[28]), "+f"(d[29]), "+f"(d[30]), "+f"(d[31]), "+f"(d[32]), "+f"(d[33]), "+f"(d[34]), "+f"(d[35]), "+f"(d[36]), "+f"(d[37]), "+f"(d[38]), "+f"(d[39]), "+f"(d[40]), "+f"(d[41]), "+f"(d[42]), "+f"(d[43]), "+f"(d[44]), "+f"(d[45]), "+f"(d[46]), "+f"(d[47]), "+f"(d[48]), "+f"(d[49]), "+f"(d[50]), "+f"(d[51]), "+f"(d[52]), "+f"(d[53]), "+f"(d[54]), "+f"(d[55]), "+f"(d[56]), "+f"(d[57]), "+f"(d[58]), "+f"(d[59]), "+f"(d[60]), "+f"(d[61]), "+f"(d[62]), "+f"(d[63]), "+f"(d[64]), "+f"(d[65]), "+f"(d[66]), "+f"(d[67]), "+f"(d[68]), "+f"(d[69]), "+f"(d[70]), "+f"(d[71]), "+f"(d[72]), "+f"(d[73]), "+f"(d[74]), "+f"(d[75]), "+f"(d[76]), "+f"(d[77]), "+f"(d[78]), "+f"(d[79]), "+f"(d[80]), "+f"(d[81]), "+f"(d[82]), "+f"(d[83]), "+f"(d[84]), "+f"(d[85]), "+f"(d[86]), "+f"(d[87]), "+f"(d[88]), "+f"(d[89]), "+f"(d[90]), "+f"(d[91]), "+f"(d[92]), "+f"(d[93]), "+f"(d[94]), "+f"(d[95])
    : "r"(a0), "r"(a1), "r"(a2), "r"(a3), "l"(db), "r"(scale_d), "n"(TB));
}

__device__ __forceinline__ uint32_t smem_u32(const void* p) { return (uint32_t)__cvta_generic_to_shared(p); }
__device__ __forceinline__ void wg_fence() { asm volatile("wgmma.fence.sync.aligned;" ::: "memory"); }
__device__ __forceinline__ void wg_commit() { asm volatile("wgmma.commit_group.sync.aligned;" ::: "memory"); }
template <int N> __device__ __forceinline__ void wg_wait() { asm volatile("wgmma.wait_group.sync.aligned %0;" ::"n"(N) : "memory"); }
__device__ __forceinline__ void sched_fence(int& keep, uint32_t zero) {
  asm volatile("{\n.reg .u32 c;\nmov.u32 c, %%clock;\nand.b32 c, c, %1;\nxor.b32 %0, %0, c;\n}\n" : "+r"(keep) : "r"(zero) : "memory");
}
template <int N> __device__ __forceinline__ void fence_regs(float (&r)[N]) {
#pragma unroll
  for (int i = 0; i < N; i++) asm volatile("" : "+f"(r[i])::"memory");
}
template <int N> __device__ __forceinline__ void fence_regs(uint32_t (&r)[N]) {
#pragma unroll
  for (int i = 0; i < N; i++) asm volatile("" : "+r"(r[i])::"memory");
}
__device__ __forceinline__ uint64_t mk_desc(uint32_t a16, uint32_t lbo, uint32_t sbo, uint32_t swz, uint32_t off = 0) {
  uint64_t d;
  asm("mov.b64 %0, {%1, %2};" : "=l"(d) : "r"(a16), "r"((sbo >> 4) | (swz << 30)));
  return d + (off + ((lbo >> 4) << 16));
}
__device__ __forceinline__ void mbar_init(uint32_t bar, uint32_t cnt) {
  asm volatile("mbarrier.init.shared::cta.b64 [%0], %1;" ::"r"(bar), "r"(cnt) : "memory");
}
__device__ __forceinline__ void mbar_expect(uint32_t bar, uint32_t tx) {
  asm volatile("mbarrier.arrive.expect_tx.shared::cta.b64 _, [%0], %1;" ::"r"(bar), "r"(tx) : "memory");
}
__device__ __forceinline__ bool mbar_test(uint32_t bar, uint32_t ph) {
  uint32_t ok;
  asm volatile("{\n.reg .pred p;\nmbarrier.test_wait.parity.shared::cta.b64 p, [%1], %2;\nselp.u32 %0, 1, 0, p;\n}\n"
               : "=r"(ok) : "r"(bar), "r"(ph) : "memory");
  return ok;
}
__device__ __forceinline__ void mbar_wait(uint32_t bar, uint32_t ph) {
  asm volatile("{\n.reg .pred p;\n.reg .u32 n;\nmov.u32 n, 0;\n"
               "LOOP:\nadd.u32 n, n, 1;\nmbarrier.try_wait.parity.shared::cta.b64 p, [%0], %1;\n@p bra DONE;\n"
               "setp.lt.u32 p, n, 0x1000000;\n@p bra LOOP;\ntrap;\n"
               "DONE:\n}\n" ::"r"(bar), "r"(ph) : "memory");
}
__device__ __forceinline__ void mbar_wait_math(uint32_t bar, uint32_t ph) {
  asm volatile("{\n.reg .pred p;\nLOOP:\nmbarrier.try_wait.parity.shared::cta.b64 p, [%0], %1;\n@!p bra LOOP;\n}\n" ::"r"(bar), "r"(ph) : "memory");
}
__device__ __forceinline__ void mbar_wait_long(uint32_t bar, uint32_t ph) {
  asm volatile("{\n.reg .pred p;\n.reg .u32 n;\nmov.u32 n, 0;\n"
               "LOOP:\nmbarrier.try_wait.parity.shared::cta.b64 p, [%0], %1, %2;\n@p bra DONE;\n"
               "add.u32 n, n, 1;\nsetp.lt.u32 p, n, 0x40000;\n@p bra LOOP;\ntrap;\n"
               "DONE:\n}\n" ::"r"(bar), "r"(ph), "r"(20000) : "memory");
}
__device__ __forceinline__ void mbar_arrive_cluster_if(bool on, uint32_t addr) {
  asm volatile("{\n.reg .pred p;\nsetp.ne.b32 p, %1, 0;\n@p mbarrier.arrive.shared::cluster.b64 _, [%0];\n}\n" ::"r"(addr), "r"((int)on) : "memory");
}
__device__ __forceinline__ void mbar_arrive_if(bool on, uint32_t addr) {
  asm volatile("{\n.reg .pred p;\nsetp.ne.b32 p, %1, 0;\n@p mbarrier.arrive.shared::cta.b64 _, [%0];\n}\n" ::"r"(addr), "r"((int)on) : "memory");
}
__device__ __forceinline__ void tma2d(uint32_t dst, const CUtensorMap* m, uint32_t bar, int c0, int c1) {
  asm volatile("cp.async.bulk.tensor.2d.shared::cluster.global.mbarrier::complete_tx::bytes [%0], [%1, {%3, %4}], [%2];"
               ::"r"(dst), "l"(m), "r"(bar), "r"(c0), "r"(c1) : "memory");
}
__device__ __forceinline__ void tma2d_mc(uint32_t dst, const CUtensorMap* m, uint32_t bar, int c0, int c1, uint16_t mask) {
  asm volatile("cp.async.bulk.tensor.2d.shared::cluster.global.mbarrier::complete_tx::bytes.multicast::cluster [%0], [%1, {%3, %4}], [%2], %5;"
               ::"r"(dst), "l"(m), "r"(bar), "r"(c0), "r"(c1), "h"(mask) : "memory");
}
__device__ __forceinline__ void bulk_load_mc(uint32_t dst, const void* src, uint32_t bytes, uint32_t bar, uint64_t pol, uint16_t mask) {
  asm volatile("cp.async.bulk.shared::cluster.global.mbarrier::complete_tx::bytes.multicast::cluster.L2::cache_hint [%0], [%1], %2, [%3], %5, %4;"
               ::"r"(dst), "l"(src), "r"(bytes), "r"(bar), "l"(pol), "h"(mask) : "memory");
}
__device__ __forceinline__ void tma3d(uint32_t dst, const CUtensorMap* m, uint32_t bar, int c0, int c1, int c2) {
  asm volatile("cp.async.bulk.tensor.3d.shared::cluster.global.mbarrier::complete_tx::bytes [%0], [%1, {%3, %4, %5}], [%2];"
               ::"r"(dst), "l"(m), "r"(bar), "r"(c0), "r"(c1), "r"(c2) : "memory");
}
__device__ __forceinline__ void tma3d_mc(uint32_t dst, const CUtensorMap* m, uint32_t bar, int c0, int c1, int c2, uint16_t mask) {
  asm volatile("cp.async.bulk.tensor.3d.shared::cluster.global.mbarrier::complete_tx::bytes.multicast::cluster"
               " [%0], [%1, {%3, %4, %5}], [%2], %6;"
               ::"r"(dst), "l"(m), "r"(bar), "r"(c0), "r"(c1), "r"(c2), "h"(mask) : "memory");
}
__device__ __forceinline__ void tma3d_store(const CUtensorMap* m, uint32_t src, int c0, int c1, int c2) {
  asm volatile("cp.async.bulk.tensor.3d.global.shared::cta.bulk_group [%0, {%2, %3, %4}], [%1];"
               ::"l"(m), "r"(src), "r"(c0), "r"(c1), "r"(c2) : "memory");
}
__device__ __forceinline__ void bar_sync(int id, int n) { asm volatile("bar.sync %0, %1;" ::"r"(id), "r"(n) : "memory"); }
__device__ __forceinline__ uint32_t pack_bf16(float lo, float hi) {
  uint32_t r;
  asm("cvt.rn.bf16x2.f32 %0, %1, %2;" : "=r"(r) : "f"(hi), "f"(lo));
  return r;
}
__device__ __forceinline__ float ex2(float x) {
  float y;
  asm("ex2.approx.ftz.f32 %0, %1;" : "=f"(y) : "f"(x));
  return y;
}
__device__ __forceinline__ float fadd(float a, float b) {
  float y;
  asm("add.f32 %0, %1, %2;" : "=f"(y) : "f"(a), "f"(b));
  return y;
}
__device__ __forceinline__ float rcp(float x) {
  float y;
  asm("rcp.approx.ftz.f32 %0, %1;" : "=f"(y) : "f"(x));
  return y;
}
__device__ __forceinline__ void stsm4(uint32_t addr, uint32_t a, uint32_t b, uint32_t c, uint32_t d) {
  asm volatile("stmatrix.sync.aligned.m8n8.x4.shared.b16 [%0], {%1, %2, %3, %4};" ::"r"(addr), "r"(a), "r"(b), "r"(c), "r"(d) : "memory");
}

__device__ __forceinline__ void tma4d_mc_hint(uint32_t dst, const CUtensorMap* m, uint32_t bar, int c3, uint64_t pol, uint16_t mask) {
  asm volatile("cp.async.bulk.tensor.4d.shared::cluster.global.mbarrier::complete_tx::bytes.multicast::cluster.L2::cache_hint"
               " [%0], [%1, {%3, %3, %3, %4}], [%2], %5, %6;"
               ::"r"(dst), "l"(m), "r"(bar), "r"(0), "r"(c3), "h"(mask), "l"(pol) : "memory");
}
__device__ __forceinline__ void tma5d_mc(uint32_t dst, const CUtensorMap* m, uint32_t bar, int c2, int c4, uint16_t mask) {
  asm volatile("cp.async.bulk.tensor.5d.shared::cluster.global.mbarrier::complete_tx::bytes.multicast::cluster"
               " [%0], [%1, {%3, %3, %4, %3, %5}], [%2], %6;"
               ::"r"(dst), "l"(m), "r"(bar), "r"(0), "r"(c2), "r"(c4), "h"(mask) : "memory");
}
__device__ __forceinline__ void bulk_load_hint(uint32_t dst, const void* src, uint32_t bytes, uint32_t bar, uint64_t pol) {
  asm volatile("cp.async.bulk.shared::cluster.global.mbarrier::complete_tx::bytes.L2::cache_hint [%0], [%1], %2, [%3], %4;"
               ::"r"(dst), "l"(src), "r"(bytes), "r"(bar), "l"(pol) : "memory");
}
__device__ __forceinline__ void stg2_if(bool on, void* p, uint32_t a, uint32_t b, uint32_t c, uint32_t d, uint32_t e, uint32_t f,
                                        uint32_t g, uint32_t h, uint64_t pol) {
  asm volatile("{\n.reg .pred p;\nsetp.ne.b32 p, %10, 0;\n"
               "@p st.global.L2::cache_hint.v4.b32 [%0], {%1, %2, %3, %4}, %9;\n"
               "@p st.global.L2::cache_hint.v4.b32 [%0 + 512], {%5, %6, %7, %8}, %9;\n}\n"
               ::"l"(p), "r"(a), "r"(b), "r"(c), "r"(d), "r"(e), "r"(f), "r"(g), "r"(h), "l"(pol), "r"((int)on) : "memory");
}
__device__ __forceinline__ uint64_t evict_first() {
  uint64_t p;
  asm("createpolicy.fractional.L2::evict_first.b64 %0, 1.0;" : "=l"(p));
  return p;
}
__device__ __forceinline__ bool elect() {
  uint32_t ok;
  asm volatile("{\n.reg .pred p;\nelect.sync _|p, 0xffffffff;\nselp.u32 %0, 1, 0, p;\n}\n" : "=r"(ok));
  return ok;
}
__device__ __forceinline__ void mbar_arrive(uint32_t bar) {
  asm volatile("mbarrier.arrive.shared::cta.b64 _, [%0];" ::"r"(bar) : "memory");
}
template <int OFF> __device__ __forceinline__ void lds2_if(bool on, uint32_t p, uint32_t* r) {
  asm volatile("{\n.reg .pred p;\nsetp.ne.b32 p, %9, 0;\n@p ld.shared.v4.b32 {%0, %1, %2, %3}, [%8 + %10];\n"
               "@p ld.shared.v4.b32 {%4, %5, %6, %7}, [%8 + %11];\n}\n"
               : "+r"(r[0]), "+r"(r[1]), "+r"(r[2]), "+r"(r[3]), "+r"(r[4]), "+r"(r[5]), "+r"(r[6]), "+r"(r[7])
               : "r"(p), "r"((int)on), "n"(OFF), "n"(OFF + 512) : "memory");
}
__device__ __forceinline__ void lds128(uint32_t p, uint32_t& a, uint32_t& b, uint32_t& c, uint32_t& d) {
  asm volatile("ld.shared.v4.b32 {%0, %1, %2, %3}, [%4];" : "=r"(a), "=r"(b), "=r"(c), "=r"(d) : "r"(p) : "memory");
}
__device__ __forceinline__ void wait_count(const unsigned int* p, uint32_t target) {
  asm volatile("{\n.reg .pred p;\n.reg .u32 n, v;\nmov.u32 n, 0;\n"
               "LOOP:\nld.acquire.gpu.global.u32 v, [%0];\nsetp.ge.u32 p, v, %1;\n@p bra DONE;\n"
               "nanosleep.u32 %2;\nadd.u32 n, n, 1;\nsetp.lt.u32 p, n, 0x400000;\n@p bra LOOP;\ntrap;\n"
               "DONE:\n}\n" ::"l"(p), "r"(target), "n"(300) : "memory");
}

__device__ __forceinline__ int o_wave(int a, int b, int i) {
  const int p = min(3, b - a - 1);
  return i < p ? b - 2 - i : i == p ? b - 1 : b - 1 - i;
}

struct Cursor {
  uint32_t n;
  __device__ __forceinline__ uint32_t off() const { return n & (8 * NBAR - 8); }
  __device__ __forceinline__ uint32_t ph() const { return (n / (8 * NBAR)) & 1; }
  __device__ __forceinline__ void next() { n += 8; }
};

constexpr float kScaleLog2 = 0.07216878364870322f * 1.4426950408889634f;
constexpr float kSumLimit = 1048576.0f;
constexpr float kMaxLag = 8.0f;

__global__ void __launch_bounds__(384, 1)
fused_kernel(const __grid_constant__ Params P) {
  extern __shared__ uint8_t smem_raw[];
  const uint32_t sbase = (smem_u32(smem_raw) + 1023) & ~1023u;
  const uint32_t full0 = sbase + RING, empty0 = full0 + 8 * NBAR, odone = empty0 + 8 * NBAR, oready0 = odone + 8;
  const uint32_t fenced = oready0 + 64, hready0 = fenced + 8, met = hready0 + 8 * MAX_PARK;
  const uint32_t rank = blockIdx.x & 1;
  const int role = (blockIdx.x >> 1) + P.role0;
  const bool wide = P.wide;
  const uint32_t sub = wide ? (blockIdx.x >> 1) & (WIDE - 1) : 0;
  asm volatile("griddepcontrol.launch_dependents;");
  const bool helper = role >= N_CL;
  const int team = helper ? 0 : role >> 2, nt = role & 3, blk = team >> 3;
  const uint32_t* prog = P.ops[helper ? N_TEAM + 2 * (role - N_CL) : team];
  auto q_role = [&](uint32_t op) { return helper ? (int)(((op >> 3) & 60) | ((op >> 12) & 3)) : role; };
  auto o_role = [&](uint32_t op) { return helper ? (int)(((op >> 26) & 56) | ((op >> 9) & 7)) : role; };
  auto spare = [&](int b) { return WIDE == 4 && wide && b >= 2 ? b - 2 : 8; };
  auto alone = [&]() {
    uint32_t v;
    mbar_wait(met, 0);
    asm volatile("ld.shared.u32 %0, [%1];" : "=r"(v) : "r"(met + 8) : "memory");
    return v;
  };
  const int wid = __shfl_sync(0xffffffffu, (int)(threadIdx.x >> 5), 0);
  const int wg = wid >> 2;

  const uint32_t op0 = P.first[helper ? N_TEAM + role - N_CL : team];
  if (__builtin_expect(wid == 8, 1)) {
    if (elect()) {
#pragma unroll
      for (int k = 0; k < EARLY; k++) mbar_init(full0 + 8 * k, 1);
      asm volatile("fence.mbarrier_init.release.cluster;" ::: "memory");
      if ((op0 & 3) == OP_Q) {
        const int qr = q_role(op0);
#pragma unroll
        for (int k = 0; k < EARLY; k++) {
          mbar_expect(full0 + 8 * k, SZ_WQ + SZ_A);
          tma2d(sbase + k * (SZ_WQ + SZ_A) + SZ_WQ, &P.x[qr >> 5], full0 + 8 * k, 64 * k, ((qr >> 2) & 7) * kSq + rank * 128);
          tma3d(sbase + k * (SZ_WQ + SZ_A), &P.wq[qr >> 5], full0 + 8 * k, 0, 64 * k, 3 * (4 * ((op0 >> 2) & 7) + (qr & 3)));
          tma3d(sbase + k * (SZ_WQ + SZ_A) + SZ_WQ / 2, &P.wq[qr >> 5], full0 + 8 * k, 0, 64 * k + 32, 3 * (4 * ((op0 >> 2) & 7) + (qr & 3)));
        }
      }
      asm volatile("prefetch.tensormap [%0];" ::"l"(&P.kv[blk]) : "memory");
      asm volatile("prefetch.tensormap [%0];" ::"l"(&P.kv[blk + 2]) : "memory");
    }
  } else if (threadIdx.x == 0) {
#pragma unroll
    for (int i = EARLY; i < 2 * NBAR + 11 + MAX_PARK; i++) mbar_init(full0 + 8 * i, i >= NBAR && i <= 2 * NBAR ? (wide ? 8 * WIDE + 8 : 16) : 1);
    asm volatile("fence.mbarrier_init.release.cluster;" ::: "memory");
  }
  __syncwarp();
  asm volatile("barrier.cluster.arrive.relaxed.aligned;\nbarrier.cluster.wait.aligned;" ::: "memory");

  if (wg == 2) {
    asm volatile("setmaxnreg.dec.sync.aligned.u32 24;");
    if (wid == 8) {
      Cursor tail{0u - 8}, head{0};
      int sh = 0;
      uint32_t cur = 0, used = 0;
      uint64_t fifo = 0;
      uint32_t oready = oready0;
      const uint64_t pol = evict_first();
      const uint16_t pair = 3 << (2 * sub), rows = (wide ? 0x55 >> (8 - 2 * WIDE) : 1) << rank;
      const uint32_t piece = wide ? SZ_A / WIDE : SZ_A;
      struct Load { uint32_t dst, bar, wbar, wph; int c0; const void* ptr; bool wait; };
      auto reserve = [&](uint32_t bytes, bool last, uint32_t off, int c0, const void* ptr) {
        uint32_t fp = bytes >> 12;
        if (cur + fp > (RING >> 12)) { fp += (RING >> 12) - cur; cur = 0; }
        used += fp;
        bool wait = false;
        while (used > (RING >> 12)) {
          wait = true;
          tail.next();
          used -= (uint32_t)fifo & 31;
          fifo >>= 5;
          sh -= 5;
        }
        fifo += (uint64_t)fp << sh;
        Load l{sbase + (cur << 12) + off, full0 + head.off(), empty0 + tail.off(), tail.ph(), c0, ptr, wait};
        cur += bytes >> 12;
        sh += last ? 5 : 0;
        head.n += last ? 8 : 0;
        asm volatile("" : "+r"(l.dst), "+r"(l.bar), "+r"(l.c0), "+l"(l.ptr), "+r"(l.wbar), "+r"(l.wph));
        return l;
      };
      auto vacated = [&](const Load& l) { if (l.wait) mbar_wait(l.wbar, l.wph); };
      auto written = [&](uint32_t flag) {
        mbar_wait(flag, 0);
        asm volatile("fence.proxy.async.global;" ::: "memory");
      };
      for (int pc = 0;; pc++) {
        if (pc == 1) prog += __shfl_sync(0xffffffffu, alone(), 0);
        const uint32_t op = prog[pc];
        const int type = op & 3, a = (op >> 2) & 7;
        if (type == OP_END) break;
        if (type == OP_Q) {
          const int qr = q_role(op);
          const CUtensorMap *mw = &P.wq[qr >> 5], *mx = &P.x[(qr >> 5) + (wide ? 2 : 0)];
          asm volatile("" : "+l"(mw), "+l"(mx));
          auto res_w = [&](int k) { return reserve(SZ_WQ, false, rank * (SZ_WQ / 2), 64 * k + 32 * rank, mw); };
          auto load_w = [&](const Load& w, int k) {
            vacated(w);
            if ((pc > 0 || k >= EARLY) && elect()) tma3d_mc(w.dst, (const CUtensorMap*)w.ptr, w.bar, 0, w.c0, 3 * (4 * a + (qr & 3)), pair);
          };
          auto load_x = [&](const Load& x, int k) {
            vacated(x);
            if ((pc > 0 || k >= EARLY) && elect()) {
              tma2d_mc(x.dst, (const CUtensorMap*)x.ptr, x.bar, x.c0, ((qr >> 2) & 7) * kSq + rank * 128 + sub * (128 / WIDE), rows);
              mbar_expect(x.bar, SZ_WQ + SZ_A);
            }
          };
#pragma unroll 1
          for (int k = 0; k < 10; k++) {
            load_w(res_w(k), k);
            load_x(reserve(SZ_A, true, sub * (SZ_A / WIDE), 64 * k, mx), k);
          }
        } else if (type == OP_A) {
          const uint32_t nop = prog[pc + 1];
          const int row8 = ((team & 7) * kH + nt) * (kSk / 8) + 4 * rank, wave8 = 4 * (kSk / 8);
          auto transit = [&]() {
            const Cursor c{head.n - 8 * (KV_TRANSIT + 1)};
            mbar_wait(full0 + c.off(), c.ph());
          };
          const char* map = (const char*)&P.kv[blk];
          asm volatile("" : "+l"(map));
          int t = (op & F_PARK) ? 1 : 0, c0 = row8 + a * wave8 + 8 * t, isv = 0;
#pragma unroll 1
          for (; t < 31; t++) {
            const Load l = reserve(SZ_KV, true, rank * (SZ_KV / 2), c0, map + isv);
            vacated(l);
            if (t >= KV_TRANSIT) transit();
            if (elect()) {
              tma4d_mc_hint(l.dst, (const CUtensorMap*)l.ptr, l.bar, l.c0, pol, pair);
              mbar_expect(l.bar, SZ_KV);
            }
            isv = (t & 1) << 8;
            c0 += isv ? -8 : t ? 16 : 8;
          }
          const int next = (nop >> 2) & 7;
          if ((nop & 3) == OP_A) written((nop & F_HELP) ? hready0 + 8 * ((nop >> 10) & 3) : fenced);
#pragma unroll 1
          for (int i = (nop & 3) == OP_A ? 0 : 3; i < 4; i++) {
            const Load l = reserve(SZ_KV, true, i < 2 ? 0 : rank * (SZ_KV / 2), i == 3 ? c0 - 8 : row8 + next * wave8,
                                   i < 2 ? (const char*)&g_o[((team * 2 + rank) * 120 + 3 * (4 * next + nt)) * 1024 + i * (SZ_PARK / 16)] : map + ((i & 1) << 8));
            vacated(l);
            if (i < 2) {
              if (elect()) bulk_load_hint(l.dst, l.ptr, SZ_PARK, l.bar, pol);
              __syncwarp();
            } else {
              transit();
              if (elect()) tma4d_mc_hint(l.dst, (const CUtensorMap*)l.ptr, l.bar, l.c0, pol, pair);
              __syncwarp();
            }
            if (elect()) mbar_expect(l.bar, SZ_KV);
          }
        } else {
          const int b = (op >> 5) & 15, ro = o_role(op);
          const CUtensorMap* mw = &P.wo[ro >> 5];
          const uint4* so = &g_o[((ro >> 2) * 2 + rank) * 120 * 1024 + sub * (1024 / WIDE)];
          asm volatile("" : "+l"(mw), "+l"(so));
#pragma unroll 1
          for (int j = 0; j < b - a; j++) {
            const int w = o_wave(a, b, j);
            written(oready);
            oready += 8;
#pragma unroll 1
            for (int k = 12 * w; k < 12 * w + 12; k++) {
              const Load o = reserve(SZ_A, false, sub * (SZ_A / WIDE), 0, so + k * 1024);
              vacated(o);
              if (elect()) bulk_load_mc(o.dst, o.ptr, piece, o.bar, pol, rows);
              const Load w = reserve(SZ_WO, true, rank * (SZ_WO / 2), 8 * k + 4 * rank, mw);
              vacated(w);
              if (elect()) {
                tma5d_mc(w.dst, (const CUtensorMap*)w.ptr, w.bar, w.c0, 5 * (ro & 3), pair);
                mbar_expect(w.bar, SZ_WO + SZ_A);
              }
            }
          }
          if ((op & F_LD) && (op & F_PARK)) written(hready0 + 8 * (MAX_PARK - 1));
#pragma unroll 1
          for (int i = (op & F_LD) ? 0 : 5; i < ((op & F_ST) ? 5 : 6); i++) {
            const Load l = reserve(i < 5 ? SZ_PART : SZ_OUT, i < 5, 0, 0, &g_o[((team * 2 + rank) * 120 + 3 * (4 * spare((op & F_PARK) ? 0 : a) + nt) + (i < 2 ? i : i + 10)) * 1024]);
            vacated(l);
            if (i < 5 && elect()) bulk_load_hint(l.dst, l.ptr, SZ_PART, l.bar, pol);
            if (elect()) mbar_expect(l.bar, i < 5 ? SZ_PART : 0);
          }
        }
      }
#pragma unroll 1
      for (Cursor c{head.n - 8 * NBAR}; c.n != head.n; c.next()) mbar_wait(empty0 + c.off(), c.ph());
    } else if (threadIdx.x == 288) {
      uint32_t ph = 0;
      bool first = true;
      prog += alone();
      for (int pc = 0;; pc++) {
        const uint32_t op = prog[pc];
        if ((op & 3) == OP_END) break;
        if ((op & 3) != OP_A && !helper) continue;
        mbar_wait_long(odone, ph);
        ph ^= 1;
        unsigned int* flag = !helper ? &g_done[(team * 2 + rank) * 8 + ((op >> 2) & 7)]
                             : (op & 3) == OP_Q ? &g_help[(q_role(op) * 2 + rank) * MAX_PARK + ((op >> 10) & 3)]
                                                : &g_help[(o_role(op) * 2 + rank) * MAX_PARK + MAX_PARK - 1];
        asm volatile("red.release.gpu.global.add.u32 [%0], 1;" ::"l"(flag) : "memory");
        if (first) mbar_arrive(fenced);
        first = false;
      }
    } else if (threadIdx.x == 320) {
      uint32_t meet = 1;
      if (wide || P.role0) {
        meet = 0;
        for (int n = 0; wide && !meet && n < 300; n++) {
          __nanosleep(100);
          asm volatile("ld.relaxed.gpu.global.u32 %0, [%1];" : "=r"(meet) : "l"(&g_meet[0]) : "memory");
        }
        if (!meet && !(meet = atomicCAS(&g_meet[0], 0u, wide ? 2u : 1u))) meet = wide ? 2 : 1;
        if (atomicAdd(&g_meet[1], 1u) == 2 * (N_CL + N_HELP) - 1) { g_meet[0] = 0; g_meet[1] = 0; }
      }
      prog += (meet - 1) * (N_ROWS * MAX_OPS);
      asm volatile("st.shared.u32 [%0], %1;" ::"r"(met + 8), "r"((meet - 1) * (N_ROWS * MAX_OPS)) : "memory");
      mbar_arrive(met);
      uint32_t oready = oready0;
      for (int pc = 0;; pc++) {
        const uint32_t op = prog[pc];
        if ((op & 3) == OP_END) break;
        if ((op & 3) == OP_O) {
          const int a = (op >> 2) & 7, b = (op >> 5) & 15;
#pragma unroll 1
          for (int i = 0; i < b - a; i++) {
            const int ci = ((o_role(op) >> 2) * 2 + rank) * 8 + o_wave(a, b, i);
            wait_count(&g_done[ci], 4);
            mbar_arrive(oready);
            oready += 8;
            if (atomicAdd(&g_seen[ci], 1u) == 3u) { g_seen[ci] = 0; g_done[ci] = 0; }
          }
        }
        if ((op & 3) != OP_Q && (op & F_HELP) && (op & F_PARK)) {
          unsigned int* flag = &g_help[(role * 2 + rank) * MAX_PARK + ((op >> 10) & 3)];
          wait_count(flag, 1);
          mbar_arrive(hready0 + 8 * ((op >> 10) & 3));
          *flag = 0;
        }
      }
    }
  } else {
    asm volatile("setmaxnreg.inc.sync.aligned.u32 240;");
    const int lane = threadIdx.x & 31, warp = wid & 3;
    uint32_t empty_rem;
    const bool tell = lane < (wide ? WIDE + 1 : 2);
    asm volatile("mapa.shared::cluster.u32 %0, %1, %2;" : "=r"(empty_rem) : "r"(empty0), "r"((2 * sub + rank) ^ (!tell ? 0 : lane < 2 ? lane : 2 * lane - 2)));
    auto release = [&](int slot) { mbar_arrive_cluster_if(tell, empty_rem + slot); };
    Cursor r{0};
    const uint32_t ring16 = (sbase & 0x3FFFF) >> 4;
    uint32_t cur = ring16;
    bool rdy0 = false, rdy1 = false;
    auto probe1 = [&]() { rdy0 = mbar_test(full0 + r.off(), r.ph()); };
    auto probe2 = [&]() {
      Cursor n = r;
      rdy0 = mbar_test(full0 + n.off(), n.ph());
      n.next();
      rdy1 = mbar_test(full0 + n.off(), n.ph());
    };
    auto take = [&](bool rdy, uint32_t bytes, uint32_t& addr) {
      const int bi = r.off();
      if (!__all_sync(0xffffffffu, rdy)) mbar_wait_math(full0 + r.off(), r.ph());
      r.next();
      if (cur > ring16 + ((RING - bytes) >> 4)) cur = ring16;
      addr = cur;
      cur += bytes >> 4;
      return bi;
    };
    auto at = [&](uint32_t a16) {
      uint32_t a = sbase + (a16 - ring16) * 16;
      asm("" : "+r"(a));
      return a;
    };
    auto second = [&](uint32_t bytes) {
      if (cur > ring16 + ((RING - bytes) >> 4)) cur = ring16;
      cur += bytes >> 4;
      return cur - (bytes >> 4);
    };
    const int row = wg * 64 + warp * 16 + (lane >> 2);
    int img0 = (row * 4 + ((lane & 3) ^ ((row >> 1) & 3))) * 16;
    uint4* pend = nullptr;
    const uint64_t spol = evict_first();
    int pc = 0;
    uint32_t op = prog[0];
    auto enter = [&]() {
      r.n = op >> 12; cur = ring16 + (((op >> 20) & 63) << 8);
    };
    auto drain = [&](uint32_t (&t)[48], uint32_t c) {
      if (!(op & (3u << 26)) || c >= 6) return;
#pragma unroll
      for (int i = 0; i < 6; i++)
        stg2_if(c == i, pend + i * 512, t[8 * i], t[8 * i + 1], t[8 * i + 2], t[8 * i + 3],
                t[8 * i + 4], t[8 * i + 5], t[8 * i + 6], t[8 * i + 7], spol);
      if ((op & (1u << 26)) && c == 5) {
        __syncwarp();
        mbar_arrive_if(tell, odone);
      }
    };
    float s[32], o[96], c[80];
    uint32_t q[48], pa[16], pb[16];
    float mc0, mc1, l0, l1;
    bool gen;
    auto soft = [&](float (&s)[32], uint32_t (&pout)[16], bool first) {
      if (first) { gen = false; mc0 = 0.f; mc1 = 0.f; }
      float b0, b1;
      for (;;) {
        if (gen) {
          float m0 = fmaxf(s[0], s[1]), m1 = fmaxf(s[2], s[3]);
#pragma unroll
          for (int i = 1; i < 8; i++) { m0 = fmaxf(m0, fmaxf(s[4 * i], s[4 * i + 1])); m1 = fmaxf(m1, fmaxf(s[4 * i + 2], s[4 * i + 3])); }
          m0 = fmaxf(m0, __shfl_xor_sync(0xffffffffu, m0, 1)); m1 = fmaxf(m1, __shfl_xor_sync(0xffffffffu, m1, 1));
          m0 = fmaxf(m0, __shfl_xor_sync(0xffffffffu, m0, 2)); m1 = fmaxf(m1, __shfl_xor_sync(0xffffffffu, m1, 2));
          if (first) {
            mc0 = m0; mc1 = m1;
          } else if (__any_sync(0xffffffffu, !(m0 <= mc0 + kMaxLag && m1 <= mc1 + kMaxLag))) {
            m0 = fmaxf(mc0, m0); m1 = fmaxf(mc1, m1);
            const float a0 = ex2(mc0 - m0), a1 = ex2(mc1 - m1);
            mc0 = m0; mc1 = m1;
            l0 *= a0; l1 *= a1;
            wg_wait<0>();
            fence_regs(o);
#pragma unroll
            for (int i = 0; i < 96; i++) o[i] *= i & 2 ? a1 : a0;
          }
#pragma unroll
          for (int i = 0; i < 32; i++) s[i] -= i & 2 ? mc1 : mc0;
        }
#pragma unroll
        for (int i = 0; i < 8; i++) {
          const float e1 = ex2(s[4 * i + 1]), e0 = ex2(s[4 * i]), e3 = ex2(s[4 * i + 3]), e2 = ex2(s[4 * i + 2]);
          pout[2 * i] = pack_bf16(e0, e1);
          b0 = i ? b0 + fadd(e1, e0) : fadd(e1, e0);
          pout[2 * i + 1] = pack_bf16(e2, e3);
          b1 = i ? b1 + fadd(e3, e2) : fadd(e3, e2);
        }
        if (!__any_sync(0xffffffffu, !gen && !(fmaxf(b0, b1) <= kSumLimit && (!first || fminf(b0, b1) >= 1.0f / kSumLimit)))) break;
        gen = __any_sync(0xffffffffu, true);
      }
      l0 = first ? b0 : l0 + b0;
      l1 = first ? b1 : l1 + b1;
    };
    auto qk = [&](float (&s)[32], uint32_t ak, int k0, int k1) {
#pragma unroll
      for (int kk = k0; kk < k1; kk++)
        wgmma_rs_n64<0>(s, q[4 * kk], q[4 * kk + 1], q[4 * kk + 2], q[4 * kk + 3], mk_desc(ak, 16, KV_SBO, 1, (kk >> 2) * KV_CH + (kk & 3) * 2), kk != 0);
      wg_commit();
    };
    auto pv = [&](uint32_t (&pin)[16], uint32_t av, int acc) {
#pragma unroll
      for (int kk = 0; kk < 4; kk++)
        wgmma_rs_n192<1>(o, pin[4 * kk], pin[4 * kk + 1], pin[4 * kk + 2], pin[4 * kk + 3], mk_desc(av, KV_CH * 16, KV_SBO, 1, kk * (KV_SBO / 8)), acc || (kk != 0));
      wg_commit();
    };
    auto xw = [&](uint32_t ad, int acc) {
      const uint32_t da = second(SZ_A) + wg * 512;
      wg_fence();
#pragma unroll
      for (int kk = 0; kk < 4; kk++)
        wgmma_ss_n192<1>(o, mk_desc(da, 16, 1024, 1, kk * 2), mk_desc(ad, 4096, 1024, 1, (kk & 1) * 128 + (kk >> 1) * 768), acc || kk != 0);
      wg_commit();
    };
    auto ow = [&](int acc, int prev) {
      uint32_t da;
      const int bi = take(rdy0, SZ_A, da);
      const uint32_t db = second(SZ_WO);
      da += wg * 256;
      wg_fence();
      wgmma_ss_n160<1>(c, mk_desc(da, 16, 512, 2), mk_desc(db, 2048, 512, 2), acc);
      wgmma_ss_n160<1>(c, mk_desc(da, 16, 512, 2, 2), mk_desc(db, 2048, 512, 2, 64), 1);
      wg_commit();
      if (acc == 1) { wg_wait<1>(); release(prev); }
      wgmma_ss_n160<1>(c, mk_desc(da, 16, 512, 2, 512), mk_desc(db, 2048, 512, 2, 640), 1);
      wgmma_ss_n160<1>(c, mk_desc(da, 16, 512, 2, 514), mk_desc(db, 2048, 512, 2, 704), 1);
      wg_commit();
      return bi;
    };
    auto st_part = [&](int i) {
      stg2_if(true, pend + i * 512, __float_as_uint(c[8 * i]), __float_as_uint(c[8 * i + 1]), __float_as_uint(c[8 * i + 2]), __float_as_uint(c[8 * i + 3]),
              __float_as_uint(c[8 * i + 4]), __float_as_uint(c[8 * i + 5]), __float_as_uint(c[8 * i + 6]), __float_as_uint(c[8 * i + 7]), spol);
    };
#pragma unroll
    for (int i = 0; i < 48; i++) q[i] = 0;
    enter();

    if ((op & 3) == OP_Q) {
      uint32_t ad;
      int bi0 = take(false, SZ_WQ, ad), k = 0, lag = 0;
      xw(ad, 0);
      for (;;) {
#pragma unroll 1
        for (;;) {
          drain(q, k - lag);
          probe1();
          wg_wait<0>();
          release(bi0);
          bi0 = take(rdy0, SZ_WQ, ad);
          if (++k == 8) break;
          xw(ad, 1);
        }
        if (wg) bar_sync(2, 256);
        xw(ad, 1);
        const int bi9 = take(false, SZ_WQ, ad);
        xw(ad, 1);
        if (!wg) asm volatile("bar.arrive 2, 256;" ::: "memory");
        k = 0; lag = 0;
        if (pc == 0) prog += __shfl_sync(0xffffffffu, alone(), 0);
        uint32_t nop = prog[++pc];
        wg_wait<1>();
        release(bi0);
        probe2();
        wg_wait<0>();
        fence_regs(o);
        release(bi9);
#pragma unroll
        for (int i = 0; i < 48; i++) q[i] = pack_bf16(o[2 * i] * kScaleLog2, o[2 * i + 1] * kScaleLog2);
        fence_regs(q);
        if (op & F_PARK) {
          const int qt = helper ? (op >> 5) & 15 : team, qm = helper ? (op >> 12) & 3 : nt;
          pend = (uint4*)((char*)&g_o[((qt * 2 + rank) * 120 + 3 * (4 * ((op >> 2) & 7) + qm)) * 1024] + img0);
          op = nop;
          enter();
          if ((op & 3) != OP_Q) break;
          const int b = take(rdy0, SZ_WQ, ad);
          xw(ad, 0);
          bi0 = take(rdy1, SZ_WQ, ad);
          xw(ad, 1);
          wg_wait<1>();
          release(b);
          k = 1; lag = 1;
          continue;
        }
        int wave = (op >> 2) & 7, sk1;
        uint32_t ak1;
        {
          float s0[32];
          const int sk0 = take(rdy0, SZ_KV, ad);
          wg_fence();
          qk(s0, ad, 0, 12);
          sk1 = take(rdy1, SZ_KV, ak1);
          wg_fence();
          qk(s, ak1, 0, S1A);
          probe1();
          wg_wait<1>();
          fence_regs(s0);
          release(sk0);
          soft(s0, pa, true);
        }
        float i0, i1;
        auto sums = [&]() {
          l0 += __shfl_xor_sync(0xffffffffu, l0, 1); l1 += __shfl_xor_sync(0xffffffffu, l1, 1);
          l0 += __shfl_xor_sync(0xffffffffu, l0, 2); l1 += __shfl_xor_sync(0xffffffffu, l1, 2);
          i0 = rcp(l0); i1 = rcp(l1);
          asm volatile("" : "+f"(i0), "+f"(i1));
        };
        auto target = [&]() {
          pend = (uint4*)((char*)&g_o[((team * 2 + rank) * 120 + 3 * (4 * wave + nt)) * 1024] + img0);
          asm volatile("" : "+l"(pend));
        };
        bool late = false;
#pragma unroll
        for (int i = 0; i < 16; i++) pb[i] = 0;
        for (;;) {
          nop = prog[++pc];
          {
            uint32_t av;
            const int sv = take(rdy0, SZ_KV, av);
            wg_fence();
            qk(s, ak1, S1A, 12);
            pv(pa, av, 0);
            if (late) {
              stg2_if(true, pend + 4 * 512, pb[0], pb[1], pb[2], pb[3], pb[4], pb[5], pb[6], pb[7], spol);
              stg2_if(true, pend + 5 * 512, pb[8], pb[9], pb[10], pb[11], pb[12], pb[13], pb[14], pb[15], spol);
              __syncwarp();
              mbar_arrive_if(tell, odone);
            }
            probe2();
            wg_wait<1>();
            fence_regs(s);
            release(sk1);
            soft(s, pb, false);
            wg_wait<0>();
            fence_regs(o);
            release(sv);
          }
          auto step = [&](uint32_t (&pin)[16], uint32_t (&pout)[16], bool hook, bool unpark) {
            uint32_t ak, av;
            const int sk = take(rdy0, SZ_KV, ak), sv = take(rdy1, SZ_KV, av);
            wg_fence();
            qk(s, ak, 0, 12);
            pv(pin, av, 1);
            if (hook && unpark) { take(false, SZ_PARK, ak); take(false, SZ_PARK, av); }
            probe2();
            wg_wait<1>();
            fence_regs(s);
            release(sk);
            if (hook) {
              lds2_if<0>(unpark, img0 + at(ak), q);
              lds2_if<8192>(unpark, img0 + at(ak), q + 8);
              lds2_if<16384>(unpark, img0 + at(ak), q + 16);
              lds2_if<0>(unpark, img0 + at(av), q + 24);
              lds2_if<8192>(unpark, img0 + at(av), q + 32);
              lds2_if<16384>(unpark, img0 + at(av), q + 40);
            }
            soft(s, pout, false);
            wg_wait<0>();
            fence_regs(o);
            release(sv);
          };
          const int jpark = (nop & 3) == OP_A ? 6 : 7;
#pragma unroll 1
          for (int jj = 0; jj < 7; jj++) {
            step(pb, pa, false, false);
            step(pa, pb, true, jj == jpark);
          }
          if ((nop & 3) != OP_A) break;
          uint32_t ak, av;
          release(Cursor{r.n - 16}.off());
          release(Cursor{r.n - 8}.off());
          const int sk0 = take(rdy0, SZ_KV, ak), sv = take(rdy1, SZ_KV, av);
          wg_fence();
          qk(s, ak, 0, 8);
          sched_fence(img0, P.zero);
          sums();
          sched_fence(img0, P.zero);
          qk(s, ak, 8, 12);
          pv(pb, av, 1);
          probe2();
          wg_wait<1>();
          fence_regs(s);
          release(sk0);
          soft(s, pa, true);
          sk1 = take(rdy0, SZ_KV, ak1);
          rdy0 = rdy1;
          wg_wait<0>();
          target();
          fence_regs(o);
          release(sv);
          uint32_t t[48];
#pragma unroll
          for (int j = 0; j < 6; j++) {
#pragma unroll
            for (int i = 0; i < 4; i++) {
              t[8 * j + i] = pack_bf16(o[16 * j + 4 * i] * i0, o[16 * j + 4 * i + 1] * i0);
              t[8 * j + i + 4] = pack_bf16(o[16 * j + 4 * i + 2] * i1, o[16 * j + 4 * i + 3] * i1);
            }
            if (j < 4)
            stg2_if(true, pend + j * 512, t[8 * j], t[8 * j + 1], t[8 * j + 2], t[8 * j + 3], t[8 * j + 4], t[8 * j + 5], t[8 * j + 6], t[8 * j + 7], spol);
            if (j == 3) { wg_fence(); qk(s, ak1, 0, 4); }
            if (j == 5) { wg_fence(); qk(s, ak1, 4, S1A); }
            sched_fence(img0, P.zero);
          }
          if (P.zero) {
#pragma unroll
            for (int j = 0; j < 4; j++)
              stg2_if(true, pend, t[8 * j], t[8 * j + 1], t[8 * j + 2], t[8 * j + 3], t[8 * j + 4], t[8 * j + 5], t[8 * j + 6], t[8 * j + 7], spol);
          }
          late = true;
#pragma unroll
          for (int i = 0; i < 16; i++) pb[i] = t[32 + i];
          wave = (nop >> 2) & 7;
        }
        const int sv = take(rdy0, SZ_KV, ad);
        wg_fence();
        pv(pb, ad, 1);
        sums();
        target();
        op = nop;
        enter();
        rdy0 = rdy1;
        auto convert = [&](float (&u)[96], int j0, int j1) {
#pragma unroll
          for (int i = 4 * j0; i < 4 * j1; i++) {
            q[8 * (i >> 2) + (i & 3)] = pack_bf16(u[4 * i], u[4 * i + 1]);
            q[8 * (i >> 2) + (i & 3) + 4] = pack_bf16(u[4 * i + 2], u[4 * i + 3]);
          }
        };
        if ((op & 3) != OP_O) {
          if ((op & 3) == OP_Q) bi0 = take(rdy0, SZ_WQ, ad);
          wg_wait<0>();
          fence_regs(o);
          release(sv);
          float u[96];
#pragma unroll
          for (int i = 0; i < 96; i++) u[i] = o[i] * (i & 2 ? i1 : i0);
          if ((op & 3) != OP_Q) { convert(u, 0, 6); break; }
          fence_regs(u);
          xw(ad, 0);
          sched_fence(img0, P.zero);
          fence_regs(u);
          convert(u, 0, 1);
          stg2_if(true, pend, q[0], q[1], q[2], q[3], q[4], q[5], q[6], q[7], spol);
          probe1();
          wg_wait<0>();
          release(bi0);
          bi0 = take(rdy0, SZ_WQ, ad);
          xw(ad, 1);
          sched_fence(img0, P.zero);
          fence_regs(u);
          convert(u, 1, 6);
          k = 1;
          continue;
        }
        int bi = ow(0, 0);
        wg_wait<2>();
        fence_regs(o);
        release(sv);
#pragma unroll
        for (int j = 0; j < 6; j++) {
          uint32_t t[8];
#pragma unroll
          for (int i = 0; i < 4; i++) {
            t[i] = pack_bf16(o[16 * j + 4 * i] * i0, o[16 * j + 4 * i + 1] * i0);
            t[i + 4] = pack_bf16(o[16 * j + 4 * i + 2] * i1, o[16 * j + 4 * i + 3] * i1);
          }
          stg2_if(true, pend + j * 512, t[0], t[1], t[2], t[3], t[4], t[5], t[6], t[7], spol);
          if (j == 5) {
            __syncwarp();
            mbar_arrive_if(tell, odone);
          }
          probe1();
          wg_wait<1>();
          bi = ow(1, bi);
          fence_regs(o);
        }
        {
          const int nk = 12 * (((op >> 5) & 15) - ((op >> 2) & 7)) - ((op & F_ST) ? 0 : 2);
#pragma unroll 1
          for (int k = 7; k < nk; k++) {
            probe1();
            wg_wait<1>();
            bi = ow(1, bi);
          }
        }
        if (!(op & F_ST)) {
          probe2();
          wg_wait<1>();
          if (wg) {
            wg_wait<0>();
            release(bi);
            bar_sync(2, 256);
          }
          bi0 = ow(2, 0);
          rdy0 = rdy1;
          const int b = ow(2, 0);
          if (!wg) asm volatile("bar.arrive 2, 256;" ::: "memory");
          wg_wait<4>();
          mbar_arrive_cluster_if(tell && !wg, empty_rem + bi);
          bi = b;
        }
        probe1();
        nop = prog[++pc];
        if (op & F_LD) {
          uint32_t t[80];
#pragma unroll
          for (int j = 0; j < 5; j++) {
            const int b = take(rdy0, SZ_PART, ad);
            probe1();
#pragma unroll
            for (int i = 4 * j; i < 4 * j + 4; i++)
              lds128(img0 + at(ad) + ((i >> 1) & 1) * 8192 + (i & 1) * 512, t[4 * i], t[4 * i + 1], t[4 * i + 2], t[4 * i + 3]);
            release(b);
          }
          wg_wait<0>();
          fence_regs(c);
#pragma unroll
          for (int i = 0; i < 80; i++) c[i] += __uint_as_float(t[i]);
        }
        if (!(op & F_ST)) {
          wg_wait<0>();
          fence_regs(c);
          release(bi0);
          release(bi);
          goto finish;
        }
        wave = spare((op >> 5) & 15);
        op = nop;
        enter();
        bi0 = take(rdy0, SZ_WQ, ad);
        xw(ad, 0);
        target();
        probe1();
        wg_wait<1>();
        fence_regs(c);
        release(bi);
        st_part(0); st_part(1);
        wg_wait<0>();
        release(bi0);
        bi0 = take(rdy0, SZ_WQ, ad);
        xw(ad, 1);
        st_part(2); st_part(3);
#pragma unroll
        for (int i = 0; i < 48; i++) q[i] = __float_as_uint(c[32 + i]);
        pend += 12 * 1024;
        k = 1; lag = 2;
      }
    }
    rdy0 = false;
    {
      uint32_t t[48];
#pragma unroll
      for (int i = 0; i < 48; i++) t[i] = q[i] ^ P.zero;
      while ((op & 3) == OP_O) {
        int bi = ow(0, 0);
#pragma unroll 1
        for (int k = 1; k < 12 * (int)(((op >> 5) & 15) - ((op >> 2) & 7)); k++) {
          drain(t, k - 1);
          probe1();
          wg_wait<1>();
          bi = ow(1, bi);
        }
        rdy0 = false;
        wg_wait<0>();
        fence_regs(c);
        pc++;
        release(bi);
        if (!(op & F_ST)) goto finish;
        const int ro = ((op >> 26) & 56) | ((op >> 9) & 7);
        pend = (uint4*)((char*)&g_o[(((ro >> 2) * 2 + rank) * 120 + 3 * (4 * spare(0) + (ro & 3))) * 1024] + img0);
#pragma unroll
        for (int i = 0; i < 4; i++) st_part(i);
        pend += 12 * 1024;
#pragma unroll
        for (int i = 0; i < 48; i++) t[i] = __float_as_uint(c[32 + i]) ^ P.zero;
        op = prog[pc];
        enter();
      }
      for (int i = 0; i < 6; i++) drain(t, i);
    }
    if (false) {
    finish:
      uint32_t ad;
      take(rdy0, SZ_OUT, ad);
      const uint32_t wstage = sbase + (ad - ring16) * 16 + (wg * 4 + warp) * 5120;
      const uint32_t sa = wstage + (lane & 15) * 64;
#pragma unroll
      for (int i = 0; i < 10; i++) {
        const int u = (i & 1) * 2 + (lane >> 4);
        stsm4(sa + (i >> 1) * 1024 + ((u ^ ((lane >> 1) & 3)) << 4), pack_bf16(c[8 * i], c[8 * i + 1]), pack_bf16(c[8 * i + 2], c[8 * i + 3]),
              pack_bf16(c[8 * i + 4], c[8 * i + 5]), pack_bf16(c[8 * i + 6], c[8 * i + 7]));
      }
      asm volatile("fence.proxy.async.shared::cta;" ::: "memory");
      __syncwarp();
      if (lane == 0) {
        tma3d_store(&P.out, wstage, 0, (team & 7) * kSq + rank * 128 + wg * 64 + warp * 16, blk * 20 + nt * 5);
        asm volatile("cp.async.bulk.commit_group;\ncp.async.bulk.wait_group.read 0;" ::: "memory");
      }
    }
  }
}

typedef CUresult (*EncodeFn)(CUtensorMap*, CUtensorMapDataType, cuuint32_t, void*, const cuuint64_t*, const cuuint64_t*,
                             const cuuint32_t*, const cuuint32_t*, CUtensorMapInterleave, CUtensorMapSwizzle,
                             CUtensorMapL2promotion, CUtensorMapFloatOOBfill);

void encode(EncodeFn fn, CUtensorMap* m, const void* ptr, int rank, const cuuint64_t* dims, const cuuint64_t* strides,
            const cuuint32_t* box, CUtensorMapSwizzle swz) {
  const cuuint32_t es[5] = {1, 1, 1, 1, 1};
  CUresult r = fn(m, CU_TENSOR_MAP_DATA_TYPE_BFLOAT16, rank, const_cast<void*>(ptr), dims, strides, box, es,
                  CU_TENSOR_MAP_INTERLEAVE_NONE, swz, CU_TENSOR_MAP_L2_PROMOTION_L2_128B, CU_TENSOR_MAP_FLOAT_OOB_FILL_NONE);
  if (r != CUDA_SUCCESS) fprintf(stderr, "cuTensorMapEncodeTiled failed: %d\n", (int)r);
}

void annotate(uint32_t* ops, int n, bool helper) {
  uint32_t items = 0, cur = 0, pend = 0;
  auto item = [&](uint32_t bytes, int count, uint32_t bytes2 = 0) {
    for (int i = 0; i < count; i++) {
      if (cur + bytes > RING) cur = 0;
      cur += bytes;
      if (cur + bytes2 > RING) cur = 0;
      cur += bytes2;
      items++;
    }
  };
  for (int i = 0; i <= n; i++) {
    const uint32_t op = ops[i];
    ops[i] |= (items % (2 * NBAR)) << 15 | (cur >> 12) << 20 | pend << 26;
    if ((op & 3) == OP_Q) { item(SZ_WQ, 10, SZ_A); pend = (op & F_PARK) ? (helper ? 1 : 2) : 0; }
    if ((op & 3) == OP_A) {
      item(SZ_KV, (op & F_PARK) ? 30 : 31);
      if ((ops[i + 1] & 3) == OP_A) { item(SZ_PARK, 2); item(SZ_KV, 1); }
      item(SZ_KV, 1);
      pend = 1;
    }
    if ((op & 3) == OP_O) {
      item(SZ_A, 12 * (((op >> 5) & 15) - ((op >> 2) & 7)), SZ_WO);
      if (op & F_LD) item(SZ_PART, 5);
      pend = (op & F_ST) ? (helper ? 1 : 2) : 0;
    }
  }
}

void compile_programs(const char* const* text, bool helpers, uint32_t (*rows)[MAX_OPS]) {
  struct Req { int when, team, wave, slot; } req[N_TEAM * MAX_PARK];
  int n_req = 0;
  for (int t = 0; t < N_TEAM; t++) {
    uint32_t* ops = rows[t];
    int n = 0, flags[8] = {0, 0, 0, 0, 0, 0, 0, 0}, n_park = 0, last_o = -1, when = 0, given = 0;
    for (const char* s = text[t]; *s; s++) {
      const int a = s[1] - '0';
      if (*s == 'Q' || (*s == 'H' && !helpers)) { ops[n++] = OP_Q | a << 2; when += 10; }
      else if (*s == 'P') { flags[a] = F_PARK; ops[n++] = OP_Q | a << 2 | flags[a]; when += 10; }
      else if (*s == 'H') { req[n_req++] = {when, t, a, n_park}; flags[a] = F_PARK | F_HELP | n_park++ << 10; }
      else if (*s == 'A') { ops[n++] = OP_A | a << 2 | flags[a]; when += 32; }
      else if (*s == 'G') { given = a; if (helpers) req[n_req++] = {1000, t, 0, -a}; }
      else if (*s == 'O') {
        ops[n] = OP_O | a << 2 | (s[2] - '0') << 5;
        if (given) ops[n] = helpers ? ops[n] | F_LD | F_PARK | (MAX_PARK - 1) << 10 : ops[n] & ~(7u << 2);
        if (last_o >= 0) { ops[last_o] |= F_ST; ops[n] |= F_LD; }
        last_o = n++;
        when += 10 * (s[2] - s[1]);
      }
    }
    for (int i = n; i < MAX_OPS; i++) ops[i] = OP_END;
    annotate(ops, n, false);
  }
  for (int i = 1; i < n_req; i++)
    for (int j = i; j > 0 && req[j].when < req[j - 1].when; j--) { Req r = req[j]; req[j] = req[j - 1]; req[j - 1] = r; }
  for (int h = 0; h < N_HELP; h++) {
    uint32_t* ops = rows[N_TEAM + 2 * h];
    int n = 0;
    for (int i = 0; i < n_req; i++)
      for (int m = h; m < 4; m += N_HELP) {
        const uint32_t ro = 4 * req[i].team + m;
        ops[n++] = req[i].slot >= 0 ? OP_Q | req[i].wave << 2 | req[i].team << 5 | F_PARK | req[i].slot << 10 | m << 12
                                    : OP_O | -req[i].slot << 5 | F_ST | (ro & 7) << 9 | (ro >> 3) << 29;
      }
    for (int i = n; i < 2 * MAX_OPS; i++) ops[i] = OP_END;
    annotate(ops, n, true);
  }
}

const char* const kPrograms[N_TEAM] = {
  "Q0A0Q1A1Q2A2Q3A3Q4A4O05Q5A5Q6A6H7A7O58",
  "Q0A0Q1A1H2A2Q3A3O03Q4A4Q5A5Q6A6Q7A7O38",
  "Q0A0H1A1Q2A2O03Q3A3Q4A4Q5A5Q6A6Q7A7O38",
  "Q0A0Q1A1Q2A2Q3A3Q4A4O05Q5A5Q6A6H7A7O58",
  "Q0A0Q1A1Q2A2Q3A3Q4A4O05Q5A5Q6A6H7A7O58",
  "Q0A0Q1A1H2A2O03Q3A3Q4A4Q5A5Q6A6Q7A7O38",
  "Q0A0Q1A1Q2A2O03Q3A3Q4A4H5A5Q6A6Q7A7O38",
  "Q0A0Q1A1Q2A2O03Q3A3H4A4Q5A5Q6A6Q7A7O38",
  "P3Q0A0Q1A1Q2A2A3Q4A4Q5A5Q6A6H7A7O08",
  "Q0A0Q1A1Q2A2Q3A3H4A4Q5A5Q6A6Q7A7O08",
  "P3P7Q0A0Q1A1Q2A2A3Q4A4H5A5Q6A6A7G1O18",
  "Q0A0Q1A1Q2A2H3A3Q4A4Q5A5Q6A6Q7A7O08",
  "P3Q0A0Q1A1Q2A2A3Q4A4Q5A5H6A6Q7A7O08",
  "P7Q0A0Q1A1Q2A2Q3A3Q4A4Q5A5Q6A6A7G1O18",
  "Q0A0Q1A1Q2A2H3A3Q4A4Q5A5Q6A6Q7A7O08",
  "P3Q0A0Q1A1Q2A2A3H4A4Q5A5Q6A6Q7A7G1O18",
};

cudaLaunchConfig_t config(int clusters, int size, cudaLaunchAttribute* at) {
  cudaLaunchConfig_t cfg = {};
  cfg.gridDim = dim3(clusters * size); cfg.blockDim = dim3(384); cfg.dynamicSmemBytes = SMEM_BYTES; cfg.stream = cudaStreamPerThread;
  at[0].id = cudaLaunchAttributeClusterDimension; at[0].val.clusterDim.x = size; at[0].val.clusterDim.y = 1; at[0].val.clusterDim.z = 1;
  at[1].id = cudaLaunchAttributeProgrammaticStreamSerialization; at[1].val.programmaticStreamSerializationAllowed = 1;
  cfg.attrs = at; cfg.numAttrs = 1;
  return cfg;
}

void launch(Params& P, int role0, int clusters, int size, bool overlap) {
  cudaLaunchAttribute at[2];
  cudaLaunchConfig_t cfg = config(clusters, size, at);
  cfg.numAttrs = overlap ? 2 : 1;
  for (int i = 0; i < 30; i++) P.first[i] = i < N_TEAM ? P.ops[i][0] : i < N_TEAM + N_HELP ? P.ops[2 * i - N_TEAM][0] : 0;
  P.role0 = role0; P.wide = size > 2;
  cudaLaunchKernelEx(&cfg, fused_kernel, P);
}

const char* const* bench_programs() {
  return kPrograms;
}

}

extern "C" void kernel_launch(void* const* d_in, const int* in_sizes, int n_in, void* d_out, int out_size) {
  (void)in_sizes; (void)n_in; (void)out_size;
  static EncodeFn fn = nullptr;
  static int n_clusters = 0, n_wide = 0;
  if (!fn) {
    cudaDriverEntryPointQueryResult qr;
    void* f = nullptr;
    cudaGetDriverEntryPoint("cuTensorMapEncodeTiled", &f, cudaEnableDefault, &qr);
    fn = (EncodeFn)f;
    cudaFuncSetAttribute(fused_kernel, cudaFuncAttributeMaxDynamicSharedMemorySize, SMEM_BYTES);
    cudaLaunchAttribute at[2];
    cudaLaunchConfig_t cfg = config(N_CL + N_HELP, 2, at);
    if (cudaOccupancyMaxActiveClusters(&n_clusters, fused_kernel, &cfg) != cudaSuccess || n_clusters < 1) n_clusters = 1;
    cfg = config(N_WIDE / WIDE, 2 * WIDE, at);
    if (cudaOccupancyMaxActiveClusters(&n_wide, fused_kernel, &cfg) != cudaSuccess) n_wide = 0;
    (void)cudaGetLastError();
  }
  Params P;
  const CUtensorMapSwizzle S128 = CU_TENSOR_MAP_SWIZZLE_128B, S64 = CU_TENSOR_MAP_SWIZZLE_64B;
  for (int blk = 0; blk < 2; blk++) {
    void* const* in = d_in + 5 * blk;
    { const cuuint64_t d[] = {kD, kB * kSq}, s[] = {kD * 2}; const cuuint32_t b[] = {64, 128};
      encode(fn, &P.x[blk], in[0], 2, d, s, b, S128);
      const cuuint32_t b2[] = {64, 128 / WIDE};
      encode(fn, &P.x[2 + blk], in[0], 2, d, s, b2, S128); }
    { const cuuint64_t d[] = {64, 8, 3, (cuuint64_t)kB * kH * kSk / 8}, s[] = {kDh * 2, 128, 8 * kDh * 2}; const cuuint32_t b[] = {64, 8, 3, 4};
      encode(fn, &P.kv[blk], in[1], 4, d, s, b, S128);
      encode(fn, &P.kv[blk + 2], in[2], 4, d, s, b, S128); }
    { const cuuint64_t d[] = {64, kD, kHD / 64}, s[] = {kHD * 2, 128}; const cuuint32_t b[] = {64, 32, 3};
      encode(fn, &P.wq[blk], in[3], 3, d, s, b, S128); }
    { const cuuint64_t d[] = {32, 2, kHD / 8, 4, kD / 32}, s[] = {kD * 2, 8 * kD * 2, 2 * kD * 2, 64}; const cuuint32_t b[] = {32, 2, 4, 4, 5};
      encode(fn, &P.wo[blk], in[4], 5, d, s, b, S64); }
  }
  { const cuuint64_t d[] = {32, kB * kSq, 2 * kD / 32}, s[] = {2 * kD * 2, 64}; const cuuint32_t b[] = {32, 16, 5};
    encode(fn, &P.out, d_out, 3, d, s, b, S64); }

  P.zero = 0;
  compile_programs(bench_programs(), false, P.ops + N_ROWS);
  if (n_clusters >= N_CL) {
    const bool helpers = n_clusters >= N_CL + N_HELP;
    compile_programs(bench_programs(), helpers, P.ops);
    if (helpers && n_wide >= N_WIDE / WIDE) {
      launch(P, 0, N_WIDE / WIDE, 2 * WIDE, false);
      launch(P, N_WIDE, N_CL + N_HELP - N_WIDE, 2, true);
    } else {
      launch(P, 0, N_CL + (helpers ? N_HELP : 0), 2, false);
    }
  } else {
    for (int phase = 0; phase < 2; phase++) {
      const char* text[N_TEAM];
      for (int t = 0; t < N_TEAM; t++) text[t] = phase ? "O08" : "Q0A0Q1A1Q2A2Q3A3Q4A4Q5A5Q6A6Q7A7";
      compile_programs(text, false, P.ops);
      launch(P, 0, N_CL, 2, false);
    }
  }
}
```

```cpp
#include <cuda_runtime.h>
#include <cuda_bf16.h>
#include <cuda.h>
#include <stdint.h>
#include <stdio.h>

namespace {

constexpr int kB = 8, kSq = 256, kD = 640, kH = 32, kSk = 1024, kDh = 192;
constexpr int kHD = kH * kDh;
constexpr uint32_t RING = 224 * 1024;
constexpr uint32_t SZ_KV = 24576;
constexpr uint32_t SZ_WQ = 24576, SZ_WO = 20480, SZ_A = 16384;
constexpr uint32_t SZ_OUT = 40960;
constexpr uint32_t SZ_PARK = 24576;
constexpr uint32_t SZ_PART = 16384;
constexpr int NBAR = 16;
constexpr int KV_TRANSIT = 4;
constexpr int EARLY = 3;
constexpr int S1A = 7;
constexpr uint32_t KV_CH = 64, KV_SBO = 3072;
constexpr int SMEM_BYTES = RING + 512 + 1024;
constexpr int N_TEAM = 16, N_CL = 64, N_HELP = 2, MAX_OPS = 20, MAX_PARK = 4;
constexpr int N_ROWS = N_TEAM + 2 * N_HELP;
constexpr int WIDE = 4, N_WIDE = 60;
enum { OP_END = 0, OP_Q = 1, OP_A = 2, OP_O = 3, F_PARK = 1 << 9, F_LD = 1 << 12, F_ST = 1 << 13, F_HELP = 1 << 12 };

struct alignas(64) Params {
  uint32_t first[30], role0, wide;
  CUtensorMap x[4], wq[2], kv[4], wo[2], out;
  uint32_t ops[2 * N_ROWS][MAX_OPS];
  uint32_t zero;
};

__device__ uint4 g_o[N_TEAM * 2 * 120 * 1024];
__device__ unsigned int g_done[N_TEAM * 2 * 8];
__device__ unsigned int g_help[N_CL * 2 * MAX_PARK];
__device__ unsigned int g_meet[2];
__device__ unsigned int g_seen[N_TEAM * 2 * 8];

template <int TB>
__device__ __forceinline__ void wgmma_rs_n64(float (&d)[32], uint32_t a0, uint32_t a1, uint32_t a2, uint32_t a3, uint64_t db, int scale_d) {
  asm volatile("{\n.reg .pred p;\nsetp.ne.b32 p, %37, 0;\n"
    "wgmma.mma_async.sync.aligned.m64n64k16.f32.bf16.bf16 {%0, %1, %2, %3, %4, %5, %6, %7, %8, %9, %10, %11, %12, %13, %14, %15, %16, %17, %18, %19, %20, %21, %22, %23, %24, %25, %26, %27, %28, %29, %30, %31}, {%32, %33, %34, %35}, %36, p, 1, 1, %38;\n}\n"
    : "+f"(d[0]), "+f"(d[1]), "+f"(d[2]), "+f"(d[3]), "+f"(d[4]), "+f"(d[5]), "+f"(d[6]), "+f"(d[7]), "+f"(d[8]), "+f"(d[9]), "+f"(d[10]), "+f"(d[11]), "+f"(d[12]), "+f"(d[13]), "+f"(d[14]), "+f"(d[15]), "+f"(d[16]), "+f"(d[17]), "+f"(d[18]), "+f"(d[19]), "+f"(d[20]), "+f"(d[21]), "+f"(d[22]), "+f"(d[23]), "+f"(d[24]), "+f"(d[25]), "+f"(d[26]), "+f"(d[27]), "+f"(d[28]), "+f"(d[29]), "+f"(d[30]), "+f"(d[31])
    : "r"(a0), "r"(a1), "r"(a2), "r"(a3), "l"(db), "r"(scale_d), "n"(TB));
}
template <int TB, int TA = 0>
__device__ __forceinline__ void wgmma_ss_n160(float (&d)[80], uint64_t da, uint64_t db, int scale_d) {
  asm volatile("{\n.reg .pred p;\nsetp.ne.b32 p, %82, 0;\n"
    "wgmma.mma_async.sync.aligned.m64n160k16.f32.bf16.bf16 {%0, %1, %2, %3, %4, %5, %6, %7, %8, %9, %10, %11, %12, %13, %14, %15, %16, %17, %18, %19, %20, %21, %22, %23, %24, %25, %26, %27, %28, %29, %30, %31, %32, %33, %34, %35, %36, %37, %38, %39, %40, %41, %42, %43, %44, %45, %46, %47, %48, %49, %50, %51, %52, %53, %54, %55, %56, %57, %58, %59, %60, %61, %62, %63, %64, %65, %66, %67, %68, %69, %70, %71, %72, %73, %74, %75, %76, %77, %78, %79}, %80, %81, p, 1, 1, %83, %84;\n}\n"
    : "+f"(d[0]), "+f"(d[1]), "+f"(d[2]), "+f"(d[3]), "+f"(d[4]), "+f"(d[5]), "+f"(d[6]), "+f"(d[7]), "+f"(d[8]), "+f"(d[9]), "+f"(d[10]), "+f"(d[11]), "+f"(d[12]), "+f"(d[13]), "+f"(d[14]), "+f"(d[15]), "+f"(d[16]), "+f"(d[17]), "+f"(d[18]), "+f"(d[19]), "+f"(d[20]), "+f"(d[21]), "+f"(d[22]), "+f"(d[23]), "+f"(d[24]), "+f"(d[25]), "+f"(d[26]), "+f"(d[27]), "+f"(d[28]), "+f"(d[29]), "+f"(d[30]), "+f"(d[31]), "+f"(d[32]), "+f"(d[33]), "+f"(d[34]), "+f"(d[35]), "+f"(d[36]), "+f"(d[37]), "+f"(d[38]), "+f"(d[39]), "+f"(d[40]), "+f"(d[41]), "+f"(d[42]), "+f"(d[43]), "+f"(d[44]), "+f"(d[45]), "+f"(d[46]), "+f"(d[47]), "+f"(d[48]), "+f"(d[49]), "+f"(d[50]), "+f"(d[51]), "+f"(d[52]), "+f"(d[53]), "+f"(d[54]), "+f"(d[55]), "+f"(d[56]), "+f"(d[57]), "+f"(d[58]), "+f"(d[59]), "+f"(d[60]), "+f"(d[61]), "+f"(d[62]), "+f"(d[63]), "+f"(d[64]), "+f"(d[65]), "+f"(d[66]), "+f"(d[67]), "+f"(d[68]), "+f"(d[69]), "+f"(d[70]), "+f"(d[71]), "+f"(d[72]), "+f"(d[73]), "+f"(d[74]), "+f"(d[75]), "+f"(d[76]), "+f"(d[77]), "+f"(d[78]), "+f"(d[79])
    : "l"(da), "l"(db), "r"(scale_d), "n"(TA), "n"(TB));
}
template <int TB, int TA = 0>
__device__ __forceinline__ void wgmma_ss_n192(float (&d)[96], uint64_t da, uint64_t db, int scale_d) {
  asm volatile("{\n.reg .pred p;\nsetp.ne.b32 p, %98, 0;\n"
    "wgmma.mma_async.sync.aligned.m64n192k16.f32.bf16.bf16 {%0, %1, %2, %3, %4, %5, %6, %7, %8, %9, %10, %11, %12, %13, %14, %15, %16, %17, %18, %19, %20, %21, %22, %23, %24, %25, %26, %27, %28, %29, %30, %31, %32, %33, %34, %35, %36, %37, %38, %39, %40, %41, %42, %43, %44, %45, %46, %47, %48, %49, %50, %51, %52, %53, %54, %55, %56, %57, %58, %59, %60, %61, %62, %63, %64, %65, %66, %67, %68, %69, %70, %71, %72, %73, %74, %75, %76, %77, %78, %79, %80, %81, %82, %83, %84, %85, %86, %87, %88, %89, %90, %91, %92, %93, %94, %95}, %96, %97, p, 1, 1, %99, %100;\n}\n"
    : "+f"(d[0]), "+f"(d[1]), "+f"(d[2]), "+f"(d[3]), "+f"(d[4]), "+f"(d[5]), "+f"(d[6]), "+f"(d[7]), "+f"(d[8]), "+f"(d[9]), "+f"(d[10]), "+f"(d[11]), "+f"(d[12]), "+f"(d[13]), "+f"(d[14]), "+f"(d[15]), "+f"(d[16]), "+f"(d[17]), "+f"(d[18]), "+f"(d[19]), "+f"(d[20]), "+f"(d[21]), "+f"(d[22]), "+f"(d[23]), "+f"(d[24]), "+f"(d[25]), "+f"(d[26]), "+f"(d[27]), "+f"(d[28]), "+f"(d[29]), "+f"(d[30]), "+f"(d[31]), "+f"(d[32]), "+f"(d[33]), "+f"(d[34]), "+f"(d[35]), "+f"(d[36]), "+f"(d[37]), "+f"(d[38]), "+f"(d[39]), "+f"(d[40]), "+f"(d[41]), "+f"(d[42]), "+f"(d[43]), "+f"(d[44]), "+f"(d[45]), "+f"(d[46]), "+f"(d[47]), "+f"(d[48]), "+f"(d[49]), "+f"(d[50]), "+f"(d[51]), "+f"(d[52]), "+f"(d[53]), "+f"(d[54]), "+f"(d[55]), "+f"(d[56]), "+f"(d[57]), "+f"(d[58]), "+f"(d[59]), "+f"(d[60]), "+f"(d[61]), "+f"(d[62]), "+f"(d[63]), "+f"(d[64]), "+f"(d[65]), "+f"(d[66]), "+f"(d[67]), "+f"(d[68]), "+f"(d[69]), "+f"(d[70]), "+f"(d[71]), "+f"(d[72]), "+f"(d[73]), "+f"(d[74]), "+f"(d[75]), "+f"(d[76]), "+f"(d[77]), "+f"(d[78]), "+f"(d[79]), "+f"(d[80]), "+f"(d[81]), "+f"(d[82]), "+f"(d[83]), "+f"(d[84]), "+f"(d[85]), "+f"(d[86]), "+f"(d[87]), "+f"(d[88]), "+f"(d[89]), "+f"(d[90]), "+f"(d[91]), "+f"(d[92]), "+f"(d[93]), "+f"(d[94]), "+f"(d[95])
    : "l"(da), "l"(db), "r"(scale_d), "n"(TA), "n"(TB));
}
template <int TB>
__device__ __forceinline__ void wgmma_rs_n192(float (&d)[96], uint32_t a0, uint32_t a1, uint32_t a2, uint32_t a3, uint64_t db, int scale_d) {
  asm volatile("{\n.reg .pred p;\nsetp.ne.b32 p, %101, 0;\n"
    "wgmma.mma_async.sync.aligned.m64n192k16.f32.bf16.bf16 {%0, %1, %2, %3, %4, %5, %6, %7, %8, %9, %10, %11, %12, %13, %14, %15, %16, %17, %18, %19, %20, %21, %22, %23, %24, %25, %26, %27, %28, %29, %30, %31, %32, %33, %34, %35, %36, %37, %38, %39, %40, %41, %42, %43, %44, %45, %46, %47, %48, %49, %50, %51, %52, %53, %54, %55, %56, %57, %58, %59, %60, %61, %62, %63, %64, %65, %66, %67, %68, %69, %70, %71, %72, %73, %74, %75, %76, %77, %78, %79, %80, %81, %82, %83, %84, %85, %86, %87, %88, %89, %90, %91, %92, %93, %94, %95}, {%96, %97, %98, %99}, %100, p, 1, 1, %102;\n}\n"
    : "+f"(d[0]), "+f"(d[1]), "+f"(d[2]), "+f"(d[3]), "+f"(d[4]), "+f"(d[5]), "+f"(d[6]), "+f"(d[7]), "+f"(d[8]), "+f"(d[9]), "+f"(d[10]), "+f"(d[11]), "+f"(d[12]), "+f"(d[13]), "+f"(d[14]), "+f"(d[15]), "+f"(d[16]), "+f"(d[17]), "+f"(d[18]), "+f"(d[19]), "+f"(d[20]), "+f"(d[21]), "+f"(d[22]), "+f"(d[23]), "+f"(d[24]), "+f"(d[25]), "+f"(d[26]), "+f"(d[27]), "+f"(d[28]), "+f"(d[29]), "+f"(d[30]), "+f"(d[31]), "+f"(d[32]), "+f"(d[33]), "+f"(d[34]), "+f"(d[35]), "+f"(d[36]), "+f"(d[37]), "+f"(d[38]), "+f"(d[39]), "+f"(d[40]), "+f"(d[41]), "+f"(d[42]), "+f"(d[43]), "+f"(d[44]), "+f"(d[45]), "+f"(d[46]), "+f"(d[47]), "+f"(d[48]), "+f"(d[49]), "+f"(d[50]), "+f"(d[51]), "+f"(d[52]), "+f"(d[53]), "+f"(d[54]), "+f"(d[55]), "+f"(d[56]), "+f"(d[57]), "+f"(d[58]), "+f"(d[59]), "+f"(d[60]), "+f"(d[61]), "+f"(d[62]), "+f"(d[63]), "+f"(d[64]), "+f"(d[65]), "+f"(d[66]), "+f"(d[67]), "+f"(d[68]), "+f"(d[69]), "+f"(d[70]), "+f"(d[71]), "+f"(d[72]), "+f"(d[73]), "+f"(d[74]), "+f"(d[75]), "+f"(d[76]), "+f"(d[77]), "+f"(d[78]), "+f"(d[79]), "+f"(d[80]), "+f"(d[81]), "+f"(d[82]), "+f"(d[83]), "+f"(d[84]), "+f"(d[85]), "+f"(d[86]), "+f"(d[87]), "+f"(d[88]), "+f"(d[89]), "+f"(d[90]), "+f"(d[91]), "+f"(d[92]), "+f"(d[93]), "+f"(d[94]), "+f"(d[95])
    : "r"(a0), "r"(a1), "r"(a2), "r"(a3), "l"(db), "r"(scale_d), "n"(TB));
}

__device__ __forceinline__ uint32_t smem_u32(const void* p) { return (uint32_t)__cvta_generic_to_shared(p); }
__device__ __forceinline__ void wg_fence() { asm volatile("wgmma.fence.sync.aligned;" ::: "memory"); }
__device__ __forceinline__ void wg_commit() { asm volatile("wgmma.commit_group.sync.aligned;" ::: "memory"); }
template <int N> __device__ __forceinline__ void wg_wait() { asm volatile("wgmma.wait_group.sync.aligned %0;" ::"n"(N) : "memory"); }
__device__ __forceinline__ void sched_fence(int& keep, uint32_t zero) {
  asm volatile("{\n.reg .u32 c;\nmov.u32 c, %%clock;\nand.b32 c, c, %1;\nxor.b32 %0, %0, c;\n}\n" : "+r"(keep) : "r"(zero) : "memory");
}
template <int N> __device__ __forceinline__ void fence_regs(float (&r)[N]) {
#pragma unroll
  for (int i = 0; i < N; i++) asm volatile("" : "+f"(r[i])::"memory");
}
template <int N> __device__ __forceinline__ void fence_regs(uint32_t (&r)[N]) {
#pragma unroll
  for (int i = 0; i < N; i++) asm volatile("" : "+r"(r[i])::"memory");
}
__device__ __forceinline__ uint64_t mk_desc(uint32_t a16, uint32_t lbo, uint32_t sbo, uint32_t swz, uint32_t off = 0) {
  uint64_t d;
  asm("mov.b64 %0, {%1, %2};" : "=l"(d) : "r"(a16), "r"((sbo >> 4) | (swz << 30)));
  return d + (off + ((lbo >> 4) << 16));
}
__device__ __forceinline__ void mbar_init(uint32_t bar, uint32_t cnt) {
  asm volatile("mbarrier.init.shared::cta.b64 [%0], %1;" ::"r"(bar), "r"(cnt) : "memory");
}
__device__ __forceinline__ void mbar_expect(uint32_t bar, uint32_t tx) {
  asm volatile("mbarrier.arrive.expect_tx.shared::cta.b64 _, [%0], %1;" ::"r"(bar), "r"(tx) : "memory");
}
__device__ __forceinline__ bool mbar_test(uint32_t bar, uint32_t ph) {
  uint32_t ok;
  asm volatile("{\n.reg .pred p;\nmbarrier.test_wait.parity.shared::cta.b64 p, [%1], %2;\nselp.u32 %0, 1, 0, p;\n}\n"
               : "=r"(ok) : "r"(bar), "r"(ph) : "memory");
  return ok;
}
__device__ __forceinline__ void mbar_wait(uint32_t bar, uint32_t ph) {
  asm volatile("{\n.reg .pred p;\n.reg .u32 n;\nmov.u32 n, 0;\n"
               "LOOP:\nadd.u32 n, n, 1;\nmbarrier.try_wait.parity.shared::cta.b64 p, [%0], %1;\n@p bra DONE;\n"
               "setp.lt.u32 p, n, 0x1000000;\n@p bra LOOP;\ntrap;\n"
               "DONE:\n}\n" ::"r"(bar), "r"(ph) : "memory");
}
__device__ __forceinline__ void mbar_wait_math(uint32_t bar, uint32_t ph) {
  asm volatile("{\n.reg .pred p;\nLOOP:\nmbarrier.try_wait.parity.shared::cta.b64 p, [%0], %1;\n@!p bra LOOP;\n}\n" ::"r"(bar), "r"(ph) : "memory");
}
__device__ __forceinline__ void mbar_wait_long(uint32_t bar, uint32_t ph) {
  asm volatile("{\n.reg .pred p;\n.reg .u32 n;\nmov.u32 n, 0;\n"
               "LOOP:\nmbarrier.try_wait.parity.shared::cta.b64 p, [%0], %1, %2;\n@p bra DONE;\n"
               "add.u32 n, n, 1;\nsetp.lt.u32 p, n, 0x40000;\n@p bra LOOP;\ntrap;\n"
               "DONE:\n}\n" ::"r"(bar), "r"(ph), "r"(20000) : "memory");
}
__device__ __forceinline__ void mbar_arrive_cluster_if(bool on, uint32_t addr) {
  asm volatile("{\n.reg .pred p;\nsetp.ne.b32 p, %1, 0;\n@p mbarrier.arrive.shared::cluster.b64 _, [%0];\n}\n" ::"r"(addr), "r"((int)on) : "memory");
}
__device__ __forceinline__ void mbar_arrive_if(bool on, uint32_t addr) {
  asm volatile("{\n.reg .pred p;\nsetp.ne.b32 p, %1, 0;\n@p mbarrier.arrive.shared::cta.b64 _, [%0];\n}\n" ::"r"(addr), "r"((int)on) : "memory");
}
__device__ __forceinline__ void tma2d(uint32_t dst, const CUtensorMap* m, uint32_t bar, int c0, int c1) {
  asm volatile("cp.async.bulk.tensor.2d.shared::cluster.global.mbarrier::complete_tx::bytes [%0], [%1, {%3, %4}], [%2];"
               ::"r"(dst), "l"(m), "r"(bar), "r"(c0), "r"(c1) : "memory");
}
__device__ __forceinline__ void tma2d_mc(uint32_t dst, const CUtensorMap* m, uint32_t bar, int c0, int c1, uint16_t mask) {
  asm volatile("cp.async.bulk.tensor.2d.shared::cluster.global.mbarrier::complete_tx::bytes.multicast::cluster [%0], [%1, {%3, %4}], [%2], %5;"
               ::"r"(dst), "l"(m), "r"(bar), "r"(c0), "r"(c1), "h"(mask) : "memory");
}
__device__ __forceinline__ void bulk_load_mc(uint32_t dst, const void* src, uint32_t bytes, uint32_t bar, uint64_t pol, uint16_t mask) {
  asm volatile("cp.async.bulk.shared::cluster.global.mbarrier::complete_tx::bytes.multicast::cluster.L2::cache_hint [%0], [%1], %2, [%3], %5, %4;"
               ::"r"(dst), "l"(src), "r"(bytes), "r"(bar), "l"(pol), "h"(mask) : "memory");
}
__device__ __forceinline__ void tma3d(uint32_t dst, const CUtensorMap* m, uint32_t bar, int c0, int c1, int c2) {
  asm volatile("cp.async.bulk.tensor.3d.shared::cluster.global.mbarrier::complete_tx::bytes [%0], [%1, {%3, %4, %5}], [%2];"
               ::"r"(dst), "l"(m), "r"(bar), "r"(c0), "r"(c1), "r"(c2) : "memory");
}
__device__ __forceinline__ void tma3d_mc(uint32_t dst, const CUtensorMap* m, uint32_t bar, int c0, int c1, int c2, uint16_t mask) {
  asm volatile("cp.async.bulk.tensor.3d.shared::cluster.global.mbarrier::complete_tx::bytes.multicast::cluster"
               " [%0], [%1, {%3, %4, %5}], [%2], %6;"
               ::"r"(dst), "l"(m), "r"(bar), "r"(c0), "r"(c1), "r"(c2), "h"(mask) : "memory");
}
__device__ __forceinline__ void tma3d_store(const CUtensorMap* m, uint32_t src, int c0, int c1, int c2) {
  asm volatile("cp.async.bulk.tensor.3d.global.shared::cta.bulk_group [%0, {%2, %3, %4}], [%1];"
               ::"l"(m), "r"(src), "r"(c0), "r"(c1), "r"(c2) : "memory");
}
__device__ __forceinline__ void bar_sync(int id, int n) { asm volatile("bar.sync %0, %1;" ::"r"(id), "r"(n) : "memory"); }
__device__ __forceinline__ uint32_t pack_bf16(float lo, float hi) {
  uint32_t r;
  asm("cvt.rn.bf16x2.f32 %0, %1, %2;" : "=r"(r) : "f"(hi), "f"(lo));
  return r;
}
__device__ __forceinline__ float ex2(float x) {
  float y;
  asm("ex2.approx.ftz.f32 %0, %1;" : "=f"(y) : "f"(x));
  return y;
}
__device__ __forceinline__ float fadd(float a, float b) {
  float y;
  asm("add.f32 %0, %1, %2;" : "=f"(y) : "f"(a), "f"(b));
  return y;
}
__device__ __forceinline__ float rcp(float x) {
  float y;
  asm("rcp.approx.ftz.f32 %0, %1;" : "=f"(y) : "f"(x));
  return y;
}
__device__ __forceinline__ void stsm4(uint32_t addr, uint32_t a, uint32_t b, uint32_t c, uint32_t d) {
  asm volatile("stmatrix.sync.aligned.m8n8.x4.shared.b16 [%0], {%1, %2, %3, %4};" ::"r"(addr), "r"(a), "r"(b), "r"(c), "r"(d) : "memory");
}

__device__ __forceinline__ void tma4d_mc_hint(uint32_t dst, const CUtensorMap* m, uint32_t bar, int c3, uint64_t pol, uint16_t mask) {
  asm volatile("cp.async.bulk.tensor.4d.shared::cluster.global.mbarrier::complete_tx::bytes.multicast::cluster.L2::cache_hint"
               " [%0], [%1, {%3, %3, %3, %4}], [%2], %5, %6;"
               ::"r"(dst), "l"(m), "r"(bar), "r"(0), "r"(c3), "h"(mask), "l"(pol) : "memory");
}
__device__ __forceinline__ void tma5d_mc(uint32_t dst, const CUtensorMap* m, uint32_t bar, int c2, int c4, uint16_t mask) {
  asm volatile("cp.async.bulk.tensor.5d.shared::cluster.global.mbarrier::complete_tx::bytes.multicast::cluster"
               " [%0], [%1, {%3, %3, %4, %3, %5}], [%2], %6;"
               ::"r"(dst), "l"(m), "r"(bar), "r"(0), "r"(c2), "r"(c4), "h"(mask) : "memory");
}
__device__ __forceinline__ void bulk_load_hint(uint32_t dst, const void* src, uint32_t bytes, uint32_t bar, uint64_t pol) {
  asm volatile("cp.async.bulk.shared::cluster.global.mbarrier::complete_tx::bytes.L2::cache_hint [%0], [%1], %2, [%3], %4;"
               ::"r"(dst), "l"(src), "r"(bytes), "r"(bar), "l"(pol) : "memory");
}
__device__ __forceinline__ void stg2_if(bool on, void* p, uint32_t a, uint32_t b, uint32_t c, uint32_t d, uint32_t e, uint32_t f,
                                        uint32_t g, uint32_t h, uint64_t pol) {
  asm volatile("{\n.reg .pred p;\nsetp.ne.b32 p, %10, 0;\n"
               "@p st.global.L2::cache_hint.v4.b32 [%0], {%1, %2, %3, %4}, %9;\n"
               "@p st.global.L2::cache_hint.v4.b32 [%0 + 512], {%5, %6, %7, %8}, %9;\n}\n"
               ::"l"(p), "r"(a), "r"(b), "r"(c), "r"(d), "r"(e), "r"(f), "r"(g), "r"(h), "l"(pol), "r"((int)on) : "memory");
}
__device__ __forceinline__ uint64_t evict_first() {
  uint64_t p;
  asm("createpolicy.fractional.L2::evict_first.b64 %0, 1.0;" : "=l"(p));
  return p;
}
__device__ __forceinline__ bool elect() {
  uint32_t ok;
  asm volatile("{\n.reg .pred p;\nelect.sync _|p, 0xffffffff;\nselp.u32 %0, 1, 0, p;\n}\n" : "=r"(ok));
  return ok;
}
__device__ __forceinline__ void mbar_arrive(uint32_t bar) {
  asm volatile("mbarrier.arrive.shared::cta.b64 _, [%0];" ::"r"(bar) : "memory");
}
template <int OFF> __device__ __forceinline__ void lds2_if(bool on, uint32_t p, uint32_t* r) {
  asm volatile("{\n.reg .pred p;\nsetp.ne.b32 p, %9, 0;\n@p ld.shared.v4.b32 {%0, %1, %2, %3}, [%8 + %10];\n"
               "@p ld.shared.v4.b32 {%4, %5, %6, %7}, [%8 + %11];\n}\n"
               : "+r"(r[0]), "+r"(r[1]), "+r"(r[2]), "+r"(r[3]), "+r"(r[4]), "+r"(r[5]), "+r"(r[6]), "+r"(r[7])
               : "r"(p), "r"((int)on), "n"(OFF), "n"(OFF + 512) : "memory");
}
__device__ __forceinline__ void lds128(uint32_t p, uint32_t& a, uint32_t& b, uint32_t& c, uint32_t& d) {
  asm volatile("ld.shared.v4.b32 {%0, %1, %2, %3}, [%4];" : "=r"(a), "=r"(b), "=r"(c), "=r"(d) : "r"(p) : "memory");
}
__device__ __forceinline__ void wait_count(const unsigned int* p, uint32_t target) {
  asm volatile("{\n.reg .pred p;\n.reg .u32 n, v;\nmov.u32 n, 0;\n"
               "LOOP:\nld.acquire.gpu.global.u32 v, [%0];\nsetp.ge.u32 p, v, %1;\n@p bra DONE;\n"
               "nanosleep.u32 %2;\nadd.u32 n, n, 1;\nsetp.lt.u32 p, n, 0x400000;\n@p bra LOOP;\ntrap;\n"
               "DONE:\n}\n" ::"l"(p), "r"(target), "n"(300) : "memory");
}

__device__ __forceinline__ int o_wave(int a, int b, int i) {
  const int p = min(3, b - a - 1);
  return i < p ? b - 2 - i : i == p ? b - 1 : b - 1 - i;
}

struct Cursor {
  uint32_t n;
  __device__ __forceinline__ uint32_t off() const { return n & (8 * NBAR - 8); }
  __device__ __forceinline__ uint32_t ph() const { return (n / (8 * NBAR)) & 1; }
  __device__ __forceinline__ void next() { n += 8; }
};

constexpr float kScaleLog2 = 0.07216878364870322f * 1.4426950408889634f;
constexpr float kSumLimit = 1048576.0f;
constexpr float kMaxLag = 8.0f;

__global__ void __launch_bounds__(384, 1)
fused_kernel(const __grid_constant__ Params P) {
  extern __shared__ uint8_t smem_raw[];
  const uint32_t sbase = (smem_u32(smem_raw) + 1023) & ~1023u;
  const uint32_t full0 = sbase + RING, empty0 = full0 + 8 * NBAR, odone = empty0 + 8 * NBAR, oready0 = odone + 8;
  const uint32_t fenced = oready0 + 64, hready0 = fenced + 8, met = hready0 + 8 * MAX_PARK;
  const uint32_t rank = blockIdx.x & 1;
  const int role = (blockIdx.x >> 1) + P.role0;
  const bool wide = P.wide;
  const uint32_t sub = wide ? (blockIdx.x >> 1) & (WIDE - 1) : 0;
  asm volatile("griddepcontrol.launch_dependents;");
  const bool helper = role >= N_CL;
  const int team = helper ? 0 : role >> 2, nt = role & 3, blk = team >> 3;
  const uint32_t* prog = P.ops[helper ? N_TEAM + 2 * (role - N_CL) : team];
  auto q_role = [&](uint32_t op) { return helper ? (int)(((op >> 3) & 60) | ((op >> 12) & 3)) : role; };
  auto o_role = [&](uint32_t op) { return helper ? (int)(((op >> 26) & 56) | ((op >> 9) & 7)) : role; };
  auto spare = [&](int b) { return WIDE == 4 && wide && b >= 2 ? b - 2 : 8; };
  auto alone = [&]() {
    uint32_t v;
    mbar_wait(met, 0);
    asm volatile("ld.shared.u32 %0, [%1];" : "=r"(v) : "r"(met + 8) : "memory");
    return v;
  };
  const int wid = __shfl_sync(0xffffffffu, (int)(threadIdx.x >> 5), 0);
  const int wg = wid >> 2;

  const uint32_t op0 = P.first[helper ? N_TEAM + role - N_CL : team];
  if (__builtin_expect(wid == 8, 1)) {
    if (elect()) {
#pragma unroll
      for (int k = 0; k < EARLY; k++) mbar_init(full0 + 8 * k, 1);
      asm volatile("fence.mbarrier_init.release.cluster;" ::: "memory");
      if ((op0 & 3) == OP_Q) {
        const int qr = q_role(op0);
#pragma unroll
        for (int k = 0; k < EARLY; k++) {
          mbar_expect(full0 + 8 * k, SZ_WQ + SZ_A);
          tma2d(sbase + k * (SZ_WQ + SZ_A) + SZ_WQ, &P.x[qr >> 5], full0 + 8 * k, 64 * k, ((qr >> 2) & 7) * kSq + rank * 128);
          tma3d(sbase + k * (SZ_WQ + SZ_A), &P.wq[qr >> 5], full0 + 8 * k, 0, 64 * k, 3 * (4 * ((op0 >> 2) & 7) + (qr & 3)));
          tma3d(sbase + k * (SZ_WQ + SZ_A) + SZ_WQ / 2, &P.wq[qr >> 5], full0 + 8 * k, 0, 64 * k + 32, 3 * (4 * ((op0 >> 2) & 7) + (qr & 3)));
        }
      }
      asm volatile("prefetch.tensormap [%0];" ::"l"(&P.kv[blk]) : "memory");
      asm volatile("prefetch.tensormap [%0];" ::"l"(&P.kv[blk + 2]) : "memory");
    }
  } else if (threadIdx.x == 0) {
#pragma unroll
    for (int i = EARLY; i < 2 * NBAR + 11 + MAX_PARK; i++) mbar_init(full0 + 8 * i, i >= NBAR && i <= 2 * NBAR ? (wide ? 8 * WIDE + 8 : 16) : 1);
    asm volatile("fence.mbarrier_init.release.cluster;" ::: "memory");
  }
  __syncwarp();
  asm volatile("barrier.cluster.arrive.relaxed.aligned;\nbarrier.cluster.wait.aligned;" ::: "memory");

  if (wg == 2) {
    asm volatile("setmaxnreg.dec.sync.aligned.u32 24;");
    if (wid == 8) {
      Cursor tail{0u - 8}, head{0};
      int sh = 0;
      uint32_t cur = 0, used = 0;
      uint64_t fifo = 0;
      uint32_t oready = oready0;
      const uint64_t pol = evict_first();
      const uint16_t pair = 3 << (2 * sub), rows = (wide ? 0x55 >> (8 - 2 * WIDE) : 1) << rank;
      const uint32_t piece = wide ? SZ_A / WIDE : SZ_A;
      struct Load { uint32_t dst, bar, wbar, wph; int c0; const void* ptr; bool wait; };
      auto reserve = [&](uint32_t bytes, bool last, uint32_t off, int c0, const void* ptr) {
        uint32_t fp = bytes >> 12;
        if (cur + fp > (RING >> 12)) { fp += (RING >> 12) - cur; cur = 0; }
        used += fp;
        bool wait = false;
        while (used > (RING >> 12)) {
          wait = true;
          tail.next();
          used -= (uint32_t)fifo & 31;
          fifo >>= 5;
          sh -= 5;
        }
        fifo += (uint64_t)fp << sh;
        Load l{sbase + (cur << 12) + off, full0 + head.off(), empty0 + tail.off(), tail.ph(), c0, ptr, wait};
        cur += bytes >> 12;
        sh += last ? 5 : 0;
        head.n += last ? 8 : 0;
        asm volatile("" : "+r"(l.dst), "+r"(l.bar), "+r"(l.c0), "+l"(l.ptr), "+r"(l.wbar), "+r"(l.wph));
        return l;
      };
      auto vacated = [&](const Load& l) { if (l.wait) mbar_wait(l.wbar, l.wph); };
      auto written = [&](uint32_t flag) {
        mbar_wait(flag, 0);
        asm volatile("fence.proxy.async.global;" ::: "memory");
      };
      for (int pc = 0;; pc++) {
        if (pc == 1) prog += __shfl_sync(0xffffffffu, alone(), 0);
        const uint32_t op = prog[pc];
        const int type = op & 3, a = (op >> 2) & 7;
        if (type == OP_END) break;
        if (type == OP_Q) {
          const int qr = q_role(op);
          const CUtensorMap *mw = &P.wq[qr >> 5], *mx = &P.x[(qr >> 5) + (wide ? 2 : 0)];
          asm volatile("" : "+l"(mw), "+l"(mx));
          auto res_w = [&](int k) { return reserve(SZ_WQ, false, rank * (SZ_WQ / 2), 64 * k + 32 * rank, mw); };
          auto load_w = [&](const Load& w, int k) {
            vacated(w);
            if ((pc > 0 || k >= EARLY) && elect()) tma3d_mc(w.dst, (const CUtensorMap*)w.ptr, w.bar, 0, w.c0, 3 * (4 * a + (qr & 3)), pair);
          };
          auto load_x = [&](const Load& x, int k) {
            vacated(x);
            if ((pc > 0 || k >= EARLY) && elect()) {
              tma2d_mc(x.dst, (const CUtensorMap*)x.ptr, x.bar, x.c0, ((qr >> 2) & 7) * kSq + rank * 128 + sub * (128 / WIDE), rows);
              mbar_expect(x.bar, SZ_WQ + SZ_A);
            }
          };
#pragma unroll 1
          for (int k = 0; k < 10; k++) {
            load_w(res_w(k), k);
            load_x(reserve(SZ_A, true, sub * (SZ_A / WIDE), 64 * k, mx), k);
          }
        } else if (type == OP_A) {
          const uint32_t nop = prog[pc + 1];
          const int row8 = ((team & 7) * kH + nt) * (kSk / 8) + 4 * rank, wave8 = 4 * (kSk / 8);
          auto transit = [&]() {
            const Cursor c{head.n - 8 * (KV_TRANSIT + 1)};
            mbar_wait(full0 + c.off(), c.ph());
          };
          const char* map = (const char*)&P.kv[blk];
          asm volatile("" : "+l"(map));
          int t = (op & F_PARK) ? 1 : 0, c0 = row8 + a * wave8 + 8 * t, isv = 0;
#pragma unroll 1
          for (; t < 31; t++) {
            const Load l = reserve(SZ_KV, true, rank * (SZ_KV / 2), c0, map + isv);
            vacated(l);
            if (t >= KV_TRANSIT) transit();
            if (elect()) {
              tma4d_mc_hint(l.dst, (const CUtensorMap*)l.ptr, l.bar, l.c0, pol, pair);
              mbar_expect(l.bar, SZ_KV);
            }
            isv = (t & 1) << 8;
            c0 += isv ? -8 : t ? 16 : 8;
          }
          const int next = (nop >> 2) & 7;
          if ((nop & 3) == OP_A) written((nop & F_HELP) ? hready0 + 8 * ((nop >> 10) & 3) : fenced);
#pragma unroll 1
          for (int i = (nop & 3) == OP_A ? 0 : 3; i < 4; i++) {
            const Load l = reserve(SZ_KV, true, i < 2 ? 0 : rank * (SZ_KV / 2), i == 3 ? c0 - 8 : row8 + next * wave8,
                                   i < 2 ? (const char*)&g_o[((team * 2 + rank) * 120 + 3 * (4 * next + nt)) * 1024 + i * (SZ_PARK / 16)] : map + ((i & 1) << 8));
            vacated(l);
            if (i < 2) {
              if (elect()) bulk_load_hint(l.dst, l.ptr, SZ_PARK, l.bar, pol);
              __syncwarp();
            } else {
              transit();
              if (elect()) tma4d_mc_hint(l.dst, (const CUtensorMap*)l.ptr, l.bar, l.c0, pol, pair);
              __syncwarp();
            }
            if (elect()) mbar_expect(l.bar, SZ_KV);
          }
        } else {
          const int b = (op >> 5) & 15, ro = o_role(op);
          const CUtensorMap* mw = &P.wo[ro >> 5];
          const uint4* so = &g_o[((ro >> 2) * 2 + rank) * 120 * 1024 + sub * (1024 / WIDE)];
          asm volatile("" : "+l"(mw), "+l"(so));
#pragma unroll 1
          for (int j = 0; j < b - a; j++) {
            const int w = o_wave(a, b, j);
            written(oready);
            oready += 8;
#pragma unroll 1
            for (int k = 12 * w; k < 12 * w + 12; k++) {
              const Load o = reserve(SZ_A, false, sub * (SZ_A / WIDE), 0, so + k * 1024);
              vacated(o);
              if (elect()) bulk_load_mc(o.dst, o.ptr, piece, o.bar, pol, rows);
              const Load w = reserve(SZ_WO, true, rank * (SZ_WO / 2), 8 * k + 4 * rank, mw);
              vacated(w);
              if (elect()) {
                tma5d_mc(w.dst, (const CUtensorMap*)w.ptr, w.bar, w.c0, 5 * (ro & 3), pair);
                mbar_expect(w.bar, SZ_WO + SZ_A);
              }
            }
          }
          if ((op & F_LD) && (op & F_PARK)) written(hready0 + 8 * (MAX_PARK - 1));
#pragma unroll 1
          for (int i = (op & F_LD) ? 0 : 5; i < ((op & F_ST) ? 5 : 6); i++) {
            const Load l = reserve(i < 5 ? SZ_PART : SZ_OUT, i < 5, 0, 0, &g_o[((team * 2 + rank) * 120 + 3 * (4 * spare((op & F_PARK) ? 0 : a) + nt) + (i < 2 ? i : i + 10)) * 1024]);
            vacated(l);
            if (i < 5 && elect()) bulk_load_hint(l.dst, l.ptr, SZ_PART, l.bar, pol);
            if (elect()) mbar_expect(l.bar, i < 5 ? SZ_PART : 0);
          }
        }
      }
#pragma unroll 1
      for (Cursor c{head.n - 8 * NBAR}; c.n != head.n; c.next()) mbar_wait(empty0 + c.off(), c.ph());
    } else if (threadIdx.x == 288) {
      uint32_t ph = 0;
      bool first = true;
      prog += alone();
      for (int pc = 0;; pc++) {
        const uint32_t op = prog[pc];
        if ((op & 3) == OP_END) break;
        if ((op & 3) != OP_A && !helper) continue;
        mbar_wait_long(odone, ph);
        ph ^= 1;
        unsigned int* flag = !helper ? &g_done[(team * 2 + rank) * 8 + ((op >> 2) & 7)]
                             : (op & 3) == OP_Q ? &g_help[(q_role(op) * 2 + rank) * MAX_PARK + ((op >> 10) & 3)]
                                                : &g_help[(o_role(op) * 2 + rank) * MAX_PARK + MAX_PARK - 1];
        asm volatile("red.release.gpu.global.add.u32 [%0], 1;" ::"l"(flag) : "memory");
        if (first) mbar_arrive(fenced);
        first = false;
      }
    } else if (threadIdx.x == 320) {
      uint32_t meet = 1;
      if (wide || P.role0) {
        const uint32_t vote = role == N_CL + N_HELP - 1 ? 1 : 2;
        meet = 0;
        for (int n = 0; vote == 2 && !meet && n < 300; n++) {
          __nanosleep(100);
          asm volatile("ld.relaxed.gpu.global.u32 %0, [%1];" : "=r"(meet) : "l"(&g_meet[0]) : "memory");
        }
        if (!meet && !(meet = atomicCAS(&g_meet[0], 0u, vote))) meet = vote;
        if (atomicAdd(&g_meet[1], 1u) == 2 * (N_CL + N_HELP) - 1) { g_meet[0] = 0; g_meet[1] = 0; }
      }
      prog += (meet - 1) * (N_ROWS * MAX_OPS);
      asm volatile("st.shared.u32 [%0], %1;" ::"r"(met + 8), "r"((meet - 1) * (N_ROWS * MAX_OPS)) : "memory");
      mbar_arrive(met);
      uint32_t oready = oready0;
      for (int pc = 0;; pc++) {
        const uint32_t op = prog[pc];
        if ((op & 3) == OP_END) break;
        if ((op & 3) == OP_O) {
          const int a = (op >> 2) & 7, b = (op >> 5) & 15;
#pragma unroll 1
          for (int i = 0; i < b - a; i++) {
            const int ci = ((o_role(op) >> 2) * 2 + rank) * 8 + o_wave(a, b, i);
            wait_count(&g_done[ci], 4);
            mbar_arrive(oready);
            oready += 8;
            if (atomicAdd(&g_seen[ci], 1u) == 3u) { g_seen[ci] = 0; g_done[ci] = 0; }
          }
        }
        if ((op & 3) != OP_Q && (op & F_HELP) && (op & F_PARK)) {
          unsigned int* flag = &g_help[(role * 2 + rank) * MAX_PARK + ((op >> 10) & 3)];
          wait_count(flag, 1);
          mbar_arrive(hready0 + 8 * ((op >> 10) & 3));
          *flag = 0;
        }
      }
    }
  } else {
    asm volatile("setmaxnreg.inc.sync.aligned.u32 240;");
    const int lane = threadIdx.x & 31, warp = wid & 3;
    uint32_t empty_rem;
    const bool tell = lane < (wide ? WIDE + 1 : 2);
    asm volatile("mapa.shared::cluster.u32 %0, %1, %2;" : "=r"(empty_rem) : "r"(empty0), "r"((2 * sub + rank) ^ (!tell ? 0 : lane < 2 ? lane : 2 * lane - 2)));
    auto release = [&](int slot) { mbar_arrive_cluster_if(tell, empty_rem + slot); };
    Cursor r{0};
    const uint32_t ring16 = (sbase & 0x3FFFF) >> 4;
    uint32_t cur = ring16;
    bool rdy0 = false, rdy1 = false;
    auto probe1 = [&]() { rdy0 = mbar_test(full0 + r.off(), r.ph()); };
    auto probe2 = [&]() {
      Cursor n = r;
      rdy0 = mbar_test(full0 + n.off(), n.ph());
      n.next();
      rdy1 = mbar_test(full0 + n.off(), n.ph());
    };
    auto take = [&](bool rdy, uint32_t bytes, uint32_t& addr) {
      const int bi = r.off();
      if (!__all_sync(0xffffffffu, rdy)) mbar_wait_math(full0 + r.off(), r.ph());
      r.next();
      if (cur > ring16 + ((RING - bytes) >> 4)) cur = ring16;
      addr = cur;
      cur += bytes >> 4;
      return bi;
    };
    auto at = [&](uint32_t a16) {
      uint32_t a = sbase + (a16 - ring16) * 16;
      asm("" : "+r"(a));
      return a;
    };
    auto second = [&](uint32_t bytes) {
      if (cur > ring16 + ((RING - bytes) >> 4)) cur = ring16;
      cur += bytes >> 4;
      return cur - (bytes >> 4);
    };
    const int row = wg * 64 + warp * 16 + (lane >> 2);
    int img0 = (row * 4 + ((lane & 3) ^ ((row >> 1) & 3))) * 16;
    uint4* pend = nullptr;
    const uint64_t spol = evict_first();
    int pc = 0;
    uint32_t op = prog[0];
    auto enter = [&]() {
      r.n = op >> 12; cur = ring16 + (((op >> 20) & 63) << 8);
    };
    auto drain = [&](uint32_t (&t)[48], uint32_t c) {
      if (!(op & (3u << 26)) || c >= 6) return;
#pragma unroll
      for (int i = 0; i < 6; i++)
        stg2_if(c == i, pend + i * 512, t[8 * i], t[8 * i + 1], t[8 * i + 2], t[8 * i + 3],
                t[8 * i + 4], t[8 * i + 5], t[8 * i + 6], t[8 * i + 7], spol);
      if ((op & (1u << 26)) && c == 5) {
        __syncwarp();
        mbar_arrive_if(tell, odone);
      }
    };
    float s[32], o[96], c[80];
    uint32_t q[48], pa[16], pb[16];
    float mc0, mc1, l0, l1;
    bool gen;
    auto soft = [&](float (&s)[32], uint32_t (&pout)[16], bool first) {
      if (first) { gen = false; mc0 = 0.f; mc1 = 0.f; }
      float b0, b1;
      for (;;) {
        if (gen) {
          float m0 = fmaxf(s[0], s[1]), m1 = fmaxf(s[2], s[3]);
#pragma unroll
          for (int i = 1; i < 8; i++) { m0 = fmaxf(m0, fmaxf(s[4 * i], s[4 * i + 1])); m1 = fmaxf(m1, fmaxf(s[4 * i + 2], s[4 * i + 3])); }
          m0 = fmaxf(m0, __shfl_xor_sync(0xffffffffu, m0, 1)); m1 = fmaxf(m1, __shfl_xor_sync(0xffffffffu, m1, 1));
          m0 = fmaxf(m0, __shfl_xor_sync(0xffffffffu, m0, 2)); m1 = fmaxf(m1, __shfl_xor_sync(0xffffffffu, m1, 2));
          if (first) {
            mc0 = m0; mc1 = m1;
          } else if (__any_sync(0xffffffffu, !(m0 <= mc0 + kMaxLag && m1 <= mc1 + kMaxLag))) {
            m0 = fmaxf(mc0, m0); m1 = fmaxf(mc1, m1);
            const float a0 = ex2(mc0 - m0), a1 = ex2(mc1 - m1);
            mc0 = m0; mc1 = m1;
            l0 *= a0; l1 *= a1;
            wg_wait<0>();
            fence_regs(o);
#pragma unroll
            for (int i = 0; i < 96; i++) o[i] *= i & 2 ? a1 : a0;
          }
#pragma unroll
          for (int i = 0; i < 32; i++) s[i] -= i & 2 ? mc1 : mc0;
        }
#pragma unroll
        for (int i = 0; i < 8; i++) {
          const float e1 = ex2(s[4 * i + 1]), e0 = ex2(s[4 * i]), e3 = ex2(s[4 * i + 3]), e2 = ex2(s[4 * i + 2]);
          pout[2 * i] = pack_bf16(e0, e1);
          b0 = i ? b0 + fadd(e1, e0) : fadd(e1, e0);
          pout[2 * i + 1] = pack_bf16(e2, e3);
          b1 = i ? b1 + fadd(e3, e2) : fadd(e3, e2);
        }
        if (!__any_sync(0xffffffffu, !gen && !(fmaxf(b0, b1) <= kSumLimit && (!first || fminf(b0, b1) >= 1.0f / kSumLimit)))) break;
        gen = __any_sync(0xffffffffu, true);
      }
      l0 = first ? b0 : l0 + b0;
      l1 = first ? b1 : l1 + b1;
    };
    auto qk = [&](float (&s)[32], uint32_t ak, int k0, int k1) {
#pragma unroll
      for (int kk = k0; kk < k1; kk++)
        wgmma_rs_n64<0>(s, q[4 * kk], q[4 * kk + 1], q[4 * kk + 2], q[4 * kk + 3], mk_desc(ak, 16, KV_SBO, 1, (kk >> 2) * KV_CH + (kk & 3) * 2), kk != 0);
      wg_commit();
    };
    auto pv = [&](uint32_t (&pin)[16], uint32_t av, int acc) {
#pragma unroll
      for (int kk = 0; kk < 4; kk++)
        wgmma_rs_n192<1>(o, pin[4 * kk], pin[4 * kk + 1], pin[4 * kk + 2], pin[4 * kk + 3], mk_desc(av, KV_CH * 16, KV_SBO, 1, kk * (KV_SBO / 8)), acc || (kk != 0));
      wg_commit();
    };
    auto xw = [&](uint32_t ad, int acc) {
      const uint32_t da = second(SZ_A) + wg * 512;
      wg_fence();
#pragma unroll
      for (int kk = 0; kk < 4; kk++)
        wgmma_ss_n192<1>(o, mk_desc(da, 16, 1024, 1, kk * 2), mk_desc(ad, 4096, 1024, 1, (kk & 1) * 128 + (kk >> 1) * 768), acc || kk != 0);
      wg_commit();
    };
    auto ow = [&](int acc, int prev) {
      uint32_t da;
      const int bi = take(rdy0, SZ_A, da);
      const uint32_t db = second(SZ_WO);
      da += wg * 256;
      wg_fence();
      wgmma_ss_n160<1>(c, mk_desc(da, 16, 512, 2), mk_desc(db, 2048, 512, 2), acc);
      wgmma_ss_n160<1>(c, mk_desc(da, 16, 512, 2, 2), mk_desc(db, 2048, 512, 2, 64), 1);
      wg_commit();
      if (acc == 1) { wg_wait<1>(); release(prev); }
      wgmma_ss_n160<1>(c, mk_desc(da, 16, 512, 2, 512), mk_desc(db, 2048, 512, 2, 640), 1);
      wgmma_ss_n160<1>(c, mk_desc(da, 16, 512, 2, 514), mk_desc(db, 2048, 512, 2, 704), 1);
      wg_commit();
      return bi;
    };
    auto st_part = [&](int i) {
      stg2_if(true, pend + i * 512, __float_as_uint(c[8 * i]), __float_as_uint(c[8 * i + 1]), __float_as_uint(c[8 * i + 2]), __float_as_uint(c[8 * i + 3]),
              __float_as_uint(c[8 * i + 4]), __float_as_uint(c[8 * i + 5]), __float_as_uint(c[8 * i + 6]), __float_as_uint(c[8 * i + 7]), spol);
    };
#pragma unroll
    for (int i = 0; i < 48; i++) q[i] = 0;
    enter();

    if ((op & 3) == OP_Q) {
      uint32_t ad;
      int bi0 = take(false, SZ_WQ, ad), k = 0, lag = 0;
      xw(ad, 0);
      for (;;) {
#pragma unroll 1
        for (;;) {
          drain(q, k - lag);
          probe1();
          wg_wait<0>();
          release(bi0);
          bi0 = take(rdy0, SZ_WQ, ad);
          if (++k == 8) break;
          xw(ad, 1);
        }
        if (wg) bar_sync(2, 256);
        xw(ad, 1);
        const int bi9 = take(false, SZ_WQ, ad);
        xw(ad, 1);
        if (!wg) asm volatile("bar.arrive 2, 256;" ::: "memory");
        k = 0; lag = 0;
        if (pc == 0) prog += __shfl_sync(0xffffffffu, alone(), 0);
        uint32_t nop = prog[++pc];
        wg_wait<1>();
        release(bi0);
        probe2();
        wg_wait<0>();
        fence_regs(o);
        release(bi9);
#pragma unroll
        for (int i = 0; i < 48; i++) q[i] = pack_bf16(o[2 * i] * kScaleLog2, o[2 * i + 1] * kScaleLog2);
        fence_regs(q);
        if (op & F_PARK) {
          const int qt = helper ? (op >> 5) & 15 : team, qm = helper ? (op >> 12) & 3 : nt;
          pend = (uint4*)((char*)&g_o[((qt * 2 + rank) * 120 + 3 * (4 * ((op >> 2) & 7) + qm)) * 1024] + img0);
          op = nop;
          enter();
          if ((op & 3) != OP_Q) break;
          const int b = take(rdy0, SZ_WQ, ad);
          xw(ad, 0);
          bi0 = take(rdy1, SZ_WQ, ad);
          xw(ad, 1);
          wg_wait<1>();
          release(b);
          k = 1; lag = 1;
          continue;
        }
        int wave = (op >> 2) & 7, sk1;
        uint32_t ak1;
        {
          float s0[32];
          const int sk0 = take(rdy0, SZ_KV, ad);
          wg_fence();
          qk(s0, ad, 0, 12);
          sk1 = take(rdy1, SZ_KV, ak1);
          wg_fence();
          qk(s, ak1, 0, S1A);
          probe1();
          wg_wait<1>();
          fence_regs(s0);
          release(sk0);
          soft(s0, pa, true);
        }
        float i0, i1;
        auto sums = [&]() {
          l0 += __shfl_xor_sync(0xffffffffu, l0, 1); l1 += __shfl_xor_sync(0xffffffffu, l1, 1);
          l0 += __shfl_xor_sync(0xffffffffu, l0, 2); l1 += __shfl_xor_sync(0xffffffffu, l1, 2);
          i0 = rcp(l0); i1 = rcp(l1);
          asm volatile("" : "+f"(i0), "+f"(i1));
        };
        auto target = [&]() {
          pend = (uint4*)((char*)&g_o[((team * 2 + rank) * 120 + 3 * (4 * wave + nt)) * 1024] + img0);
          asm volatile("" : "+l"(pend));
        };
        bool late = false;
#pragma unroll
        for (int i = 0; i < 16; i++) pb[i] = 0;
        for (;;) {
          nop = prog[++pc];
          {
            uint32_t av;
            const int sv = take(rdy0, SZ_KV, av);
            wg_fence();
            qk(s, ak1, S1A, 12);
            pv(pa, av, 0);
            if (late) {
              stg2_if(true, pend + 4 * 512, pb[0], pb[1], pb[2], pb[3], pb[4], pb[5], pb[6], pb[7], spol);
              stg2_if(true, pend + 5 * 512, pb[8], pb[9], pb[10], pb[11], pb[12], pb[13], pb[14], pb[15], spol);
              __syncwarp();
              mbar_arrive_if(tell, odone);
            }
            probe2();
            wg_wait<1>();
            fence_regs(s);
            release(sk1);
            soft(s, pb, false);
            wg_wait<0>();
            fence_regs(o);
            release(sv);
          }
          auto step = [&](uint32_t (&pin)[16], uint32_t (&pout)[16], bool hook, bool unpark) {
            uint32_t ak, av;
            const int sk = take(rdy0, SZ_KV, ak), sv = take(rdy1, SZ_KV, av);
            wg_fence();
            qk(s, ak, 0, 12);
            pv(pin, av, 1);
            if (hook && unpark) { take(false, SZ_PARK, ak); take(false, SZ_PARK, av); }
            probe2();
            wg_wait<1>();
            fence_regs(s);
            release(sk);
            if (hook) {
              lds2_if<0>(unpark, img0 + at(ak), q);
              lds2_if<8192>(unpark, img0 + at(ak), q + 8);
              lds2_if<16384>(unpark, img0 + at(ak), q + 16);
              lds2_if<0>(unpark, img0 + at(av), q + 24);
              lds2_if<8192>(unpark, img0 + at(av), q + 32);
              lds2_if<16384>(unpark, img0 + at(av), q + 40);
            }
            soft(s, pout, false);
            wg_wait<0>();
            fence_regs(o);
            release(sv);
          };
          const int jpark = (nop & 3) == OP_A ? 6 : 7;
#pragma unroll 1
          for (int jj = 0; jj < 7; jj++) {
            step(pb, pa, false, false);
            step(pa, pb, true, jj == jpark);
          }
          if ((nop & 3) != OP_A) break;
          uint32_t ak, av;
          release(Cursor{r.n - 16}.off());
          release(Cursor{r.n - 8}.off());
          const int sk0 = take(rdy0, SZ_KV, ak), sv = take(rdy1, SZ_KV, av);
          wg_fence();
          qk(s, ak, 0, 8);
          sched_fence(img0, P.zero);
          sums();
          sched_fence(img0, P.zero);
          qk(s, ak, 8, 12);
          pv(pb, av, 1);
          probe2();
          wg_wait<1>();
          fence_regs(s);
          release(sk0);
          soft(s, pa, true);
          sk1 = take(rdy0, SZ_KV, ak1);
          rdy0 = rdy1;
          wg_wait<0>();
          target();
          fence_regs(o);
          release(sv);
          uint32_t t[48];
#pragma unroll
          for (int j = 0; j < 6; j++) {
#pragma unroll
            for (int i = 0; i < 4; i++) {
              t[8 * j + i] = pack_bf16(o[16 * j + 4 * i] * i0, o[16 * j + 4 * i + 1] * i0);
              t[8 * j + i + 4] = pack_bf16(o[16 * j + 4 * i + 2] * i1, o[16 * j + 4 * i + 3] * i1);
            }
            if (j < 4)
            stg2_if(true, pend + j * 512, t[8 * j], t[8 * j + 1], t[8 * j + 2], t[8 * j + 3], t[8 * j + 4], t[8 * j + 5], t[8 * j + 6], t[8 * j + 7], spol);
            if (j == 3) { wg_fence(); qk(s, ak1, 0, 4); }
            if (j == 5) { wg_fence(); qk(s, ak1, 4, S1A); }
            sched_fence(img0, P.zero);
          }
          if (P.zero) {
#pragma unroll
            for (int j = 0; j < 4; j++)
              stg2_if(true, pend, t[8 * j], t[8 * j + 1], t[8 * j + 2], t[8 * j + 3], t[8 * j + 4], t[8 * j + 5], t[8 * j + 6], t[8 * j + 7], spol);
          }
          late = true;
#pragma unroll
          for (int i = 0; i < 16; i++) pb[i] = t[32 + i];
          wave = (nop >> 2) & 7;
        }
        const int sv = take(rdy0, SZ_KV, ad);
        wg_fence();
        pv(pb, ad, 1);
        sums();
        target();
        op = nop;
        enter();
        rdy0 = rdy1;
        auto convert = [&](float (&u)[96], int j0, int j1) {
#pragma unroll
          for (int i = 4 * j0; i < 4 * j1; i++) {
            q[8 * (i >> 2) + (i & 3)] = pack_bf16(u[4 * i], u[4 * i + 1]);
            q[8 * (i >> 2) + (i & 3) + 4] = pack_bf16(u[4 * i + 2], u[4 * i + 3]);
          }
        };
        if ((op & 3) != OP_O) {
          if ((op & 3) == OP_Q) bi0 = take(rdy0, SZ_WQ, ad);
          wg_wait<0>();
          fence_regs(o);
          release(sv);
          float u[96];
#pragma unroll
          for (int i = 0; i < 96; i++) u[i] = o[i] * (i & 2 ? i1 : i0);
          if ((op & 3) != OP_Q) { convert(u, 0, 6); break; }
          fence_regs(u);
          xw(ad, 0);
          sched_fence(img0, P.zero);
          fence_regs(u);
          convert(u, 0, 1);
          stg2_if(true, pend, q[0], q[1], q[2], q[3], q[4], q[5], q[6], q[7], spol);
          probe1();
          wg_wait<0>();
          release(bi0);
          bi0 = take(rdy0, SZ_WQ, ad);
          xw(ad, 1);
          sched_fence(img0, P.zero);
          fence_regs(u);
          convert(u, 1, 6);
          k = 1;
          continue;
        }
        int bi = ow(0, 0);
        wg_wait<2>();
        fence_regs(o);
        release(sv);
#pragma unroll
        for (int j = 0; j < 6; j++) {
          uint32_t t[8];
#pragma unroll
          for (int i = 0; i < 4; i++) {
            t[i] = pack_bf16(o[16 * j + 4 * i] * i0, o[16 * j + 4 * i + 1] * i0);
            t[i + 4] = pack_bf16(o[16 * j + 4 * i + 2] * i1, o[16 * j + 4 * i + 3] * i1);
          }
          stg2_if(true, pend + j * 512, t[0], t[1], t[2], t[3], t[4], t[5], t[6], t[7], spol);
          if (j == 5) {
            __syncwarp();
            mbar_arrive_if(tell, odone);
          }
          probe1();
          wg_wait<1>();
          bi = ow(1, bi);
          fence_regs(o);
        }
        {
          const int nk = 12 * (((op >> 5) & 15) - ((op >> 2) & 7)) - ((op & F_ST) ? 0 : 2);
#pragma unroll 1
          for (int k = 7; k < nk; k++) {
            probe1();
            wg_wait<1>();
            bi = ow(1, bi);
          }
        }
        if (!(op & F_ST)) {
          probe2();
          wg_wait<1>();
          if (wg) {
            wg_wait<0>();
            release(bi);
            bar_sync(2, 256);
          }
          bi0 = ow(2, 0);
          rdy0 = rdy1;
          const int b = ow(2, 0);
          if (!wg) asm volatile("bar.arrive 2, 256;" ::: "memory");
          wg_wait<4>();
          mbar_arrive_cluster_if(tell && !wg, empty_rem + bi);
          bi = b;
        }
        probe1();
        nop = prog[++pc];
        if (op & F_LD) {
          uint32_t t[80];
#pragma unroll
          for (int j = 0; j < 5; j++) {
            const int b = take(rdy0, SZ_PART, ad);
            probe1();
#pragma unroll
            for (int i = 4 * j; i < 4 * j + 4; i++)
              lds128(img0 + at(ad) + ((i >> 1) & 1) * 8192 + (i & 1) * 512, t[4 * i], t[4 * i + 1], t[4 * i + 2], t[4 * i + 3]);
            release(b);
          }
          wg_wait<0>();
          fence_regs(c);
#pragma unroll
          for (int i = 0; i < 80; i++) c[i] += __uint_as_float(t[i]);
        }
        if (!(op & F_ST)) {
          wg_wait<0>();
          fence_regs(c);
          release(bi0);
          release(bi);
          goto finish;
        }
        wave = spare((op >> 5) & 15);
        op = nop;
        enter();
        bi0 = take(rdy0, SZ_WQ, ad);
        if (wg) bar_sync(2, 256);
        xw(ad, 0);
        if (!wg) asm volatile("bar.arrive 2, 256;" ::: "memory");
        target();
        probe1();
        wg_wait<1>();
        fence_regs(c);
        release(bi);
        st_part(0); st_part(1);
        wg_wait<0>();
        release(bi0);
        bi0 = take(rdy0, SZ_WQ, ad);
        xw(ad, 1);
        st_part(2); st_part(3);
#pragma unroll
        for (int i = 0; i < 48; i++) q[i] = __float_as_uint(c[32 + i]);
        pend += 12 * 1024;
        k = 1; lag = 2;
      }
    }
    rdy0 = false;
    {
      uint32_t t[48];
#pragma unroll
      for (int i = 0; i < 48; i++) t[i] = q[i] ^ P.zero;
      while ((op & 3) == OP_O) {
        int bi = ow(0, 0);
#pragma unroll 1
        for (int k = 1; k < 12 * (int)(((op >> 5) & 15) - ((op >> 2) & 7)); k++) {
          drain(t, k - 1);
          probe1();
          wg_wait<1>();
          bi = ow(1, bi);
        }
        rdy0 = false;
        wg_wait<0>();
        fence_regs(c);
        pc++;
        release(bi);
        if (!(op & F_ST)) goto finish;
        const int ro = ((op >> 26) & 56) | ((op >> 9) & 7);
        pend = (uint4*)((char*)&g_o[(((ro >> 2) * 2 + rank) * 120 + 3 * (4 * spare(0) + (ro & 3))) * 1024] + img0);
#pragma unroll
        for (int i = 0; i < 4; i++) st_part(i);
        pend += 12 * 1024;
#pragma unroll
        for (int i = 0; i < 48; i++) t[i] = __float_as_uint(c[32 + i]) ^ P.zero;
        op = prog[pc];
        enter();
      }
      for (int i = 0; i < 6; i++) drain(t, i);
    }
    if (false) {
    finish:
      uint32_t ad;
      take(rdy0, SZ_OUT, ad);
      const uint32_t wstage = sbase + (ad - ring16) * 16 + (wg * 4 + warp) * 5120;
      const uint32_t sa = wstage + (lane & 15) * 64;
#pragma unroll
      for (int i = 0; i < 10; i++) {
        const int u = (i & 1) * 2 + (lane >> 4);
        stsm4(sa + (i >> 1) * 1024 + ((u ^ ((lane >> 1) & 3)) << 4), pack_bf16(c[8 * i], c[8 * i + 1]), pack_bf16(c[8 * i + 2], c[8 * i + 3]),
              pack_bf16(c[8 * i + 4], c[8 * i + 5]), pack_bf16(c[8 * i + 6], c[8 * i + 7]));
      }
      asm volatile("fence.proxy.async.shared::cta;" ::: "memory");
      __syncwarp();
      if (lane == 0) {
        tma3d_store(&P.out, wstage, 0, (team & 7) * kSq + rank * 128 + wg * 64 + warp * 16, blk * 20 + nt * 5);
        asm volatile("cp.async.bulk.commit_group;\ncp.async.bulk.wait_group.read 0;" ::: "memory");
      }
    }
  }
}

typedef CUresult (*EncodeFn)(CUtensorMap*, CUtensorMapDataType, cuuint32_t, void*, const cuuint64_t*, const cuuint64_t*,
                             const cuuint32_t*, const cuuint32_t*, CUtensorMapInterleave, CUtensorMapSwizzle,
                             CUtensorMapL2promotion, CUtensorMapFloatOOBfill);

void encode(EncodeFn fn, CUtensorMap* m, const void* ptr, int rank, const cuuint64_t* dims, const cuuint64_t* strides,
            const cuuint32_t* box, CUtensorMapSwizzle swz) {
  const cuuint32_t es[5] = {1, 1, 1, 1, 1};
  CUresult r = fn(m, CU_TENSOR_MAP_DATA_TYPE_BFLOAT16, rank, const_cast<void*>(ptr), dims, strides, box, es,
                  CU_TENSOR_MAP_INTERLEAVE_NONE, swz, CU_TENSOR_MAP_L2_PROMOTION_L2_128B, CU_TENSOR_MAP_FLOAT_OOB_FILL_NONE);
  if (r != CUDA_SUCCESS) fprintf(stderr, "cuTensorMapEncodeTiled failed: %d\n", (int)r);
}

void annotate(uint32_t* ops, int n, bool helper) {
  uint32_t items = 0, cur = 0, pend = 0;
  auto item = [&](uint32_t bytes, int count, uint32_t bytes2 = 0) {
    for (int i = 0; i < count; i++) {
      if (cur + bytes > RING) cur = 0;
      cur += bytes;
      if (cur + bytes2 > RING) cur = 0;
      cur += bytes2;
      items++;
    }
  };
  for (int i = 0; i <= n; i++) {
    const uint32_t op = ops[i];
    ops[i] |= (items % (2 * NBAR)) << 15 | (cur >> 12) << 20 | pend << 26;
    if ((op & 3) == OP_Q) { item(SZ_WQ, 10, SZ_A); pend = (op & F_PARK) ? (helper ? 1 : 2) : 0; }
    if ((op & 3) == OP_A) {
      item(SZ_KV, (op & F_PARK) ? 30 : 31);
      if ((ops[i + 1] & 3) == OP_A) { item(SZ_PARK, 2); item(SZ_KV, 1); }
      item(SZ_KV, 1);
      pend = 1;
    }
    if ((op & 3) == OP_O) {
      item(SZ_A, 12 * (((op >> 5) & 15) - ((op >> 2) & 7)), SZ_WO);
      if (op & F_LD) item(SZ_PART, 5);
      pend = (op & F_ST) ? (helper ? 1 : 2) : 0;
    }
  }
}

void compile_programs(const char* const* text, bool helpers, uint32_t (*rows)[MAX_OPS]) {
  struct Req { int when, team, wave, slot; } req[N_TEAM * MAX_PARK];
  int n_req = 0;
  for (int t = 0; t < N_TEAM; t++) {
    uint32_t* ops = rows[t];
    int n = 0, flags[8] = {0, 0, 0, 0, 0, 0, 0, 0}, n_park = 0, last_o = -1, when = 0, given = 0;
    for (const char* s = text[t]; *s; s++) {
      const int a = s[1] - '0';
      if (*s == 'Q' || (*s == 'H' && !helpers)) { ops[n++] = OP_Q | a << 2; when += 10; }
      else if (*s == 'P') { flags[a] = F_PARK; ops[n++] = OP_Q | a << 2 | flags[a]; when += 10; }
      else if (*s == 'H') { req[n_req++] = {when, t, a, n_park}; flags[a] = F_PARK | F_HELP | n_park++ << 10; }
      else if (*s == 'A') { ops[n++] = OP_A | a << 2 | flags[a]; when += 32; }
      else if (*s == 'G') { given = a; if (helpers) req[n_req++] = {1000, t, 0, -a}; }
      else if (*s == 'O') {
        ops[n] = OP_O | a << 2 | (s[2] - '0') << 5;
        if (given) ops[n] = helpers ? ops[n] | F_LD | F_PARK | (MAX_PARK - 1) << 10 : ops[n] & ~(7u << 2);
        if (last_o >= 0) { ops[last_o] |= F_ST; ops[n] |= F_LD; }
        last_o = n++;
        when += 10 * (s[2] - s[1]);
      }
    }
    for (int i = n; i < MAX_OPS; i++) ops[i] = OP_END;
    annotate(ops, n, false);
  }
  for (int i = 1; i < n_req; i++)
    for (int j = i; j > 0 && req[j].when < req[j - 1].when; j--) { Req r = req[j]; req[j] = req[j - 1]; req[j - 1] = r; }
  for (int h = 0; h < N_HELP; h++) {
    uint32_t* ops = rows[N_TEAM + 2 * h];
    int n = 0;
    for (int i = 0; i < n_req; i++)
      for (int m = h; m < 4; m += N_HELP) {
        const uint32_t ro = 4 * req[i].team + m;
        ops[n++] = req[i].slot >= 0 ? OP_Q | req[i].wave << 2 | req[i].team << 5 | F_PARK | req[i].slot << 10 | m << 12
                                    : OP_O | -req[i].slot << 5 | F_ST | (ro & 7) << 9 | (ro >> 3) << 29;
      }
    for (int i = n; i < 2 * MAX_OPS; i++) ops[i] = OP_END;
    annotate(ops, n, true);
  }
}

const char* const kPrograms[N_TEAM] = {
  "Q0A0Q1A1Q2A2Q3A3Q4A4O05Q5A5Q6A6H7A7O58",
  "Q0A0Q1A1H2A2O03Q3A3Q4A4Q5A5Q6A6Q7A7O38",
  "Q0A0H1A1Q2A2O03Q3A3Q4A4Q5A5Q6A6Q7A7O38",
  "Q0A0Q1A1Q2A2Q3A3Q4A4O05Q5A5Q6A6H7A7O58",
  "Q0A0Q1A1Q2A2Q3A3Q4A4O05Q5A5H6A6Q7A7O58",
  "Q0A0Q1A1H2A2O03Q3A3Q4A4Q5A5Q6A6Q7A7O38",
  "Q0A0Q1A1Q2A2Q3A3Q4A4O05Q5A5Q6A6H7A7O58",
  "Q0A0Q1A1Q2A2O03Q3A3H4A4Q5A5Q6A6Q7A7O38",
  "P3Q0A0Q1A1Q2A2A3Q4A4H5A5Q6A6Q7A7O08",
  "P3Q0A0Q1A1Q2A2A3H4A4Q5A5Q6A6Q7A7O08",
  "P4Q0A0Q1A1Q2A2Q3A3A4Q5A5Q6A6Q7A7G1O18",
  "P4Q0A0Q1A1Q2A2H3A3A4Q5A5Q6A6Q7A7O08",
  "Q0A0Q1A1Q2A2H3A3Q4A4Q5A5Q6A6Q7A7O08",
  "P3P7Q0A0Q1A1Q2A2A3Q4A4H5A5Q6A6A7G1O18",
  "P4P7Q0A0Q1A1Q2A2Q3A3A4Q5A5H6A6A7O08",
  "P2P3Q0A0Q1A1A2A3Q4A4H5A5Q6A6Q7A7G1O18",
};

cudaLaunchConfig_t config(int clusters, int size, cudaLaunchAttribute* at) {
  cudaLaunchConfig_t cfg = {};
  cfg.gridDim = dim3(clusters * size); cfg.blockDim = dim3(384); cfg.dynamicSmemBytes = SMEM_BYTES; cfg.stream = cudaStreamPerThread;
  at[0].id = cudaLaunchAttributeClusterDimension; at[0].val.clusterDim.x = size; at[0].val.clusterDim.y = 1; at[0].val.clusterDim.z = 1;
  at[1].id = cudaLaunchAttributeProgrammaticStreamSerialization; at[1].val.programmaticStreamSerializationAllowed = 1;
  cfg.attrs = at; cfg.numAttrs = 1;
  return cfg;
}

void launch(Params& P, int role0, int clusters, int size, bool overlap) {
  cudaLaunchAttribute at[2];
  cudaLaunchConfig_t cfg = config(clusters, size, at);
  cfg.numAttrs = overlap ? 2 : 1;
  for (int i = 0; i < 30; i++) P.first[i] = i < N_TEAM ? P.ops[i][0] : i < N_TEAM + N_HELP ? P.ops[2 * i - N_TEAM][0] : 0;
  P.role0 = role0; P.wide = size > 2;
  cudaLaunchKernelEx(&cfg, fused_kernel, P);
}

const char* const* bench_programs() {
  return kPrograms;
}

}

extern "C" void kernel_launch(void* const* d_in, const int* in_sizes, int n_in, void* d_out, int out_size) {
  (void)in_sizes; (void)n_in; (void)out_size;
  static EncodeFn fn = nullptr;
  static int n_clusters = 0, n_wide = 0;
  if (!fn) {
    cudaDriverEntryPointQueryResult qr;
    void* f = nullptr;
    cudaGetDriverEntryPoint("cuTensorMapEncodeTiled", &f, cudaEnableDefault, &qr);
    fn = (EncodeFn)f;
    cudaFuncSetAttribute(fused_kernel, cudaFuncAttributeMaxDynamicSharedMemorySize, SMEM_BYTES);
    cudaLaunchAttribute at[2];
    cudaLaunchConfig_t cfg = config(N_CL + N_HELP, 2, at);
    if (cudaOccupancyMaxActiveClusters(&n_clusters, fused_kernel, &cfg) != cudaSuccess || n_clusters < 1) n_clusters = 1;
    cfg = config(N_WIDE / WIDE, 2 * WIDE, at);
    if (cudaOccupancyMaxActiveClusters(&n_wide, fused_kernel, &cfg) != cudaSuccess) n_wide = 0;
    (void)cudaGetLastError();
  }
  Params P;
  const CUtensorMapSwizzle S128 = CU_TENSOR_MAP_SWIZZLE_128B, S64 = CU_TENSOR_MAP_SWIZZLE_64B;
  for (int blk = 0; blk < 2; blk++) {
    void* const* in = d_in + 5 * blk;
    { const cuuint64_t d[] = {kD, kB * kSq}, s[] = {kD * 2}; const cuuint32_t b[] = {64, 128};
      encode(fn, &P.x[blk], in[0], 2, d, s, b, S128);
      const cuuint32_t b2[] = {64, 128 / WIDE};
      encode(fn, &P.x[2 + blk], in[0], 2, d, s, b2, S128); }
    { const cuuint64_t d[] = {64, 8, 3, (cuuint64_t)kB * kH * kSk / 8}, s[] = {kDh * 2, 128, 8 * kDh * 2}; const cuuint32_t b[] = {64, 8, 3, 4};
      encode(fn, &P.kv[blk], in[1], 4, d, s, b, S128);
      encode(fn, &P.kv[blk + 2], in[2], 4, d, s, b, S128); }
    { const cuuint64_t d[] = {64, kD, kHD / 64}, s[] = {kHD * 2, 128}; const cuuint32_t b[] = {64, 32, 3};
      encode(fn, &P.wq[blk], in[3], 3, d, s, b, S128); }
    { const cuuint64_t d[] = {32, 2, kHD / 8, 4, kD / 32}, s[] = {kD * 2, 8 * kD * 2, 2 * kD * 2, 64}; const cuuint32_t b[] = {32, 2, 4, 4, 5};
      encode(fn, &P.wo[blk], in[4], 5, d, s, b, S64); }
  }
  { const cuuint64_t d[] = {32, kB * kSq, 2 * kD / 32}, s[] = {2 * kD * 2, 64}; const cuuint32_t b[] = {32, 16, 5};
    encode(fn, &P.out, d_out, 3, d, s, b, S64); }

  P.zero = 0;
  compile_programs(bench_programs(), false, P.ops + N_ROWS);
  if (n_clusters >= N_CL) {
    const bool helpers = n_clusters >= N_CL + N_HELP;
    compile_programs(bench_programs(), helpers, P.ops);
    if (helpers && n_wide >= N_WIDE / WIDE) {
      launch(P, 0, N_WIDE / WIDE, 2 * WIDE, false);
      launch(P, N_WIDE, N_CL + N_HELP - N_WIDE, 2, true);
    } else {
      launch(P, 0, N_CL + (helpers ? N_HELP : 0), 2, false);
    }
  } else {
    for (int phase = 0; phase < 2; phase++) {
      const char* text[N_TEAM];
      for (int t = 0; t < N_TEAM; t++) text[t] = phase ? "O08" : "Q0A0Q1A1Q2A2Q3A3Q4A4Q5A5Q6A6Q7A7";
      compile_programs(text, false, P.ops);
      launch(P, 0, N_CL, 2, false);
    }
  }
}
```
